```python
import torch

def _softmax(x, axis=-1):
    return torch.softmax(x, dim=axis)

def _gelu(x):
    return torch.nn.functional.gelu(x, approximate='tanh')

def _silu(x):
    return torch.nn.functional.silu(x)

def _sigmoid(x):
    return torch.sigmoid(x)

def _layernorm(x, axis=-1, eps=1e-05):
    m = x.mean(dim=axis, keepdim=True)
    v = x.var(dim=axis, keepdim=True, unbiased=False)
    return (x - m) / torch.sqrt(v + eps)

def _scatter_add(tgt, idx, src, axis=0):
    return tgt.clone().index_add_(axis, idx, src)

def _segment_sum(src, seg, n):
    out = torch.zeros((n,) + src.shape[1:], dtype=src.dtype)
    return out.index_add_(0, seg, src)

def _pad(x, pw):
    flat = tuple((v for pair in reversed(pw) for v in pair))
    return torch.nn.functional.pad(x, flat)
kernel_name = 'interleave_layers__linear_attn_block__memory_aug_recurrent_mem_tr__prompt'

def setup_inputs():

    _w = lambda a: (lambda t: t.to(torch.bfloat16) if t.is_floating_point() else t)(torch.as_tensor(a))

    def _A_setup():
        B, S, D = (1, 2048, 640)
        return {'x': _w((lambda *s: torch.randn(*s, dtype=torch.bfloat16) * 0.05)(B, S, D)), 'wqkv': _w((lambda *s: torch.randn(*s, dtype=torch.bfloat16) * 0.05)(D, 3 * D)), 'wo': _w((lambda *s: torch.randn(*s, dtype=torch.bfloat16) * 0.05)(D, D))}
    _A_in = _A_setup()

    def _B_setup():
        B, S, Dm = (1, 2048, 640)
        H, Dh = (32, 192)
        M, seg = (8, 32)
        seg = min(seg, S)
        S = S // seg * seg
        return {'x': _w((lambda *s: torch.randn(*s, dtype=torch.bfloat16) * 0.05)(B, S, Dm)), 'mem0': _w((lambda *s: torch.randn(*s, dtype=torch.bfloat16) * 0.8)(B, M, Dm)), 'Wq': _w((lambda *s: torch.randn(*s, dtype=torch.bfloat16) * 1.6)(Dm, H, Dh) * Dm ** (-0.5)), 'Wk': _w((lambda *s: torch.randn(*s, dtype=torch.bfloat16) * 1.6)(Dm, H, Dh) * Dm ** (-0.5)), 'Wv': _w((lambda *s: torch.randn(*s, dtype=torch.bfloat16) * 0.8)(Dm, H, Dh) * Dm ** (-0.5)), 'Wo': _w((lambda *s: torch.randn(*s, dtype=torch.bfloat16) * 0.8)(H, Dh, Dm) * (H * Dh) ** (-0.5)), 'seg_len': seg}
    _B_in = _B_setup()
    return {'A_x': _A_in['x'], 'A_wqkv': _A_in['wqkv'], 'A_wo': _A_in['wo'], 'B_x': _B_in['x'], 'B_mem0': _B_in['mem0'], 'B_Wq': _B_in['Wq'], 'B_Wk': _B_in['Wk'], 'B_Wv': _B_in['Wv'], 'B_Wo': _B_in['Wo'], 'B_seg_len': _B_in['seg_len']}

def reference(A_x, A_wqkv, A_wo, B_x, B_mem0, B_Wq, B_Wk, B_Wv, B_Wo, B_seg_len):

    def _A_ref(x, wqkv, wo):
        B, S, D = x.shape
        H = 32
        Dh = D // H
        qkv = (lambda x, *d: x.permute(*d))((x @ wqkv).reshape(B, S, 3, H, Dh), 2, 0, 3, 1, 4)
        q, k, v = (qkv[0], qkv[1], qkv[2])
        phi = lambda t: torch.where(t > 0, t + 1, torch.exp(t)) + 1e-06
        pq, pk = (phi(q), phi(k))
        kv = torch.einsum('bhsd,bhse->bhde', pk, v)
        z = torch.einsum('bhsd->bhd', pk)
        num = torch.einsum('bhqd,bhde->bhqe', pq, kv)
        den = torch.einsum('bhqd,bhd->bhq', pq, z)[..., None] + 1e-06
        o = num / den
        return (lambda x, *d: x.permute(*d))(o, 0, 2, 1, 3).reshape(B, S, D) @ wo

    def _B_ref(x, mem0, Wq, Wk, Wv, Wo, seg_len):
        B, S, Dm = x.shape
        H, Dh = (Wq.shape[1], Wq.shape[2])
        M = mem0.shape[1]
        scale = Dh ** (-0.5)
        n_seg = S // seg_len
        L = M + seg_len
        idx = torch.arange(L)
        mask = (idx[:, None] < M) | (idx[:, None] >= idx[None, :])
        mem = mem0
        outs = []
        for s in range(n_seg):
            xs = x[:, s * seg_len:(s + 1) * seg_len, :].clone()
            h = torch.concatenate([mem, xs], axis=1)
            q = torch.einsum('btd,dhe->bhte', h, Wq)
            k = torch.einsum('btd,dhe->bhte', h, Wk)
            v = torch.einsum('btd,dhe->bhte', h, Wv)
            scores = torch.einsum('bhqe,bhke->bhqk', q, k) * scale
            scores = torch.where(mask[None, None], scores, -1000000000.0)
            p = _softmax(scores, axis=-1)
            o = torch.einsum('bhqk,bhke->bhqe', p, v)
            o = torch.einsum('bhte,hed->btd', o, Wo)
            mem = o[:, :M, :].clone()
            outs.append(o[:, M:, :])
        return torch.concatenate(outs, axis=1)
    x = A_x
    x = x + _A_ref(_layernorm(x, axis=-1), A_wqkv, A_wo)
    x = x + _B_ref(_layernorm(x, axis=-1), B_mem0, B_Wq, B_Wk, B_Wv, B_Wo, B_seg_len)
    x = x + _A_ref(_layernorm(x, axis=-1), A_wqkv, A_wo)
    x = x + _B_ref(_layernorm(x, axis=-1), B_mem0, B_Wq, B_Wk, B_Wv, B_Wo, B_seg_len)
    return x
```

```cpp
#include <cuda_runtime.h>
#include <cuda_bf16.h>
#include <cuda.h>
#include <stdint.h>

typedef __nv_bfloat16 bf16;
typedef unsigned long long u64;

constexpr int S_TOK = 2048, DM = 640, NH = 32, DH = 192, HE = 6144, NSEG = 64;

constexpr int AR_GROUP = 98304;
constexpr int AR_LAYER = 16 * AR_GROUP;
__device__ __align__(1024) uint8_t g_ar[2 * AR_LAYER + 32768];
__device__ __align__(1024) uint8_t g_xn[NSEG * 40960];
__device__ __align__(1024) uint8_t g_ot[32 * HE * 128];
__device__ float g_norm[1024];
__device__ float g_x[S_TOK * DM];
__device__ bf16 g_xa[S_TOK * DM];
__device__ float g_qkv[S_TOK * 1920];
__device__ float g_kv[2 * 32 * 21 * 20];
__device__ bf16 g_oa[S_TOK * DM];

__device__ __forceinline__ uint32_t smem_u32(const void* p) { return (uint32_t)__cvta_generic_to_shared(p); }
__device__ __forceinline__ uint32_t mapa(uint32_t a, uint32_t r) { uint32_t o; asm("mapa.shared::cluster.u32 %0, %1, %2;" : "=r"(o) : "r"(a), "r"(r)); return o; }
__device__ __forceinline__ void mbar_init(uint32_t bar, uint32_t cnt) { asm volatile("mbarrier.init.shared::cta.b64 [%0], %1;" :: "r"(bar), "r"(cnt) : "memory"); }
__device__ __forceinline__ void mbar_expect(uint32_t bar, uint32_t tx) { asm volatile("mbarrier.arrive.expect_tx.shared::cta.b64 _, [%0], %1;" :: "r"(bar), "r"(tx) : "memory"); }
__device__ __forceinline__ void mbar_arrive(uint32_t bar) { asm volatile("mbarrier.arrive.shared::cta.b64 _, [%0];" :: "r"(bar) : "memory"); }
__device__ __forceinline__ void mbar_wait(uint32_t bar, uint32_t par) {
  asm volatile("{\n.reg .pred p;\n.reg .u32 c;\nmov.u32 c, 0;\n"
               "LW:\nmbarrier.try_wait.parity.shared::cta.b64 p, [%0], %1;\n@p bra LD;\n"
               "add.u32 c, c, 1;\nsetp.lt.u32 p, c, 4000000;\n@p bra LW;\ntrap;\nLD:\n}" :: "r"(bar), "r"(par) : "memory");
}
__device__ __forceinline__ void mbar_wait_cl(uint32_t bar, uint32_t par) {
  asm volatile("{\n.reg .pred p;\n.reg .u32 c;\nmov.u32 c, 0;\n"
               "LW:\nmbarrier.try_wait.parity.acquire.cluster.shared::cta.b64 p, [%0], %1;\n@p bra LD;\n"
               "add.u32 c, c, 1;\nsetp.lt.u32 p, c, 4000000;\n@p bra LW;\ntrap;\nLD:\n}" :: "r"(bar), "r"(par) : "memory");
}
template <int ID, int N> __device__ __forceinline__ void bar_sync() { asm volatile("barrier.sync %0, %1;" :: "n"(ID), "n"(N) : "memory"); }
template <int ID, int N> __device__ __forceinline__ void bar_arrive() { asm volatile("barrier.arrive %0, %1;" :: "n"(ID), "n"(N) : "memory"); }
__device__ __forceinline__ void fence_async() { asm volatile("fence.proxy.async.shared::cta;" ::: "memory"); }
__device__ __forceinline__ void cluster_sync() { asm volatile("barrier.cluster.arrive.aligned;\nbarrier.cluster.wait.aligned;" ::: "memory"); }
__device__ __forceinline__ void wg_fence() { asm volatile("wgmma.fence.sync.aligned;" ::: "memory"); }
__device__ __forceinline__ void wg_commit() { asm volatile("wgmma.commit_group.sync.aligned;" ::: "memory"); }
template <int N> __device__ __forceinline__ void wg_wait() { asm volatile("wgmma.wait_group.sync.aligned %0;" :: "n"(N) : "memory"); }
template <int N> __device__ __forceinline__ void pin(float* d) {
#pragma unroll
  for (int i = 0; i < N; i++) asm volatile("" : "+f"(d[i]) :: "memory");
}
__device__ __forceinline__ uint64_t mkdesc(uint32_t addr, uint32_t lbo, uint32_t sbo, int sw) {
  return (uint64_t)((addr & 0x3FFFF) >> 4) | ((uint64_t)(lbo >> 4) << 16) | ((uint64_t)(sbo >> 4) << 32) | ((uint64_t)sw << 62);
}
__device__ __forceinline__ uint32_t opaque(uint32_t v) { uint32_t o; asm volatile("mov.u32 %0, %1;" : "=r"(o) : "r"(v)); return o; }
__device__ __forceinline__ uint32_t pack2(float lo, float hi) { uint32_t r; asm("cvt.rn.bf16x2.f32 %0, %1, %2;" : "=r"(r) : "f"(hi), "f"(lo)); return r; }
__device__ __forceinline__ void ldsm4(uint32_t* r, uint32_t a) { asm volatile("ldmatrix.sync.aligned.m8n8.x4.shared.b16 {%0,%1,%2,%3}, [%4];" : "=r"(r[0]), "=r"(r[1]), "=r"(r[2]), "=r"(r[3]) : "r"(a) : "memory"); }
__device__ __forceinline__ void ldsm4t(uint32_t* r, uint32_t a) { asm volatile("ldmatrix.sync.aligned.m8n8.x4.trans.shared.b16 {%0,%1,%2,%3}, [%4];" : "=r"(r[0]), "=r"(r[1]), "=r"(r[2]), "=r"(r[3]) : "r"(a) : "memory"); }
__device__ __forceinline__ void ldsm1(uint32_t& r, uint32_t a) { asm volatile("ldmatrix.sync.aligned.m8n8.x1.shared.b16 {%0}, [%1];" : "=r"(r) : "r"(a) : "memory"); }
__device__ __forceinline__ void stsm4(uint32_t a, uint32_t r0, uint32_t r1, uint32_t r2, uint32_t r3) { asm volatile("stmatrix.sync.aligned.m8n8.x4.shared.b16 [%0], {%1,%2,%3,%4};" :: "r"(a), "r"(r0), "r"(r1), "r"(r2), "r"(r3) : "memory"); }
__device__ __forceinline__ void stsm1(uint32_t a, uint32_t r0) { asm volatile("stmatrix.sync.aligned.m8n8.x1.shared.b16 [%0], {%1};" :: "r"(a), "r"(r0) : "memory"); }
__device__ __forceinline__ void stsm4t(uint32_t a, uint32_t r0, uint32_t r1, uint32_t r2, uint32_t r3) { asm volatile("stmatrix.sync.aligned.m8n8.x4.trans.shared.b16 [%0], {%1,%2,%3,%4};" :: "r"(a), "r"(r0), "r"(r1), "r"(r2), "r"(r3) : "memory"); }
__device__ __forceinline__ void stsm2t(uint32_t a, uint32_t r0, uint32_t r1) { asm volatile("stmatrix.sync.aligned.m8n8.x2.trans.shared.b16 [%0], {%1,%2};" :: "r"(a), "r"(r0), "r"(r1) : "memory"); }
__device__ __forceinline__ void mma16816(float* c, const uint32_t* a, uint32_t b0, uint32_t b1) {
  asm volatile("mma.sync.aligned.m16n8k16.row.col.f32.bf16.bf16.f32 {%0,%1,%2,%3}, {%4,%5,%6,%7}, {%8,%9}, {%0,%1,%2,%3};"
               : "+f"(c[0]), "+f"(c[1]), "+f"(c[2]), "+f"(c[3]) : "r"(a[0]), "r"(a[1]), "r"(a[2]), "r"(a[3]), "r"(b0), "r"(b1));
}
__device__ __forceinline__ void mma1688(float* c, uint32_t a0, uint32_t a1, uint32_t b0) {
  asm volatile("mma.sync.aligned.m16n8k8.row.col.f32.bf16.bf16.f32 {%0,%1,%2,%3}, {%4,%5}, {%6}, {%0,%1,%2,%3};"
               : "+f"(c[0]), "+f"(c[1]), "+f"(c[2]), "+f"(c[3]) : "r"(a0), "r"(a1), "r"(b0));
}
__device__ __forceinline__ void sta1(uint32_t a, uint32_t v, uint32_t bar) { asm volatile("st.async.weak.shared::cluster.mbarrier::complete_tx::bytes.b32 [%0], %1, [%2];" :: "r"(a), "r"(v), "r"(bar) : "memory"); }
__device__ __forceinline__ void sta2(uint32_t a, uint32_t v0, uint32_t v1, uint32_t bar) { asm volatile("st.async.weak.shared::cluster.mbarrier::complete_tx::bytes.v2.b32 [%0], {%1,%2}, [%3];" :: "r"(a), "r"(v0), "r"(v1), "r"(bar) : "memory"); }
__device__ __forceinline__ void sta2f(uint32_t a, float v0, float v1, uint32_t bar) { asm volatile("st.async.weak.shared::cluster.mbarrier::complete_tx::bytes.v2.f32 [%0], {%1,%2}, [%3];" :: "r"(a), "f"(v0), "f"(v1), "r"(bar) : "memory"); }
__device__ __forceinline__ void sta4f(uint32_t a, float v0, float v1, float v2, float v3, uint32_t bar) { asm volatile("st.async.weak.shared::cluster.mbarrier::complete_tx::bytes.v4.f32 [%0], {%1,%2,%3,%4}, [%5];" :: "r"(a), "f"(v0), "f"(v1), "f"(v2), "f"(v3), "r"(bar) : "memory"); }
__device__ __forceinline__ float4 lds4f(uint32_t a) { float4 v; asm volatile("ld.shared.v4.f32 {%0,%1,%2,%3}, [%4];" : "=f"(v.x), "=f"(v.y), "=f"(v.z), "=f"(v.w) : "r"(a) : "memory"); return v; }
__device__ __forceinline__ float2 lds2f(uint32_t a) { float2 v; asm volatile("ld.shared.v2.f32 {%0,%1}, [%2];" : "=f"(v.x), "=f"(v.y) : "r"(a) : "memory"); return v; }
__device__ __forceinline__ uint4 lds4(uint32_t a) { uint4 v; asm volatile("ld.shared.v4.u32 {%0,%1,%2,%3}, [%4];" : "=r"(v.x), "=r"(v.y), "=r"(v.z), "=r"(v.w) : "r"(a) : "memory"); return v; }
__device__ __forceinline__ void sts1(uint32_t a, uint32_t v) { asm volatile("st.shared.u32 [%0], %1;" :: "r"(a), "r"(v) : "memory"); }
__device__ __forceinline__ void bulk_g2s(uint32_t dst, const void* src, uint32_t bytes, uint32_t bar) {
  asm volatile("cp.async.bulk.shared::cluster.global.mbarrier::complete_tx::bytes [%0], [%1], %2, [%3];" :: "r"(dst), "l"(src), "r"(bytes), "r"(bar) : "memory");
}
__device__ __forceinline__ void tma2d(uint32_t dst, const CUtensorMap* m, int c0, int c1, uint32_t bar) {
  asm volatile("cp.async.bulk.tensor.2d.shared::cluster.global.mbarrier::complete_tx::bytes [%0], [%1, {%3, %4}], [%2];" :: "r"(dst), "l"((uint64_t)m), "r"(bar), "r"(c0), "r"(c1) : "memory");
}
__device__ __forceinline__ void red64(void* p, uint32_t lo, uint32_t hi) { asm volatile("{\n.reg .b64 t;\nmov.b64 t, {%1,%2};\nred.relaxed.gpu.global.add.u64 [%0], t;\n}" :: "l"(p), "r"(lo), "r"(hi) : "memory"); }
__device__ __forceinline__ uint4 ld_poll(const void* p) {
  uint4 v;
  asm volatile("{\n.reg .b64 a, b;\nld.relaxed.gpu.global.v2.b64 {a, b}, [%4];\nmov.b64 {%0,%1}, a;\nmov.b64 {%2,%3}, b;\n}" : "=r"(v.x), "=r"(v.y), "=r"(v.z), "=r"(v.w) : "l"(p) : "memory");
  return v;
}
__device__ __forceinline__ uint32_t clk() { uint32_t c; asm volatile("mov.u32 %0, %%clock;" : "=r"(c) :: "memory"); return c; }
__device__ __forceinline__ float ex2(float x) { float y; asm("ex2.approx.ftz.f32 %0, %1;" : "=f"(y) : "f"(x)); return y; }

__device__ __forceinline__ void wg_rs_n32_tb0(float* d, const uint32_t* a, uint64_t b, int sc) {
  asm volatile("{\n.reg .pred p;\nsetp.ne.b32 p, %21, 0;\nwgmma.mma_async.sync.aligned.m64n32k16.f32.bf16.bf16 {%0, %1, %2, %3, %4, %5, %6, %7, %8, %9, %10, %11, %12, %13, %14, %15}, {%16, %17, %18, %19}, %20, p, 1, 1, 0;\n}\n"
    : "+f"(d[0]), "+f"(d[1]), "+f"(d[2]), "+f"(d[3]), "+f"(d[4]), "+f"(d[5]), "+f"(d[6]), "+f"(d[7]), "+f"(d[8]), "+f"(d[9]), "+f"(d[10]), "+f"(d[11]), "+f"(d[12]), "+f"(d[13]), "+f"(d[14]), "+f"(d[15])
    : "r"(a[0]), "r"(a[1]), "r"(a[2]), "r"(a[3]), "l"(b), "r"(sc));
}
__device__ __forceinline__ void wg_rs_n8_tb1(float* d, const uint32_t* a, uint64_t b, int sc) {
  asm volatile("{\n.reg .pred p;\nsetp.ne.b32 p, %9, 0;\nwgmma.mma_async.sync.aligned.m64n8k16.f32.bf16.bf16 {%0, %1, %2, %3}, {%4, %5, %6, %7}, %8, p, 1, 1, 1;\n}\n"
    : "+f"(d[0]), "+f"(d[1]), "+f"(d[2]), "+f"(d[3])
    : "r"(a[0]), "r"(a[1]), "r"(a[2]), "r"(a[3]), "l"(b), "r"(sc));
}
__device__ __forceinline__ void wg_ss_n40_ta0_tb0(float* d, uint64_t a, uint64_t b, int sc) {
  asm volatile("{\n.reg .pred p;\nsetp.ne.b32 p, %22, 0;\nwgmma.mma_async.sync.aligned.m64n40k16.f32.bf16.bf16 {%0, %1, %2, %3, %4, %5, %6, %7, %8, %9, %10, %11, %12, %13, %14, %15, %16, %17, %18, %19}, %20, %21, p, 1, 1, 0, 0;\n}\n"
    : "+f"(d[0]), "+f"(d[1]), "+f"(d[2]), "+f"(d[3]), "+f"(d[4]), "+f"(d[5]), "+f"(d[6]), "+f"(d[7]), "+f"(d[8]), "+f"(d[9]), "+f"(d[10]), "+f"(d[11]), "+f"(d[12]), "+f"(d[13]), "+f"(d[14]), "+f"(d[15]), "+f"(d[16]), "+f"(d[17]), "+f"(d[18]), "+f"(d[19])
    : "l"(a), "l"(b), "r"(sc));
}
__device__ __forceinline__ void wg_ss_n40_ta1_tb0(float* d, uint64_t a, uint64_t b, int sc) {
  asm volatile("{\n.reg .pred p;\nsetp.ne.b32 p, %22, 0;\nwgmma.mma_async.sync.aligned.m64n40k16.f32.bf16.bf16 {%0, %1, %2, %3, %4, %5, %6, %7, %8, %9, %10, %11, %12, %13, %14, %15, %16, %17, %18, %19}, %20, %21, p, 1, 1, 1, 0;\n}\n"
    : "+f"(d[0]), "+f"(d[1]), "+f"(d[2]), "+f"(d[3]), "+f"(d[4]), "+f"(d[5]), "+f"(d[6]), "+f"(d[7]), "+f"(d[8]), "+f"(d[9]), "+f"(d[10]), "+f"(d[11]), "+f"(d[12]), "+f"(d[13]), "+f"(d[14]), "+f"(d[15]), "+f"(d[16]), "+f"(d[17]), "+f"(d[18]), "+f"(d[19])
    : "l"(a), "l"(b), "r"(sc));
}
__device__ __forceinline__ void wg_ss_n8_ta1_tb1(float* d, uint64_t a, uint64_t b, int sc) {
  asm volatile("{\n.reg .pred p;\nsetp.ne.b32 p, %6, 0;\nwgmma.mma_async.sync.aligned.m64n8k16.f32.bf16.bf16 {%0, %1, %2, %3}, %4, %5, p, 1, 1, 1, 1;\n}\n"
    : "+f"(d[0]), "+f"(d[1]), "+f"(d[2]), "+f"(d[3])
    : "l"(a), "l"(b), "r"(sc));
}

constexpr int O_WV = 0, O_WO = 81920, O_H = 155648, O_Q = 206848, O_K = 211968, O_OG = 217088, O_SX = 220160, O_MISC = 230912;
constexpr int SX_SLOT = 5376;
constexpr int O_MAXS = O_MISC;
constexpr int O_BAR = O_MISC + 64;
constexpr int MB_XF = 0, MB_MF = 2, MB_SM = 6, MB_SX = 7, MB_OG = 8, MB_W = 9;
constexpr int REC_SMEM = O_BAR + 8 * 24;
constexpr int B_QK = 1, B_VGO = 2, B_SISS = 3, B_PM = 4, B_PX = 5, B_XGO = 6, B_PFREE = 7, B_WG2 = 8, B_WG0 = 9, B_VDONE = 10, B_ALL = 11;
#define POLL_DELAY 600
#define TS(idx) do {} while (0)

__device__ __forceinline__ void fix_red(uint8_t* p, const float* a, float sc) {
  int v0 = __float2int_rn(a[0] * sc), v1 = __float2int_rn(a[1] * sc), v2 = __float2int_rn(a[2] * sc), v3 = __float2int_rn(a[3] * sc);
  red64(p, ((uint32_t)v0 << 7) | 1u, ((uint32_t)v2 << 3) + (uint32_t)(v0 >> 25));
  red64(p + 1024, ((uint32_t)v1 << 7) | 1u, ((uint32_t)v3 << 3) + (uint32_t)(v1 >> 25));
}

__global__ void __launch_bounds__(384, 1)
rec_kernel(const __grid_constant__ CUtensorMap tmq, const __grid_constant__ CUtensorMap tmk,
           const __grid_constant__ CUtensorMap tmv, const __grid_constant__ CUtensorMap tmo,
           const bf16* __restrict__ mem0, uint8_t* __restrict__ ar) {
  extern __shared__ __align__(1024) uint8_t smem[];
  const uint32_t sb = smem_u32(smem);
  const int tid = threadIdx.x, wid = __shfl_sync(~0u, tid >> 5, 0), wg = wid >> 2, w = wid & 3, lane = tid & 31, g = lane >> 2, i4 = lane & 3;
  uint32_t rank; asm("mov.u32 %0, %%cluster_ctarank;" : "=r"(rank));
  const int head = blockIdx.x / 3;
  const int e0 = head * DH + rank * 64;
  const uint32_t bar = sb + O_BAR;
  const uint32_t r1 = rank == 2 ? 0 : rank + 1, r2 = rank == 0 ? 2 : rank - 1;
  const uint32_t sb1 = mapa(sb, r1), sb2 = mapa(sb, r2);

  if (tid == 0) {
    for (int k = 0; k < 24; k++) mbar_init(bar + 8 * k, 1);
    asm volatile("fence.mbarrier_init.release.cluster;" ::: "memory");
    fence_async();
    for (int p = 0; p < 5; p++) {
      mbar_expect(bar + 8 * (MB_W + p), 16384);
      tma2d(sb + p * 16384, &tmq, e0, p * 128, bar + 8 * (MB_W + p));
      mbar_expect(bar + 8 * (MB_W + 5 + p), 16384);
      tma2d(sb + 81920 + p * 16384, &tmk, e0, p * 128, bar + 8 * (MB_W + 5 + p));
    }
    mbar_expect(bar + 8 * (MB_W + 10), 8192);
    tma2d(sb + O_H + 16384, &tmo, 576, e0, bar + 8 * (MB_W + 10));
  }
  __syncthreads();

  if (wg < 2) {
    asm volatile("setmaxnreg.inc.sync.aligned.u32 208;");
    uint32_t a[40][4];
    {
      const uint32_t la = sb + wg * 81920 + ((lane >> 4) * 8 + (lane & 7)) * 128 + (((2 * w + ((lane >> 3) & 1)) ^ (lane & 7)) << 4);
#pragma unroll
      for (int p = 0; p < 5; p++) {
        mbar_wait(bar + 8 * (MB_W + wg * 5 + p), 0);
#pragma unroll
        for (int k = 0; k < 8; k++) ldsm4t(a[p * 8 + k], la + (p * 8 + k) * 2048);
      }
    }
    bar_sync<B_ALL, 384>();
    cluster_sync();
    const uint32_t qk = sb + (wg == 0 ? O_Q : O_K);
    const uint32_t swz = ((2 * w + ((lane >> 3) & 1)) ^ (lane & 7)) << 4;
    const uint32_t st_x = qk + (wg == 0 ? 0 : 1024) + ((lane >> 4) * 8 + (lane & 7)) * 128 + swz;
    const uint32_t st_m = qk + (wg == 0 ? 4096 : 0) + (lane & 7) * 128 + swz;
    const uint32_t ld_m = sb + O_H + (lane & 7) * 128 + (((lane >> 3) ^ (lane & 7)) << 4);

    for (int s = 0; s < NSEG; s++) {
      const uint32_t par = s & 1;
      if (s > 0) bar_sync<B_XGO, 384>();
      if (tid == 0) TS(0);
      {
        float ax[16];
        const uint64_t db = mkdesc(opaque(sb) + O_H + 1024, 16, 1024, 1);
        mbar_wait(bar + 8 * MB_XF, par);
        wg_fence();
#pragma unroll
        for (int k = 0; k < 20; k++) wg_rs_n32_tb0(ax, a[k], db + (((k >> 2) * 5120 + (k & 3) * 32) >> 4), k);
        mbar_wait(bar + 8 * (MB_XF + 1), par);
        wg_fence();
#pragma unroll
        for (int k = 20; k < 40; k++) wg_rs_n32_tb0(ax, a[k], db + (((k >> 2) * 5120 + (k & 3) * 32) >> 4), 1);
        wg_commit();
        if (wg == 0 && s > 0) bar_sync<B_PFREE, 256>();
        wg_wait<0>();
        pin<16>(ax);
        if (tid == 0) TS(1);
        stsm4t(st_x, pack2(ax[0], ax[1]), pack2(ax[2], ax[3]), pack2(ax[4], ax[5]), pack2(ax[6], ax[7]));
        stsm4t(st_x + 2048, pack2(ax[8], ax[9]), pack2(ax[10], ax[11]), pack2(ax[12], ax[13]), pack2(ax[14], ax[15]));
      }
      {
        float c0[4] = {0.f, 0.f, 0.f, 0.f}, c1[4] = {0.f, 0.f, 0.f, 0.f};
#pragma unroll
        for (int wv = 0; wv < 4; wv++) {
          mbar_wait_cl(bar + 8 * (MB_MF + wv), par);
          if (tid == 0) TS(2 + wv);
#pragma unroll
          for (int r = 0; r < (wv == 0 ? 1 : 3); r++) {
            const int c = wv == 0 ? 9 : 3 * r + wv - 1;
            uint32_t b0[4], b1[4];
            ldsm4(b0, ld_m + c * 5120);
            ldsm4(b1, (ld_m ^ 64) + c * 5120);
            mma16816(c0, a[4 * c], b0[0], b0[1]);
            mma16816(c1, a[4 * c + 1], b0[2], b0[3]);
            mma16816(c0, a[4 * c + 2], b1[0], b1[1]);
            mma16816(c1, a[4 * c + 3], b1[2], b1[3]);
          }
        }
        bar_arrive<B_VGO, 384>();
        stsm2t(st_m, pack2(c0[0] + c1[0], c0[1] + c1[1]), pack2(c0[2] + c1[2], c0[3] + c1[3]));
        fence_async();
      }
      if (wg == 0) {
        bar_sync<B_QK, 256>();
        if (tid == 0) TS(6);
        float sv[20];
        {
          const uint64_t da = mkdesc(opaque(sb) + O_Q, 16, 1024, 1);
          const uint64_t db = da + ((O_K - O_Q) >> 4);
          wg_fence();
#pragma unroll
          for (int k = 0; k < 4; k++) wg_ss_n40_ta0_tb0(sv, da + 2 * k, db + 2 * k, k);
          wg_commit();
          bar_arrive<B_SISS, 256>();
          wg_wait<0>();
          pin<20>(sv);
        }
        constexpr float SCL = 0.07216878364870322f;
        constexpr float L2E = 1.4426950408889634f;
        if (w == 2) {
          const uint32_t o = O_SX + 4096 + lane * 16;
          if (lane == 0) mbar_expect(bar + 8 * MB_SM, 2 * 1280 + 48);
          sta4f(sb1 + o + SX_SLOT, sv[0], sv[1], sv[4], sv[5], sb1 + O_BAR + 8 * MB_SM);
          sta4f(sb2 + o, sv[0], sv[1], sv[4], sv[5], sb2 + O_BAR + 8 * MB_SM);
          sta4f(sb1 + o + SX_SLOT + 512, sv[8], sv[9], sv[12], sv[13], sb1 + O_BAR + 8 * MB_SM);
          sta4f(sb2 + o + 512, sv[8], sv[9], sv[12], sv[13], sb2 + O_BAR + 8 * MB_SM);
          sta2f(sb1 + o + SX_SLOT + 1024 - lane * 8, sv[16], sv[17], sb1 + O_BAR + 8 * MB_SM);
          sta2f(sb2 + o + 1024 - lane * 8, sv[16], sv[17], sb2 + O_BAR + 8 * MB_SM);
          bar_arrive<B_WG0, 96>();
          TS(7);
          mbar_wait_cl(bar + 8 * MB_SM, par);
          TS(8);
          float t[10];
          {
            float4 u0 = lds4f(sb + o), u1 = lds4f(sb + o + 512), v0 = lds4f(sb + o + SX_SLOT), v1 = lds4f(sb + o + SX_SLOT + 512);
            float2 u2 = lds2f(sb + o + 1024 - lane * 8), v2 = lds2f(sb + o + SX_SLOT + 1024 - lane * 8);
            t[0] = sv[0] + u0.x + v0.x; t[1] = sv[1] + u0.y + v0.y; t[2] = sv[4] + u0.z + v0.z; t[3] = sv[5] + u0.w + v0.w;
            t[4] = sv[8] + u1.x + v1.x; t[5] = sv[9] + u1.y + v1.y; t[6] = sv[12] + u1.z + v1.z; t[7] = sv[13] + u1.w + v1.w;
            t[8] = sv[16] + u2.x + v2.x; t[9] = sv[17] + u2.y + v2.y;
          }
          float m = fmaxf(fmaxf(fmaxf(t[0], t[1]), fmaxf(t[2], t[3])), fmaxf(fmaxf(t[4], t[5]), fmaxf(t[6], t[7])));
          m = fmaxf(m, fmaxf(t[8], t[9]));
          m = fmaxf(m, __shfl_xor_sync(~0u, m, 1));
          m = fmaxf(m, __shfl_xor_sync(~0u, m, 2));
          const float mm = m * (SCL * L2E);
          float sum = 0.f;
#pragma unroll
          for (int k = 0; k < 10; k++) { t[k] = ex2(fmaf(t[k], SCL * L2E, -mm)); sum += t[k]; }
          sum += __shfl_xor_sync(~0u, sum, 1);
          sum += __shfl_xor_sync(~0u, sum, 2);
          const float inv = __fdividef(1.f, sum);
          const uint32_t pa = sb + O_Q + 4096 + (lane & 7) * 128;
          stsm4(pa + (((lane >> 3) ^ (lane & 7)) << 4), pack2(t[0] * inv, t[1] * inv), pack2(t[2] * inv, t[3] * inv), pack2(t[4] * inv, t[5] * inv), pack2(t[6] * inv, t[7] * inv));
          stsm1(pa + ((4 ^ (lane & 7)) << 4), pack2(t[8] * inv, t[9] * inv));
          bar_arrive<B_PM, 160>();
          TS(9);
        } else if (w < 2) {
          const uint32_t o = O_SX + w * 1536 + lane * 16;
          if (tid == 0) mbar_expect(bar + 8 * MB_SX, 2 * 4096);
          bar_sync<B_WG0, 96>();
#pragma unroll
          for (int k = 0; k < 5; k++)
            if (k < 3 || w == 1) {
              sta4f(sb1 + o + SX_SLOT + k * 512, sv[4 * k], sv[4 * k + 1], sv[4 * k + 2], sv[4 * k + 3], sb1 + O_BAR + 8 * MB_SX);
              sta4f(sb2 + o + k * 512, sv[4 * k], sv[4 * k + 1], sv[4 * k + 2], sv[4 * k + 3], sb2 + O_BAR + 8 * MB_SX);
            }
          mbar_wait_cl(bar + 8 * MB_SX, par);
          const int q0 = 16 * w + g;
          float m0 = -1e9f, m1 = -1e9f;
#pragma unroll
          for (int k = 0; k < 5; k++) {
            if (k < 3 || w == 1) {
              float4 u = lds4f(sb + o + k * 512), v = lds4f(sb + o + SX_SLOT + k * 512);
              sv[4 * k] = (sv[4 * k] + u.x + v.x) * SCL; sv[4 * k + 1] = (sv[4 * k + 1] + u.y + v.y) * SCL;
              sv[4 * k + 2] = (sv[4 * k + 2] + u.z + v.z) * SCL; sv[4 * k + 3] = (sv[4 * k + 3] + u.w + v.w) * SCL;
            }
            if (k > 0) {
              const int kx = 8 * (k - 1) + 2 * i4;
              if (kx > q0) sv[4 * k] = -1e9f;
              if (kx + 1 > q0) sv[4 * k + 1] = -1e9f;
              if (kx > q0 + 8) sv[4 * k + 2] = -1e9f;
              if (kx + 1 > q0 + 8) sv[4 * k + 3] = -1e9f;
            }
            if (k == 0) { m0 = fmaxf(sv[0], sv[1]); m1 = fmaxf(sv[2], sv[3]); }
            else { m0 = fmaxf(m0, fmaxf(sv[4 * k], sv[4 * k + 1])); m1 = fmaxf(m1, fmaxf(sv[4 * k + 2], sv[4 * k + 3])); }
          }
          m0 = fmaxf(m0, __shfl_xor_sync(~0u, m0, 1)); m1 = fmaxf(m1, __shfl_xor_sync(~0u, m1, 1));
          m0 = fmaxf(m0, __shfl_xor_sync(~0u, m0, 2)); m1 = fmaxf(m1, __shfl_xor_sync(~0u, m1, 2));
          float s0 = 0.f, s1 = 0.f;
#pragma unroll
          for (int k = 0; k < 5; k++) {
            sv[4 * k] = ex2((sv[4 * k] - m0) * L2E); sv[4 * k + 1] = ex2((sv[4 * k + 1] - m0) * L2E);
            sv[4 * k + 2] = ex2((sv[4 * k + 2] - m1) * L2E); sv[4 * k + 3] = ex2((sv[4 * k + 3] - m1) * L2E);
            s0 += sv[4 * k] + sv[4 * k + 1]; s1 += sv[4 * k + 2] + sv[4 * k + 3];
          }
          s0 += __shfl_xor_sync(~0u, s0, 1); s1 += __shfl_xor_sync(~0u, s1, 1);
          s0 += __shfl_xor_sync(~0u, s0, 2); s1 += __shfl_xor_sync(~0u, s1, 2);
          const float i0 = __fdividef(1.f, s0), i1 = __fdividef(1.f, s1);
          const int rho = lane & 7, hf = (lane >> 3) & 1, ch = lane >> 4;
          const int n = 8 * (rho >> 1) + 2 * (2 * w + hf) + (rho & 1);
          const uint32_t pa = sb + O_Q + n * 128;
          stsm4(pa + ((ch ^ (n & 7)) << 4), pack2(sv[0] * i0, sv[1] * i0), pack2(sv[2] * i1, sv[3] * i1), pack2(sv[4] * i0, sv[5] * i0), pack2(sv[6] * i1, sv[7] * i1));
          stsm4(pa + (((2 + ch) ^ (n & 7)) << 4), pack2(sv[8] * i0, sv[9] * i0), pack2(sv[10] * i1, sv[11] * i1), pack2(sv[12] * i0, sv[13] * i0), pack2(sv[14] * i1, sv[15] * i1));
          stsm4(pa + (((4 + ch) ^ (n & 7)) << 4), pack2(sv[16] * i0, sv[17] * i0), pack2(sv[18] * i1, sv[19] * i1), 0u, 0u);
          fence_async();
          bar_arrive<B_PX, 192>();
          if (w == 1) TS(10);
        }
      } else {
        bar_arrive<B_QK, 256>();
        if (w == 0) {
          bar_sync<B_VDONE, 160>();
          if (s + 1 < NSEG) {
            if (lane < 2) mbar_expect(bar + 8 * (MB_XF + lane), 20480);
            __syncwarp();
            if (lane < 10) bulk_g2s(sb + O_H + lane * 5120 + 1024, g_xn + (s + 1) * 40960 + lane * 4096, 4096, bar + 8 * (MB_XF + (lane >= 5)));
            const int ln = blockIdx.x * 2 + (lane - 16), s2 = s + 2;
            if (lane >= 16 && lane < 18 && ln < 160 && s2 < NSEG - 1) {
              const int tile = ln >> 4, off = (ln & 15) << 7;
              const uint8_t* p = ar + (s2 >> 2) * AR_GROUP + (s2 & 1) * 128 + ((s2 >> 1) & 1) * 512 + ((tile >> 2) * 8 + (tile & 3)) * 4096 +
                                 (off >> 10) * 16384 + ((off >> 7) & 1) * 256 + ((off >> 8) & 3) * 1024;
              asm volatile("prefetch.global.L2 [%0];" :: "l"(p));
            }
          }
        }
      }
    }
  } else {
    asm volatile("setmaxnreg.dec.sync.aligned.u32 88;");
    uint32_t a9[4][4];
    {
      const uint32_t la = sb + O_H + 16384 + ((lane >> 4) * 8 + (lane & 7)) * 128 + (((2 * w + ((lane >> 3) & 1)) ^ (lane & 7)) << 4);
      mbar_wait(bar + 8 * (MB_W + 10), 0);
#pragma unroll
      for (int k = 0; k < 4; k++) ldsm4t(a9[k], la + k * 2048);
    }
    bar_sync<B_ALL, 384>();
    if (tid == 256) {
      fence_async();
      mbar_expect(bar + 8 * MB_XF, 20480);
      mbar_expect(bar + 8 * (MB_XF + 1), 20480);
      for (int c = 0; c < 10; c++) bulk_g2s(sb + O_H + c * 5120 + 1024, g_xn + c * 4096, 4096, bar + 8 * (MB_XF + (c >= 5)));
      mbar_expect(bar + 8 * (MB_W + 11), 81920);
      for (int p = 0; p < 5; p++) tma2d(sb + O_WV + p * 16384, &tmv, e0, p * 128, bar + 8 * (MB_W + 11));
      mbar_expect(bar + 8 * (MB_W + 12), 73728);
      for (int p = 0; p < 9; p++) tma2d(sb + O_WO + p * 8192, &tmo, (rank * 3 + p / 3) * 64, head * DH + (p % 3) * 64, bar + 8 * (MB_W + 12));
    }
    float cbound;
    {
      float mx = 0.f;
      for (int c = lane; c < DM; c += 32) mx = fmaxf(mx, g_norm[c]);
#pragma unroll
      for (int o = 16; o; o >>= 1) mx = fmaxf(mx, __shfl_xor_sync(~0u, mx, o));
      cbound = sqrtf(mx) * sqrtf(g_norm[640]) * (25.2982213f * 1.1f);
    }
    cluster_sync();
    const int t = tid & 127;
    const int tok = 2 * ((lane >> 2) & 3) + (lane >> 4);
    const uint32_t fw_off = O_H + tok * 128 + (((2 * w + (i4 & 1)) ^ tok) << 4) + (i4 >> 1) * 8;
    const uint32_t sb0 = mapa(sb, rank);
    const uint32_t prod_off = (w >> 1) * 16384 + (i4 >> 1) * 256 + (w & 1) * 2048 + ((i4 & 1) * 8 + g) * 8;
    const uint32_t cons_off = (w >> 1) * 16384 + ((lane >> 3) & 1) * 256 + ((w & 1) * 2 + (lane >> 4)) * 1024 + (lane & 7) * 16;
    uint32_t tile_off[3];
#pragma unroll
    for (int k = 0; k < 3; k++) { const int T = rank * 3 + k; tile_off[k] = ((T >> 2) * 8 + (T & 3)) * 4096; }
    constexpr uint32_t T9_OFF = 17 * 4096;

    auto forward = [&](int wv, uint32_t p0, uint32_t p1, uint32_t& mx) {
      mx = __vmaxu2(mx, __vmaxu2(p0 & 0x7FFF7FFFu, p1 & 0x7FFF7FFFu));
      const uint32_t oth = __shfl_xor_sync(~0u, (i4 & 1) ? p0 : p1, 1);
      const uint32_t v0 = (i4 & 1) ? oth : p0, v1 = (i4 & 1) ? p1 : oth;
      const uint32_t o = fw_off + (wv == 0 ? 9 : rank * 3 + wv - 1) * 5120, bo = O_BAR + 8 * (MB_MF + wv);
      if (wv > 0) { sta2(sb1 + o, v0, v1, sb1 + bo); sta2(sb2 + o, v0, v1, sb2 + bo); }
      sta2(sb0 + o, v0, v1, sb0 + bo);
    };
    auto send_max = [&](uint32_t mx) {
      mx = max(mx & 0xFFFFu, mx >> 16);
      mx = __reduce_max_sync(~0u, mx);
      if (lane < 3) { const uint32_t b = mapa(sb, lane); sta1(b + O_MAXS + (rank * 4 + w) * 4, mx << 16, b + O_BAR + 8 * MB_SM); }
    };
    {
      if (t < 4) mbar_expect(bar + 8 * (MB_MF + t), t == 0 ? 1024 : 3072);
      uint32_t mx = 0;
#pragma unroll
      for (int wv = 0; wv < 4; wv++) {
        const int T = wv == 0 ? 9 : rank * 3 + wv - 1;
        const uint32_t* mp = (const uint32_t*)(mem0 + tok * DM + T * 64 + 16 * w + 2 * i4);
        forward(wv, mp[0], mp[4], mx);
      }
      send_max(mx);
    }
    mbar_wait(bar + 8 * (MB_W + 11), 0);
    mbar_wait(bar + 8 * (MB_W + 12), 0);

    for (int s = 0; s < NSEG; s++) {
      const uint32_t par = s & 1;
      uint32_t vf[10];
      uint32_t pm[5];
      float sc, isc;
      {
        float av[20];
        const uint64_t da = mkdesc(opaque(sb) + O_WV, 1024, 1024, 1);
        const uint64_t db = mkdesc(opaque(sb) + O_H, 16, 1024, 1);
        bar_sync<B_VGO, 384>();
        if (w == 0) TS(11);
        fence_async();
        wg_fence();
#pragma unroll
        for (int k = 0; k < 5; k++) wg_ss_n40_ta1_tb0(av, da + k * 128, db + (((k >> 2) * 5120 + (k & 3) * 32) >> 4), k);
        bar_sync<B_SISS, 256>();
        wg_fence();
#pragma unroll
        for (int k = 5; k < 40; k++) wg_ss_n40_ta1_tb0(av, da + k * 128, db + (((k >> 2) * 5120 + (k & 3) * 32) >> 4), 1);
        wg_commit();
        if (w == 0) TS(12);
        bar_sync<B_PM, 160>();
        const uint32_t pa = sb + O_Q + 4096 + (lane & 7) * 128;
        ldsm4(pm, pa + (((lane >> 3) ^ (lane & 7)) << 4));
        ldsm1(pm[4], pa + ((4 ^ (lane & 7)) << 4));
        {
          uint4 m0 = lds4(sb + O_MAXS), m1 = lds4(sb + O_MAXS + 16), m2 = lds4(sb + O_MAXS + 32);
          uint32_t mx = max(max(max(m0.x, m0.y), max(m0.z, m0.w)), max(max(m1.x, m1.y), max(m1.z, m1.w)));
          mx = max(mx, max(max(m2.x, m2.y), max(m2.z, m2.w)));
          const float b = cbound * fmaxf(1.f, __uint_as_float(mx));
          const uint32_t eb = min(max(__float_as_uint(b) >> 23, 27u), 254u);
          sc = __uint_as_float((280u - eb) << 23);
          isc = __uint_as_float((eb - 26u) << 23);
        }
        wg_wait<0>();
        pin<20>(av);
        bar_arrive<B_VDONE, 160>();
        if (w == 0) TS(13);
#pragma unroll
        for (int k = 0; k < 10; k++) vf[k] = pack2(av[2 * k], av[2 * k + 1]);
      }
      const uint32_t vz[4] = {vf[8], vf[9], 0u, 0u};
      float ox[16];
      const uint64_t dp = mkdesc(opaque(sb) + O_Q, 16, 1024, 1);
      uint8_t* arp = ar + (s >> 2) * AR_GROUP + (s & 1) * 128 + ((s >> 1) & 1) * 512;
      uint32_t t1 = 0;
      if (s + 1 < NSEG) {
        {
          float o0[4] = {0.f, 0.f, 0.f, 0.f}, o1[4] = {0.f, 0.f, 0.f, 0.f};
          mma16816(o0, vf, pm[0], pm[1]);
          mma16816(o1, vf + 4, pm[2], pm[3]);
          mma1688(o0, vf[8], vf[9], pm[4]);
          const uint32_t p0 = pack2(o0[0] + o1[0], o0[1] + o1[1]), p1 = pack2(o0[2] + o1[2], o0[3] + o1[3]);
          const uint32_t o = O_OG + rank * 1024 + w * 256 + lane * 4;
          sts1(sb + o, p0); sts1(sb + o + 128, p1);
          sta1(sb1 + o, p0, sb1 + O_BAR + 8 * MB_OG); sta1(sb1 + o + 128, p1, sb1 + O_BAR + 8 * MB_OG);
          sta1(sb2 + o, p0, sb2 + O_BAR + 8 * MB_OG); sta1(sb2 + o + 128, p1, sb2 + O_BAR + 8 * MB_OG);
          if (t == 0) mbar_expect(bar + 8 * MB_OG, 2048);
          fence_async();
          bar_sync<B_WG2, 128>();
        }
        if (w == 0) TS(14);
        float c9[4], ca[4], cb[4], cc[4];
        const uint32_t sbo = opaque(sb);
        const uint64_t da = mkdesc(sbo + O_WO, 1024, 1024, 1), db = mkdesc(sbo + O_OG, 128, 128, 0);
        const uint64_t da0 = da + rank * 512, db0 = db + rank * 64;
        const uint64_t da1 = da + r1 * 512, db1 = db + r1 * 64;
        const uint64_t da2 = da + r2 * 512, db2 = db + r2 * 64;
        wg_fence();
#pragma unroll
        for (int k = 0; k < 4; k++) wg_rs_n8_tb1(c9, a9[k], db0 + k * 16, k);
        wg_commit();
#pragma unroll
        for (int k = 0; k < 4; k++) wg_ss_n8_ta1_tb1(ca, da0 + k * 128, db0 + k * 16, k);
#pragma unroll
        for (int k = 0; k < 4; k++) wg_ss_n8_ta1_tb1(cb, da0 + 1536 + k * 128, db0 + k * 16, k);
        wg_commit();
        wg_wait<1>();
        pin<4>(c9);
        fix_red(arp + T9_OFF + prod_off, c9, sc);
        wg_fence();
#pragma unroll
        for (int k = 0; k < 4; k++) wg_ss_n8_ta1_tb1(cc, da0 + 3072 + k * 128, db0 + k * 16, k);
        mbar_wait_cl(bar + 8 * MB_OG, par);
        fence_async();
        if (w == 0) TS(15);
        wg_fence();
#pragma unroll
        for (int k = 0; k < 4; k++) wg_ss_n8_ta1_tb1(ca, da1 + k * 128, db1 + k * 16, 1);
#pragma unroll
        for (int k = 0; k < 4; k++) wg_ss_n8_ta1_tb1(ca, da2 + k * 128, db2 + k * 16, 1);
        wg_commit();
#pragma unroll
        for (int k = 0; k < 4; k++) wg_ss_n8_ta1_tb1(cb, da1 + 1536 + k * 128, db1 + k * 16, 1);
#pragma unroll
        for (int k = 0; k < 4; k++) wg_ss_n8_ta1_tb1(cb, da2 + 1536 + k * 128, db2 + k * 16, 1);
        wg_commit();
        wg_wait<1>();
        pin<4>(ca);
        fix_red(arp + tile_off[0] + prod_off, ca, sc);
        t1 = clk();
        if (w == 0) TS(16);
        wg_fence();
#pragma unroll
        for (int k = 0; k < 4; k++) wg_ss_n8_ta1_tb1(cc, da1 + 3072 + k * 128, db1 + k * 16, 1);
#pragma unroll
        for (int k = 0; k < 4; k++) wg_ss_n8_ta1_tb1(cc, da2 + 3072 + k * 128, db2 + k * 16, 1);
        wg_commit();
        wg_wait<1>();
        pin<4>(cb);
        fix_red(arp + tile_off[1] + prod_off, cb, sc);
        bar_sync<B_PX, 192>();
        wg_fence();
        wg_rs_n32_tb0(ox, vf, dp, 0);
        wg_rs_n32_tb0(ox, vf + 4, dp + 2, 1);
        wg_rs_n32_tb0(ox, vz, dp + 4, 1);
        wg_commit();
        bar_arrive<B_XGO, 384>();
        wg_wait<1>();
        pin<4>(cc);
        fix_red(arp + tile_off[2] + prod_off, cc, sc);
        if (w == 0) TS(17);
        wg_wait<0>();
        pin<16>(ox);
        bar_arrive<B_PFREE, 256>();
      } else {
        bar_sync<B_PX, 192>();
        wg_fence();
        wg_rs_n32_tb0(ox, vf, dp, 0);
        wg_rs_n32_tb0(ox, vf + 4, dp + 2, 1);
        wg_rs_n32_tb0(ox, vz, dp + 4, 1);
        wg_commit();
        wg_wait<0>();
        pin<16>(ox);
      }
      {
        uint8_t* op = g_ot + (size_t)(s >> 1) * (HE * 128) + (e0 + 16 * w + g) * 128 + ((((s & 1) * 4 + i4) ^ g) << 4);
        *(uint4*)op = make_uint4(pack2(ox[0], ox[1]), pack2(ox[4], ox[5]), pack2(ox[8], ox[9]), pack2(ox[12], ox[13]));
        *(uint4*)(op + 1024) = make_uint4(pack2(ox[2], ox[3]), pack2(ox[6], ox[7]), pack2(ox[10], ox[11]), pack2(ox[14], ox[15]));
      }
      if (s + 1 < NSEG) {
        if (t < 4) mbar_expect(bar + 8 * (MB_MF + t), t == 0 ? 1024 : 3072);
        const uint8_t* cp = arp + cons_off;
        uint4 y[4];
        if (w == 0) TS(18);
        y[0] = ld_poll(cp + T9_OFF);
        while ((int)(clk() - t1) < POLL_DELAY) {}
        y[1] = ld_poll(cp + tile_off[0]);
        while ((int)(clk() - t1) < POLL_DELAY + 144) {}
        y[2] = ld_poll(cp + tile_off[1]);
        while ((int)(clk() - t1) < POLL_DELAY + 288) {}
        y[3] = ld_poll(cp + tile_off[2]);
        uint32_t mx = 0;
#pragma unroll
        for (int wv = 0; wv < 4; wv++) {
          const uint32_t need = wv == 0 ? 96 : 32;
          int it = 0;
          while (((y[wv].x & 127u) != need) | ((y[wv].z & 127u) != need)) {
            y[wv] = ld_poll(cp + (wv == 0 ? T9_OFF : tile_off[wv > 0 ? wv - 1 : 0]));
            if (++it > 2000000) __trap();
          }
          __syncwarp();
          const float l0 = (float)((int)__funnelshift_r(y[wv].x, y[wv].y, 3) >> 4) * isc, h0 = (float)((int)(y[wv].y + 4u) >> 3) * isc;
          const float l1 = (float)((int)__funnelshift_r(y[wv].z, y[wv].w, 3) >> 4) * isc, h1 = (float)((int)(y[wv].w + 4u) >> 3) * isc;
          forward(wv, pack2(l0, l1), pack2(h0, h1), mx);
          if (w == 0) TS(19 + wv);
        }
        send_max(mx);
      }
    }
  }
  cluster_sync();
}

__global__ void k_norms(const bf16* __restrict__ wv, const bf16* __restrict__ wo) {
  if (blockIdx.x < 96) {
    const int c = threadIdx.x * 2;
    float s0 = 0.f, s1 = 0.f;
    for (int r = 0; r < 64; r++) { float2 v = __bfloat1622float2(*(const __nv_bfloat162*)(wo + (blockIdx.x * 64 + r) * DM + c)); s0 += v.x * v.x; s1 += v.y * v.y; }
    atomicAdd(&g_norm[c], s0); atomicAdd(&g_norm[c + 1], s1);
  } else {
    const int b = blockIdx.x - 96;
    float s = 0.f;
    for (int r = 0; r < 64; r++) { float2 v = __bfloat1622float2(*(const __nv_bfloat162*)(wv + (b * 64 + r) * DM + threadIdx.x * 2)); s += v.x * v.x + v.y * v.y; }
    for (int o = 16; o; o >>= 1) s += __shfl_xor_sync(~0u, s, o);
    if ((threadIdx.x & 31) == 0) atomicAdd(&g_norm[640], s);
  }
}
__global__ void k_cvt_in(const bf16* __restrict__ x) { int i = blockIdx.x * blockDim.x + threadIdx.x; g_x[i] = __bfloat162float(x[i]); }
__global__ void k_cvt_out(bf16* __restrict__ o) { int i = blockIdx.x * blockDim.x + threadIdx.x; o[i] = __float2bfloat16(g_x[i]); }
__global__ void k_ln(int mode) {
  const int row = blockIdx.x * 8 + (threadIdx.x >> 5), lane = threadIdx.x & 31;
  float v[20]; float s = 0.f;
  for (int k = 0; k < 10; k++) { float2 t = *(const float2*)(g_x + row * DM + k * 64 + lane * 2); v[2 * k] = t.x; v[2 * k + 1] = t.y; s += t.x + t.y; }
  for (int o = 16; o; o >>= 1) s += __shfl_xor_sync(~0u, s, o);
  const float m = s * (1.f / DM); float q = 0.f;
  for (int k = 0; k < 20; k++) { v[k] -= m; q += v[k] * v[k]; }
  for (int o = 16; o; o >>= 1) q += __shfl_xor_sync(~0u, q, o);
  const float r = rsqrtf(q * (1.f / DM) + 1e-5f);
  for (int k = 0; k < 10; k++) {
    const uint32_t p = pack2(v[2 * k] * r, v[2 * k + 1] * r);
    if (mode == 0) *(uint32_t*)(g_xa + row * DM + k * 64 + lane * 2) = p;
    else *(uint32_t*)(g_xn + (row >> 5) * 40960 + k * 4096 + (row & 31) * 128 + (((lane >> 2) ^ (row & 7)) << 4) + (lane & 3) * 4) = p;
  }
}
__global__ void k_gemm(const bf16* __restrict__ A, const bf16* __restrict__ B, float* __restrict__ C, int N, int K, int amode, int accum) {
  __shared__ float As[32][65], Bs[32][64];
  const int tx = threadIdx.x & 15, ty = threadIdx.x >> 4, m0 = blockIdx.y * 64, n0 = blockIdx.x * 64;
  float acc[4][4] = {};
  for (int k0 = 0; k0 < K; k0 += 32) {
    for (int e = threadIdx.x; e < 2048; e += 256) {
      if (amode == 0) { int m = e >> 5, k = e & 31; As[k][m] = __bfloat162float(A[(size_t)(m0 + m) * K + k0 + k]); }
      else { int k = e >> 6, m = e & 63, he = k0 + k; As[k][m] = __bfloat162float(*(const bf16*)(g_ot + (size_t)blockIdx.y * (HE * 128) + he * 128 + (((m >> 3) ^ (he & 7)) << 4) + (m & 7) * 2)); }
      int k = e >> 6, n = e & 63; Bs[k][n] = __bfloat162float(B[(size_t)(k0 + k) * N + n0 + n]);
    }
    __syncthreads();
    for (int k = 0; k < 32; k++) {
      float a[4], b[4];
      for (int r = 0; r < 4; r++) { a[r] = As[k][ty * 4 + r]; b[r] = Bs[k][tx * 4 + r]; }
      for (int r = 0; r < 4; r++) for (int c = 0; c < 4; c++) acc[r][c] += a[r] * b[c];
    }
    __syncthreads();
  }
  for (int r = 0; r < 4; r++) for (int c = 0; c < 4; c++) {
    float* p = C + (size_t)(m0 + ty * 4 + r) * N + n0 + tx * 4 + c;
    *p = accum ? *p + acc[r][c] : acc[r][c];
  }
}
__device__ __forceinline__ float phi(float t) { return (t > 0.f ? t + 1.f : __expf(t)) + 1e-6f; }
__global__ void k_kv(float* kv) {
  const int h = blockIdx.x, e = threadIdx.x / 20, d = threadIdx.x % 20;
  float s = 0.f;
  for (int t = blockIdx.y * 128; t < blockIdx.y * 128 + 128; t++) {
    const float pk = phi(g_qkv[t * 1920 + 640 + h * 20 + d]);
    s += pk * (e < 20 ? g_qkv[t * 1920 + 1280 + h * 20 + e] : 1.f);
  }
  atomicAdd(&kv[(h * 21 + e) * 20 + d], s);
}
__global__ void k_lo(const float* kv) {
  const int t = blockIdx.x, c = threadIdx.x, h = c / 20, e = c % 20;
  float num = 0.f, den = 0.f;
  for (int d = 0; d < 20; d++) { const float pq = phi(g_qkv[t * 1920 + h * 20 + d]); num += pq * kv[(h * 21 + e) * 20 + d]; den += pq * kv[(h * 21 + 20) * 20 + d]; }
  g_oa[t * DM + c] = __float2bfloat16(num / (den + 1e-6f));
}

typedef CUresult (*EncodeFn)(CUtensorMap*, CUtensorMapDataType, cuuint32_t, void*, const cuuint64_t*, const cuuint64_t*, const cuuint32_t*,
                             const cuuint32_t*, CUtensorMapInterleave, CUtensorMapSwizzle, CUtensorMapL2promotion, CUtensorMapFloatOOBfill);
static void make_map(EncodeFn fn, CUtensorMap* m, const void* p, uint64_t cols, uint64_t rows, uint32_t bc, uint32_t br) {
  cuuint64_t dims[2] = {cols, rows}; cuuint64_t strides[1] = {cols * 2}; cuuint32_t box[2] = {bc, br}; cuuint32_t es[2] = {1, 1};
  fn(m, CU_TENSOR_MAP_DATA_TYPE_BFLOAT16, 2, (void*)p, dims, strides, box, es, CU_TENSOR_MAP_INTERLEAVE_NONE, CU_TENSOR_MAP_SWIZZLE_128B,
     CU_TENSOR_MAP_L2_PROMOTION_L2_128B, CU_TENSOR_MAP_FLOAT_OOB_FILL_NONE);
}

extern "C" void kernel_launch(void* const* d_in, const int* in_sizes, int n_in, void* d_out, int out_size) {
  const bf16* x = (const bf16*)d_in[0];
  const bf16* wqkv = (const bf16*)d_in[1];
  const bf16* wo_a = (const bf16*)d_in[2];
  const bf16* mem0 = (const bf16*)d_in[4];
  const bf16* Wq = (const bf16*)d_in[5];
  const bf16* Wk = (const bf16*)d_in[6];
  const bf16* Wv = (const bf16*)d_in[7];
  const bf16* Wo = (const bf16*)d_in[8];
  cudaStream_t st = cudaStreamPerThread;

  static EncodeFn enc = nullptr;
  static uint8_t* p_ar; static float *p_norm, *p_kv, *p_x, *p_qkv; static bf16 *p_xa, *p_oa;
  if (!enc) {
    cudaDriverEntryPointQueryResult qr;
    void* fn = nullptr;
    cudaGetDriverEntryPoint("cuTensorMapEncodeTiled", &fn, cudaEnableDefault, &qr);
    enc = (EncodeFn)fn;
    cudaFuncSetAttribute(rec_kernel, cudaFuncAttributeMaxDynamicSharedMemorySize, REC_SMEM);
    cudaGetSymbolAddress((void**)&p_ar, g_ar); p_ar = (uint8_t*)(((uintptr_t)p_ar + 32767) & ~(uintptr_t)32767);
    cudaGetSymbolAddress((void**)&p_norm, g_norm); cudaGetSymbolAddress((void**)&p_kv, g_kv); cudaGetSymbolAddress((void**)&p_x, g_x);
    cudaGetSymbolAddress((void**)&p_qkv, g_qkv); cudaGetSymbolAddress((void**)&p_xa, g_xa); cudaGetSymbolAddress((void**)&p_oa, g_oa);
  }
  CUtensorMap tmq, tmk, tmv, tmo;
  make_map(enc, &tmq, Wq, HE, DM, 64, 128);
  make_map(enc, &tmk, Wk, HE, DM, 64, 128);
  make_map(enc, &tmv, Wv, HE, DM, 64, 128);
  make_map(enc, &tmo, Wo, DM, HE, 64, 64);

  cudaMemsetAsync(p_ar, 0, 2 * AR_LAYER, st);
  cudaMemsetAsync(p_norm, 0, 1024 * 4, st);
  cudaMemsetAsync(p_kv, 0, 2 * 32 * 21 * 20 * 4, st);
  k_norms<<<192, 320, 0, st>>>(Wv, Wo);
  k_cvt_in<<<S_TOK * DM / 256, 256, 0, st>>>(x);
  for (int l = 0; l < 2; l++) {
    k_ln<<<256, 256, 0, st>>>(0);
    k_gemm<<<dim3(30, 32), 256, 0, st>>>(p_xa, wqkv, p_qkv, 1920, DM, 0, 0);
    k_kv<<<dim3(32, 16), 420, 0, st>>>(p_kv + l * 13440);
    k_lo<<<S_TOK, 640, 0, st>>>(p_kv + l * 13440);
    k_gemm<<<dim3(10, 32), 256, 0, st>>>(p_oa, wo_a, p_x, DM, DM, 0, 1);
    k_ln<<<256, 256, 0, st>>>(1);
    cudaLaunchConfig_t cfg = {};
    cfg.gridDim = dim3(96); cfg.blockDim = dim3(384); cfg.dynamicSmemBytes = REC_SMEM; cfg.stream = st;
    cudaLaunchAttribute at[1];
    at[0].id = cudaLaunchAttributeClusterDimension; at[0].val.clusterDim.x = 3; at[0].val.clusterDim.y = 1; at[0].val.clusterDim.z = 1;
    cfg.attrs = at; cfg.numAttrs = 1;
    cudaLaunchKernelEx(&cfg, rec_kernel, tmq, tmk, tmv, tmo, mem0, p_ar + l * AR_LAYER);
    k_gemm<<<dim3(10, 32), 256, 0, st>>>(nullptr, Wo, p_x, DM, HE, 1, 1);
  }
  k_cvt_out<<<S_TOK * DM / 256, 256, 0, st>>>((bf16*)d_out);
}
```

```cpp
#include <cuda_runtime.h>
#include <cuda_bf16.h>
#include <cuda.h>
#include <stdint.h>

typedef __nv_bfloat16 bf16;
typedef unsigned long long u64;

constexpr int S_TOK = 2048, DM = 640, NH = 32, DH = 192, HE = 6144, NSEG = 64;

constexpr int AR_GROUP = 98304;
constexpr int AR_LAYER = 16 * AR_GROUP;
__device__ __align__(1024) uint8_t g_ar[2 * AR_LAYER + 32768];
__device__ __align__(1024) uint8_t g_xn[NSEG * 40960];
__device__ __align__(1024) uint8_t g_ot[32 * HE * 128];
__device__ float g_norm[1024];
__device__ float g_x[S_TOK * DM];
__device__ bf16 g_xa[S_TOK * DM];
__device__ float g_qkv[S_TOK * 1920];
__device__ float g_kv[2 * 32 * 21 * 20];
__device__ bf16 g_oa[S_TOK * DM];

__device__ __forceinline__ uint32_t smem_u32(const void* p) { return (uint32_t)__cvta_generic_to_shared(p); }
__device__ __forceinline__ uint32_t mapa(uint32_t a, uint32_t r) { uint32_t o; asm("mapa.shared::cluster.u32 %0, %1, %2;" : "=r"(o) : "r"(a), "r"(r)); return o; }
__device__ __forceinline__ void mbar_init(uint32_t bar, uint32_t cnt) { asm volatile("mbarrier.init.shared::cta.b64 [%0], %1;" :: "r"(bar), "r"(cnt) : "memory"); }
__device__ __forceinline__ void mbar_expect(uint32_t bar, uint32_t tx) { asm volatile("mbarrier.arrive.expect_tx.shared::cta.b64 _, [%0], %1;" :: "r"(bar), "r"(tx) : "memory"); }
__device__ __forceinline__ void mbar_arrive(uint32_t bar) { asm volatile("mbarrier.arrive.shared::cta.b64 _, [%0];" :: "r"(bar) : "memory"); }
__device__ __forceinline__ void mbar_wait(uint32_t bar, uint32_t par) {
  asm volatile("{\n.reg .pred p;\n.reg .u32 c;\nmov.u32 c, 0;\n"
               "LW:\nmbarrier.try_wait.parity.shared::cta.b64 p, [%0], %1;\n@p bra LD;\n"
               "add.u32 c, c, 1;\nsetp.lt.u32 p, c, 4000000;\n@p bra LW;\ntrap;\nLD:\n}" :: "r"(bar), "r"(par) : "memory");
}
template <int ID, int N> __device__ __forceinline__ void bar_sync() { asm volatile("barrier.sync %0, %1;" :: "n"(ID), "n"(N) : "memory"); }
template <int ID, int N> __device__ __forceinline__ void bar_arrive() { asm volatile("barrier.arrive %0, %1;" :: "n"(ID), "n"(N) : "memory"); }
__device__ __forceinline__ void fence_async() { asm volatile("fence.proxy.async.shared::cta;" ::: "memory"); }
__device__ __forceinline__ void cluster_sync() { asm volatile("barrier.cluster.arrive.aligned;\nbarrier.cluster.wait.aligned;" ::: "memory"); }
__device__ __forceinline__ void wg_fence() { asm volatile("wgmma.fence.sync.aligned;" ::: "memory"); }
__device__ __forceinline__ void wg_commit() { asm volatile("wgmma.commit_group.sync.aligned;" ::: "memory"); }
template <int N> __device__ __forceinline__ void wg_wait() { asm volatile("wgmma.wait_group.sync.aligned %0;" :: "n"(N) : "memory"); }
template <int N> __device__ __forceinline__ void pin(float* d) {
#pragma unroll
  for (int i = 0; i < N; i++) asm volatile("" : "+f"(d[i]) :: "memory");
}
__device__ __forceinline__ uint64_t mkdesc(uint32_t addr, uint32_t lbo, uint32_t sbo, int sw) {
  return (uint64_t)((addr & 0x3FFFF) >> 4) | ((uint64_t)(lbo >> 4) << 16) | ((uint64_t)(sbo >> 4) << 32) | ((uint64_t)sw << 62);
}
__device__ __forceinline__ uint32_t opaque(uint32_t v) { uint32_t o; asm volatile("mov.u32 %0, %1;" : "=r"(o) : "r"(v)); return o; }
__device__ __forceinline__ uint32_t pack2(float lo, float hi) { uint32_t r; asm("cvt.rn.bf16x2.f32 %0, %1, %2;" : "=r"(r) : "f"(hi), "f"(lo)); return r; }
__device__ __forceinline__ void ldsm4(uint32_t* r, uint32_t a) { asm volatile("ldmatrix.sync.aligned.m8n8.x4.shared.b16 {%0,%1,%2,%3}, [%4];" : "=r"(r[0]), "=r"(r[1]), "=r"(r[2]), "=r"(r[3]) : "r"(a) : "memory"); }
__device__ __forceinline__ void ldsm4t(uint32_t* r, uint32_t a) { asm volatile("ldmatrix.sync.aligned.m8n8.x4.trans.shared.b16 {%0,%1,%2,%3}, [%4];" : "=r"(r[0]), "=r"(r[1]), "=r"(r[2]), "=r"(r[3]) : "r"(a) : "memory"); }
__device__ __forceinline__ void ldsm1(uint32_t& r, uint32_t a) { asm volatile("ldmatrix.sync.aligned.m8n8.x1.shared.b16 {%0}, [%1];" : "=r"(r) : "r"(a) : "memory"); }
__device__ __forceinline__ void stsm4(uint32_t a, uint32_t r0, uint32_t r1, uint32_t r2, uint32_t r3) { asm volatile("stmatrix.sync.aligned.m8n8.x4.shared.b16 [%0], {%1,%2,%3,%4};" :: "r"(a), "r"(r0), "r"(r1), "r"(r2), "r"(r3) : "memory"); }
__device__ __forceinline__ void stsm1(uint32_t a, uint32_t r0) { asm volatile("stmatrix.sync.aligned.m8n8.x1.shared.b16 [%0], {%1};" :: "r"(a), "r"(r0) : "memory"); }
__device__ __forceinline__ void stsm4t(uint32_t a, uint32_t r0, uint32_t r1, uint32_t r2, uint32_t r3) { asm volatile("stmatrix.sync.aligned.m8n8.x4.trans.shared.b16 [%0], {%1,%2,%3,%4};" :: "r"(a), "r"(r0), "r"(r1), "r"(r2), "r"(r3) : "memory"); }
__device__ __forceinline__ void stsm2t(uint32_t a, uint32_t r0, uint32_t r1) { asm volatile("stmatrix.sync.aligned.m8n8.x2.trans.shared.b16 [%0], {%1,%2};" :: "r"(a), "r"(r0), "r"(r1) : "memory"); }
__device__ __forceinline__ void mma16816(float* c, const uint32_t* a, uint32_t b0, uint32_t b1) {
  asm volatile("mma.sync.aligned.m16n8k16.row.col.f32.bf16.bf16.f32 {%0,%1,%2,%3}, {%4,%5,%6,%7}, {%8,%9}, {%0,%1,%2,%3};"
               : "+f"(c[0]), "+f"(c[1]), "+f"(c[2]), "+f"(c[3]) : "r"(a[0]), "r"(a[1]), "r"(a[2]), "r"(a[3]), "r"(b0), "r"(b1));
}
__device__ __forceinline__ void mma1688(float* c, uint32_t a0, uint32_t a1, uint32_t b0) {
  asm volatile("mma.sync.aligned.m16n8k8.row.col.f32.bf16.bf16.f32 {%0,%1,%2,%3}, {%4,%5}, {%6}, {%0,%1,%2,%3};"
               : "+f"(c[0]), "+f"(c[1]), "+f"(c[2]), "+f"(c[3]) : "r"(a0), "r"(a1), "r"(b0));
}
__device__ __forceinline__ void sta1(uint32_t a, uint32_t v, uint32_t bar) { asm volatile("st.async.weak.shared::cluster.mbarrier::complete_tx::bytes.b32 [%0], %1, [%2];" :: "r"(a), "r"(v), "r"(bar) : "memory"); }
__device__ __forceinline__ void sta2(uint32_t a, uint32_t v0, uint32_t v1, uint32_t bar) { asm volatile("st.async.weak.shared::cluster.mbarrier::complete_tx::bytes.v2.b32 [%0], {%1,%2}, [%3];" :: "r"(a), "r"(v0), "r"(v1), "r"(bar) : "memory"); }
__device__ __forceinline__ void sta4(uint32_t a, uint32_t v0, uint32_t v1, uint32_t v2, uint32_t v3, uint32_t bar) { asm volatile("st.async.weak.shared::cluster.mbarrier::complete_tx::bytes.v4.b32 [%0], {%1,%2,%3,%4}, [%5];" :: "r"(a), "r"(v0), "r"(v1), "r"(v2), "r"(v3), "r"(bar) : "memory"); }
__device__ __forceinline__ float bflo(uint32_t v) { return __uint_as_float(v << 16); }
__device__ __forceinline__ float bfhi(uint32_t v) { return __uint_as_float(v & 0xFFFF0000u); }
__device__ __forceinline__ void sta2f(uint32_t a, float v0, float v1, uint32_t bar) { asm volatile("st.async.weak.shared::cluster.mbarrier::complete_tx::bytes.v2.f32 [%0], {%1,%2}, [%3];" :: "r"(a), "f"(v0), "f"(v1), "r"(bar) : "memory"); }
__device__ __forceinline__ void sta4f(uint32_t a, float v0, float v1, float v2, float v3, uint32_t bar) { asm volatile("st.async.weak.shared::cluster.mbarrier::complete_tx::bytes.v4.f32 [%0], {%1,%2,%3,%4}, [%5];" :: "r"(a), "f"(v0), "f"(v1), "f"(v2), "f"(v3), "r"(bar) : "memory"); }
__device__ __forceinline__ float4 lds4f(uint32_t a) { float4 v; asm volatile("ld.shared.v4.f32 {%0,%1,%2,%3}, [%4];" : "=f"(v.x), "=f"(v.y), "=f"(v.z), "=f"(v.w) : "r"(a) : "memory"); return v; }
__device__ __forceinline__ float2 lds2f(uint32_t a) { float2 v; asm volatile("ld.shared.v2.f32 {%0,%1}, [%2];" : "=f"(v.x), "=f"(v.y) : "r"(a) : "memory"); return v; }
__device__ __forceinline__ uint4 lds4(uint32_t a) { uint4 v; asm volatile("ld.shared.v4.u32 {%0,%1,%2,%3}, [%4];" : "=r"(v.x), "=r"(v.y), "=r"(v.z), "=r"(v.w) : "r"(a) : "memory"); return v; }
__device__ __forceinline__ uint32_t lds1(uint32_t a) { uint32_t v; asm volatile("ld.shared.u32 %0, [%1];" : "=r"(v) : "r"(a) : "memory"); return v; }
__device__ __forceinline__ void stsm2(uint32_t a, uint32_t r0, uint32_t r1) { asm volatile("stmatrix.sync.aligned.m8n8.x2.shared.b16 [%0], {%1,%2};" :: "r"(a), "r"(r0), "r"(r1) : "memory"); }
__device__ __forceinline__ float rcp(float x) { float y; asm("rcp.approx.ftz.f32 %0, %1;" : "=f"(y) : "f"(x)); return y; }
__device__ __forceinline__ void sts4(uint32_t a, uint32_t v0, uint32_t v1, uint32_t v2, uint32_t v3) { asm volatile("st.shared.v4.u32 [%0], {%1,%2,%3,%4};" :: "r"(a), "r"(v0), "r"(v1), "r"(v2), "r"(v3) : "memory"); }
__device__ __forceinline__ void bulk_s2c(uint32_t dst, uint32_t src, uint32_t bytes, uint32_t bar) {
  asm volatile("cp.async.bulk.shared::cluster.shared::cta.mbarrier::complete_tx::bytes [%0], [%1], %2, [%3];" :: "r"(dst), "r"(src), "r"(bytes), "r"(bar) : "memory");
}
__device__ __forceinline__ void sts1(uint32_t a, uint32_t v) { asm volatile("st.shared.u32 [%0], %1;" :: "r"(a), "r"(v) : "memory"); }
__device__ __forceinline__ void bulk_g2s(uint32_t dst, const void* src, uint32_t bytes, uint32_t bar) {
  asm volatile("cp.async.bulk.shared::cluster.global.mbarrier::complete_tx::bytes [%0], [%1], %2, [%3];" :: "r"(dst), "l"(src), "r"(bytes), "r"(bar) : "memory");
}
__device__ __forceinline__ void tma2d(uint32_t dst, const CUtensorMap* m, int c0, int c1, uint32_t bar) {
  asm volatile("cp.async.bulk.tensor.2d.shared::cluster.global.mbarrier::complete_tx::bytes [%0], [%1, {%3, %4}], [%2];" :: "r"(dst), "l"((uint64_t)m), "r"(bar), "r"(c0), "r"(c1) : "memory");
}
__device__ __forceinline__ void tma5d(uint32_t dst, const CUtensorMap* m, int c0, int c4, uint32_t bar) {
  asm volatile("cp.async.bulk.tensor.5d.shared::cluster.global.mbarrier::complete_tx::bytes [%0], [%1, {%3, %5, %5, %5, %4}], [%2];" :: "r"(dst), "l"((uint64_t)m), "r"(bar), "r"(c0), "r"(c4), "r"(0) : "memory");
}
__device__ __forceinline__ void red64(void* p, uint32_t lo, uint32_t hi) { asm volatile("{\n.reg .b64 t;\nmov.b64 t, {%1,%2};\nred.relaxed.gpu.global.add.u64 [%0], t;\n}" :: "l"(p), "r"(lo), "r"(hi) : "memory"); }
__device__ __forceinline__ uint4 ld_poll(const void* p) {
  uint4 v;
  asm volatile("{\n.reg .b64 a, b;\nld.relaxed.gpu.global.v2.b64 {a, b}, [%4];\nmov.b64 {%0,%1}, a;\nmov.b64 {%2,%3}, b;\n}" : "=r"(v.x), "=r"(v.y), "=r"(v.z), "=r"(v.w) : "l"(p) : "memory");
  return v;
}
__device__ __forceinline__ uint32_t clk() { uint32_t c; asm volatile("mov.u32 %0, %%clock;" : "=r"(c) :: "memory"); return c; }
__device__ __forceinline__ float ex2(float x) { float y; asm("ex2.approx.ftz.f32 %0, %1;" : "=f"(y) : "f"(x)); return y; }

__device__ __forceinline__ void wg_rs_n32_tb0(float* d, const uint32_t* a, uint64_t b, int sc) {
  asm volatile("{\n.reg .pred p;\nsetp.ne.b32 p, %21, 0;\nwgmma.mma_async.sync.aligned.m64n32k16.f32.bf16.bf16 {%0, %1, %2, %3, %4, %5, %6, %7, %8, %9, %10, %11, %12, %13, %14, %15}, {%16, %17, %18, %19}, %20, p, 1, 1, 0;\n}\n"
    : "+f"(d[0]), "+f"(d[1]), "+f"(d[2]), "+f"(d[3]), "+f"(d[4]), "+f"(d[5]), "+f"(d[6]), "+f"(d[7]), "+f"(d[8]), "+f"(d[9]), "+f"(d[10]), "+f"(d[11]), "+f"(d[12]), "+f"(d[13]), "+f"(d[14]), "+f"(d[15])
    : "r"(a[0]), "r"(a[1]), "r"(a[2]), "r"(a[3]), "l"(b), "r"(sc));
}
__device__ __forceinline__ void wg_rs_n40_tb0(float* d, const uint32_t* a, uint64_t b, int sc) {
  asm volatile("{\n.reg .pred p;\nsetp.ne.b32 p, %25, 0;\nwgmma.mma_async.sync.aligned.m64n40k16.f32.bf16.bf16 {%0, %1, %2, %3, %4, %5, %6, %7, %8, %9, %10, %11, %12, %13, %14, %15, %16, %17, %18, %19}, {%20, %21, %22, %23}, %24, p, 1, 1, 0;\n}\n"
    : "+f"(d[0]), "+f"(d[1]), "+f"(d[2]), "+f"(d[3]), "+f"(d[4]), "+f"(d[5]), "+f"(d[6]), "+f"(d[7]), "+f"(d[8]), "+f"(d[9]), "+f"(d[10]), "+f"(d[11]), "+f"(d[12]), "+f"(d[13]), "+f"(d[14]), "+f"(d[15]), "+f"(d[16]), "+f"(d[17]), "+f"(d[18]), "+f"(d[19])
    : "r"(a[0]), "r"(a[1]), "r"(a[2]), "r"(a[3]), "l"(b), "r"(sc));
}
__device__ __forceinline__ void wg_rs_n8_tb1(float* d, const uint32_t* a, uint64_t b, int sc) {
  asm volatile("{\n.reg .pred p;\nsetp.ne.b32 p, %9, 0;\nwgmma.mma_async.sync.aligned.m64n8k16.f32.bf16.bf16 {%0, %1, %2, %3}, {%4, %5, %6, %7}, %8, p, 1, 1, 1;\n}\n"
    : "+f"(d[0]), "+f"(d[1]), "+f"(d[2]), "+f"(d[3])
    : "r"(a[0]), "r"(a[1]), "r"(a[2]), "r"(a[3]), "l"(b), "r"(sc));
}
__device__ __forceinline__ void wg_ss_n40_ta0_tb0(float* d, uint64_t a, uint64_t b, int sc) {
  asm volatile("{\n.reg .pred p;\nsetp.ne.b32 p, %22, 0;\nwgmma.mma_async.sync.aligned.m64n40k16.f32.bf16.bf16 {%0, %1, %2, %3, %4, %5, %6, %7, %8, %9, %10, %11, %12, %13, %14, %15, %16, %17, %18, %19}, %20, %21, p, 1, 1, 0, 0;\n}\n"
    : "+f"(d[0]), "+f"(d[1]), "+f"(d[2]), "+f"(d[3]), "+f"(d[4]), "+f"(d[5]), "+f"(d[6]), "+f"(d[7]), "+f"(d[8]), "+f"(d[9]), "+f"(d[10]), "+f"(d[11]), "+f"(d[12]), "+f"(d[13]), "+f"(d[14]), "+f"(d[15]), "+f"(d[16]), "+f"(d[17]), "+f"(d[18]), "+f"(d[19])
    : "l"(a), "l"(b), "r"(sc));
}
__device__ __forceinline__ void wg_ss_n40_ta1_tb0(float* d, uint64_t a, uint64_t b, int sc) {
  asm volatile("{\n.reg .pred p;\nsetp.ne.b32 p, %22, 0;\nwgmma.mma_async.sync.aligned.m64n40k16.f32.bf16.bf16 {%0, %1, %2, %3, %4, %5, %6, %7, %8, %9, %10, %11, %12, %13, %14, %15, %16, %17, %18, %19}, %20, %21, p, 1, 1, 1, 0;\n}\n"
    : "+f"(d[0]), "+f"(d[1]), "+f"(d[2]), "+f"(d[3]), "+f"(d[4]), "+f"(d[5]), "+f"(d[6]), "+f"(d[7]), "+f"(d[8]), "+f"(d[9]), "+f"(d[10]), "+f"(d[11]), "+f"(d[12]), "+f"(d[13]), "+f"(d[14]), "+f"(d[15]), "+f"(d[16]), "+f"(d[17]), "+f"(d[18]), "+f"(d[19])
    : "l"(a), "l"(b), "r"(sc));
}
__device__ __forceinline__ void wg_ss_n8_ta1_tb1(float* d, uint64_t a, uint64_t b, int sc) {
  asm volatile("{\n.reg .pred p;\nsetp.ne.b32 p, %6, 0;\nwgmma.mma_async.sync.aligned.m64n8k16.f32.bf16.bf16 {%0, %1, %2, %3}, %4, %5, p, 1, 1, 1, 1;\n}\n"
    : "+f"(d[0]), "+f"(d[1]), "+f"(d[2]), "+f"(d[3])
    : "l"(a), "l"(b), "r"(sc));
}

constexpr int O_WV = 0, O_WO = 81920, O_H = 163840, O_QK = 215040, O_SM = 228352, O_MISC = 230912;
constexpr int O_QM = O_QK + 1024, O_K = O_QK + 3072, O_OG = O_QK + 8192;
constexpr int SM_SLOT = 640;
constexpr int O_MAXS = O_MISC;
constexpr int O_BAR = O_MISC + 64;
constexpr int MB_XF = 0, MB_MF = 2, MB_SM = 6, MB_SX = 7, MB_OG = 8, MB_W = 9;
constexpr int O_PROF = O_BAR + 8 * 24;
constexpr int REC_SMEM = O_PROF + 128;
constexpr int B_QK = 1, B_VGO = 2, B_SISS = 3, B_PM = 4, B_PX = 5, B_XGO = 6, B_PFREE = 7, B_WG2 = 8, B_VHALF = 9, B_VDONE = 10, B_ALL = 11,
              B_SSENT = 12, B_SLD = 13, B_VEND = 14, B_XGO1 = 15;
#define POLL_DELAY 650
#define POLL_STEP 50
#define NBUF 3
#define REG_A 208
#define REG_B 88
#define REG_C 208
#define FENCE_RX() fence_async()
#define STR2(x) #x
#define STR(x) STR2(x)
#define TS0(idx) do {} while (0)
#define TS(idx) do {} while (0)
#define V_RS 6
#define V_K1 8
#define V_K2 18
#define V_K3 28

__device__ __forceinline__ void fix_red(uint8_t* p, const float* a, float sc) {
  int v0 = __float2int_rn(a[0] * sc), v1 = __float2int_rn(a[1] * sc), v2 = __float2int_rn(a[2] * sc), v3 = __float2int_rn(a[3] * sc);
  red64(p, ((uint32_t)v0 << 7) | 1u, ((uint32_t)v2 << 3) + (uint32_t)(v0 >> 25));
  red64(p + 1024, ((uint32_t)v1 << 7) | 1u, ((uint32_t)v3 << 3) + (uint32_t)(v1 >> 25));
}

template <int wg>
__device__ __forceinline__ void qk_role(const uint32_t sb, const uint32_t sb1, const uint32_t sb2, const int tid, const int w, const uint8_t* __restrict__ ar) {
    const int lane = tid & 31;
    const uint32_t bar = sb + O_BAR;
    uint32_t a[40][4];
    {
      const uint32_t la = sb + wg * 81920 + ((lane >> 4) * 8 + (lane & 7)) * 128 + (((2 * w + ((lane >> 3) & 1)) ^ (lane & 7)) << 4);
#pragma unroll
      for (int p = 0; p < 5; p++) {
        mbar_wait(bar + 8 * (MB_W + wg * 5 + p), 0);
#pragma unroll
        for (int k = 0; k < 8; k++) ldsm4t(a[p * 8 + k], la + (p * 8 + k) * 2048);
      }
    }
    bar_sync<B_ALL, 384>();
    cluster_sync();
    const uint32_t swz = (lane & 7) * 128 + (((2 * w + ((lane >> 3) & 1)) ^ (lane & 7)) << 4);
    const uint32_t ld_m = sb + O_H + (lane & 7) * 128 + (((lane >> 3) ^ (lane & 7)) << 4);

    for (int s = 0; s < NSEG; s++) {
      const uint32_t par = s & 1;
      if (wg == 0 && w == 0) TS0(0);
      {
        float ax[16];
        const uint64_t db = mkdesc(opaque(sb) + O_H + 1024, 16, 1024, 1);
        mbar_wait(bar + 8 * MB_XF, par);
        wg_fence();
#pragma unroll
        for (int k = 0; k < 20; k++) wg_rs_n32_tb0(ax, a[k], db + (((k >> 2) * 5120 + (k & 3) * 32) >> 4), k);
        mbar_wait(bar + 8 * (MB_XF + 1), par);
        wg_fence();
#pragma unroll
        for (int k = 20; k < 40; k++) wg_rs_n32_tb0(ax, a[k], db + (((k >> 2) * 5120 + (k & 3) * 32) >> 4), 1);
        wg_commit();
        if (s > 0) bar_sync<B_PFREE, 384>();
        const uint32_t st_x = sb + (wg == 0 ? O_QK : O_K + 2048) + (lane >> 4) * 2048 + swz;
        wg_wait<0>();
        pin<16>(ax);
        if (w == 0) TS(1 + 22 * wg);
        stsm4t(st_x, pack2(ax[0], ax[1]), pack2(ax[2], ax[3]), pack2(ax[4], ax[5]), pack2(ax[6], ax[7]));
        stsm4t(st_x + 4096, pack2(ax[8], ax[9]), pack2(ax[10], ax[11]), pack2(ax[12], ax[13]), pack2(ax[14], ax[15]));
      }
      if (wg == 1 && tid == 192) { mbar_expect(bar + 8 * MB_SM, 2 * SM_SLOT + 48 + 48); mbar_expect(bar + 8 * MB_SX, 2 * 2176); }
      {
        float c0[4] = {0.f, 0.f, 0.f, 0.f}, c1[4] = {0.f, 0.f, 0.f, 0.f};
#pragma unroll
        for (int wv = 0; wv < 4; wv++) {
          mbar_wait(bar + 8 * (MB_MF + wv), par);
          if (wg == 0 && w == 0) TS(2 + wv);
          uint32_t b[6][4];
#pragma unroll
          for (int r = 0; r < (wv == 0 ? 1 : 3); r++) {
            const int c = wv == 0 ? 9 : 3 * r + wv - 1;
            ldsm4(b[2 * r], ld_m + c * 5120);
            ldsm4(b[2 * r + 1], (ld_m ^ 64) + c * 5120);
          }
#pragma unroll
          for (int r = 0; r < (wv == 0 ? 1 : 3); r++) {
            const int c = wv == 0 ? 9 : 3 * r + wv - 1;
            mma16816(c0, a[4 * c], b[2 * r][0], b[2 * r][1]);
            mma16816(c1, a[4 * c + 1], b[2 * r][2], b[2 * r][3]);
            mma16816(c0, a[4 * c + 2], b[2 * r + 1][0], b[2 * r + 1][1]);
            mma16816(c1, a[4 * c + 3], b[2 * r + 1][2], b[2 * r + 1][3]);
          }
        }
        bar_arrive<B_VGO, 384>();
        stsm2t(sb + (wg == 0 ? O_QM : O_K) + swz, pack2(c0[0] + c1[0], c0[1] + c1[1]), pack2(c0[2] + c1[2], c0[3] + c1[3]));
        fence_async();
      }
      if (wg == 0) {
        bar_sync<B_QK, 256>();
        float sv[20];
        {
          const uint64_t da = mkdesc(opaque(sb) + O_QK, 16, 1024, 1);
          const uint64_t db = mkdesc(opaque(sb) + O_K, 16, 2048, 1);
          wg_fence();
#pragma unroll
          for (int k = 0; k < 4; k++) wg_ss_n40_ta0_tb0(sv, da + 2 * k, db + 2 * k, k);
          wg_commit();
          bar_arrive<B_SISS, 256>();
          if (w == 0) TS(6);
          wg_wait<0>();
          pin<20>(sv);
        }
        constexpr float SCL = 0.07216878364870322f;
        constexpr float L2E = 1.4426950408889634f;
        const uint32_t om = O_SM + opaque(lane) * 16, om2 = O_SM + 512 + opaque(lane) * 4;
        const uint32_t m0 = pack2(sv[2], sv[3]), m1 = pack2(sv[6], sv[7]), m2 = pack2(sv[10], sv[11]), m3 = pack2(sv[14], sv[15]), m4 = pack2(sv[18], sv[19]);
        if (w == 0) {
          sta4(sb1 + om + SM_SLOT, m0, m1, m2, m3, sb1 + O_BAR + 8 * MB_SM);
          sta4(sb2 + om, m0, m1, m2, m3, sb2 + O_BAR + 8 * MB_SM);
          sta1(sb1 + om2 + SM_SLOT, m4, sb1 + O_BAR + 8 * MB_SM);
          sta1(sb2 + om2, m4, sb2 + O_BAR + 8 * MB_SM);
        }
        if (lane < 3) { const uint32_t b = mapa(sb, lane); sta1(b + O_MAXS + 48, 0u, b + O_BAR + 8 * MB_SM); }
        bar_arrive<B_SSENT, 256>();
        const uint32_t ox = O_K + w * 2048 + opaque(lane) * 16, ox2 = O_K + 8192 + opaque(lane) * 4;
        const uint32_t p0 = pack2(sv[0], sv[1]), p1 = pack2(sv[4], sv[5]), p2 = pack2(sv[8], sv[9]), p3 = pack2(sv[12], sv[13]), p4 = pack2(sv[16], sv[17]);
        if (w == 0) TS(7);
        mbar_wait(bar + 8 * MB_SM, par);
#define ACC2(k, p, u, v) { t[k] = bflo(p) + bflo(u) + bflo(v); t[k + 1] = bfhi(p) + bfhi(u) + bfhi(v); }
        if (w == 0) {
          float t[10];
          {
            const uint4 u = lds4(sb + om), v = lds4(sb + om + SM_SLOT);
            const uint32_t u4 = lds1(sb + om2), v4 = lds1(sb + om2 + SM_SLOT);
            sta4(sb1 + ox + 512, p0, p1, p2, p3, sb1 + O_BAR + 8 * MB_SX);
            sta4(sb2 + ox, p0, p1, p2, p3, sb2 + O_BAR + 8 * MB_SX);
            bar_arrive<B_SLD, 256>();
            TS(8);
            ACC2(0, m0, u.x, v.x) ACC2(2, m1, u.y, v.y) ACC2(4, m2, u.z, v.z) ACC2(6, m3, u.w, v.w) ACC2(8, m4, u4, v4)
          }
          float m = fmaxf(fmaxf(fmaxf(t[0], t[1]), fmaxf(t[2], t[3])), fmaxf(fmaxf(t[4], t[5]), fmaxf(t[6], t[7])));
          m = fmaxf(m, fmaxf(t[8], t[9]));
          m = fmaxf(m, __shfl_xor_sync(~0u, m, 1));
          m = fmaxf(m, __shfl_xor_sync(~0u, m, 2));
          const float mm = m * (SCL * L2E);
#pragma unroll
          for (int k = 0; k < 10; k++) t[k] = ex2(fmaf(t[k], SCL * L2E, -mm));
          float sum = ((t[0] + t[1]) + (t[2] + t[3])) + ((t[4] + t[5]) + (t[6] + t[7])) + (t[8] + t[9]);
          sum += __shfl_xor_sync(~0u, sum, 1);
          sum += __shfl_xor_sync(~0u, sum, 2);
          const float inv = rcp(sum);
          const uint32_t ln = opaque(lane), pa = sb + O_QM + (ln & 7) * 128;
          stsm4(pa + (((ln >> 3) ^ (ln & 7)) << 4), pack2(t[0] * inv, t[1] * inv), pack2(t[2] * inv, t[3] * inv), pack2(t[4] * inv, t[5] * inv), pack2(t[6] * inv, t[7] * inv));
          stsm1(pa + ((4 ^ (ln & 7)) << 4), pack2(t[8] * inv, t[9] * inv));
          bar_arrive<B_PM, 160>();
          TS(9);
        } else {
          sta4(sb1 + ox + 512, p0, p1, p2, p3, sb1 + O_BAR + 8 * MB_SX);
          sta4(sb2 + ox, p0, p1, p2, p3, sb2 + O_BAR + 8 * MB_SX);
          if (w == 3) { sta1(sb1 + ox2 + 128, p4, sb1 + O_BAR + 8 * MB_SX); sta1(sb2 + ox2, p4, sb2 + O_BAR + 8 * MB_SX); }
          bar_arrive<B_SLD, 256>();
        }
        mbar_wait(bar + 8 * MB_SX, par);
        bar_sync<B_VEND, 256>();
        {
          float t[10];
          const uint4 u = lds4(sb + ox), v = lds4(sb + ox + 512);
          const uint32_t u4 = lds1(sb + ox2), v4 = lds1(sb + ox2 + 128);
          ACC2(0, p0, u.x, v.x) ACC2(2, p1, u.y, v.y) ACC2(4, p2, u.z, v.z) ACC2(6, p3, u.w, v.w) ACC2(8, p4, u4, v4)
          const int ln = opaque(lane), dq = 8 * w + (ln >> 2) - 2 * (ln & 3);
#pragma unroll
          for (int k = 1; k < 5; k++) {
            if (8 * (k - 1) > dq) t[2 * k] = -1e9f / SCL;
            if (8 * (k - 1) + 1 > dq) t[2 * k + 1] = -1e9f / SCL;
          }
          float m = fmaxf(fmaxf(fmaxf(t[0], t[1]), fmaxf(t[2], t[3])), fmaxf(fmaxf(t[4], t[5]), fmaxf(t[6], t[7])));
          m = fmaxf(m, fmaxf(t[8], t[9]));
          m = fmaxf(m, __shfl_xor_sync(~0u, m, 1));
          m = fmaxf(m, __shfl_xor_sync(~0u, m, 2));
          const float mm = m * (SCL * L2E);
#pragma unroll
          for (int k = 0; k < 10; k++) t[k] = ex2(fmaf(t[k], SCL * L2E, -mm));
          float sum = ((t[0] + t[1]) + (t[2] + t[3])) + ((t[4] + t[5]) + (t[6] + t[7])) + (t[8] + t[9]);
          sum += __shfl_xor_sync(~0u, sum, 1);
          sum += __shfl_xor_sync(~0u, sum, 2);
          const float inv = rcp(sum);
          const int rr = 2 * w + (ln & 1);
          const uint32_t pa = sb + O_QK + ((ln >> 1) & 3) * 2048 + rr * 128;
          stsm4(pa + (((ln >> 3) ^ rr) << 4), pack2(t[0] * inv, t[1] * inv), pack2(t[2] * inv, t[3] * inv), pack2(t[4] * inv, t[5] * inv), pack2(t[6] * inv, t[7] * inv));
          stsm2(pa + (((4 + ((ln >> 3) & 1)) ^ rr) << 4), pack2(t[8] * inv, t[9] * inv), 0u);
          fence_async();
          bar_arrive<B_PX, 256>();
          if (w == 0) TS(10);
        }
      } else {
        bar_arrive<B_QK, 256>();
        if (w == 0 && s + 1 < NSEG) {
          if (lane < 2) mbar_expect(bar + 8 * (MB_XF + lane), 20480);
          const int ln = blockIdx.x * 2 + (lane - 16), s2 = s + 2;
          if (lane >= 16 && lane < 18 && ln < 160 && s2 < NSEG - 1) {
            const int tile = ln >> 4, off = (ln & 15) << 7;
            const uint8_t* p = ar + (s2 >> 2) * AR_GROUP + (s2 & 1) * 128 + ((s2 >> 1) & 1) * 512 + ((tile >> 2) * 8 + (tile & 3)) * 4096 +
                               (off >> 10) * 16384 + ((off >> 7) & 1) * 256 + ((off >> 8) & 3) * 1024;
            asm volatile("prefetch.global.L2 [%0];" :: "l"(p));
          }
          bar_sync<B_VHALF, 160>();
          if (lane < 5) bulk_g2s(sb + O_H + lane * 5120 + 1024, g_xn + (s + 1) * 40960 + lane * 4096, 4096, bar + 8 * MB_XF);
          bar_sync<B_VDONE, 160>();
          if (lane < 5) bulk_g2s(sb + O_H + (lane + 5) * 5120 + 1024, g_xn + (s + 1) * 40960 + (lane + 5) * 4096, 4096, bar + 8 * (MB_XF + 1));
        }
      }
      if (s + 1 < NSEG) bar_sync<wg == 0 ? B_XGO : B_XGO1, 256>();
    }
}

__global__ void __launch_bounds__(384, 1)
rec_kernel(const __grid_constant__ CUtensorMap tmq, const __grid_constant__ CUtensorMap tmk,
           const __grid_constant__ CUtensorMap tmv, const __grid_constant__ CUtensorMap tmo,
           const bf16* __restrict__ mem0, uint8_t* __restrict__ ar) {
  extern __shared__ __align__(1024) uint8_t smem[];
  const uint32_t sb = smem_u32(smem);
  const int tid = threadIdx.x, wid = __shfl_sync(~0u, tid >> 5, 0), wg = wid >> 2, w = wid & 3, lane = tid & 31, g = lane >> 2, i4 = lane & 3;
  uint32_t rank; asm("mov.u32 %0, %%cluster_ctarank;" : "=r"(rank));
  const int head = blockIdx.x / 3;
  const int e0 = head * DH + rank * 64;
  const uint32_t bar = sb + O_BAR;
  const uint32_t r1 = rank == 2 ? 0 : rank + 1, r2 = rank == 0 ? 2 : rank - 1;
  const uint32_t sb1 = mapa(sb, r1), sb2 = mapa(sb, r2);

  if (tid == 0) {
    for (int k = 0; k < 24; k++) mbar_init(bar + 8 * k, 1);
    asm volatile("fence.mbarrier_init.release.cluster;" ::: "memory");
    fence_async();
    for (int p = 0; p < 5; p++) {
      mbar_expect(bar + 8 * (MB_W + p), 16384);
      tma5d(sb + p * 16384, &tmq, e0, p * 8, bar + 8 * (MB_W + p));
      mbar_expect(bar + 8 * (MB_W + 5 + p), 16384);
      tma5d(sb + 81920 + p * 16384, &tmk, e0, p * 8, bar + 8 * (MB_W + 5 + p));
    }
    mbar_expect(bar + 8 * MB_XF, 20480);
    mbar_expect(bar + 8 * (MB_XF + 1), 20480);
    for (int c = 0; c < 10; c++) bulk_g2s(sb + O_H + c * 5120 + 1024, g_xn + c * 4096, 4096, bar + 8 * (MB_XF + (c >= 5)));
  }
  __syncthreads();

  if (wg == 0) {
    asm volatile("setmaxnreg.inc.sync.aligned.u32 " STR(REG_A) ";");
    qk_role<0>(sb, sb1, sb2, tid, w, ar);
  } else if (wg == 1) {
    asm volatile("setmaxnreg.inc.sync.aligned.u32 " STR(REG_C) ";");
    qk_role<1>(sb, sb1, sb2, tid, w, ar);
  } else {
    asm volatile("setmaxnreg.dec.sync.aligned.u32 " STR(REG_B) ";");
    bar_sync<B_ALL, 384>();
    if (tid == 256) {
      fence_async();
      mbar_expect(bar + 8 * (MB_W + 11), 81920);
      for (int p = 0; p < 5; p++) tma5d(sb + O_WV + p * 16384, &tmv, e0, p * 8, bar + 8 * (MB_W + 11));
      mbar_expect(bar + 8 * (MB_W + 12), 81920);
      tma2d(sb + O_WO + 73728, &tmo, 576, e0, bar + 8 * (MB_W + 12));
      for (int p = 0; p < 9; p++) tma2d(sb + O_WO + p * 8192, &tmo, (rank * 3 + p / 3) * 64, head * DH + (p % 3) * 64, bar + 8 * (MB_W + 12));
    }
    float cbound;
    {
      float mx = 0.f;
      for (int c = lane; c < DM; c += 32) mx = fmaxf(mx, g_norm[c]);
#pragma unroll
      for (int o = 16; o; o >>= 1) mx = fmaxf(mx, __shfl_xor_sync(~0u, mx, o));
      cbound = sqrtf(mx) * sqrtf(g_norm[640]) * (25.2982213f * 1.1f);
    }
    cluster_sync();
    const int t = tid & 127;
    const int myT = w == 0 ? 9 : rank * 3 + w - 1;
    const int tok = 2 * ((lane >> 1) & 3) + ((lane >> 3) & 1);
    const uint32_t fw_off = O_H + myT * 5120 + tok * 128 + (((2 * (lane >> 4) + (lane & 1)) ^ tok) << 4);
    const uint32_t prod_off = (w >> 1) * 16384 + (w & 1) * 2048 + ((g >> 1) & 1) * 256 + (i4 * 2 + (g >> 2)) * 16 + (g & 1) * 8;
    const uint32_t cons_off = ((myT >> 2) * 8 + (myT & 3)) * 4096 + (lane >> 3) * 1024 + (lane & 7) * 16;
    uint32_t tile_off[3];
#pragma unroll
    for (int k = 0; k < 3; k++) { const int T = rank * 3 + k; tile_off[k] = ((T >> 2) * 8 + (T & 3)) * 4096; }
    constexpr uint32_t T9_OFF = 17 * 4096;

    auto forward = [&](const uint32_t* p) {
      const uint32_t o = opaque(fw_off), bo = O_BAR + 8 * (MB_MF + w);
      if (w > 0) {
        sta4(sb1 + o, p[0], p[1], p[2], p[3], sb1 + bo); sta4(sb2 + o, p[0], p[1], p[2], p[3], sb2 + bo);
        sta4(sb1 + (o ^ 64), p[4], p[5], p[6], p[7], sb1 + bo); sta4(sb2 + (o ^ 64), p[4], p[5], p[6], p[7], sb2 + bo);
      }
      sts4(sb + o, p[0], p[1], p[2], p[3]);
      sts4(sb + (o ^ 64), p[4], p[5], p[6], p[7]);
      __syncwarp();
      if (lane == 0) { if (w > 0) mbar_expect(sb + bo, 2048); else mbar_arrive(sb + bo); }
      fence_async();
      uint32_t mx = 0;
#pragma unroll
      for (int k = 0; k < 8; k++) mx = __vmaxu2(mx, p[k] & 0x7FFF7FFFu);
      mx = max(mx & 0xFFFFu, mx >> 16);
      mx = __reduce_max_sync(~0u, mx);
      if (lane < 3) { const uint32_t b = mapa(sb, lane); sta1(b + O_MAXS + (rank * 4 + w) * 4, mx << 16, b + O_BAR + 8 * MB_SM); }
    };
    {
      if (t == 4) mbar_expect(bar + 8 * MB_OG, 2048);
      const uint32_t* mp = (const uint32_t*)(mem0 + tok * DM + myT * 64 + 16 * (lane >> 4) + 4 * (lane & 1));
      const uint32_t p[8] = {mp[0], mp[4], mp[1], mp[5], mp[16], mp[20], mp[17], mp[21]};
      forward(p);
    }
    mbar_wait(bar + 8 * (MB_W + 11), 0);
    mbar_wait(bar + 8 * (MB_W + 12), 0);

    const uint32_t la_w = sb + ((lane >> 4) * 8 + (lane & 7)) * 128 + (((2 * w + ((lane >> 3) & 1)) ^ (lane & 7)) << 4);
    for (int s = 0; s < NSEG; s++) {
      const uint32_t par = s & 1;
      uint32_t vf[10];
      uint32_t pm[5];
      float sc, isc;
      {
        float av[20];
        uint32_t af[V_RS][4];
        const uint64_t da = mkdesc(opaque(sb) + O_WV, 1024, 1024, 1);
        const uint64_t db = mkdesc(opaque(sb) + O_H, 16, 1024, 1);
#pragma unroll
        for (int k = 0; k < V_RS; k++) ldsm4t(af[k], la_w + O_WV + k * 2048);
        bar_sync<B_VGO, 384>();
        wg_fence();
#pragma unroll
        for (int k = 0; k < V_RS; k++) wg_rs_n40_tb0(av, af[k], db + (((k >> 2) * 5120 + (k & 3) * 32) >> 4), k);
        if (w == 0) TS(11);
        bar_sync<B_SISS, 256>();
        wg_fence();
#pragma unroll
        for (int k = V_RS; k < V_K1; k++) wg_ss_n40_ta1_tb0(av, da + k * 128, db + (((k >> 2) * 5120 + (k & 3) * 32) >> 4), 1);
        bar_sync<B_SSENT, 256>();
        wg_fence();
#pragma unroll
        for (int k = V_K1; k < V_K2; k++) wg_ss_n40_ta1_tb0(av, da + k * 128, db + (((k >> 2) * 5120 + (k & 3) * 32) >> 4), 1);
        bar_sync<B_SLD, 256>();
        wg_fence();
#pragma unroll
        for (int k = V_K2; k < 20; k++) wg_ss_n40_ta1_tb0(av, da + k * 128, db + (((k >> 2) * 5120 + (k & 3) * 32) >> 4), 1);
        wg_commit();
#pragma unroll
        for (int k = (V_K2 > 20 ? V_K2 : 20); k < V_K3; k++) wg_ss_n40_ta1_tb0(av, da + k * 128, db + (((k >> 2) * 5120 + (k & 3) * 32) >> 4), 1);
        wg_commit();
        wg_wait<1>();
        if (s + 1 < NSEG) bar_arrive<B_VHALF, 160>();
        wg_fence();
#pragma unroll
        for (int k = V_K3; k < 40; k++) wg_ss_n40_ta1_tb0(av, da + k * 128, db + (((k >> 2) * 5120 + (k & 3) * 32) >> 4), 1);
        wg_commit();
        if (w == 0) TS(12);
        bar_sync<B_PM, 160>();
        const uint32_t ln = opaque(lane), pa = sb + O_QM + (ln & 7) * 128;
        ldsm4(pm, pa + (((ln >> 3) ^ (ln & 7)) << 4));
        ldsm1(pm[4], pa + ((4 ^ (ln & 7)) << 4));
        bar_arrive<B_VEND, 256>();
        wg_wait<0>();
        pin<20>(av);
        if (w == 0) TS(13);
#pragma unroll
        for (int k = 0; k < 10; k++) vf[k] = pack2(av[2 * k], av[2 * k + 1]);
      }
      uint8_t* arp = ar + (s >> 2) * AR_GROUP + (s & 1) * 128 + ((s >> 1) & 1) * 512;
      uint32_t t1 = 0;
      if (s + 1 < NSEG) {
        {
          float o0[4] = {0.f, 0.f, 0.f, 0.f}, o1[4] = {0.f, 0.f, 0.f, 0.f};
          mma16816(o0, vf, pm[0], pm[1]);
          mma16816(o1, vf + 4, pm[2], pm[3]);
          mma1688(o0, vf[8], vf[9], pm[4]);
          const uint32_t mxl = lds1(sb + O_MAXS + 4 * min(opaque(lane), 11u));
          const uint32_t p0 = pack2(o0[0] + o1[0], o0[1] + o1[1]), p1 = pack2(o0[2] + o1[2], o0[3] + o1[3]);
          const uint32_t o = O_OG + rank * 2048 + w * 256 + opaque(lane) * 4;
          sta1(sb1 + o, p0, sb1 + O_BAR + 8 * MB_OG); sta1(sb1 + o + 128, p1, sb1 + O_BAR + 8 * MB_OG);
          sta1(sb2 + o, p0, sb2 + O_BAR + 8 * MB_OG); sta1(sb2 + o + 128, p1, sb2 + O_BAR + 8 * MB_OG);
          sts1(sb + o, p0); sts1(sb + o + 128, p1);
          fence_async();
          bar_sync<B_WG2, 128>();
          const float b = cbound * fmaxf(1.f, __uint_as_float(__reduce_max_sync(~0u, mxl)));
          const uint32_t eb = min(max(__float_as_uint(b) >> 23, 27u), 254u);
          sc = __uint_as_float((280u - eb) << 23);
          isc = __uint_as_float((eb - 26u) << 23);
        }
        float c9[4], ca[4], cb[4], cc[4];
        uint8_t* pp = arp + opaque(prod_off);
        const uint32_t sbo = opaque(sb);
        const uint64_t da = mkdesc(sbo + O_WO, 1024, 1024, 1), db = mkdesc(sbo + O_OG, 128, 128, 0);
        const uint64_t da0 = da + rank * 512, db0 = db + rank * 128;
        const uint64_t da1 = da + r1 * 512, db1 = db + r1 * 128;
        const uint64_t da2 = da + r2 * 512, db2 = db + r2 * 128;
        wg_fence();
#pragma unroll
        for (int k = 0; k < 4; k++) wg_ss_n8_ta1_tb1(c9, da + 4608 + k * 128, db0 + k * 16, k);
        wg_commit();
        if (w == 0) TS(14);
#pragma unroll
        for (int k = 0; k < 4; k++) wg_ss_n8_ta1_tb1(ca, da0 + k * 128, db0 + k * 16, k);
#pragma unroll
        for (int k = 0; k < 4; k++) wg_ss_n8_ta1_tb1(cb, da0 + 1536 + k * 128, db0 + k * 16, k);
#pragma unroll
        for (int k = 0; k < 4; k++) wg_ss_n8_ta1_tb1(cc, da0 + 3072 + k * 128, db0 + k * 16, k);
        wg_commit();
        wg_wait<1>();
        pin<4>(c9);
        fix_red(pp + T9_OFF, c9, sc);
        bar_arrive<B_VDONE, 160>();
        mbar_wait(bar + 8 * MB_OG, par);
        FENCE_RX();
        wg_fence();
#pragma unroll
        for (int k = 0; k < 4; k++) wg_ss_n8_ta1_tb1(ca, da1 + k * 128, db1 + k * 16, 1);
        if (w == 0) TS(15);
#pragma unroll
        for (int k = 0; k < 4; k++) wg_ss_n8_ta1_tb1(ca, da2 + k * 128, db2 + k * 16, 1);
        wg_commit();
#pragma unroll
        for (int k = 0; k < 4; k++) wg_ss_n8_ta1_tb1(cb, da1 + 1536 + k * 128, db1 + k * 16, 1);
#pragma unroll
        for (int k = 0; k < 4; k++) wg_ss_n8_ta1_tb1(cb, da2 + 1536 + k * 128, db2 + k * 16, 1);
        wg_commit();
        wg_wait<1>();
        pin<4>(ca);
        fix_red(pp + tile_off[0], ca, sc);
        if (w == 0) TS(16);
        wg_fence();
#pragma unroll
        for (int k = 0; k < 4; k++) wg_ss_n8_ta1_tb1(cc, da1 + 3072 + k * 128, db1 + k * 16, 1);
#pragma unroll
        for (int k = 0; k < 4; k++) wg_ss_n8_ta1_tb1(cc, da2 + 3072 + k * 128, db2 + k * 16, 1);
        wg_commit();
        wg_wait<1>();
        pin<4>(cb);
        fix_red(pp + tile_off[1], cb, sc);
        wg_wait<0>();
        pin<4>(cc);
        fix_red(pp + tile_off[2], cc, sc);
        t1 = clk();
        bar_arrive<B_XGO1, 256>();
        bar_arrive<B_XGO, 256>();
        if (w == 0) TS(17);
      }
      {
        float ox[16];
        const uint32_t vz[4] = {vf[8], vf[9], 0u, 0u};
        const uint64_t dp = mkdesc(opaque(sb) + O_QK, 16, 2048, 1);
        bar_sync<B_PX, 256>();
        wg_fence();
        wg_rs_n32_tb0(ox, vf, dp, 0);
        wg_rs_n32_tb0(ox, vf + 4, dp + 2, 1);
        wg_rs_n32_tb0(ox, vz, dp + 4, 1);
        wg_commit();
        const uint32_t ln = opaque(lane);
        uint8_t* op = g_ot + (size_t)(s >> 1) * (HE * 128) + (e0 + 16 * w + (ln >> 2)) * 128 + ((((s & 1) * 4 + (ln & 3)) ^ (ln >> 2)) << 4);
        wg_wait<0>();
        pin<16>(ox);
        if (s + 1 < NSEG) bar_arrive<B_PFREE, 384>();
        *(uint4*)op = make_uint4(pack2(ox[0], ox[1]), pack2(ox[4], ox[5]), pack2(ox[8], ox[9]), pack2(ox[12], ox[13]));
        *(uint4*)(op + 1024) = make_uint4(pack2(ox[2], ox[3]), pack2(ox[6], ox[7]), pack2(ox[10], ox[11]), pack2(ox[14], ox[15]));
        if (w == 0) TS(28);
      }
      if (s + 1 < NSEG) {
        if (t == 4) mbar_expect(bar + 8 * MB_OG, 2048);
        const uint8_t* cp = arp + opaque(cons_off);
        const uint32_t need = w == 0 ? 96 : 32;
        const int dly = w == 0 ? 0 : POLL_DELAY - (3 - w) * POLL_STEP;
        uint4 y[4];
        int it = 0;
        while ((int)(clk() - t1) < dly) {}
        if (w == 3) TS(18);
        while (true) {
          y[0] = ld_poll(cp); y[1] = ld_poll(cp + 256); y[2] = ld_poll(cp + 16384); y[3] = ld_poll(cp + 16384 + 256);
          const uint32_t bad = (y[0].x ^ need) | (y[0].z ^ need) | (y[1].x ^ need) | (y[1].z ^ need) | (y[2].x ^ need) | (y[2].z ^ need) | (y[3].x ^ need) | (y[3].z ^ need);
          if (!__any_sync(~0u, (bad & 127u) != 0)) break;
          if (++it > 2000000) __trap();
        }
        uint32_t p[8];
#pragma unroll
        for (int k = 0; k < 4; k++) {
          const float l0 = (float)((int)__funnelshift_r(y[k].x, y[k].y, 3) >> 4) * isc, h0 = (float)((int)(y[k].y + 4u) >> 3) * isc;
          const float l1 = (float)((int)__funnelshift_r(y[k].z, y[k].w, 3) >> 4) * isc, h1 = (float)((int)(y[k].w + 4u) >> 3) * isc;
          p[2 * k] = pack2(l0, l1); p[2 * k + 1] = pack2(h0, h1);
        }
        TS(19 + w);
        forward(p);
      }
    }
  }
  cluster_sync();
}

__global__ void k_norms(const bf16* __restrict__ wv, const bf16* __restrict__ wo) {
  if (blockIdx.x < 96) {
    const int c = threadIdx.x * 2;
    float s0 = 0.f, s1 = 0.f;
    for (int r = 0; r < 64; r++) { float2 v = __bfloat1622float2(*(const __nv_bfloat162*)(wo + (blockIdx.x * 64 + r) * DM + c)); s0 += v.x * v.x; s1 += v.y * v.y; }
    atomicAdd(&g_norm[c], s0); atomicAdd(&g_norm[c + 1], s1);
  } else {
    const int b = blockIdx.x - 96;
    float s = 0.f;
    for (int r = 0; r < 64; r++) { float2 v = __bfloat1622float2(*(const __nv_bfloat162*)(wv + (b * 64 + r) * DM + threadIdx.x * 2)); s += v.x * v.x + v.y * v.y; }
    for (int o = 16; o; o >>= 1) s += __shfl_xor_sync(~0u, s, o);
    if ((threadIdx.x & 31) == 0) atomicAdd(&g_norm[640], s);
  }
}
__global__ void k_cvt_in(const bf16* __restrict__ x) { int i = blockIdx.x * blockDim.x + threadIdx.x; g_x[i] = __bfloat162float(x[i]); }
__global__ void k_cvt_out(bf16* __restrict__ o) { int i = blockIdx.x * blockDim.x + threadIdx.x; o[i] = __float2bfloat16(g_x[i]); }
__global__ void k_ln(int mode) {
  const int row = blockIdx.x * 8 + (threadIdx.x >> 5), lane = threadIdx.x & 31;
  float v[20]; float s = 0.f;
  for (int k = 0; k < 10; k++) { float2 t = *(const float2*)(g_x + row * DM + k * 64 + lane * 2); v[2 * k] = t.x; v[2 * k + 1] = t.y; s += t.x + t.y; }
  for (int o = 16; o; o >>= 1) s += __shfl_xor_sync(~0u, s, o);
  const float m = s * (1.f / DM); float q = 0.f;
  for (int k = 0; k < 20; k++) { v[k] -= m; q += v[k] * v[k]; }
  for (int o = 16; o; o >>= 1) q += __shfl_xor_sync(~0u, q, o);
  const float r = rsqrtf(q * (1.f / DM) + 1e-5f);
  for (int k = 0; k < 10; k++) {
    const uint32_t p = pack2(v[2 * k] * r, v[2 * k + 1] * r);
    if (mode == 0) *(uint32_t*)(g_xa + row * DM + k * 64 + lane * 2) = p;
    else { const int pj = (lane & 24) + 2 * (lane & 3) + ((lane >> 2) & 1);
      *(uint32_t*)(g_xn + (row >> 5) * 40960 + k * 4096 + (row & 31) * 128 + (((pj >> 2) ^ (row & 7)) << 4) + (pj & 3) * 4) = p; }
  }
}
__global__ void k_gemm(const bf16* __restrict__ A, const bf16* __restrict__ B, float* __restrict__ C, int N, int K, int amode, int accum) {
  __shared__ float As[32][65], Bs[32][64];
  const int tx = threadIdx.x & 15, ty = threadIdx.x >> 4, m0 = blockIdx.y * 64, n0 = blockIdx.x * 64;
  float acc[4][4] = {};
  for (int k0 = 0; k0 < K; k0 += 32) {
    for (int e = threadIdx.x; e < 2048; e += 256) {
      if (amode == 0) { int m = e >> 5, k = e & 31; As[k][m] = __bfloat162float(A[(size_t)(m0 + m) * K + k0 + k]); }
      else { int k = e >> 6, m = e & 63, he = k0 + k; As[k][m] = __bfloat162float(*(const bf16*)(g_ot + (size_t)blockIdx.y * (HE * 128) + he * 128 + (((m >> 3) ^ (he & 7)) << 4) + (m & 7) * 2)); }
      int k = e >> 6, n = e & 63; Bs[k][n] = __bfloat162float(B[(size_t)(k0 + k) * N + n0 + n]);
    }
    __syncthreads();
    for (int k = 0; k < 32; k++) {
      float a[4], b[4];
      for (int r = 0; r < 4; r++) { a[r] = As[k][ty * 4 + r]; b[r] = Bs[k][tx * 4 + r]; }
      for (int r = 0; r < 4; r++) for (int c = 0; c < 4; c++) acc[r][c] += a[r] * b[c];
    }
    __syncthreads();
  }
  for (int r = 0; r < 4; r++) for (int c = 0; c < 4; c++) {
    float* p = C + (size_t)(m0 + ty * 4 + r) * N + n0 + tx * 4 + c;
    *p = accum ? *p + acc[r][c] : acc[r][c];
  }
}
__device__ __forceinline__ float phi(float t) { return (t > 0.f ? t + 1.f : __expf(t)) + 1e-6f; }
__global__ void k_kv(float* kv) {
  const int h = blockIdx.x, e = threadIdx.x / 20, d = threadIdx.x % 20;
  float s = 0.f;
  for (int t = blockIdx.y * 128; t < blockIdx.y * 128 + 128; t++) {
    const float pk = phi(g_qkv[t * 1920 + 640 + h * 20 + d]);
    s += pk * (e < 20 ? g_qkv[t * 1920 + 1280 + h * 20 + e] : 1.f);
  }
  atomicAdd(&kv[(h * 21 + e) * 20 + d], s);
}
__global__ void k_lo(const float* kv) {
  const int t = blockIdx.x, c = threadIdx.x, h = c / 20, e = c % 20;
  float num = 0.f, den = 0.f;
  for (int d = 0; d < 20; d++) { const float pq = phi(g_qkv[t * 1920 + h * 20 + d]); num += pq * kv[(h * 21 + e) * 20 + d]; den += pq * kv[(h * 21 + 20) * 20 + d]; }
  g_oa[t * DM + c] = __float2bfloat16(num / (den + 1e-6f));
}

typedef CUresult (*EncodeFn)(CUtensorMap*, CUtensorMapDataType, cuuint32_t, void*, const cuuint64_t*, const cuuint64_t*, const cuuint32_t*,
                             const cuuint32_t*, CUtensorMapInterleave, CUtensorMapSwizzle, CUtensorMapL2promotion, CUtensorMapFloatOOBfill);
static void make_map(EncodeFn fn, CUtensorMap* m, const void* p, uint64_t cols, uint64_t rows, uint32_t bc, uint32_t br) {
  cuuint64_t dims[2] = {cols, rows}; cuuint64_t strides[1] = {cols * 2}; cuuint32_t box[2] = {bc, br}; cuuint32_t es[2] = {1, 1};
  fn(m, CU_TENSOR_MAP_DATA_TYPE_BFLOAT16, 2, (void*)p, dims, strides, box, es, CU_TENSOR_MAP_INTERLEAVE_NONE, CU_TENSOR_MAP_SWIZZLE_128B,
     CU_TENSOR_MAP_L2_PROMOTION_L2_128B, CU_TENSOR_MAP_FLOAT_OOB_FILL_NONE);
}

static void make_map_perm(EncodeFn fn, CUtensorMap* m, const void* p) {
  cuuint64_t dims[5] = {HE, 2, 2, 4, 40}; const cuuint64_t r = HE * 2; cuuint64_t strides[4] = {r, 8 * r, 2 * r, 16 * r};
  cuuint32_t box[5] = {64, 2, 2, 4, 8}; cuuint32_t es[5] = {1, 1, 1, 1, 1};
  fn(m, CU_TENSOR_MAP_DATA_TYPE_BFLOAT16, 5, (void*)p, dims, strides, box, es, CU_TENSOR_MAP_INTERLEAVE_NONE, CU_TENSOR_MAP_SWIZZLE_128B,
     CU_TENSOR_MAP_L2_PROMOTION_L2_128B, CU_TENSOR_MAP_FLOAT_OOB_FILL_NONE);
}

extern "C" void kernel_launch(void* const* d_in, const int* in_sizes, int n_in, void* d_out, int out_size) {
  const bf16* x = (const bf16*)d_in[0];
  const bf16* wqkv = (const bf16*)d_in[1];
  const bf16* wo_a = (const bf16*)d_in[2];
  const bf16* mem0 = (const bf16*)d_in[4];
  const bf16* Wq = (const bf16*)d_in[5];
  const bf16* Wk = (const bf16*)d_in[6];
  const bf16* Wv = (const bf16*)d_in[7];
  const bf16* Wo = (const bf16*)d_in[8];
  cudaStream_t st = cudaStreamPerThread;

  static EncodeFn enc = nullptr;
  static uint8_t* p_ar; static float *p_norm, *p_kv, *p_x, *p_qkv; static bf16 *p_xa, *p_oa;
  if (!enc) {
    cudaDriverEntryPointQueryResult qr;
    void* fn = nullptr;
    cudaGetDriverEntryPoint("cuTensorMapEncodeTiled", &fn, cudaEnableDefault, &qr);
    enc = (EncodeFn)fn;
    cudaFuncSetAttribute(rec_kernel, cudaFuncAttributeMaxDynamicSharedMemorySize, REC_SMEM);
    cudaGetSymbolAddress((void**)&p_ar, g_ar); p_ar = (uint8_t*)(((uintptr_t)p_ar + 32767) & ~(uintptr_t)32767);
    cudaGetSymbolAddress((void**)&p_norm, g_norm); cudaGetSymbolAddress((void**)&p_kv, g_kv); cudaGetSymbolAddress((void**)&p_x, g_x);
    cudaGetSymbolAddress((void**)&p_qkv, g_qkv); cudaGetSymbolAddress((void**)&p_xa, g_xa); cudaGetSymbolAddress((void**)&p_oa, g_oa);
  }
  CUtensorMap tmq, tmk, tmv, tmo;
  make_map_perm(enc, &tmq, Wq);
  make_map_perm(enc, &tmk, Wk);
  make_map_perm(enc, &tmv, Wv);
  make_map(enc, &tmo, Wo, DM, HE, 64, 64);

  cudaMemsetAsync(p_ar, 0, 2 * AR_LAYER, st);
  cudaMemsetAsync(p_norm, 0, 1024 * 4, st);
  cudaMemsetAsync(p_kv, 0, 2 * 32 * 21 * 20 * 4, st);
  k_norms<<<192, 320, 0, st>>>(Wv, Wo);
  k_cvt_in<<<S_TOK * DM / 256, 256, 0, st>>>(x);
  for (int l = 0; l < 2; l++) {
    k_ln<<<256, 256, 0, st>>>(0);
    k_gemm<<<dim3(30, 32), 256, 0, st>>>(p_xa, wqkv, p_qkv, 1920, DM, 0, 0);
    k_kv<<<dim3(32, 16), 420, 0, st>>>(p_kv + l * 13440);
    k_lo<<<S_TOK, 640, 0, st>>>(p_kv + l * 13440);
    k_gemm<<<dim3(10, 32), 256, 0, st>>>(p_oa, wo_a, p_x, DM, DM, 0, 1);
    k_ln<<<256, 256, 0, st>>>(1);
    cudaLaunchConfig_t cfg = {};
    cfg.gridDim = dim3(96); cfg.blockDim = dim3(384); cfg.dynamicSmemBytes = REC_SMEM; cfg.stream = st;
    cudaLaunchAttribute at[1];
    at[0].id = cudaLaunchAttributeClusterDimension; at[0].val.clusterDim.x = 3; at[0].val.clusterDim.y = 1; at[0].val.clusterDim.z = 1;
    cfg.attrs = at; cfg.numAttrs = 1;
    cudaLaunchKernelEx(&cfg, rec_kernel, tmq, tmk, tmv, tmo, mem0, p_ar + l * AR_LAYER);
    k_gemm<<<dim3(10, 32), 256, 0, st>>>(nullptr, Wo, p_x, DM, HE, 1, 1);
  }
  k_cvt_out<<<S_TOK * DM / 256, 256, 0, st>>>((bf16*)d_out);
}
```

```cpp
#include <cuda_runtime.h>
#include <cuda_bf16.h>
#include <cuda.h>
#include <stdint.h>

typedef __nv_bfloat16 bf16;
typedef unsigned long long u64;

constexpr int S_TOK = 2048, DM = 640, NH = 32, DH = 192, HE = 6144, NSEG = 64;

constexpr int AR_GROUP = 98304;
constexpr int AR_LAYER = 16 * AR_GROUP;
__device__ __align__(1024) uint8_t g_ar[2 * AR_LAYER + 32768];
__device__ __align__(1024) uint8_t g_xn[NSEG * 40960];
__device__ __align__(1024) uint8_t g_ot[NSEG * HE * 64];
__device__ __align__(1024) float g_acc[2 * S_TOK * DM];
constexpr int FL_A = 0, FL_B = 64 * 6 * 8, FL_LAYER = FL_B + 64 * 8;
__device__ __align__(128) uint32_t g_flags[2 * FL_LAYER];
__device__ float g_norm[1024];
__device__ float g_x[S_TOK * DM];
__device__ bf16 g_xa[S_TOK * DM];
__device__ __align__(1024) uint8_t g_xt[S_TOK * DM * 2];
__device__ float g_qkv[S_TOK * 1920];
__device__ float g_kv[2 * 32 * 21 * 20];
__device__ bf16 g_oa[S_TOK * DM];
#define GT(slot, k) do {} while (0)

__device__ __forceinline__ uint32_t smem_u32(const void* p) { return (uint32_t)__cvta_generic_to_shared(p); }
__device__ __forceinline__ uint32_t mapa(uint32_t a, uint32_t r) { uint32_t o; asm("mapa.shared::cluster.u32 %0, %1, %2;" : "=r"(o) : "r"(a), "r"(r)); return o; }
__device__ __forceinline__ void mbar_init(uint32_t bar, uint32_t cnt) { asm volatile("mbarrier.init.shared::cta.b64 [%0], %1;" :: "r"(bar), "r"(cnt) : "memory"); }
__device__ __forceinline__ void mbar_expect(uint32_t bar, uint32_t tx) { asm volatile("mbarrier.arrive.expect_tx.shared::cta.b64 _, [%0], %1;" :: "r"(bar), "r"(tx) : "memory"); }
__device__ __forceinline__ void mbar_arrive(uint32_t bar) { asm volatile("mbarrier.arrive.shared::cta.b64 _, [%0];" :: "r"(bar) : "memory"); }
__device__ __forceinline__ void mbar_wait(uint32_t bar, uint32_t par) {
  asm volatile("{\n.reg .pred p;\n.reg .u32 c;\nmov.u32 c, 0;\n"
               "LW:\nmbarrier.try_wait.parity.shared::cta.b64 p, [%0], %1;\n@p bra LD;\n"
               "add.u32 c, c, 1;\nsetp.lt.u32 p, c, 4000000;\n@p bra LW;\ntrap;\nLD:\n}" :: "r"(bar), "r"(par) : "memory");
}
template <int ID, int N> __device__ __forceinline__ void bar_sync() { asm volatile("barrier.sync %0, %1;" :: "n"(ID), "n"(N) : "memory"); }
template <int ID, int N> __device__ __forceinline__ void bar_arrive() { asm volatile("barrier.arrive %0, %1;" :: "n"(ID), "n"(N) : "memory"); }
__device__ __forceinline__ void fence_async() { asm volatile("fence.proxy.async.shared::cta;" ::: "memory"); }
__device__ __forceinline__ void cluster_sync() { asm volatile("barrier.cluster.arrive.aligned;\nbarrier.cluster.wait.aligned;" ::: "memory"); }
__device__ __forceinline__ void wg_fence() { asm volatile("wgmma.fence.sync.aligned;" ::: "memory"); }
__device__ __forceinline__ void wg_commit() { asm volatile("wgmma.commit_group.sync.aligned;" ::: "memory"); }
template <int N> __device__ __forceinline__ void wg_wait() { asm volatile("wgmma.wait_group.sync.aligned %0;" :: "n"(N) : "memory"); }
template <int N> __device__ __forceinline__ void pin(float* d) {
#pragma unroll
  for (int i = 0; i < N; i++) asm volatile("" : "+f"(d[i]) :: "memory");
}
__device__ __forceinline__ uint64_t mkdesc(uint32_t addr, uint32_t lbo, uint32_t sbo, int sw) {
  return (uint64_t)((addr & 0x3FFFF) >> 4) | ((uint64_t)(lbo >> 4) << 16) | ((uint64_t)(sbo >> 4) << 32) | ((uint64_t)sw << 62);
}
__device__ __forceinline__ uint32_t opaque(uint32_t v) { uint32_t o; asm volatile("mov.u32 %0, %1;" : "=r"(o) : "r"(v)); return o; }
__device__ __forceinline__ uint32_t pack2(float lo, float hi) { uint32_t r; asm("cvt.rn.bf16x2.f32 %0, %1, %2;" : "=r"(r) : "f"(hi), "f"(lo)); return r; }
__device__ __forceinline__ void ldsm4(uint32_t* r, uint32_t a) { asm volatile("ldmatrix.sync.aligned.m8n8.x4.shared.b16 {%0,%1,%2,%3}, [%4];" : "=r"(r[0]), "=r"(r[1]), "=r"(r[2]), "=r"(r[3]) : "r"(a) : "memory"); }
__device__ __forceinline__ void ldsm4t(uint32_t* r, uint32_t a) { asm volatile("ldmatrix.sync.aligned.m8n8.x4.trans.shared.b16 {%0,%1,%2,%3}, [%4];" : "=r"(r[0]), "=r"(r[1]), "=r"(r[2]), "=r"(r[3]) : "r"(a) : "memory"); }
__device__ __forceinline__ void ldsm1(uint32_t& r, uint32_t a) { asm volatile("ldmatrix.sync.aligned.m8n8.x1.shared.b16 {%0}, [%1];" : "=r"(r) : "r"(a) : "memory"); }
__device__ __forceinline__ void stsm4(uint32_t a, uint32_t r0, uint32_t r1, uint32_t r2, uint32_t r3) { asm volatile("stmatrix.sync.aligned.m8n8.x4.shared.b16 [%0], {%1,%2,%3,%4};" :: "r"(a), "r"(r0), "r"(r1), "r"(r2), "r"(r3) : "memory"); }
__device__ __forceinline__ void stsm1(uint32_t a, uint32_t r0) { asm volatile("stmatrix.sync.aligned.m8n8.x1.shared.b16 [%0], {%1};" :: "r"(a), "r"(r0) : "memory"); }
__device__ __forceinline__ void stsm4t(uint32_t a, uint32_t r0, uint32_t r1, uint32_t r2, uint32_t r3) { asm volatile("stmatrix.sync.aligned.m8n8.x4.trans.shared.b16 [%0], {%1,%2,%3,%4};" :: "r"(a), "r"(r0), "r"(r1), "r"(r2), "r"(r3) : "memory"); }
__device__ __forceinline__ void stsm2t(uint32_t a, uint32_t r0, uint32_t r1) { asm volatile("stmatrix.sync.aligned.m8n8.x2.trans.shared.b16 [%0], {%1,%2};" :: "r"(a), "r"(r0), "r"(r1) : "memory"); }
__device__ __forceinline__ void mma16816(float* c, const uint32_t* a, uint32_t b0, uint32_t b1) {
  asm volatile("mma.sync.aligned.m16n8k16.row.col.f32.bf16.bf16.f32 {%0,%1,%2,%3}, {%4,%5,%6,%7}, {%8,%9}, {%0,%1,%2,%3};"
               : "+f"(c[0]), "+f"(c[1]), "+f"(c[2]), "+f"(c[3]) : "r"(a[0]), "r"(a[1]), "r"(a[2]), "r"(a[3]), "r"(b0), "r"(b1));
}
__device__ __forceinline__ void mma1688(float* c, uint32_t a0, uint32_t a1, uint32_t b0) {
  asm volatile("mma.sync.aligned.m16n8k8.row.col.f32.bf16.bf16.f32 {%0,%1,%2,%3}, {%4,%5}, {%6}, {%0,%1,%2,%3};"
               : "+f"(c[0]), "+f"(c[1]), "+f"(c[2]), "+f"(c[3]) : "r"(a0), "r"(a1), "r"(b0));
}
__device__ __forceinline__ void sta1(uint32_t a, uint32_t v, uint32_t bar) { asm volatile("st.async.weak.shared::cluster.mbarrier::complete_tx::bytes.b32 [%0], %1, [%2];" :: "r"(a), "r"(v), "r"(bar) : "memory"); }
__device__ __forceinline__ void sta2(uint32_t a, uint32_t v0, uint32_t v1, uint32_t bar) { asm volatile("st.async.weak.shared::cluster.mbarrier::complete_tx::bytes.v2.b32 [%0], {%1,%2}, [%3];" :: "r"(a), "r"(v0), "r"(v1), "r"(bar) : "memory"); }
__device__ __forceinline__ void sta4(uint32_t a, uint32_t v0, uint32_t v1, uint32_t v2, uint32_t v3, uint32_t bar) { asm volatile("st.async.weak.shared::cluster.mbarrier::complete_tx::bytes.v4.b32 [%0], {%1,%2,%3,%4}, [%5];" :: "r"(a), "r"(v0), "r"(v1), "r"(v2), "r"(v3), "r"(bar) : "memory"); }
__device__ __forceinline__ float bflo(uint32_t v) { return __uint_as_float(v << 16); }
__device__ __forceinline__ float bfhi(uint32_t v) { return __uint_as_float(v & 0xFFFF0000u); }
__device__ __forceinline__ void sta2f(uint32_t a, float v0, float v1, uint32_t bar) { asm volatile("st.async.weak.shared::cluster.mbarrier::complete_tx::bytes.v2.f32 [%0], {%1,%2}, [%3];" :: "r"(a), "f"(v0), "f"(v1), "r"(bar) : "memory"); }
__device__ __forceinline__ void sta4f(uint32_t a, float v0, float v1, float v2, float v3, uint32_t bar) { asm volatile("st.async.weak.shared::cluster.mbarrier::complete_tx::bytes.v4.f32 [%0], {%1,%2,%3,%4}, [%5];" :: "r"(a), "f"(v0), "f"(v1), "f"(v2), "f"(v3), "r"(bar) : "memory"); }
__device__ __forceinline__ float4 lds4f(uint32_t a) { float4 v; asm volatile("ld.shared.v4.f32 {%0,%1,%2,%3}, [%4];" : "=f"(v.x), "=f"(v.y), "=f"(v.z), "=f"(v.w) : "r"(a) : "memory"); return v; }
__device__ __forceinline__ float2 lds2f(uint32_t a) { float2 v; asm volatile("ld.shared.v2.f32 {%0,%1}, [%2];" : "=f"(v.x), "=f"(v.y) : "r"(a) : "memory"); return v; }
__device__ __forceinline__ uint4 lds4(uint32_t a) { uint4 v; asm volatile("ld.shared.v4.u32 {%0,%1,%2,%3}, [%4];" : "=r"(v.x), "=r"(v.y), "=r"(v.z), "=r"(v.w) : "r"(a) : "memory"); return v; }
__device__ __forceinline__ uint32_t lds1(uint32_t a) { uint32_t v; asm volatile("ld.shared.u32 %0, [%1];" : "=r"(v) : "r"(a) : "memory"); return v; }
__device__ __forceinline__ void stsm2(uint32_t a, uint32_t r0, uint32_t r1) { asm volatile("stmatrix.sync.aligned.m8n8.x2.shared.b16 [%0], {%1,%2};" :: "r"(a), "r"(r0), "r"(r1) : "memory"); }
__device__ __forceinline__ float rcp(float x) { float y; asm("rcp.approx.ftz.f32 %0, %1;" : "=f"(y) : "f"(x)); return y; }
__device__ __forceinline__ void sts4(uint32_t a, uint32_t v0, uint32_t v1, uint32_t v2, uint32_t v3) { asm volatile("st.shared.v4.u32 [%0], {%1,%2,%3,%4};" :: "r"(a), "r"(v0), "r"(v1), "r"(v2), "r"(v3) : "memory"); }
__device__ __forceinline__ void bulk_s2c(uint32_t dst, uint32_t src, uint32_t bytes, uint32_t bar) {
  asm volatile("cp.async.bulk.shared::cluster.shared::cta.mbarrier::complete_tx::bytes [%0], [%1], %2, [%3];" :: "r"(dst), "r"(src), "r"(bytes), "r"(bar) : "memory");
}
__device__ __forceinline__ void stg4(void* p, uint4 v) { asm volatile("st.global.v4.u32 [%0], {%1,%2,%3,%4};" :: "l"(p), "r"(v.x), "r"(v.y), "r"(v.z), "r"(v.w) : "memory"); }
__device__ __forceinline__ void red_add(uint32_t* p, uint32_t v) { asm volatile("red.relaxed.gpu.global.add.u32 [%0], %1;" :: "l"(p), "r"(v) : "memory"); }
__device__ __forceinline__ void red4f(float* p, float a, float b, float c, float d) { asm volatile("red.relaxed.gpu.global.add.v4.f32 [%0], {%1,%2,%3,%4};" :: "l"(p), "f"(a), "f"(b), "f"(c), "f"(d) : "memory"); }
__device__ __forceinline__ void wait_flag(const uint32_t* p, uint32_t target) {
  uint32_t v; int it = 0;
  while (true) {
    asm volatile("ld.acquire.gpu.global.u32 %0, [%1];" : "=r"(v) : "l"(p) : "memory");
    if (v >= target) break;
    if (++it > 4000000) __trap();
    __nanosleep(40);
  }
}
__device__ __forceinline__ void sts1(uint32_t a, uint32_t v) { asm volatile("st.shared.u32 [%0], %1;" :: "r"(a), "r"(v) : "memory"); }
__device__ __forceinline__ void bulk_g2s(uint32_t dst, const void* src, uint32_t bytes, uint32_t bar) {
  asm volatile("cp.async.bulk.shared::cluster.global.mbarrier::complete_tx::bytes [%0], [%1], %2, [%3];" :: "r"(dst), "l"(src), "r"(bytes), "r"(bar) : "memory");
}
__device__ __forceinline__ void tma2d(uint32_t dst, const CUtensorMap* m, int c0, int c1, uint32_t bar) {
  asm volatile("cp.async.bulk.tensor.2d.shared::cluster.global.mbarrier::complete_tx::bytes [%0], [%1, {%3, %4}], [%2];" :: "r"(dst), "l"((uint64_t)m), "r"(bar), "r"(c0), "r"(c1) : "memory");
}
__device__ __forceinline__ void tma5d(uint32_t dst, const CUtensorMap* m, int c0, int c4, uint32_t bar) {
  asm volatile("cp.async.bulk.tensor.5d.shared::cluster.global.mbarrier::complete_tx::bytes [%0], [%1, {%3, %5, %5, %5, %4}], [%2];" :: "r"(dst), "l"((uint64_t)m), "r"(bar), "r"(c0), "r"(c4), "r"(0) : "memory");
}
__device__ __forceinline__ void red64(void* p, uint32_t lo, uint32_t hi) { asm volatile("{\n.reg .b64 t;\nmov.b64 t, {%1,%2};\nred.relaxed.gpu.global.add.u64 [%0], t;\n}" :: "l"(p), "r"(lo), "r"(hi) : "memory"); }
__device__ __forceinline__ uint4 ld_poll(const void* p) {
  uint4 v;
  asm volatile("{\n.reg .b64 a, b;\nld.relaxed.gpu.global.v2.b64 {a, b}, [%4];\nmov.b64 {%0,%1}, a;\nmov.b64 {%2,%3}, b;\n}" : "=r"(v.x), "=r"(v.y), "=r"(v.z), "=r"(v.w) : "l"(p) : "memory");
  return v;
}
__device__ __forceinline__ uint32_t clk() { uint32_t c; asm volatile("mov.u32 %0, %%clock;" : "=r"(c) :: "memory"); return c; }
__device__ __forceinline__ float ex2(float x) { float y; asm("ex2.approx.ftz.f32 %0, %1;" : "=f"(y) : "f"(x)); return y; }

__device__ __forceinline__ void wg_rs_n32_tb1(float* d, const uint32_t* a, uint64_t b, int sc) {
  asm volatile("{\n.reg .pred p;\nsetp.ne.b32 p, %21, 0;\nwgmma.mma_async.sync.aligned.m64n32k16.f32.bf16.bf16 {%0, %1, %2, %3, %4, %5, %6, %7, %8, %9, %10, %11, %12, %13, %14, %15}, {%16, %17, %18, %19}, %20, p, 1, 1, 1;\n}\n"
    : "+f"(d[0]), "+f"(d[1]), "+f"(d[2]), "+f"(d[3]), "+f"(d[4]), "+f"(d[5]), "+f"(d[6]), "+f"(d[7]), "+f"(d[8]), "+f"(d[9]), "+f"(d[10]), "+f"(d[11]), "+f"(d[12]), "+f"(d[13]), "+f"(d[14]), "+f"(d[15])
    : "r"(a[0]), "r"(a[1]), "r"(a[2]), "r"(a[3]), "l"(b), "r"(sc));
}
__device__ __forceinline__ void wg_ss_n32_ta1_tb1(float* d, uint64_t a, uint64_t b, int sc) {
  asm volatile("{\n.reg .pred p;\nsetp.ne.b32 p, %18, 0;\nwgmma.mma_async.sync.aligned.m64n32k16.f32.bf16.bf16 {%0, %1, %2, %3, %4, %5, %6, %7, %8, %9, %10, %11, %12, %13, %14, %15}, %16, %17, p, 1, 1, 1, 1;\n}\n"
    : "+f"(d[0]), "+f"(d[1]), "+f"(d[2]), "+f"(d[3]), "+f"(d[4]), "+f"(d[5]), "+f"(d[6]), "+f"(d[7]), "+f"(d[8]), "+f"(d[9]), "+f"(d[10]), "+f"(d[11]), "+f"(d[12]), "+f"(d[13]), "+f"(d[14]), "+f"(d[15])
    : "l"(a), "l"(b), "r"(sc));
}
__device__ __forceinline__ void wg_rs_n32_tb0(float* d, const uint32_t* a, uint64_t b, int sc) {
  asm volatile("{\n.reg .pred p;\nsetp.ne.b32 p, %21, 0;\nwgmma.mma_async.sync.aligned.m64n32k16.f32.bf16.bf16 {%0, %1, %2, %3, %4, %5, %6, %7, %8, %9, %10, %11, %12, %13, %14, %15}, {%16, %17, %18, %19}, %20, p, 1, 1, 0;\n}\n"
    : "+f"(d[0]), "+f"(d[1]), "+f"(d[2]), "+f"(d[3]), "+f"(d[4]), "+f"(d[5]), "+f"(d[6]), "+f"(d[7]), "+f"(d[8]), "+f"(d[9]), "+f"(d[10]), "+f"(d[11]), "+f"(d[12]), "+f"(d[13]), "+f"(d[14]), "+f"(d[15])
    : "r"(a[0]), "r"(a[1]), "r"(a[2]), "r"(a[3]), "l"(b), "r"(sc));
}
__device__ __forceinline__ void wg_rs_n40_tb0(float* d, const uint32_t* a, uint64_t b, int sc) {
  asm volatile("{\n.reg .pred p;\nsetp.ne.b32 p, %25, 0;\nwgmma.mma_async.sync.aligned.m64n40k16.f32.bf16.bf16 {%0, %1, %2, %3, %4, %5, %6, %7, %8, %9, %10, %11, %12, %13, %14, %15, %16, %17, %18, %19}, {%20, %21, %22, %23}, %24, p, 1, 1, 0;\n}\n"
    : "+f"(d[0]), "+f"(d[1]), "+f"(d[2]), "+f"(d[3]), "+f"(d[4]), "+f"(d[5]), "+f"(d[6]), "+f"(d[7]), "+f"(d[8]), "+f"(d[9]), "+f"(d[10]), "+f"(d[11]), "+f"(d[12]), "+f"(d[13]), "+f"(d[14]), "+f"(d[15]), "+f"(d[16]), "+f"(d[17]), "+f"(d[18]), "+f"(d[19])
    : "r"(a[0]), "r"(a[1]), "r"(a[2]), "r"(a[3]), "l"(b), "r"(sc));
}
__device__ __forceinline__ void wg_rs_n8_tb1(float* d, const uint32_t* a, uint64_t b, int sc) {
  asm volatile("{\n.reg .pred p;\nsetp.ne.b32 p, %9, 0;\nwgmma.mma_async.sync.aligned.m64n8k16.f32.bf16.bf16 {%0, %1, %2, %3}, {%4, %5, %6, %7}, %8, p, 1, 1, 1;\n}\n"
    : "+f"(d[0]), "+f"(d[1]), "+f"(d[2]), "+f"(d[3])
    : "r"(a[0]), "r"(a[1]), "r"(a[2]), "r"(a[3]), "l"(b), "r"(sc));
}
__device__ __forceinline__ void wg_ss_n40_ta0_tb0(float* d, uint64_t a, uint64_t b, int sc) {
  asm volatile("{\n.reg .pred p;\nsetp.ne.b32 p, %22, 0;\nwgmma.mma_async.sync.aligned.m64n40k16.f32.bf16.bf16 {%0, %1, %2, %3, %4, %5, %6, %7, %8, %9, %10, %11, %12, %13, %14, %15, %16, %17, %18, %19}, %20, %21, p, 1, 1, 0, 0;\n}\n"
    : "+f"(d[0]), "+f"(d[1]), "+f"(d[2]), "+f"(d[3]), "+f"(d[4]), "+f"(d[5]), "+f"(d[6]), "+f"(d[7]), "+f"(d[8]), "+f"(d[9]), "+f"(d[10]), "+f"(d[11]), "+f"(d[12]), "+f"(d[13]), "+f"(d[14]), "+f"(d[15]), "+f"(d[16]), "+f"(d[17]), "+f"(d[18]), "+f"(d[19])
    : "l"(a), "l"(b), "r"(sc));
}
__device__ __forceinline__ void wg_ss_n40_ta1_tb0(float* d, uint64_t a, uint64_t b, int sc) {
  asm volatile("{\n.reg .pred p;\nsetp.ne.b32 p, %22, 0;\nwgmma.mma_async.sync.aligned.m64n40k16.f32.bf16.bf16 {%0, %1, %2, %3, %4, %5, %6, %7, %8, %9, %10, %11, %12, %13, %14, %15, %16, %17, %18, %19}, %20, %21, p, 1, 1, 1, 0;\n}\n"
    : "+f"(d[0]), "+f"(d[1]), "+f"(d[2]), "+f"(d[3]), "+f"(d[4]), "+f"(d[5]), "+f"(d[6]), "+f"(d[7]), "+f"(d[8]), "+f"(d[9]), "+f"(d[10]), "+f"(d[11]), "+f"(d[12]), "+f"(d[13]), "+f"(d[14]), "+f"(d[15]), "+f"(d[16]), "+f"(d[17]), "+f"(d[18]), "+f"(d[19])
    : "l"(a), "l"(b), "r"(sc));
}
__device__ __forceinline__ void wg_ss_n8_ta1_tb1(float* d, uint64_t a, uint64_t b, int sc) {
  asm volatile("{\n.reg .pred p;\nsetp.ne.b32 p, %6, 0;\nwgmma.mma_async.sync.aligned.m64n8k16.f32.bf16.bf16 {%0, %1, %2, %3}, %4, %5, p, 1, 1, 1, 1;\n}\n"
    : "+f"(d[0]), "+f"(d[1]), "+f"(d[2]), "+f"(d[3])
    : "l"(a), "l"(b), "r"(sc));
}

constexpr int O_WV = 0, O_WO = 81920, O_H = 163840, O_QK = 215040, O_SM = 228352, O_MISC = 230912;
constexpr int O_QM = O_QK + 1024, O_K = O_QK + 3072, O_OG = O_QK + 8192;
constexpr int SM_SLOT = 640;
constexpr int O_MAXS = O_MISC;
constexpr int O_BAR = O_MISC + 64;
constexpr int MB_XF = 0, MB_MF = 2, MB_SM = 6, MB_SX = 7, MB_OG = 8, MB_W = 9;
constexpr int O_PROF = O_BAR + 8 * 24;
constexpr int REC_SMEM = O_PROF + 128;
constexpr int B_QK = 1, B_VGO = 2, B_SISS = 3, B_PM = 4, B_PX = 5, B_XGO = 6, B_PFREE = 7, B_WG2 = 8, B_VHALF = 9, B_VDONE = 10, B_ALL = 11, B_VOWN = 11,
              B_SSENT = 12, B_SLD = 13, B_VEND = 14, B_XGO1 = 15;
#define POLL_DELAY 700
#define POLL_D0 300
#define POLL_STEP 100
#define NBUF 3
#define REG_A 208
#define REG_B 88
#define REG_C 208
#define FENCE_RX() do {} while (0)
#define STR2(x) #x
#define STR(x) STR2(x)
#define TS0(idx) do {} while (0)
#define TS(idx) do {} while (0)
#define OPC_PDL 1
#define MP_D 2
#define MP_CH 4
#define OX_POS 1
#define V_RS 4
#define V_K1 6
#define V_K2 24
#define V_K3 28

__device__ __forceinline__ void fix_red(uint8_t* p, const float* a, float sc) {
  int v0 = __float2int_rn(a[0] * sc), v1 = __float2int_rn(a[1] * sc), v2 = __float2int_rn(a[2] * sc), v3 = __float2int_rn(a[3] * sc);
  red64(p, ((uint32_t)v0 << 7) | 1u, ((uint32_t)v2 << 3) + (uint32_t)(v0 >> 25));
  red64(p + 1024, ((uint32_t)v1 << 7) | 1u, ((uint32_t)v3 << 3) + (uint32_t)(v1 >> 25));
}

template <int wg>
__device__ __forceinline__ void qk_role(const uint32_t sb, const uint32_t sb1, const uint32_t sb2, const int tid, const int w, const uint32_t rank, const uint8_t* __restrict__ ar, uint32_t* __restrict__ flag, int layer) {
    const int lane = tid & 31;
    const uint32_t bar = sb + O_BAR;
    uint32_t a[40][4];
    {
      const uint32_t la = sb + wg * 81920 + ((lane >> 4) * 8 + (lane & 7)) * 128 + (((2 * w + ((lane >> 3) & 1)) ^ (lane & 7)) << 4);
#pragma unroll
      for (int p = 0; p < 5; p++) {
        mbar_wait(bar + 8 * (MB_W + wg * 5 + p), 0);
#pragma unroll
        for (int k = 0; k < 8; k++) ldsm4t(a[p * 8 + k], la + (p * 8 + k) * 2048);
      }
    }
    bar_sync<B_ALL, 384>();
    cluster_sync();
    const uint32_t swz = (lane & 7) * 128 + (((2 * w + ((lane >> 3) & 1)) ^ (lane & 7)) << 4);
    const uint32_t ld_m = sb + O_H + (lane & 7) * 128 + (((lane >> 3) ^ (lane & 7)) << 4);

    for (int s = 0; s < NSEG; s++) {
      const uint32_t par = s & 1;
      if (wg == 0 && w == 0) TS0(0);
      if (s == 1) GT(layer * 4 + 1, 1);
      {
        float ax[16];
        const uint64_t db = mkdesc(opaque(sb) + O_H + 1024, 16, 1024, 1);
        mbar_wait(bar + 8 * MB_XF, par);
        wg_fence();
#pragma unroll
        for (int k = 0; k < 40; k++) wg_rs_n32_tb0(ax, a[k], db + (((k >> 2) * 5120 + (k & 3) * 32) >> 4), k);
        wg_commit();
        if (s > 0) bar_sync<B_PFREE, 384>();
        const uint32_t st_x = sb + (wg == 0 ? O_QK : O_K + 2048) + (lane >> 4) * 2048 + swz;
        wg_wait<0>();
        pin<16>(ax);
        if (w == 0) TS(1 + 22 * wg);
        stsm4t(st_x, pack2(ax[0], ax[1]), pack2(ax[2], ax[3]), pack2(ax[4], ax[5]), pack2(ax[6], ax[7]));
        stsm4t(st_x + 4096, pack2(ax[8], ax[9]), pack2(ax[10], ax[11]), pack2(ax[12], ax[13]), pack2(ax[14], ax[15]));
        bar_arrive<B_VOWN, 384>();
      }
      if (wg == 1 && tid == 192) { mbar_expect(bar + 8 * MB_SM, 2 * SM_SLOT + 48 + 48); mbar_expect(bar + 8 * MB_SX, 2 * 2176); }
      {
        float c0[4] = {0.f, 0.f, 0.f, 0.f}, c1[4] = {0.f, 0.f, 0.f, 0.f}, c2[4] = {0.f, 0.f, 0.f, 0.f}, c3[4] = {0.f, 0.f, 0.f, 0.f};
        uint32_t b[MP_D][2][4];
#pragma unroll
        for (int j = 0; j < 10 + MP_D - 1; j++) {
          if (j < 10) {
            const int c = j == 0 ? 9 : ((j - 1) % 3) * 3 + (j - 1) / 3;
            if (j == 0 || j % 3 == 1) { mbar_wait(bar + 8 * (MB_MF + (j + 2) / 3), par); if (wg == 0 && w == 0) TS(2 + (j + 2) / 3); }
            ldsm4(b[j % MP_D][0], ld_m + c * 5120);
            ldsm4(b[j % MP_D][1], (ld_m ^ 64) + c * 5120);
          }
          const int u = j - (MP_D - 1);
          if (u >= 0) {
            const int c = u == 0 ? 9 : ((u - 1) % 3) * 3 + (u - 1) / 3;
            mma16816(c0, a[4 * c], b[u % MP_D][0][0], b[u % MP_D][0][1]);
            mma16816(c1, a[4 * c + 1], b[u % MP_D][0][2], b[u % MP_D][0][3]);
            mma16816(MP_CH == 4 ? c2 : c0, a[4 * c + 2], b[u % MP_D][1][0], b[u % MP_D][1][1]);
            mma16816(MP_CH == 4 ? c3 : c1, a[4 * c + 3], b[u % MP_D][1][2], b[u % MP_D][1][3]);
          }
        }
        if (MP_CH == 4) {
#pragma unroll
          for (int k = 0; k < 4; k++) { c0[k] += c2[k]; c1[k] += c3[k]; }
        }
        bar_arrive<B_VGO, 384>();
        stsm2t(sb + (wg == 0 ? O_QM : O_K) + swz, pack2(c0[0] + c1[0], c0[1] + c1[1]), pack2(c0[2] + c1[2], c0[3] + c1[3]));
        fence_async();
      }
      if (wg == 0) {
        bar_sync<B_QK, 256>();
        float sv[20];
        {
          const uint64_t da = mkdesc(opaque(sb) + O_QK, 16, 1024, 1);
          const uint64_t db = mkdesc(opaque(sb) + O_K, 16, 2048, 1);
          wg_fence();
#pragma unroll
          for (int k = 0; k < 4; k++) wg_ss_n40_ta0_tb0(sv, da + 2 * k, db + 2 * k, k);
          wg_commit();
          bar_arrive<B_SISS, 256>();
          if (w == 0) TS(6);
          wg_wait<0>();
          pin<20>(sv);
        }
        constexpr float SCL = 0.07216878364870322f;
        constexpr float L2E = 1.4426950408889634f;
        const uint32_t om = O_SM + opaque(lane) * 16, om2 = O_SM + 512 + opaque(lane) * 4;
        const uint32_t m0 = pack2(sv[2], sv[3]), m1 = pack2(sv[6], sv[7]), m2 = pack2(sv[10], sv[11]), m3 = pack2(sv[14], sv[15]), m4 = pack2(sv[18], sv[19]);
        if (w == 0) {
          sta4(sb1 + om + SM_SLOT, m0, m1, m2, m3, sb1 + O_BAR + 8 * MB_SM);
          sta4(sb2 + om, m0, m1, m2, m3, sb2 + O_BAR + 8 * MB_SM);
          sta1(sb1 + om2 + SM_SLOT, m4, sb1 + O_BAR + 8 * MB_SM);
          sta1(sb2 + om2, m4, sb2 + O_BAR + 8 * MB_SM);
        }
        if (lane < 3) { const uint32_t b = mapa(sb, lane); sta1(b + O_MAXS + 48, 0u, b + O_BAR + 8 * MB_SM); }
        bar_arrive<B_SSENT, 256>();
        const uint32_t ox = O_K + w * 2048 + opaque(lane) * 16, ox2 = O_K + 8192 + opaque(lane) * 4;
        const uint32_t p0 = pack2(sv[0], sv[1]), p1 = pack2(sv[4], sv[5]), p2 = pack2(sv[8], sv[9]), p3 = pack2(sv[12], sv[13]), p4 = pack2(sv[16], sv[17]);
        if (w == 0) TS(7);
        mbar_wait(bar + 8 * MB_SM, par);
#define ACC2(k, p, u, v) { t[k] = bflo(p) + bflo(u) + bflo(v); t[k + 1] = bfhi(p) + bfhi(u) + bfhi(v); }
        if (w == 0) {
          float t[10];
          {
            const uint4 u = lds4(sb + om), v = lds4(sb + om + SM_SLOT);
            const uint32_t u4 = lds1(sb + om2), v4 = lds1(sb + om2 + SM_SLOT);
            sta4(sb1 + ox + 512, p0, p1, p2, p3, sb1 + O_BAR + 8 * MB_SX);
            sta4(sb2 + ox, p0, p1, p2, p3, sb2 + O_BAR + 8 * MB_SX);
            if (V_K2 < 24) bar_arrive<B_SLD, 256>();
            TS(8);
            ACC2(0, m0, u.x, v.x) ACC2(2, m1, u.y, v.y) ACC2(4, m2, u.z, v.z) ACC2(6, m3, u.w, v.w) ACC2(8, m4, u4, v4)
          }
          float m = fmaxf(fmaxf(fmaxf(t[0], t[1]), fmaxf(t[2], t[3])), fmaxf(fmaxf(t[4], t[5]), fmaxf(t[6], t[7])));
          m = fmaxf(m, fmaxf(t[8], t[9]));
          m = fmaxf(m, __shfl_xor_sync(~0u, m, 1));
          m = fmaxf(m, __shfl_xor_sync(~0u, m, 2));
          const float mm = m * (SCL * L2E);
#pragma unroll
          for (int k = 0; k < 10; k++) t[k] = ex2(fmaf(t[k], SCL * L2E, -mm));
          float sum = ((t[0] + t[1]) + (t[2] + t[3])) + ((t[4] + t[5]) + (t[6] + t[7])) + (t[8] + t[9]);
          sum += __shfl_xor_sync(~0u, sum, 1);
          sum += __shfl_xor_sync(~0u, sum, 2);
          const float inv = rcp(sum);
          const uint32_t ln = opaque(lane), pa = sb + O_QM + (ln & 7) * 128;
          stsm4(pa + (((ln >> 3) ^ (ln & 7)) << 4), pack2(t[0] * inv, t[1] * inv), pack2(t[2] * inv, t[3] * inv), pack2(t[4] * inv, t[5] * inv), pack2(t[6] * inv, t[7] * inv));
          stsm1(pa + ((4 ^ (ln & 7)) << 4), pack2(t[8] * inv, t[9] * inv));
          bar_arrive<B_PM, 160>();
          TS(9);
        } else {
          sta4(sb1 + ox + 512, p0, p1, p2, p3, sb1 + O_BAR + 8 * MB_SX);
          sta4(sb2 + ox, p0, p1, p2, p3, sb2 + O_BAR + 8 * MB_SX);
          if (w == 3) { sta1(sb1 + ox2 + 128, p4, sb1 + O_BAR + 8 * MB_SX); sta1(sb2 + ox2, p4, sb2 + O_BAR + 8 * MB_SX); }
          if (V_K2 < 24) bar_arrive<B_SLD, 256>();
        }
        mbar_wait(bar + 8 * MB_SX, par);
        {
          float t[10];
          const uint4 u = lds4(sb + ox), v = lds4(sb + ox + 512);
          const uint32_t u4 = lds1(sb + ox2), v4 = lds1(sb + ox2 + 128);
          ACC2(0, p0, u.x, v.x) ACC2(2, p1, u.y, v.y) ACC2(4, p2, u.z, v.z) ACC2(6, p3, u.w, v.w) ACC2(8, p4, u4, v4)
          const int ln = opaque(lane), dq = 8 * w + (ln >> 2) - 2 * (ln & 3);
#pragma unroll
          for (int k = 1; k < 5; k++) {
            if (8 * (k - 1) > dq) t[2 * k] = -1e9f / SCL;
            if (8 * (k - 1) + 1 > dq) t[2 * k + 1] = -1e9f / SCL;
          }
          float m = fmaxf(fmaxf(fmaxf(t[0], t[1]), fmaxf(t[2], t[3])), fmaxf(fmaxf(t[4], t[5]), fmaxf(t[6], t[7])));
          m = fmaxf(m, fmaxf(t[8], t[9]));
          m = fmaxf(m, __shfl_xor_sync(~0u, m, 1));
          m = fmaxf(m, __shfl_xor_sync(~0u, m, 2));
          const float mm = m * (SCL * L2E);
#pragma unroll
          for (int k = 0; k < 10; k++) t[k] = ex2(fmaf(t[k], SCL * L2E, -mm));
          float sum = ((t[0] + t[1]) + (t[2] + t[3])) + ((t[4] + t[5]) + (t[6] + t[7])) + (t[8] + t[9]);
          sum += __shfl_xor_sync(~0u, sum, 1);
          sum += __shfl_xor_sync(~0u, sum, 2);
          const float inv = rcp(sum);
          const int rr = 2 * w + (ln & 1);
          const uint32_t pa = sb + O_QK + ((ln >> 1) & 3) * 2048 + rr * 128;
          stsm4(pa + (((ln >> 3) ^ rr) << 4), pack2(t[0] * inv, t[1] * inv), pack2(t[2] * inv, t[3] * inv), pack2(t[4] * inv, t[5] * inv), pack2(t[6] * inv, t[7] * inv));
          stsm2(pa + (((4 + ((ln >> 3) & 1)) ^ rr) << 4), pack2(t[8] * inv, t[9] * inv), 0u);
          fence_async();
          bar_arrive<B_PX, 256>();
          if (w == 0) TS(10);
        }
      } else {
        bar_arrive<B_QK, 256>();
        if (w == 2) {
          bar_sync<B_VHALF, 192>();
          if (lane == 0 && s > 0) { __threadfence(); red_add(flag + (s - 1) * 48, 1); }
          __syncwarp();
        }
        if (w == 0 && s + 1 == NSEG) bar_sync<B_VHALF, 192>();
        if (w == 0 && s + 1 < NSEG) {
          if (lane == 0) mbar_expect(bar + 8 * MB_XF, 40960);
          const int ln = blockIdx.x * 2 + (lane - 16), s2 = s + 2;
          if (lane >= 16 && lane < 18 && ln < 160 && s2 < NSEG - 1) {
            const int tile = ln >> 4, off = (ln & 15) << 7;
            const uint8_t* p = ar + (s2 >> 2) * AR_GROUP + (s2 & 1) * 128 + ((s2 >> 1) & 1) * 512 + ((tile >> 2) * 8 + (tile & 3)) * 4096 +
                               (off >> 10) * 16384 + ((off >> 7) & 1) * 256 + ((off >> 8) & 3) * 1024;
            asm volatile("prefetch.global.L2 [%0];" :: "l"(p));
          }
          const bool own = lane == 9 || (uint32_t)(lane - 3 * rank) < 3u;
          bar_sync<B_VHALF, 192>();
          if (lane < 10 && own) bulk_g2s(sb + O_H + lane * 5120 + 1024, g_xn + (s + 1) * 40960 + lane * 4096, 4096, bar + 8 * MB_XF);
          bar_sync<B_VDONE, 160>();
          if (lane < 10 && !own) bulk_g2s(sb + O_H + lane * 5120 + 1024, g_xn + (s + 1) * 40960 + lane * 4096, 4096, bar + 8 * MB_XF);
        }
      }
      if (s + 1 < NSEG) bar_sync<wg == 0 ? B_XGO : B_XGO1, 256>();
    }
}

__global__ void __launch_bounds__(384, 1)
rec_kernel(const __grid_constant__ CUtensorMap tmq, const __grid_constant__ CUtensorMap tmk,
           const __grid_constant__ CUtensorMap tmv, const __grid_constant__ CUtensorMap tmo,
           const bf16* __restrict__ mem0, uint8_t* __restrict__ ar, uint32_t* __restrict__ flags, int layer) {
  extern __shared__ __align__(1024) uint8_t smem[];
  const uint32_t sb = smem_u32(smem);
  const int tid = threadIdx.x, wid = __shfl_sync(~0u, tid >> 5, 0), wg = wid >> 2, w = wid & 3, lane = tid & 31, g = lane >> 2, i4 = lane & 3;
  uint32_t rank; asm("mov.u32 %0, %%cluster_ctarank;" : "=r"(rank));
  const int head = blockIdx.x / 3;
  const int e0 = head * DH + rank * 64;
  const uint32_t bar = sb + O_BAR;
  const uint32_t r1 = rank == 2 ? 0 : rank + 1, r2 = rank == 0 ? 2 : rank - 1;
  const uint32_t sb1 = mapa(sb, r1), sb2 = mapa(sb, r2);

  asm volatile("griddepcontrol.launch_dependents;");
  GT(layer * 4 + 1, 0);
  if (tid == 0) {
    for (int k = 0; k < 24; k++) mbar_init(bar + 8 * k, 1);
    asm volatile("fence.mbarrier_init.release.cluster;" ::: "memory");
    fence_async();
    for (int p = 0; p < 5; p++) {
      mbar_expect(bar + 8 * (MB_W + p), 16384);
      tma5d(sb + p * 16384, &tmq, e0, p * 8, bar + 8 * (MB_W + p));
      mbar_expect(bar + 8 * (MB_W + 5 + p), 16384);
      tma5d(sb + 81920 + p * 16384, &tmk, e0, p * 8, bar + 8 * (MB_W + 5 + p));
    }
    mbar_expect(bar + 8 * MB_XF, 40960);
    for (int c = 0; c < 10; c++) bulk_g2s(sb + O_H + c * 5120 + 1024, g_xn + c * 4096, 4096, bar + 8 * MB_XF);
  }
  __syncthreads();

  if (wg == 0) {
    asm volatile("setmaxnreg.inc.sync.aligned.u32 " STR(REG_A) ";");
    qk_role<0>(sb, sb1, sb2, tid, w, rank, ar, flags + (e0 >> 10) * 8, layer);
  } else if (wg == 1) {
    asm volatile("setmaxnreg.inc.sync.aligned.u32 " STR(REG_C) ";");
    qk_role<1>(sb, sb1, sb2, tid, w, rank, ar, flags + (e0 >> 10) * 8, layer);
  } else {
    asm volatile("setmaxnreg.dec.sync.aligned.u32 " STR(REG_B) ";");
    bar_sync<B_ALL, 384>();
    if (tid == 256) {
      fence_async();
      mbar_expect(bar + 8 * (MB_W + 11), 81920);
      for (int p = 0; p < 5; p++) tma5d(sb + O_WV + p * 16384, &tmv, e0, p * 8, bar + 8 * (MB_W + 11));
      mbar_expect(bar + 8 * (MB_W + 12), 81920);
      tma2d(sb + O_WO + 73728, &tmo, 576, e0, bar + 8 * (MB_W + 12));
      for (int p = 0; p < 9; p++) tma2d(sb + O_WO + p * 8192, &tmo, (rank * 3 + p / 3) * 64, head * DH + (p % 3) * 64, bar + 8 * (MB_W + 12));
    }
    float cbound;
    {
      float mx = 0.f;
      for (int c = lane; c < DM; c += 32) mx = fmaxf(mx, g_norm[c]);
#pragma unroll
      for (int o = 16; o; o >>= 1) mx = fmaxf(mx, __shfl_xor_sync(~0u, mx, o));
      cbound = sqrtf(mx) * sqrtf(g_norm[640]) * (25.2982213f * 1.1f);
    }
    cluster_sync();
    const int t = tid & 127;
    const int myT = w == 0 ? 9 : rank * 3 + w - 1;
    const int tok = 2 * ((lane >> 1) & 3) + ((lane >> 3) & 1);
    const uint32_t fw_off = O_H + myT * 5120 + tok * 128 + (((2 * (lane >> 4) + (lane & 1)) ^ tok) << 4);
    const uint32_t prod_off = (w >> 1) * 16384 + (w & 1) * 2048 + ((g >> 1) & 1) * 256 + (i4 * 2 + (g >> 2)) * 16 + (g & 1) * 8;
    const uint32_t cons_off = ((myT >> 2) * 8 + (myT & 3)) * 4096 + (lane >> 3) * 1024 + (lane & 7) * 16;
    uint32_t tile_off[3];
#pragma unroll
    for (int k = 0; k < 3; k++) { const int T = rank * 3 + k; tile_off[k] = ((T >> 2) * 8 + (T & 3)) * 4096; }
    constexpr uint32_t T9_OFF = 17 * 4096;

    auto forward = [&](const uint32_t* p) {
      const uint32_t o = opaque(fw_off), bo = O_BAR + 8 * (MB_MF + w);
      sts4(sb + o, p[0], p[1], p[2], p[3]);
      sts4(sb + (o ^ 64), p[4], p[5], p[6], p[7]);
      fence_async();
      __syncwarp();
      if (lane == 0) {
        const uint32_t c = O_H + myT * 5120;
        if (w > 0) { bulk_s2c(sb1 + c, sb + c, 1024, sb1 + bo); bulk_s2c(sb2 + c, sb + c, 1024, sb2 + bo); mbar_expect(sb + bo, 2048); }
        else mbar_arrive(sb + bo);
      }
      uint32_t mx = 0;
#pragma unroll
      for (int k = 0; k < 8; k++) mx = __vmaxu2(mx, p[k] & 0x7FFF7FFFu);
      mx = max(mx & 0xFFFFu, mx >> 16);
      mx = __reduce_max_sync(~0u, mx);
      if (lane < 3) { const uint32_t b = mapa(sb, lane); sta1(b + O_MAXS + (rank * 4 + w) * 4, mx << 16, b + O_BAR + 8 * MB_SM); }
    };
    {
      if (t == 4) mbar_expect(bar + 8 * MB_OG, 2048);
      const uint32_t* mp = (const uint32_t*)(mem0 + tok * DM + myT * 64 + 16 * (lane >> 4) + 4 * (lane & 1));
      const uint32_t p[8] = {mp[0], mp[4], mp[1], mp[5], mp[16], mp[20], mp[17], mp[21]};
      forward(p);
    }
    mbar_wait(bar + 8 * (MB_W + 11), 0);
    mbar_wait(bar + 8 * (MB_W + 12), 0);

    const uint32_t la_w = sb + ((lane >> 4) * 8 + (lane & 7)) * 128 + (((2 * w + ((lane >> 3) & 1)) ^ (lane & 7)) << 4);
    for (int s = 0; s < NSEG; s++) {
      const uint32_t par = s & 1;
      uint32_t vf[10];
      uint32_t pm[5];
      float sc, isc;
      {
        float av[20];
        uint32_t af[V_RS > 0 ? V_RS : 1][4];
        const uint32_t sbo = opaque(sb);
        const uint64_t da = mkdesc(sbo + O_WV, 1024, 1024, 1), db = mkdesc(sbo + O_H, 16, 1024, 1);
#pragma unroll
        for (int k = 0; k < V_RS; k++) ldsm4t(af[k], la_w + O_WV + r1 * 24576 + k * 2048);
        bar_sync<B_VOWN, 384>();
        wg_fence();
#pragma unroll
        for (int k = 0; k < 4; k++) wg_ss_n40_ta1_tb0(av, da + (36 + k) * 128, db + ((9 * 5120 + k * 32) >> 4), k);
        {
          const uint64_t da0 = da + rank * 1536, db0 = db + rank * 960;
#pragma unroll
          for (int k = 0; k < 12; k++) wg_ss_n40_ta1_tb0(av, da0 + k * 128, db0 + (((k >> 2) * 5120 + (k & 3) * 32) >> 4), 1);
        }
        wg_commit();
        if (w == 0) TS(29);
        const uint64_t da1 = da + r1 * 1536, db1 = db + r1 * 960, da2 = da + r2 * 1536, db2 = db + r2 * 960;
#define VREST(k0, k1) _Pragma("unroll") for (int k = k0; k < k1; k++) \
          wg_ss_n40_ta1_tb0(av, (k < 12 ? da1 : da2) + (k % 12) * 128, (k < 12 ? db1 : db2) + ((((k % 12) >> 2) * 5120 + (k & 3) * 32) >> 4), 1);
        bar_sync<B_VGO, 384>();
        wg_wait<0>();
        wg_fence();
#pragma unroll
        for (int k = 0; k < V_RS; k++) wg_rs_n40_tb0(av, af[k], db1 + (((k >> 2) * 5120 + (k & 3) * 32) >> 4), 1);
        if (w == 0) TS(11);
        bar_sync<B_SISS, 256>();
        wg_fence();
        VREST(V_RS, V_K1)
        bar_sync<B_SSENT, 256>();
        bar_arrive<B_VHALF, 192>();
        wg_fence();
        VREST(V_K1, V_K2)
        if (V_K2 < 24) {
          bar_sync<B_SLD, 256>();
          wg_fence();
          VREST(V_K2, 24)
        }
        wg_commit();
        if (w == 0) TS(12);
        const uint32_t ln = opaque(lane), pa = sb + O_QM + (ln & 7) * 128;
        wg_wait<0>();
        pin<20>(av);
        if (s + 1 < NSEG) bar_arrive<B_VDONE, 160>();
        if (w == 0) TS(13);
#pragma unroll
        for (int k = 0; k < 10; k++) vf[k] = pack2(av[2 * k], av[2 * k + 1]);
        bar_sync<B_PM, 160>();
        ldsm4(pm, pa + (((ln >> 3) ^ (ln & 7)) << 4));
        ldsm1(pm[4], pa + ((4 ^ (ln & 7)) << 4));
      }
      uint8_t* arp = ar + (s >> 2) * AR_GROUP + (s & 1) * 128 + ((s >> 1) & 1) * 512;
      uint32_t t1 = 0;
      if (s + 1 < NSEG) {
        {
          float o0[4] = {0.f, 0.f, 0.f, 0.f}, o1[4] = {0.f, 0.f, 0.f, 0.f};
          mma16816(o0, vf, pm[0], pm[1]);
          mma16816(o1, vf + 4, pm[2], pm[3]);
          mma1688(o0, vf[8], vf[9], pm[4]);
          const uint32_t mxl = lds1(sb + O_MAXS + 4 * min(opaque(lane), 11u));
          const uint32_t p0 = pack2(o0[0] + o1[0], o0[1] + o1[1]), p1 = pack2(o0[2] + o1[2], o0[3] + o1[3]);
          const uint32_t o = O_OG + rank * 2048 + w * 256 + opaque(lane) * 4;
          sta1(sb1 + o, p0, sb1 + O_BAR + 8 * MB_OG); sta1(sb1 + o + 128, p1, sb1 + O_BAR + 8 * MB_OG);
          sta1(sb2 + o, p0, sb2 + O_BAR + 8 * MB_OG); sta1(sb2 + o + 128, p1, sb2 + O_BAR + 8 * MB_OG);
          sts1(sb + o, p0); sts1(sb + o + 128, p1);
          fence_async();
          bar_sync<B_WG2, 128>();
          const float b = cbound * fmaxf(1.f, __uint_as_float(__reduce_max_sync(~0u, mxl)));
          const uint32_t eb = min(max(__float_as_uint(b) >> 23, 27u), 254u);
          sc = __uint_as_float((280u - eb) << 23);
          isc = __uint_as_float((eb - 26u) << 23);
        }
        float c9[4], ca[4], cb[4], cc[4];
        uint8_t* pp = arp + opaque(prod_off);
        const uint32_t sbo = opaque(sb);
        const uint64_t da = mkdesc(sbo + O_WO, 1024, 1024, 1), db = mkdesc(sbo + O_OG, 128, 128, 0);
        const uint64_t da0 = da + rank * 512, db0 = db + rank * 128;
        const uint64_t da1 = da + r1 * 512, db1 = db + r1 * 128;
        const uint64_t da2 = da + r2 * 512, db2 = db + r2 * 128;
        wg_fence();
#pragma unroll
        for (int k = 0; k < 4; k++) wg_ss_n8_ta1_tb1(c9, da + 4608 + k * 128, db0 + k * 16, k);
        wg_commit();
        if (w == 0) TS(14);
#pragma unroll
        for (int k = 0; k < 4; k++) wg_ss_n8_ta1_tb1(ca, da0 + k * 128, db0 + k * 16, k);
#pragma unroll
        for (int k = 0; k < 4; k++) wg_ss_n8_ta1_tb1(cb, da0 + 1536 + k * 128, db0 + k * 16, k);
#pragma unroll
        for (int k = 0; k < 4; k++) wg_ss_n8_ta1_tb1(cc, da0 + 3072 + k * 128, db0 + k * 16, k);
        wg_commit();
        wg_wait<1>();
        pin<4>(c9);
        fix_red(pp + T9_OFF, c9, sc);
        mbar_wait(bar + 8 * MB_OG, par);
        FENCE_RX();
        wg_fence();
#pragma unroll
        for (int k = 0; k < 4; k++) wg_ss_n8_ta1_tb1(ca, da1 + k * 128, db1 + k * 16, 1);
        if (w == 0) TS(15);
#pragma unroll
        for (int k = 0; k < 4; k++) wg_ss_n8_ta1_tb1(ca, da2 + k * 128, db2 + k * 16, 1);
        wg_commit();
#pragma unroll
        for (int k = 0; k < 4; k++) wg_ss_n8_ta1_tb1(cb, da1 + 1536 + k * 128, db1 + k * 16, 1);
#pragma unroll
        for (int k = 0; k < 4; k++) wg_ss_n8_ta1_tb1(cb, da2 + 1536 + k * 128, db2 + k * 16, 1);
        wg_commit();
        wg_wait<1>();
        pin<4>(ca);
        fix_red(pp + tile_off[0], ca, sc);
        if (w == 0) TS(16);
        wg_fence();
#pragma unroll
        for (int k = 0; k < 4; k++) wg_ss_n8_ta1_tb1(cc, da1 + 3072 + k * 128, db1 + k * 16, 1);
#pragma unroll
        for (int k = 0; k < 4; k++) wg_ss_n8_ta1_tb1(cc, da2 + 3072 + k * 128, db2 + k * 16, 1);
        wg_commit();
        wg_wait<1>();
        pin<4>(cb);
        fix_red(pp + tile_off[1], cb, sc);
        wg_wait<0>();
        pin<4>(cc);
        fix_red(pp + tile_off[2], cc, sc);
        t1 = clk();
        bar_arrive<B_XGO1, 256>();
        bar_arrive<B_XGO, 256>();
        if (w == 0) TS(17);
      }
      uint4 oq0, oq1;
      uint8_t* op;
      {
        float ox[16];
        const uint32_t vz[4] = {vf[8], vf[9], 0u, 0u};
        const uint64_t dp = mkdesc(opaque(sb) + O_QK, 16, 2048, 1);
        bar_sync<B_PX, 256>();
        wg_fence();
        wg_rs_n32_tb0(ox, vf, dp, 0);
        wg_rs_n32_tb0(ox, vf + 4, dp + 2, 1);
        wg_rs_n32_tb0(ox, vz, dp + 4, 1);
        wg_commit();
        const uint32_t ln = opaque(lane);
        op = g_ot + (size_t)s * (HE * 64) + (e0 + 16 * w) * 64 + (ln & 3) * 128 + (ln >> 2) * 16;
        wg_wait<0>();
        pin<16>(ox);
        if (s + 1 < NSEG) bar_arrive<B_PFREE, 384>();
        oq0 = make_uint4(pack2(ox[0], ox[1]), pack2(ox[4], ox[5]), pack2(ox[8], ox[9]), pack2(ox[12], ox[13]));
        oq1 = make_uint4(pack2(ox[2], ox[3]), pack2(ox[6], ox[7]), pack2(ox[10], ox[11]), pack2(ox[14], ox[15]));
        if (OX_POS == 0 || s + 1 == NSEG) { stg4(op, oq0); stg4(op + 512, oq1); }
        if (w == 0) TS(28);
      }
      if (s + 1 < NSEG) {
        if (t == 4) mbar_expect(bar + 8 * MB_OG, 2048);
        const uint8_t* cp = arp + opaque(cons_off);
        const uint32_t need = w == 0 ? 96 : 32;
        const int dly = w == 0 ? POLL_D0 : POLL_DELAY - (3 - w) * POLL_STEP;
        uint4 y[4];
        int it = 0;
        while ((int)(clk() - t1) < dly) {}
        if (w == 3) TS(18);
        while (true) {
          y[0] = ld_poll(cp); y[1] = ld_poll(cp + 256); y[2] = ld_poll(cp + 16384); y[3] = ld_poll(cp + 16384 + 256);
          if (OX_POS == 1 && it == 0) { stg4(op, oq0); stg4(op + 512, oq1); }
          const uint32_t bad = (y[0].x ^ need) | (y[0].z ^ need) | (y[1].x ^ need) | (y[1].z ^ need) | (y[2].x ^ need) | (y[2].z ^ need) | (y[3].x ^ need) | (y[3].z ^ need);
          if (!__any_sync(~0u, (bad & 127u) != 0)) break;
          if (++it > 2000000) __trap();
        }
        uint32_t p[8];
#pragma unroll
        for (int k = 0; k < 4; k++) {
          const float l0 = (float)((int)__funnelshift_r(y[k].x, y[k].y, 3) >> 4) * isc, h0 = (float)((int)(y[k].y + 4u) >> 3) * isc;
          const float l1 = (float)((int)__funnelshift_r(y[k].z, y[k].w, 3) >> 4) * isc, h1 = (float)((int)(y[k].w + 4u) >> 3) * isc;
          p[2 * k] = pack2(l0, l1); p[2 * k + 1] = pack2(h0, h1);
        }
        TS(19 + w);
        forward(p);
        if (OX_POS == 2) { stg4(op, oq0); stg4(op + 512, oq1); }
      }
    }
    bar_sync<B_WG2, 128>();
    if (t == 0) { __threadfence(); red_add(flags + (e0 >> 10) * 8 + (NSEG - 1) * 48, 1); }
    __syncwarp();
  }
  cluster_sync();
  GT(layer * 4 + 1, 2);
}

constexpr int P_B = 0, P_A = 131072, P_BAR = 196608, OPC_SMEM = P_BAR + 256;
constexpr int OP_KR = 48;

__global__ void __launch_bounds__(384, 1)
opc_kernel(const __grid_constant__ CUtensorMap tmo, uint32_t* __restrict__ flags, float* __restrict__ acc,
           float* __restrict__ xres, uint8_t* __restrict__ xa, bf16* __restrict__ out) {
  const int layer = out != nullptr;
  GT(layer * 4 + 2, 0);
  extern __shared__ __align__(1024) uint8_t smem[];
  const uint32_t sb = smem_u32(smem);
  const int tid = threadIdx.x, wid = __shfl_sync(~0u, tid >> 5, 0), wg = wid >> 2, w = wid & 3, lane = tid & 31;
  const uint32_t bar = sb + P_BAR;
  if (blockIdx.x < 30) {
    const int cg = blockIdx.x % 5, kg = blockIdx.x / 5;
    if (tid == 0) {
      for (int k = 0; k < 16; k++) mbar_init(bar + 8 * k, (k == 8 || k == 9) ? 8 : 1);
      fence_async();
      mbar_expect(bar + 80, 131072);
      for (int p = 0; p < 16; p++) tma2d(sb + P_B + p * 8192, &tmo, cg * 128 + (p >> 3) * 64, kg * 1024 + (p & 7) * 64, bar + 80);
      mbar_expect(bar + 96, 65536);
      for (int p = 0; p < 8; p++) tma2d(sb + P_A + p * 8192, &tmo, cg * 128 + (p >> 2) * 64, kg * 1024 + 768 + (p & 3) * 64, bar + 96);
    }
    __syncthreads();
    if (wg < 2) {
      asm volatile("setmaxnreg.inc.sync.aligned.u32 240;");
      uint32_t a[OP_KR][4];
      const uint32_t la = sb + P_B + ((lane >> 4) * 8 + (lane & 7)) * 128 + (((2 * w + ((lane >> 3) & 1)) ^ (lane & 7)) << 4);
      mbar_wait(bar + 80, 0);
#pragma unroll
      for (int k = 0; k < 32; k++) ldsm4t(a[k], la + wg * 65536 + k * 2048);
      bar_sync<1, 256>();
      if (tid == 0) {
        fence_async();
        mbar_expect(bar + 88, 65536);
        for (int p = 0; p < 8; p++) tma2d(sb + P_B + p * 8192, &tmo, cg * 128 + (p >> 2) * 64, kg * 1024 + 512 + (p & 3) * 64, bar + 88);
      }
      mbar_wait(bar + 88, 0);
#pragma unroll
      for (int k = 0; k < 16; k++) ldsm4t(a[32 + k], la + wg * 32768 + k * 2048);
      fence_async();
      bar_arrive<2, 288>();
      mbar_wait(bar + 96, 0);
      float* ap = acc + (cg * 8 + wg * 4 + w) * 512 + lane * 4;
      for (int s = 0; s < NSEG; s++) {
        const int buf = s & 1;
        const uint32_t par = (s >> 1) & 1;
        float d[16];
        const uint32_t sbo = opaque(sb);
        const uint64_t db = mkdesc(sbo + P_B + buf * 65536, 512, 128, 0), da = mkdesc(sbo + P_A + wg * 32768, 1024, 1024, 1);
#pragma unroll
        for (int q = 0; q < 4; q++) {
          mbar_wait(bar + 8 * (buf * 4 + q), par);
          wg_fence();
#pragma unroll
          for (int k = 16 * q; k < 16 * q + 16; k++) {
            if (k < OP_KR) wg_rs_n32_tb1(d, a[k < OP_KR ? k : 0], db + k * 64, k);
            else wg_ss_n32_ta1_tb1(d, da + (k - OP_KR) * 128, db + k * 64, 1);
          }
        }
        wg_commit();
        wg_wait<0>();
        pin<16>(d);
        if (lane == 0) mbar_arrive(bar + 8 * (8 + buf));
        float* p = ap + s * (32 * DM);
        red4f(p, d[0], d[1], d[4], d[5]);
        red4f(p + 128, d[8], d[9], d[12], d[13]);
        red4f(p + 256, d[2], d[3], d[6], d[7]);
        red4f(p + 384, d[10], d[11], d[14], d[15]);
        bar_sync<1, 256>();
        if (tid == 0) { __threadfence(); red_add(flags + FL_B + s * 8, 1); }
        __syncwarp();
      }
    } else {
      asm volatile("setmaxnreg.dec.sync.aligned.u32 24;");
      if (w == 0) {
        bar_sync<2, 288>();
        if (lane == 0) {
          for (int s = 0; s < NSEG; s++) {
            const int buf = s & 1;
            if (s >= 2) mbar_wait(bar + 8 * (8 + buf), ((s >> 1) & 1) ^ 1);
            wait_flag(flags + FL_A + s * 48 + kg * 8, 16);
            asm volatile("fence.proxy.async;" ::: "memory");
            for (int q = 0; q < 4; q++) {
              mbar_expect(bar + 8 * (buf * 4 + q), 16384);
              bulk_g2s(sb + P_B + buf * 65536 + q * 16384, g_ot + (size_t)s * (HE * 64) + kg * 65536 + q * 16384, 16384, bar + 8 * (buf * 4 + q));
            }
          }
        }
        __syncwarp();
      }
    }
  } else {
    constexpr int LD = 644;
    float* xs = (float*)smem;
    for (int s = blockIdx.x - 30; s < NSEG; s += 6) {
      float2 r[3][10];
#pragma unroll
      for (int j = 0; j < 3; j++) {
        const int row = wid + 12 * j;
        if (row < 32) {
#pragma unroll
          for (int k = 0; k < 10; k++) r[j][k] = __ldcg((const float2*)(xres + (s * 32 + row) * DM + k * 64 + lane * 2));
        }
      }
      if (tid == 0) wait_flag(flags + FL_B + s * 8, 30);
      __syncthreads();
      if (wid < 10) {
        float4 v[16];
#pragma unroll
        for (int k = 0; k < 16; k++) v[k] = __ldcg((const float4*)(acc + s * (32 * DM) + (wid * 16 + k) * 128 + lane * 4));
#pragma unroll
        for (int k = 0; k < 16; k++) {
          const int col = (wid * 4 + (k >> 2)) * 16 + ((k >> 1) & 1) * 8 + (lane >> 2), t0 = (k & 1) * 16 + (lane & 3) * 2;
          xs[t0 * LD + col] = v[k].x; xs[(t0 + 1) * LD + col] = v[k].y; xs[(t0 + 8) * LD + col] = v[k].z; xs[(t0 + 9) * LD + col] = v[k].w;
        }
      }
      __syncthreads();
#pragma unroll
      for (int j = 0; j < 3; j++) {
        const int row = wid + 12 * j, tk = s * 32 + row;
        if (row < 32) {
          float sum = 0.f;
#pragma unroll
          for (int k = 0; k < 10; k++) {
            const float2 u = *(const float2*)(xs + row * LD + k * 64 + lane * 2);
            r[j][k].x += u.x; r[j][k].y += u.y; sum += r[j][k].x + r[j][k].y;
          }
          if (out) {
#pragma unroll
            for (int k = 0; k < 10; k++) *(uint32_t*)(out + tk * DM + k * 64 + lane * 2) = pack2(r[j][k].x, r[j][k].y);
          } else {
#pragma unroll
            for (int k = 0; k < 10; k++) *(float2*)(xres + tk * DM + k * 64 + lane * 2) = r[j][k];
#pragma unroll
            for (int o = 16; o; o >>= 1) sum += __shfl_xor_sync(~0u, sum, o);
            const float m = sum * (1.f / DM);
            float q = 0.f;
#pragma unroll
            for (int k = 0; k < 10; k++) { r[j][k].x -= m; r[j][k].y -= m; q += r[j][k].x * r[j][k].x + r[j][k].y * r[j][k].y; }
#pragma unroll
            for (int o = 16; o; o >>= 1) q += __shfl_xor_sync(~0u, q, o);
            const float rs = rsqrtf(q * (1.f / DM) + 1e-5f);
#pragma unroll
            for (int k = 0; k < 10; k++)
              *(uint32_t*)(xa + ((tk >> 7) * 10 + k) * 16384 + (tk & 127) * 128 + (((lane >> 2) ^ (tk & 7)) << 4) + (lane & 3) * 4) = pack2(r[j][k].x * rs, r[j][k].y * rs);
          }
        }
      }
      __syncthreads();
    }
  }
  GT(layer * 4 + 2, 1);
  asm volatile("griddepcontrol.wait;" ::: "memory");
  GT(layer * 4 + 2, 2);
}

__global__ void k_norms(const bf16* __restrict__ wv, const bf16* __restrict__ wo) {
  if (blockIdx.x < 96) {
    const int c = threadIdx.x * 2;
    float s0 = 0.f, s1 = 0.f;
    for (int r = 0; r < 64; r++) { float2 v = __bfloat1622float2(*(const __nv_bfloat162*)(wo + (blockIdx.x * 64 + r) * DM + c)); s0 += v.x * v.x; s1 += v.y * v.y; }
    atomicAdd(&g_norm[c], s0); atomicAdd(&g_norm[c + 1], s1);
  } else {
    const int b = blockIdx.x - 96;
    float s = 0.f;
    for (int r = 0; r < 64; r++) { float2 v = __bfloat1622float2(*(const __nv_bfloat162*)(wv + (b * 64 + r) * DM + threadIdx.x * 2)); s += v.x * v.x + v.y * v.y; }
    for (int o = 16; o; o >>= 1) s += __shfl_xor_sync(~0u, s, o);
    if ((threadIdx.x & 31) == 0) atomicAdd(&g_norm[640], s);
  }
}
__global__ void k_cvt_in(const bf16* __restrict__ x) { int i = blockIdx.x * blockDim.x + threadIdx.x; g_x[i] = __bfloat162float(x[i]); }
__global__ void k_cvt_out(bf16* __restrict__ o) { int i = blockIdx.x * blockDim.x + threadIdx.x; o[i] = __float2bfloat16(g_x[i]); }
__global__ void k_ln(int mode) {
  const int row = blockIdx.x * 8 + (threadIdx.x >> 5), lane = threadIdx.x & 31;
  float v[20]; float s = 0.f;
  for (int k = 0; k < 10; k++) { float2 t = *(const float2*)(g_x + row * DM + k * 64 + lane * 2); v[2 * k] = t.x; v[2 * k + 1] = t.y; s += t.x + t.y; }
  for (int o = 16; o; o >>= 1) s += __shfl_xor_sync(~0u, s, o);
  const float m = s * (1.f / DM); float q = 0.f;
  for (int k = 0; k < 20; k++) { v[k] -= m; q += v[k] * v[k]; }
  for (int o = 16; o; o >>= 1) q += __shfl_xor_sync(~0u, q, o);
  const float r = rsqrtf(q * (1.f / DM) + 1e-5f);
  for (int k = 0; k < 10; k++) {
    const uint32_t p = pack2(v[2 * k] * r, v[2 * k + 1] * r);
    if (mode == 0) *(uint32_t*)(g_xa + row * DM + k * 64 + lane * 2) = p;
    else { const int pj = (lane & 24) + 2 * (lane & 3) + ((lane >> 2) & 1);
      *(uint32_t*)(g_xn + (row >> 5) * 40960 + k * 4096 + (row & 31) * 128 + (((pj >> 2) ^ (row & 7)) << 4) + (pj & 3) * 4) = p; }
  }
}
__global__ void k_gemm(const bf16* __restrict__ A, const bf16* __restrict__ B, float* __restrict__ C, int N, int K, int amode, int accum) {
  __shared__ float As[32][65], Bs[32][64];
  const int tx = threadIdx.x & 15, ty = threadIdx.x >> 4, m0 = blockIdx.y * 64, n0 = blockIdx.x * 64;
  float acc[4][4] = {};
  for (int k0 = 0; k0 < K; k0 += 32) {
    for (int e = threadIdx.x; e < 2048; e += 256) {
      if (amode == 0) { int m = e >> 5, k = e & 31; As[k][m] = __bfloat162float(A[(size_t)(m0 + m) * K + k0 + k]); }
      else { int k = e >> 6, m = e & 63, he = k0 + k; As[k][m] = __bfloat162float(*(const bf16*)(g_ot + (size_t)blockIdx.y * (HE * 128) + he * 128 + (((m >> 3) ^ (he & 7)) << 4) + (m & 7) * 2)); }
      int k = e >> 6, n = e & 63; Bs[k][n] = __bfloat162float(B[(size_t)(k0 + k) * N + n0 + n]);
    }
    __syncthreads();
    for (int k = 0; k < 32; k++) {
      float a[4], b[4];
      for (int r = 0; r < 4; r++) { a[r] = As[k][ty * 4 + r]; b[r] = Bs[k][tx * 4 + r]; }
      for (int r = 0; r < 4; r++) for (int c = 0; c < 4; c++) acc[r][c] += a[r] * b[c];
    }
    __syncthreads();
  }
  for (int r = 0; r < 4; r++) for (int c = 0; c < 4; c++) {
    float* p = C + (size_t)(m0 + ty * 4 + r) * N + n0 + tx * 4 + c;
    *p = accum ? *p + acc[r][c] : acc[r][c];
  }
}
__device__ __forceinline__ float phi(float t) { return (t > 0.f ? t + 1.f : __expf(t)) + 1e-6f; }
__global__ void k_kv(float* kv) {
  const int h = blockIdx.x, e = threadIdx.x / 20, d = threadIdx.x % 20;
  float s = 0.f;
  for (int t = blockIdx.y * 128; t < blockIdx.y * 128 + 128; t++) {
    const float pk = phi(g_qkv[t * 1920 + 640 + h * 20 + d]);
    s += pk * (e < 20 ? g_qkv[t * 1920 + 1280 + h * 20 + e] : 1.f);
  }
  atomicAdd(&kv[(h * 21 + e) * 20 + d], s);
}
__global__ void k_lo(const float* kv) {
  const int t = blockIdx.x, c = threadIdx.x, h = c / 20, e = c % 20;
  float num = 0.f, den = 0.f;
  for (int d = 0; d < 20; d++) { const float pq = phi(g_qkv[t * 1920 + h * 20 + d]); num += pq * kv[(h * 21 + e) * 20 + d]; den += pq * kv[(h * 21 + 20) * 20 + d]; }
  g_oa[t * DM + c] = __float2bfloat16(num / (den + 1e-6f));
}

typedef CUresult (*EncodeFn)(CUtensorMap*, CUtensorMapDataType, cuuint32_t, void*, const cuuint64_t*, const cuuint64_t*, const cuuint32_t*,
                             const cuuint32_t*, CUtensorMapInterleave, CUtensorMapSwizzle, CUtensorMapL2promotion, CUtensorMapFloatOOBfill);
static void make_map(EncodeFn fn, CUtensorMap* m, const void* p, uint64_t cols, uint64_t rows, uint32_t bc, uint32_t br) {
  cuuint64_t dims[2] = {cols, rows}; cuuint64_t strides[1] = {cols * 2}; cuuint32_t box[2] = {bc, br}; cuuint32_t es[2] = {1, 1};
  fn(m, CU_TENSOR_MAP_DATA_TYPE_BFLOAT16, 2, (void*)p, dims, strides, box, es, CU_TENSOR_MAP_INTERLEAVE_NONE, CU_TENSOR_MAP_SWIZZLE_128B,
     CU_TENSOR_MAP_L2_PROMOTION_L2_128B, CU_TENSOR_MAP_FLOAT_OOB_FILL_NONE);
}

static void make_map_perm(EncodeFn fn, CUtensorMap* m, const void* p) {
  cuuint64_t dims[5] = {HE, 2, 2, 4, 40}; const cuuint64_t r = HE * 2; cuuint64_t strides[4] = {r, 8 * r, 2 * r, 16 * r};
  cuuint32_t box[5] = {64, 2, 2, 4, 8}; cuuint32_t es[5] = {1, 1, 1, 1, 1};
  fn(m, CU_TENSOR_MAP_DATA_TYPE_BFLOAT16, 5, (void*)p, dims, strides, box, es, CU_TENSOR_MAP_INTERLEAVE_NONE, CU_TENSOR_MAP_SWIZZLE_128B,
     CU_TENSOR_MAP_L2_PROMOTION_L2_128B, CU_TENSOR_MAP_FLOAT_OOB_FILL_NONE);
}

extern "C" void kernel_launch(void* const* d_in, const int* in_sizes, int n_in, void* d_out, int out_size) {
  const bf16* x = (const bf16*)d_in[0];
  const bf16* wqkv = (const bf16*)d_in[1];
  const bf16* wo_a = (const bf16*)d_in[2];
  const bf16* mem0 = (const bf16*)d_in[4];
  const bf16* Wq = (const bf16*)d_in[5];
  const bf16* Wk = (const bf16*)d_in[6];
  const bf16* Wv = (const bf16*)d_in[7];
  const bf16* Wo = (const bf16*)d_in[8];
  cudaStream_t st = cudaStreamPerThread;

  static EncodeFn enc = nullptr;
  static uint8_t *p_ar, *p_xt; static uint32_t* p_flags; static float* p_acc; static float *p_norm, *p_kv, *p_x, *p_qkv; static bf16 *p_xa, *p_oa;
  if (!enc) {
    cudaDriverEntryPointQueryResult qr;
    void* fn = nullptr;
    cudaGetDriverEntryPoint("cuTensorMapEncodeTiled", &fn, cudaEnableDefault, &qr);
    enc = (EncodeFn)fn;
    cudaFuncSetAttribute(rec_kernel, cudaFuncAttributeMaxDynamicSharedMemorySize, REC_SMEM);
    cudaGetSymbolAddress((void**)&p_ar, g_ar); p_ar = (uint8_t*)(((uintptr_t)p_ar + 32767) & ~(uintptr_t)32767);
    cudaFuncSetAttribute(opc_kernel, cudaFuncAttributeMaxDynamicSharedMemorySize, OPC_SMEM);
    cudaGetSymbolAddress((void**)&p_xt, g_xt); cudaGetSymbolAddress((void**)&p_flags, g_flags); cudaGetSymbolAddress((void**)&p_acc, g_acc);
    cudaGetSymbolAddress((void**)&p_norm, g_norm); cudaGetSymbolAddress((void**)&p_kv, g_kv); cudaGetSymbolAddress((void**)&p_x, g_x);
    cudaGetSymbolAddress((void**)&p_qkv, g_qkv); cudaGetSymbolAddress((void**)&p_xa, g_xa); cudaGetSymbolAddress((void**)&p_oa, g_oa);
  }
  CUtensorMap tmq, tmk, tmv, tmo;
  make_map_perm(enc, &tmq, Wq);
  make_map_perm(enc, &tmk, Wk);
  make_map_perm(enc, &tmv, Wv);
  make_map(enc, &tmo, Wo, DM, HE, 64, 64);

  cudaMemsetAsync(p_ar, 0, 2 * AR_LAYER, st);
  cudaMemsetAsync(p_norm, 0, 1024 * 4, st);
  cudaMemsetAsync(p_flags, 0, 2 * FL_LAYER * 4, st);
  cudaMemsetAsync(p_acc, 0, 2 * S_TOK * DM * 4, st);
  cudaMemsetAsync(p_kv, 0, 2 * 32 * 21 * 20 * 4, st);
  k_norms<<<192, 320, 0, st>>>(Wv, Wo);
  k_cvt_in<<<S_TOK * DM / 256, 256, 0, st>>>(x);
  for (int l = 0; l < 2; l++) {
    k_ln<<<256, 256, 0, st>>>(0);
    k_gemm<<<dim3(30, 32), 256, 0, st>>>(p_xa, wqkv, p_qkv, 1920, DM, 0, 0);
    k_kv<<<dim3(32, 16), 420, 0, st>>>(p_kv + l * 13440);
    k_lo<<<S_TOK, 640, 0, st>>>(p_kv + l * 13440);
    k_gemm<<<dim3(10, 32), 256, 0, st>>>(p_oa, wo_a, p_x, DM, DM, 0, 1);
    k_ln<<<256, 256, 0, st>>>(1);
    cudaLaunchConfig_t cfg = {};
    cfg.gridDim = dim3(96); cfg.blockDim = dim3(384); cfg.dynamicSmemBytes = REC_SMEM; cfg.stream = st;
    cudaLaunchAttribute at[1];
    at[0].id = cudaLaunchAttributeClusterDimension; at[0].val.clusterDim.x = 3; at[0].val.clusterDim.y = 1; at[0].val.clusterDim.z = 1;
    cfg.attrs = at; cfg.numAttrs = 1;
    cudaLaunchKernelEx(&cfg, rec_kernel, tmq, tmk, tmv, tmo, mem0, p_ar + l * AR_LAYER, p_flags + l * FL_LAYER, l);
    cudaLaunchConfig_t cf2 = {};
    cf2.gridDim = dim3(36); cf2.blockDim = dim3(384); cf2.dynamicSmemBytes = OPC_SMEM; cf2.stream = st;
    cudaLaunchAttribute a2[1];
    a2[0].id = cudaLaunchAttributeProgrammaticStreamSerialization; a2[0].val.programmaticStreamSerializationAllowed = 1;
    cf2.attrs = a2; cf2.numAttrs = OPC_PDL;
    cudaLaunchKernelEx(&cf2, opc_kernel, tmo, p_flags + l * FL_LAYER, p_acc + l * S_TOK * DM, p_x, p_xt, l == 1 ? (bf16*)d_out : (bf16*)nullptr);
  }
}
```

```cpp
#include <cuda_runtime.h>
#include <cuda_bf16.h>
#include <cuda.h>
#include <stdint.h>

typedef __nv_bfloat16 bf16;
typedef unsigned long long u64;

constexpr int S_TOK = 2048, DM = 640, DH = 192, HE = 6144, NSEG = 64;

constexpr int AR_GROUP = 98304;
constexpr int AR_LAYER = 16 * AR_GROUP;
__device__ __align__(1024) uint8_t g_ar[AR_LAYER + 32768];
__device__ __align__(1024) uint8_t g_xn[NSEG * 40960];
__device__ __align__(1024) uint8_t g_xt[S_TOK * DM * 2];
__device__ __align__(1024) uint8_t g_ot[NSEG * HE * 64];
__device__ __align__(1024) uint8_t g_oa[S_TOK * DM * 2];
__device__ __align__(1024) uint8_t g_w1[DM * 1920 * 2];
__device__ __align__(1024) uint8_t g_w2[DM * DM * 2];
__device__ __align__(1024) float g_acc[S_TOK * DM];
__device__ __align__(1024) float g_x[S_TOK * DM];
constexpr int FL_A = 0, FL_B = 64 * 6 * 8, FL_KV = FL_B + 64 * 8, FL_O = FL_KV + 8 * 8, FL_LAYER = FL_O + 16 * 8;
constexpr int Z_FLAGS = 0, Z_NORM = 2 * FL_LAYER, Z_KV = Z_NORM + 1024, KV_LAYER = 8 * 80 * 24, Z_END = Z_KV + 2 * KV_LAYER;
__device__ __align__(128) uint32_t g_zero[Z_END];
__device__ __align__(128) float2 g_stats[2 * S_TOK * 8];
#define GT(slot, k) do {} while (0)

__device__ __forceinline__ uint32_t smem_u32(const void* p) { return (uint32_t)__cvta_generic_to_shared(p); }
__device__ __forceinline__ uint32_t mapa(uint32_t a, uint32_t r) { uint32_t o; asm("mapa.shared::cluster.u32 %0, %1, %2;" : "=r"(o) : "r"(a), "r"(r)); return o; }
__device__ __forceinline__ void mbar_init(uint32_t bar, uint32_t cnt) { asm volatile("mbarrier.init.shared::cta.b64 [%0], %1;" :: "r"(bar), "r"(cnt) : "memory"); }
__device__ __forceinline__ void mbar_expect(uint32_t bar, uint32_t tx) { asm volatile("mbarrier.arrive.expect_tx.shared::cta.b64 _, [%0], %1;" :: "r"(bar), "r"(tx) : "memory"); }
__device__ __forceinline__ void mbar_arrive(uint32_t bar) { asm volatile("mbarrier.arrive.shared::cta.b64 _, [%0];" :: "r"(bar) : "memory"); }
__device__ __forceinline__ void mbar_wait(uint32_t bar, uint32_t par) {
  asm volatile("{\n.reg .pred p;\n.reg .u32 c;\nmov.u32 c, 0;\n"
               "LW:\nmbarrier.try_wait.parity.shared::cta.b64 p, [%0], %1;\n@p bra LD;\n"
               "add.u32 c, c, 1;\nsetp.lt.u32 p, c, 4000000;\n@p bra LW;\ntrap;\nLD:\n}" :: "r"(bar), "r"(par) : "memory");
}
template <int ID, int N> __device__ __forceinline__ void bar_sync() { asm volatile("barrier.sync %0, %1;" :: "n"(ID), "n"(N) : "memory"); }
template <int ID, int N> __device__ __forceinline__ void bar_arrive() { asm volatile("barrier.arrive %0, %1;" :: "n"(ID), "n"(N) : "memory"); }
__device__ __forceinline__ void fence_async() { asm volatile("fence.proxy.async.shared::cta;" ::: "memory"); }
__device__ __forceinline__ void cluster_sync() { asm volatile("barrier.cluster.arrive.aligned;\nbarrier.cluster.wait.aligned;" ::: "memory"); }
__device__ __forceinline__ void wg_fence() { asm volatile("wgmma.fence.sync.aligned;" ::: "memory"); }
__device__ __forceinline__ void wg_commit() { asm volatile("wgmma.commit_group.sync.aligned;" ::: "memory"); }
template <int N> __device__ __forceinline__ void wg_wait() { asm volatile("wgmma.wait_group.sync.aligned %0;" :: "n"(N) : "memory"); }
template <int N> __device__ __forceinline__ void pin(float* d) {
#pragma unroll
  for (int i = 0; i < N; i++) asm volatile("" : "+f"(d[i]) :: "memory");
}
__device__ __forceinline__ uint64_t mkdesc(uint32_t addr, uint32_t lbo, uint32_t sbo, int sw) {
  return (uint64_t)((addr & 0x3FFFF) >> 4) | ((uint64_t)(lbo >> 4) << 16) | ((uint64_t)(sbo >> 4) << 32) | ((uint64_t)sw << 62);
}
__device__ __forceinline__ uint32_t opaque(uint32_t v) { uint32_t o; asm volatile("mov.u32 %0, %1;" : "=r"(o) : "r"(v)); return o; }
__device__ __forceinline__ uint32_t pack2(float lo, float hi) { uint32_t r; asm("cvt.rn.bf16x2.f32 %0, %1, %2;" : "=r"(r) : "f"(hi), "f"(lo)); return r; }
__device__ __forceinline__ void ldsm4(uint32_t* r, uint32_t a) { asm volatile("ldmatrix.sync.aligned.m8n8.x4.shared.b16 {%0,%1,%2,%3}, [%4];" : "=r"(r[0]), "=r"(r[1]), "=r"(r[2]), "=r"(r[3]) : "r"(a) : "memory"); }
__device__ __forceinline__ void ldsm4t(uint32_t* r, uint32_t a) { asm volatile("ldmatrix.sync.aligned.m8n8.x4.trans.shared.b16 {%0,%1,%2,%3}, [%4];" : "=r"(r[0]), "=r"(r[1]), "=r"(r[2]), "=r"(r[3]) : "r"(a) : "memory"); }
__device__ __forceinline__ void ldsm1(uint32_t& r, uint32_t a) { asm volatile("ldmatrix.sync.aligned.m8n8.x1.shared.b16 {%0}, [%1];" : "=r"(r) : "r"(a) : "memory"); }
__device__ __forceinline__ void stsm4(uint32_t a, uint32_t r0, uint32_t r1, uint32_t r2, uint32_t r3) { asm volatile("stmatrix.sync.aligned.m8n8.x4.shared.b16 [%0], {%1,%2,%3,%4};" :: "r"(a), "r"(r0), "r"(r1), "r"(r2), "r"(r3) : "memory"); }
__device__ __forceinline__ void stsm1(uint32_t a, uint32_t r0) { asm volatile("stmatrix.sync.aligned.m8n8.x1.shared.b16 [%0], {%1};" :: "r"(a), "r"(r0) : "memory"); }
__device__ __forceinline__ void stsm4t(uint32_t a, uint32_t r0, uint32_t r1, uint32_t r2, uint32_t r3) { asm volatile("stmatrix.sync.aligned.m8n8.x4.trans.shared.b16 [%0], {%1,%2,%3,%4};" :: "r"(a), "r"(r0), "r"(r1), "r"(r2), "r"(r3) : "memory"); }
__device__ __forceinline__ void stsm2t(uint32_t a, uint32_t r0, uint32_t r1) { asm volatile("stmatrix.sync.aligned.m8n8.x2.trans.shared.b16 [%0], {%1,%2};" :: "r"(a), "r"(r0), "r"(r1) : "memory"); }
__device__ __forceinline__ void mma16816(float* c, const uint32_t* a, uint32_t b0, uint32_t b1) {
  asm volatile("mma.sync.aligned.m16n8k16.row.col.f32.bf16.bf16.f32 {%0,%1,%2,%3}, {%4,%5,%6,%7}, {%8,%9}, {%0,%1,%2,%3};"
               : "+f"(c[0]), "+f"(c[1]), "+f"(c[2]), "+f"(c[3]) : "r"(a[0]), "r"(a[1]), "r"(a[2]), "r"(a[3]), "r"(b0), "r"(b1));
}
__device__ __forceinline__ void mma1688(float* c, uint32_t a0, uint32_t a1, uint32_t b0) {
  asm volatile("mma.sync.aligned.m16n8k8.row.col.f32.bf16.bf16.f32 {%0,%1,%2,%3}, {%4,%5}, {%6}, {%0,%1,%2,%3};"
               : "+f"(c[0]), "+f"(c[1]), "+f"(c[2]), "+f"(c[3]) : "r"(a0), "r"(a1), "r"(b0));
}
__device__ __forceinline__ void sta1(uint32_t a, uint32_t v, uint32_t bar) { asm volatile("st.async.weak.shared::cluster.mbarrier::complete_tx::bytes.b32 [%0], %1, [%2];" :: "r"(a), "r"(v), "r"(bar) : "memory"); }
__device__ __forceinline__ void sta2(uint32_t a, uint32_t v0, uint32_t v1, uint32_t bar) { asm volatile("st.async.weak.shared::cluster.mbarrier::complete_tx::bytes.v2.b32 [%0], {%1,%2}, [%3];" :: "r"(a), "r"(v0), "r"(v1), "r"(bar) : "memory"); }
__device__ __forceinline__ void sta4(uint32_t a, uint32_t v0, uint32_t v1, uint32_t v2, uint32_t v3, uint32_t bar) { asm volatile("st.async.weak.shared::cluster.mbarrier::complete_tx::bytes.v4.b32 [%0], {%1,%2,%3,%4}, [%5];" :: "r"(a), "r"(v0), "r"(v1), "r"(v2), "r"(v3), "r"(bar) : "memory"); }
__device__ __forceinline__ float bflo(uint32_t v) { return __uint_as_float(v << 16); }
__device__ __forceinline__ float bfhi(uint32_t v) { return __uint_as_float(v & 0xFFFF0000u); }
__device__ __forceinline__ void sta2f(uint32_t a, float v0, float v1, uint32_t bar) { asm volatile("st.async.weak.shared::cluster.mbarrier::complete_tx::bytes.v2.f32 [%0], {%1,%2}, [%3];" :: "r"(a), "f"(v0), "f"(v1), "r"(bar) : "memory"); }
__device__ __forceinline__ void sta4f(uint32_t a, float v0, float v1, float v2, float v3, uint32_t bar) { asm volatile("st.async.weak.shared::cluster.mbarrier::complete_tx::bytes.v4.f32 [%0], {%1,%2,%3,%4}, [%5];" :: "r"(a), "f"(v0), "f"(v1), "f"(v2), "f"(v3), "r"(bar) : "memory"); }
__device__ __forceinline__ float4 lds4f(uint32_t a) { float4 v; asm volatile("ld.shared.v4.f32 {%0,%1,%2,%3}, [%4];" : "=f"(v.x), "=f"(v.y), "=f"(v.z), "=f"(v.w) : "r"(a) : "memory"); return v; }
__device__ __forceinline__ float2 lds2f(uint32_t a) { float2 v; asm volatile("ld.shared.v2.f32 {%0,%1}, [%2];" : "=f"(v.x), "=f"(v.y) : "r"(a) : "memory"); return v; }
__device__ __forceinline__ uint4 lds4(uint32_t a) { uint4 v; asm volatile("ld.shared.v4.u32 {%0,%1,%2,%3}, [%4];" : "=r"(v.x), "=r"(v.y), "=r"(v.z), "=r"(v.w) : "r"(a) : "memory"); return v; }
__device__ __forceinline__ uint32_t lds1(uint32_t a) { uint32_t v; asm volatile("ld.shared.u32 %0, [%1];" : "=r"(v) : "r"(a) : "memory"); return v; }
__device__ __forceinline__ void stsm2(uint32_t a, uint32_t r0, uint32_t r1) { asm volatile("stmatrix.sync.aligned.m8n8.x2.shared.b16 [%0], {%1,%2};" :: "r"(a), "r"(r0), "r"(r1) : "memory"); }
__device__ __forceinline__ float rcp(float x) { float y; asm("rcp.approx.ftz.f32 %0, %1;" : "=f"(y) : "f"(x)); return y; }
__device__ __forceinline__ void sts4(uint32_t a, uint32_t v0, uint32_t v1, uint32_t v2, uint32_t v3) { asm volatile("st.shared.v4.u32 [%0], {%1,%2,%3,%4};" :: "r"(a), "r"(v0), "r"(v1), "r"(v2), "r"(v3) : "memory"); }
__device__ __forceinline__ void bulk_s2c(uint32_t dst, uint32_t src, uint32_t bytes, uint32_t bar) {
  asm volatile("cp.async.bulk.shared::cluster.shared::cta.mbarrier::complete_tx::bytes [%0], [%1], %2, [%3];" :: "r"(dst), "r"(src), "r"(bytes), "r"(bar) : "memory");
}
__device__ __forceinline__ void stg4(void* p, uint4 v) { asm volatile("st.global.v4.u32 [%0], {%1,%2,%3,%4};" :: "l"(p), "r"(v.x), "r"(v.y), "r"(v.z), "r"(v.w) : "memory"); }
__device__ __forceinline__ void red_add(uint32_t* p, uint32_t v) { asm volatile("red.relaxed.gpu.global.add.u32 [%0], %1;" :: "l"(p), "r"(v) : "memory"); }
__device__ __forceinline__ void red4f(float* p, float a, float b, float c, float d) { asm volatile("red.relaxed.gpu.global.add.v4.f32 [%0], {%1,%2,%3,%4};" :: "l"(p), "f"(a), "f"(b), "f"(c), "f"(d) : "memory"); }
__device__ __forceinline__ void wait_flag(const uint32_t* p, uint32_t target) {
  uint32_t v; int it = 0;
  while (true) {
    asm volatile("ld.acquire.gpu.global.u32 %0, [%1];" : "=r"(v) : "l"(p) : "memory");
    if (v >= target) break;
    if (++it > 4000000) __trap();
    __nanosleep(40);
  }
}
__device__ __forceinline__ void sts1(uint32_t a, uint32_t v) { asm volatile("st.shared.u32 [%0], %1;" :: "r"(a), "r"(v) : "memory"); }
__device__ __forceinline__ void bulk_g2s(uint32_t dst, const void* src, uint32_t bytes, uint32_t bar) {
  asm volatile("cp.async.bulk.shared::cluster.global.mbarrier::complete_tx::bytes [%0], [%1], %2, [%3];" :: "r"(dst), "l"(src), "r"(bytes), "r"(bar) : "memory");
}
__device__ __forceinline__ void tma2d(uint32_t dst, const CUtensorMap* m, int c0, int c1, uint32_t bar) {
  asm volatile("cp.async.bulk.tensor.2d.shared::cluster.global.mbarrier::complete_tx::bytes [%0], [%1, {%3, %4}], [%2];" :: "r"(dst), "l"((uint64_t)m), "r"(bar), "r"(c0), "r"(c1) : "memory");
}
__device__ __forceinline__ void tma5d(uint32_t dst, const CUtensorMap* m, int c0, int c4, uint32_t bar) {
  asm volatile("cp.async.bulk.tensor.5d.shared::cluster.global.mbarrier::complete_tx::bytes [%0], [%1, {%3, %5, %5, %5, %4}], [%2];" :: "r"(dst), "l"((uint64_t)m), "r"(bar), "r"(c0), "r"(c4), "r"(0) : "memory");
}
__device__ __forceinline__ void red64(void* p, uint32_t lo, uint32_t hi) { asm volatile("{\n.reg .b64 t;\nmov.b64 t, {%1,%2};\nred.relaxed.gpu.global.add.u64 [%0], t;\n}" :: "l"(p), "r"(lo), "r"(hi) : "memory"); }
__device__ __forceinline__ uint4 ld_poll(const void* p) {
  uint4 v;
  asm volatile("{\n.reg .b64 a, b;\nld.relaxed.gpu.global.v2.b64 {a, b}, [%4];\nmov.b64 {%0,%1}, a;\nmov.b64 {%2,%3}, b;\n}" : "=r"(v.x), "=r"(v.y), "=r"(v.z), "=r"(v.w) : "l"(p) : "memory");
  return v;
}
__device__ __forceinline__ uint32_t clk() { uint32_t c; asm volatile("mov.u32 %0, %%clock;" : "=r"(c) :: "memory"); return c; }
__device__ __forceinline__ float ex2(float x) { float y; asm("ex2.approx.ftz.f32 %0, %1;" : "=f"(y) : "f"(x)); return y; }

__device__ __forceinline__ void wg_ss_n240_ta0_tb1(float* d, uint64_t a, uint64_t b, int sc) {
  asm volatile("{\n.reg .pred p;\nsetp.ne.b32 p, %122, 0;\nwgmma.mma_async.sync.aligned.m64n240k16.f32.bf16.bf16 {%0, %1, %2, %3, %4, %5, %6, %7, %8, %9, %10, %11, %12, %13, %14, %15, %16, %17, %18, %19, %20, %21, %22, %23, %24, %25, %26, %27, %28, %29, %30, %31, %32, %33, %34, %35, %36, %37, %38, %39, %40, %41, %42, %43, %44, %45, %46, %47, %48, %49, %50, %51, %52, %53, %54, %55, %56, %57, %58, %59, %60, %61, %62, %63, %64, %65, %66, %67, %68, %69, %70, %71, %72, %73, %74, %75, %76, %77, %78, %79, %80, %81, %82, %83, %84, %85, %86, %87, %88, %89, %90, %91, %92, %93, %94, %95, %96, %97, %98, %99, %100, %101, %102, %103, %104, %105, %106, %107, %108, %109, %110, %111, %112, %113, %114, %115, %116, %117, %118, %119}, %120, %121, p, 1, 1, 0, 1;\n}\n"
    : "+f"(d[0]), "+f"(d[1]), "+f"(d[2]), "+f"(d[3]), "+f"(d[4]), "+f"(d[5]), "+f"(d[6]), "+f"(d[7]), "+f"(d[8]), "+f"(d[9]), "+f"(d[10]), "+f"(d[11]), "+f"(d[12]), "+f"(d[13]), "+f"(d[14]), "+f"(d[15]), "+f"(d[16]), "+f"(d[17]), "+f"(d[18]), "+f"(d[19]), "+f"(d[20]), "+f"(d[21]), "+f"(d[22]), "+f"(d[23]), "+f"(d[24]), "+f"(d[25]), "+f"(d[26]), "+f"(d[27]), "+f"(d[28]), "+f"(d[29]), "+f"(d[30]), "+f"(d[31]), "+f"(d[32]), "+f"(d[33]), "+f"(d[34]), "+f"(d[35]), "+f"(d[36]), "+f"(d[37]), "+f"(d[38]), "+f"(d[39]), "+f"(d[40]), "+f"(d[41]), "+f"(d[42]), "+f"(d[43]), "+f"(d[44]), "+f"(d[45]), "+f"(d[46]), "+f"(d[47]), "+f"(d[48]), "+f"(d[49]), "+f"(d[50]), "+f"(d[51]), "+f"(d[52]), "+f"(d[53]), "+f"(d[54]), "+f"(d[55]), "+f"(d[56]), "+f"(d[57]), "+f"(d[58]), "+f"(d[59]), "+f"(d[60]), "+f"(d[61]), "+f"(d[62]), "+f"(d[63]), "+f"(d[64]), "+f"(d[65]), "+f"(d[66]), "+f"(d[67]), "+f"(d[68]), "+f"(d[69]), "+f"(d[70]), "+f"(d[71]), "+f"(d[72]), "+f"(d[73]), "+f"(d[74]), "+f"(d[75]), "+f"(d[76]), "+f"(d[77]), "+f"(d[78]), "+f"(d[79]), "+f"(d[80]), "+f"(d[81]), "+f"(d[82]), "+f"(d[83]), "+f"(d[84]), "+f"(d[85]), "+f"(d[86]), "+f"(d[87]), "+f"(d[88]), "+f"(d[89]), "+f"(d[90]), "+f"(d[91]), "+f"(d[92]), "+f"(d[93]), "+f"(d[94]), "+f"(d[95]), "+f"(d[96]), "+f"(d[97]), "+f"(d[98]), "+f"(d[99]), "+f"(d[100]), "+f"(d[101]), "+f"(d[102]), "+f"(d[103]), "+f"(d[104]), "+f"(d[105]), "+f"(d[106]), "+f"(d[107]), "+f"(d[108]), "+f"(d[109]), "+f"(d[110]), "+f"(d[111]), "+f"(d[112]), "+f"(d[113]), "+f"(d[114]), "+f"(d[115]), "+f"(d[116]), "+f"(d[117]), "+f"(d[118]), "+f"(d[119])
    : "l"(a), "l"(b), "r"(sc));
}
__device__ __forceinline__ void wg_ss_n88_ta1_tb1(float* d, uint64_t a, uint64_t b, int sc) {
  asm volatile("{\n.reg .pred p;\nsetp.ne.b32 p, %46, 0;\nwgmma.mma_async.sync.aligned.m64n88k16.f32.bf16.bf16 {%0, %1, %2, %3, %4, %5, %6, %7, %8, %9, %10, %11, %12, %13, %14, %15, %16, %17, %18, %19, %20, %21, %22, %23, %24, %25, %26, %27, %28, %29, %30, %31, %32, %33, %34, %35, %36, %37, %38, %39, %40, %41, %42, %43}, %44, %45, p, 1, 1, 1, 1;\n}\n"
    : "+f"(d[0]), "+f"(d[1]), "+f"(d[2]), "+f"(d[3]), "+f"(d[4]), "+f"(d[5]), "+f"(d[6]), "+f"(d[7]), "+f"(d[8]), "+f"(d[9]), "+f"(d[10]), "+f"(d[11]), "+f"(d[12]), "+f"(d[13]), "+f"(d[14]), "+f"(d[15]), "+f"(d[16]), "+f"(d[17]), "+f"(d[18]), "+f"(d[19]), "+f"(d[20]), "+f"(d[21]), "+f"(d[22]), "+f"(d[23]), "+f"(d[24]), "+f"(d[25]), "+f"(d[26]), "+f"(d[27]), "+f"(d[28]), "+f"(d[29]), "+f"(d[30]), "+f"(d[31]), "+f"(d[32]), "+f"(d[33]), "+f"(d[34]), "+f"(d[35]), "+f"(d[36]), "+f"(d[37]), "+f"(d[38]), "+f"(d[39]), "+f"(d[40]), "+f"(d[41]), "+f"(d[42]), "+f"(d[43])
    : "l"(a), "l"(b), "r"(sc));
}
__device__ __forceinline__ void wg_rs_n160_tb1(float* d, const uint32_t* a, uint64_t b, int sc) {
  asm volatile("{\n.reg .pred p;\nsetp.ne.b32 p, %85, 0;\nwgmma.mma_async.sync.aligned.m64n160k16.f32.bf16.bf16 {%0, %1, %2, %3, %4, %5, %6, %7, %8, %9, %10, %11, %12, %13, %14, %15, %16, %17, %18, %19, %20, %21, %22, %23, %24, %25, %26, %27, %28, %29, %30, %31, %32, %33, %34, %35, %36, %37, %38, %39, %40, %41, %42, %43, %44, %45, %46, %47, %48, %49, %50, %51, %52, %53, %54, %55, %56, %57, %58, %59, %60, %61, %62, %63, %64, %65, %66, %67, %68, %69, %70, %71, %72, %73, %74, %75, %76, %77, %78, %79}, {%80, %81, %82, %83}, %84, p, 1, 1, 1;\n}\n"
    : "+f"(d[0]), "+f"(d[1]), "+f"(d[2]), "+f"(d[3]), "+f"(d[4]), "+f"(d[5]), "+f"(d[6]), "+f"(d[7]), "+f"(d[8]), "+f"(d[9]), "+f"(d[10]), "+f"(d[11]), "+f"(d[12]), "+f"(d[13]), "+f"(d[14]), "+f"(d[15]), "+f"(d[16]), "+f"(d[17]), "+f"(d[18]), "+f"(d[19]), "+f"(d[20]), "+f"(d[21]), "+f"(d[22]), "+f"(d[23]), "+f"(d[24]), "+f"(d[25]), "+f"(d[26]), "+f"(d[27]), "+f"(d[28]), "+f"(d[29]), "+f"(d[30]), "+f"(d[31]), "+f"(d[32]), "+f"(d[33]), "+f"(d[34]), "+f"(d[35]), "+f"(d[36]), "+f"(d[37]), "+f"(d[38]), "+f"(d[39]), "+f"(d[40]), "+f"(d[41]), "+f"(d[42]), "+f"(d[43]), "+f"(d[44]), "+f"(d[45]), "+f"(d[46]), "+f"(d[47]), "+f"(d[48]), "+f"(d[49]), "+f"(d[50]), "+f"(d[51]), "+f"(d[52]), "+f"(d[53]), "+f"(d[54]), "+f"(d[55]), "+f"(d[56]), "+f"(d[57]), "+f"(d[58]), "+f"(d[59]), "+f"(d[60]), "+f"(d[61]), "+f"(d[62]), "+f"(d[63]), "+f"(d[64]), "+f"(d[65]), "+f"(d[66]), "+f"(d[67]), "+f"(d[68]), "+f"(d[69]), "+f"(d[70]), "+f"(d[71]), "+f"(d[72]), "+f"(d[73]), "+f"(d[74]), "+f"(d[75]), "+f"(d[76]), "+f"(d[77]), "+f"(d[78]), "+f"(d[79])
    : "r"(a[0]), "r"(a[1]), "r"(a[2]), "r"(a[3]), "l"(b), "r"(sc));
}
__device__ __forceinline__ void wg_ss_n80_ta0_tb1(float* d, uint64_t a, uint64_t b, int sc) {
  asm volatile("{\n.reg .pred p;\nsetp.ne.b32 p, %42, 0;\nwgmma.mma_async.sync.aligned.m64n80k16.f32.bf16.bf16 {%0, %1, %2, %3, %4, %5, %6, %7, %8, %9, %10, %11, %12, %13, %14, %15, %16, %17, %18, %19, %20, %21, %22, %23, %24, %25, %26, %27, %28, %29, %30, %31, %32, %33, %34, %35, %36, %37, %38, %39}, %40, %41, p, 1, 1, 0, 1;\n}\n"
    : "+f"(d[0]), "+f"(d[1]), "+f"(d[2]), "+f"(d[3]), "+f"(d[4]), "+f"(d[5]), "+f"(d[6]), "+f"(d[7]), "+f"(d[8]), "+f"(d[9]), "+f"(d[10]), "+f"(d[11]), "+f"(d[12]), "+f"(d[13]), "+f"(d[14]), "+f"(d[15]), "+f"(d[16]), "+f"(d[17]), "+f"(d[18]), "+f"(d[19]), "+f"(d[20]), "+f"(d[21]), "+f"(d[22]), "+f"(d[23]), "+f"(d[24]), "+f"(d[25]), "+f"(d[26]), "+f"(d[27]), "+f"(d[28]), "+f"(d[29]), "+f"(d[30]), "+f"(d[31]), "+f"(d[32]), "+f"(d[33]), "+f"(d[34]), "+f"(d[35]), "+f"(d[36]), "+f"(d[37]), "+f"(d[38]), "+f"(d[39])
    : "l"(a), "l"(b), "r"(sc));
}
__device__ __forceinline__ void wg_rs_n32_tb1(float* d, const uint32_t* a, uint64_t b, int sc) {
  asm volatile("{\n.reg .pred p;\nsetp.ne.b32 p, %21, 0;\nwgmma.mma_async.sync.aligned.m64n32k16.f32.bf16.bf16 {%0, %1, %2, %3, %4, %5, %6, %7, %8, %9, %10, %11, %12, %13, %14, %15}, {%16, %17, %18, %19}, %20, p, 1, 1, 1;\n}\n"
    : "+f"(d[0]), "+f"(d[1]), "+f"(d[2]), "+f"(d[3]), "+f"(d[4]), "+f"(d[5]), "+f"(d[6]), "+f"(d[7]), "+f"(d[8]), "+f"(d[9]), "+f"(d[10]), "+f"(d[11]), "+f"(d[12]), "+f"(d[13]), "+f"(d[14]), "+f"(d[15])
    : "r"(a[0]), "r"(a[1]), "r"(a[2]), "r"(a[3]), "l"(b), "r"(sc));
}
__device__ __forceinline__ void wg_ss_n32_ta1_tb1(float* d, uint64_t a, uint64_t b, int sc) {
  asm volatile("{\n.reg .pred p;\nsetp.ne.b32 p, %18, 0;\nwgmma.mma_async.sync.aligned.m64n32k16.f32.bf16.bf16 {%0, %1, %2, %3, %4, %5, %6, %7, %8, %9, %10, %11, %12, %13, %14, %15}, %16, %17, p, 1, 1, 1, 1;\n}\n"
    : "+f"(d[0]), "+f"(d[1]), "+f"(d[2]), "+f"(d[3]), "+f"(d[4]), "+f"(d[5]), "+f"(d[6]), "+f"(d[7]), "+f"(d[8]), "+f"(d[9]), "+f"(d[10]), "+f"(d[11]), "+f"(d[12]), "+f"(d[13]), "+f"(d[14]), "+f"(d[15])
    : "l"(a), "l"(b), "r"(sc));
}
__device__ __forceinline__ void wg_rs_n32_tb0(float* d, const uint32_t* a, uint64_t b, int sc) {
  asm volatile("{\n.reg .pred p;\nsetp.ne.b32 p, %21, 0;\nwgmma.mma_async.sync.aligned.m64n32k16.f32.bf16.bf16 {%0, %1, %2, %3, %4, %5, %6, %7, %8, %9, %10, %11, %12, %13, %14, %15}, {%16, %17, %18, %19}, %20, p, 1, 1, 0;\n}\n"
    : "+f"(d[0]), "+f"(d[1]), "+f"(d[2]), "+f"(d[3]), "+f"(d[4]), "+f"(d[5]), "+f"(d[6]), "+f"(d[7]), "+f"(d[8]), "+f"(d[9]), "+f"(d[10]), "+f"(d[11]), "+f"(d[12]), "+f"(d[13]), "+f"(d[14]), "+f"(d[15])
    : "r"(a[0]), "r"(a[1]), "r"(a[2]), "r"(a[3]), "l"(b), "r"(sc));
}
__device__ __forceinline__ void wg_rs_n40_tb0(float* d, const uint32_t* a, uint64_t b, int sc) {
  asm volatile("{\n.reg .pred p;\nsetp.ne.b32 p, %25, 0;\nwgmma.mma_async.sync.aligned.m64n40k16.f32.bf16.bf16 {%0, %1, %2, %3, %4, %5, %6, %7, %8, %9, %10, %11, %12, %13, %14, %15, %16, %17, %18, %19}, {%20, %21, %22, %23}, %24, p, 1, 1, 0;\n}\n"
    : "+f"(d[0]), "+f"(d[1]), "+f"(d[2]), "+f"(d[3]), "+f"(d[4]), "+f"(d[5]), "+f"(d[6]), "+f"(d[7]), "+f"(d[8]), "+f"(d[9]), "+f"(d[10]), "+f"(d[11]), "+f"(d[12]), "+f"(d[13]), "+f"(d[14]), "+f"(d[15]), "+f"(d[16]), "+f"(d[17]), "+f"(d[18]), "+f"(d[19])
    : "r"(a[0]), "r"(a[1]), "r"(a[2]), "r"(a[3]), "l"(b), "r"(sc));
}
__device__ __forceinline__ void wg_rs_n8_tb1(float* d, const uint32_t* a, uint64_t b, int sc) {
  asm volatile("{\n.reg .pred p;\nsetp.ne.b32 p, %9, 0;\nwgmma.mma_async.sync.aligned.m64n8k16.f32.bf16.bf16 {%0, %1, %2, %3}, {%4, %5, %6, %7}, %8, p, 1, 1, 1;\n}\n"
    : "+f"(d[0]), "+f"(d[1]), "+f"(d[2]), "+f"(d[3])
    : "r"(a[0]), "r"(a[1]), "r"(a[2]), "r"(a[3]), "l"(b), "r"(sc));
}
__device__ __forceinline__ void wg_ss_n40_ta0_tb0(float* d, uint64_t a, uint64_t b, int sc) {
  asm volatile("{\n.reg .pred p;\nsetp.ne.b32 p, %22, 0;\nwgmma.mma_async.sync.aligned.m64n40k16.f32.bf16.bf16 {%0, %1, %2, %3, %4, %5, %6, %7, %8, %9, %10, %11, %12, %13, %14, %15, %16, %17, %18, %19}, %20, %21, p, 1, 1, 0, 0;\n}\n"
    : "+f"(d[0]), "+f"(d[1]), "+f"(d[2]), "+f"(d[3]), "+f"(d[4]), "+f"(d[5]), "+f"(d[6]), "+f"(d[7]), "+f"(d[8]), "+f"(d[9]), "+f"(d[10]), "+f"(d[11]), "+f"(d[12]), "+f"(d[13]), "+f"(d[14]), "+f"(d[15]), "+f"(d[16]), "+f"(d[17]), "+f"(d[18]), "+f"(d[19])
    : "l"(a), "l"(b), "r"(sc));
}
__device__ __forceinline__ void wg_ss_n40_ta1_tb0(float* d, uint64_t a, uint64_t b, int sc) {
  asm volatile("{\n.reg .pred p;\nsetp.ne.b32 p, %22, 0;\nwgmma.mma_async.sync.aligned.m64n40k16.f32.bf16.bf16 {%0, %1, %2, %3, %4, %5, %6, %7, %8, %9, %10, %11, %12, %13, %14, %15, %16, %17, %18, %19}, %20, %21, p, 1, 1, 1, 0;\n}\n"
    : "+f"(d[0]), "+f"(d[1]), "+f"(d[2]), "+f"(d[3]), "+f"(d[4]), "+f"(d[5]), "+f"(d[6]), "+f"(d[7]), "+f"(d[8]), "+f"(d[9]), "+f"(d[10]), "+f"(d[11]), "+f"(d[12]), "+f"(d[13]), "+f"(d[14]), "+f"(d[15]), "+f"(d[16]), "+f"(d[17]), "+f"(d[18]), "+f"(d[19])
    : "l"(a), "l"(b), "r"(sc));
}
__device__ __forceinline__ void wg_ss_n8_ta1_tb1(float* d, uint64_t a, uint64_t b, int sc) {
  asm volatile("{\n.reg .pred p;\nsetp.ne.b32 p, %6, 0;\nwgmma.mma_async.sync.aligned.m64n8k16.f32.bf16.bf16 {%0, %1, %2, %3}, %4, %5, p, 1, 1, 1, 1;\n}\n"
    : "+f"(d[0]), "+f"(d[1]), "+f"(d[2]), "+f"(d[3])
    : "l"(a), "l"(b), "r"(sc));
}

constexpr int O_WV = 0, O_WO = 81920, O_H = 163840, O_QK = 215040, O_SM = 228352, O_MISC = 230912;
constexpr int O_QM = O_QK + 1024, O_K = O_QK + 3072, O_OG = O_QK + 8192;
constexpr int SM_SLOT = 640;
constexpr int O_MAXS = O_MISC;
constexpr int O_BAR = O_MISC + 64;
constexpr int MB_XF = 0, MB_MF = 2, MB_SM = 6, MB_SX = 7, MB_OG = 8, MB_W = 9;
constexpr int O_PROF = O_BAR + 8 * 24;
constexpr int REC_SMEM = O_PROF + 128;
constexpr int B_QK = 1, B_VGO = 2, B_SISS = 3, B_PM = 4, B_PX = 5, B_XGO = 6, B_PFREE = 7, B_WG2 = 8, B_VHALF = 9, B_VDONE = 10, B_ALL = 11, B_VOWN = 11,
              B_SSENT = 12, B_SLD = 13, B_VEND = 14, B_XGO1 = 15;
#define POLL_DELAY 700
#define POLL_D0 300
#define POLL_STEP 100
#define NBUF 3
#define REG_A 208
#define REG_B 88
#define REG_C 208
#define FENCE_RX() do {} while (0)
#define STR2(x) #x
#define STR(x) STR2(x)
#define TS0(idx) do {} while (0)
#define TS(idx) do {} while (0)
#define OPC_PDL 1
#define LA_PDL 1
#define REC_PDL 1
#define MP_D 2
#define MP_CH 4
#define OX_POS 1
#define V_RS 4
#define V_K1 6
#define V_K2 24
#define V_K3 28

__device__ __forceinline__ void fix_red(uint8_t* p, const float* a, float sc) {
  int v0 = __float2int_rn(a[0] * sc), v1 = __float2int_rn(a[1] * sc), v2 = __float2int_rn(a[2] * sc), v3 = __float2int_rn(a[3] * sc);
  red64(p, ((uint32_t)v0 << 7) | 1u, ((uint32_t)v2 << 3) + (uint32_t)(v0 >> 25));
  red64(p + 1024, ((uint32_t)v1 << 7) | 1u, ((uint32_t)v3 << 3) + (uint32_t)(v1 >> 25));
}

template <int wg>
__device__ __forceinline__ void qk_role(const uint32_t sb, const uint32_t sb1, const uint32_t sb2, const int tid, const int w, const uint32_t rank, const uint8_t* __restrict__ ar, uint32_t* __restrict__ flag, int layer) {
    const int lane = tid & 31;
    const uint32_t bar = sb + O_BAR;
    uint32_t a[40][4];
    {
      const uint32_t la = sb + wg * 81920 + ((lane >> 4) * 8 + (lane & 7)) * 128 + (((2 * w + ((lane >> 3) & 1)) ^ (lane & 7)) << 4);
#pragma unroll
      for (int p = 0; p < 5; p++) {
        mbar_wait(bar + 8 * (MB_W + wg * 5 + p), 0);
#pragma unroll
        for (int k = 0; k < 8; k++) ldsm4t(a[p * 8 + k], la + (p * 8 + k) * 2048);
      }
    }
    bar_sync<B_ALL, 384>();
    cluster_sync();
    const uint32_t swz = (lane & 7) * 128 + (((2 * w + ((lane >> 3) & 1)) ^ (lane & 7)) << 4);
    const uint32_t ld_m = sb + O_H + (lane & 7) * 128 + (((lane >> 3) ^ (lane & 7)) << 4);

    for (int s = 0; s < NSEG; s++) {
      const uint32_t par = s & 1;
      if (wg == 0 && w == 0) TS0(0);
      if (s == 1) GT(layer * 4 + 1, 1);
      {
        float ax[16];
        const uint64_t db = mkdesc(opaque(sb) + O_H + 1024, 16, 1024, 1);
        mbar_wait(bar + 8 * MB_XF, par);
        wg_fence();
#pragma unroll
        for (int k = 0; k < 40; k++) wg_rs_n32_tb0(ax, a[k], db + (((k >> 2) * 5120 + (k & 3) * 32) >> 4), k);
        wg_commit();
        if (s > 0) bar_sync<B_PFREE, 384>();
        const uint32_t st_x = sb + (wg == 0 ? O_QK : O_K + 2048) + (lane >> 4) * 2048 + swz;
        wg_wait<0>();
        pin<16>(ax);
        if (w == 0) TS(1 + 22 * wg);
        stsm4t(st_x, pack2(ax[0], ax[1]), pack2(ax[2], ax[3]), pack2(ax[4], ax[5]), pack2(ax[6], ax[7]));
        stsm4t(st_x + 4096, pack2(ax[8], ax[9]), pack2(ax[10], ax[11]), pack2(ax[12], ax[13]), pack2(ax[14], ax[15]));
        bar_arrive<B_VOWN, 384>();
      }
      if (wg == 1 && tid == 192) { mbar_expect(bar + 8 * MB_SM, 2 * SM_SLOT + 48 + 48); mbar_expect(bar + 8 * MB_SX, 2 * 2176); }
      {
        float c0[4] = {0.f, 0.f, 0.f, 0.f}, c1[4] = {0.f, 0.f, 0.f, 0.f}, c2[4] = {0.f, 0.f, 0.f, 0.f}, c3[4] = {0.f, 0.f, 0.f, 0.f};
        uint32_t b[MP_D][2][4];
#pragma unroll
        for (int j = 0; j < 10 + MP_D - 1; j++) {
          if (j < 10) {
            const int c = j == 0 ? 9 : ((j - 1) % 3) * 3 + (j - 1) / 3;
            if (j == 0 || j % 3 == 1) { mbar_wait(bar + 8 * (MB_MF + (j + 2) / 3), par); if (wg == 0 && w == 0) TS(2 + (j + 2) / 3); }
            ldsm4(b[j % MP_D][0], ld_m + c * 5120);
            ldsm4(b[j % MP_D][1], (ld_m ^ 64) + c * 5120);
          }
          const int u = j - (MP_D - 1);
          if (u >= 0) {
            const int c = u == 0 ? 9 : ((u - 1) % 3) * 3 + (u - 1) / 3;
            mma16816(c0, a[4 * c], b[u % MP_D][0][0], b[u % MP_D][0][1]);
            mma16816(c1, a[4 * c + 1], b[u % MP_D][0][2], b[u % MP_D][0][3]);
            mma16816(MP_CH == 4 ? c2 : c0, a[4 * c + 2], b[u % MP_D][1][0], b[u % MP_D][1][1]);
            mma16816(MP_CH == 4 ? c3 : c1, a[4 * c + 3], b[u % MP_D][1][2], b[u % MP_D][1][3]);
          }
        }
        if (MP_CH == 4) {
#pragma unroll
          for (int k = 0; k < 4; k++) { c0[k] += c2[k]; c1[k] += c3[k]; }
        }
        bar_arrive<B_VGO, 384>();
        stsm2t(sb + (wg == 0 ? O_QM : O_K) + swz, pack2(c0[0] + c1[0], c0[1] + c1[1]), pack2(c0[2] + c1[2], c0[3] + c1[3]));
        fence_async();
      }
      if (wg == 0) {
        bar_sync<B_QK, 256>();
        float sv[20];
        {
          const uint64_t da = mkdesc(opaque(sb) + O_QK, 16, 1024, 1);
          const uint64_t db = mkdesc(opaque(sb) + O_K, 16, 2048, 1);
          wg_fence();
#pragma unroll
          for (int k = 0; k < 4; k++) wg_ss_n40_ta0_tb0(sv, da + 2 * k, db + 2 * k, k);
          wg_commit();
          bar_arrive<B_SISS, 256>();
          if (w == 0) TS(6);
          wg_wait<0>();
          pin<20>(sv);
        }
        constexpr float SCL = 0.07216878364870322f;
        constexpr float L2E = 1.4426950408889634f;
        const uint32_t om = O_SM + opaque(lane) * 16, om2 = O_SM + 512 + opaque(lane) * 4;
        const uint32_t m0 = pack2(sv[2], sv[3]), m1 = pack2(sv[6], sv[7]), m2 = pack2(sv[10], sv[11]), m3 = pack2(sv[14], sv[15]), m4 = pack2(sv[18], sv[19]);
        if (w == 0) {
          sta4(sb1 + om + SM_SLOT, m0, m1, m2, m3, sb1 + O_BAR + 8 * MB_SM);
          sta4(sb2 + om, m0, m1, m2, m3, sb2 + O_BAR + 8 * MB_SM);
          sta1(sb1 + om2 + SM_SLOT, m4, sb1 + O_BAR + 8 * MB_SM);
          sta1(sb2 + om2, m4, sb2 + O_BAR + 8 * MB_SM);
        }
        if (lane < 3) { const uint32_t b = mapa(sb, lane); sta1(b + O_MAXS + 48, 0u, b + O_BAR + 8 * MB_SM); }
        bar_arrive<B_SSENT, 256>();
        const uint32_t ox = O_K + w * 2048 + opaque(lane) * 16, ox2 = O_K + 8192 + opaque(lane) * 4;
        const uint32_t p0 = pack2(sv[0], sv[1]), p1 = pack2(sv[4], sv[5]), p2 = pack2(sv[8], sv[9]), p3 = pack2(sv[12], sv[13]), p4 = pack2(sv[16], sv[17]);
        if (w == 0) TS(7);
        mbar_wait(bar + 8 * MB_SM, par);
#define ACC2(k, p, u, v) { t[k] = bflo(p) + bflo(u) + bflo(v); t[k + 1] = bfhi(p) + bfhi(u) + bfhi(v); }
        if (w == 0) {
          float t[10];
          {
            const uint4 u = lds4(sb + om), v = lds4(sb + om + SM_SLOT);
            const uint32_t u4 = lds1(sb + om2), v4 = lds1(sb + om2 + SM_SLOT);
            sta4(sb1 + ox + 512, p0, p1, p2, p3, sb1 + O_BAR + 8 * MB_SX);
            sta4(sb2 + ox, p0, p1, p2, p3, sb2 + O_BAR + 8 * MB_SX);
            if (V_K2 < 24) bar_arrive<B_SLD, 256>();
            TS(8);
            ACC2(0, m0, u.x, v.x) ACC2(2, m1, u.y, v.y) ACC2(4, m2, u.z, v.z) ACC2(6, m3, u.w, v.w) ACC2(8, m4, u4, v4)
          }
          float m = fmaxf(fmaxf(fmaxf(t[0], t[1]), fmaxf(t[2], t[3])), fmaxf(fmaxf(t[4], t[5]), fmaxf(t[6], t[7])));
          m = fmaxf(m, fmaxf(t[8], t[9]));
          m = fmaxf(m, __shfl_xor_sync(~0u, m, 1));
          m = fmaxf(m, __shfl_xor_sync(~0u, m, 2));
          const float mm = m * (SCL * L2E);
#pragma unroll
          for (int k = 0; k < 10; k++) t[k] = ex2(fmaf(t[k], SCL * L2E, -mm));
          float sum = ((t[0] + t[1]) + (t[2] + t[3])) + ((t[4] + t[5]) + (t[6] + t[7])) + (t[8] + t[9]);
          sum += __shfl_xor_sync(~0u, sum, 1);
          sum += __shfl_xor_sync(~0u, sum, 2);
          const float inv = rcp(sum);
          const uint32_t ln = opaque(lane), pa = sb + O_QM + (ln & 7) * 128;
          stsm4(pa + (((ln >> 3) ^ (ln & 7)) << 4), pack2(t[0] * inv, t[1] * inv), pack2(t[2] * inv, t[3] * inv), pack2(t[4] * inv, t[5] * inv), pack2(t[6] * inv, t[7] * inv));
          stsm1(pa + ((4 ^ (ln & 7)) << 4), pack2(t[8] * inv, t[9] * inv));
          bar_arrive<B_PM, 160>();
          TS(9);
        } else {
          sta4(sb1 + ox + 512, p0, p1, p2, p3, sb1 + O_BAR + 8 * MB_SX);
          sta4(sb2 + ox, p0, p1, p2, p3, sb2 + O_BAR + 8 * MB_SX);
          if (w == 3) { sta1(sb1 + ox2 + 128, p4, sb1 + O_BAR + 8 * MB_SX); sta1(sb2 + ox2, p4, sb2 + O_BAR + 8 * MB_SX); }
          if (V_K2 < 24) bar_arrive<B_SLD, 256>();
        }
        mbar_wait(bar + 8 * MB_SX, par);
        {
          float t[10];
          const uint4 u = lds4(sb + ox), v = lds4(sb + ox + 512);
          const uint32_t u4 = lds1(sb + ox2), v4 = lds1(sb + ox2 + 128);
          ACC2(0, p0, u.x, v.x) ACC2(2, p1, u.y, v.y) ACC2(4, p2, u.z, v.z) ACC2(6, p3, u.w, v.w) ACC2(8, p4, u4, v4)
          const int ln = opaque(lane), dq = 8 * w + (ln >> 2) - 2 * (ln & 3);
#pragma unroll
          for (int k = 1; k < 5; k++) {
            if (8 * (k - 1) > dq) t[2 * k] = -1e9f / SCL;
            if (8 * (k - 1) + 1 > dq) t[2 * k + 1] = -1e9f / SCL;
          }
          float m = fmaxf(fmaxf(fmaxf(t[0], t[1]), fmaxf(t[2], t[3])), fmaxf(fmaxf(t[4], t[5]), fmaxf(t[6], t[7])));
          m = fmaxf(m, fmaxf(t[8], t[9]));
          m = fmaxf(m, __shfl_xor_sync(~0u, m, 1));
          m = fmaxf(m, __shfl_xor_sync(~0u, m, 2));
          const float mm = m * (SCL * L2E);
#pragma unroll
          for (int k = 0; k < 10; k++) t[k] = ex2(fmaf(t[k], SCL * L2E, -mm));
          float sum = ((t[0] + t[1]) + (t[2] + t[3])) + ((t[4] + t[5]) + (t[6] + t[7])) + (t[8] + t[9]);
          sum += __shfl_xor_sync(~0u, sum, 1);
          sum += __shfl_xor_sync(~0u, sum, 2);
          const float inv = rcp(sum);
          const int rr = 2 * w + (ln & 1);
          const uint32_t pa = sb + O_QK + ((ln >> 1) & 3) * 2048 + rr * 128;
          stsm4(pa + (((ln >> 3) ^ rr) << 4), pack2(t[0] * inv, t[1] * inv), pack2(t[2] * inv, t[3] * inv), pack2(t[4] * inv, t[5] * inv), pack2(t[6] * inv, t[7] * inv));
          stsm2(pa + (((4 + ((ln >> 3) & 1)) ^ rr) << 4), pack2(t[8] * inv, t[9] * inv), 0u);
          fence_async();
          bar_arrive<B_PX, 256>();
          if (w == 0) TS(10);
        }
      } else {
        bar_arrive<B_QK, 256>();
        if (w == 2) {
          bar_sync<B_VHALF, 192>();
          if (lane == 0 && s > 0) { __threadfence(); red_add(flag + (s - 1) * 48, 1); }
          __syncwarp();
        }
        if (w == 0 && s + 1 == NSEG) bar_sync<B_VHALF, 192>();
        if (w == 0 && s + 1 < NSEG) {
          if (lane == 0) mbar_expect(bar + 8 * MB_XF, 40960);
          const int ln = blockIdx.x * 2 + (lane - 16), s2 = s + 2;
          if (lane >= 16 && lane < 18 && ln < 160 && s2 < NSEG - 1) {
            const int tile = ln >> 4, off = (ln & 15) << 7;
            const uint8_t* p = ar + (s2 >> 2) * AR_GROUP + (s2 & 1) * 128 + ((s2 >> 1) & 1) * 512 + ((tile >> 2) * 8 + (tile & 3)) * 4096 +
                               (off >> 10) * 16384 + ((off >> 7) & 1) * 256 + ((off >> 8) & 3) * 1024;
            asm volatile("prefetch.global.L2 [%0];" :: "l"(p));
          }
          const bool own = lane == 9 || (uint32_t)(lane - 3 * rank) < 3u;
          bar_sync<B_VHALF, 192>();
          if (lane < 10 && own) bulk_g2s(sb + O_H + lane * 5120 + 1024, g_xn + (s + 1) * 40960 + lane * 4096, 4096, bar + 8 * MB_XF);
          bar_sync<B_VDONE, 160>();
          if (lane < 10 && !own) bulk_g2s(sb + O_H + lane * 5120 + 1024, g_xn + (s + 1) * 40960 + lane * 4096, 4096, bar + 8 * MB_XF);
        }
      }
      if (s + 1 < NSEG) bar_sync<wg == 0 ? B_XGO : B_XGO1, 256>();
    }
}

__global__ void __launch_bounds__(384, 1)
rec_kernel(const __grid_constant__ CUtensorMap tmq, const __grid_constant__ CUtensorMap tmk,
           const __grid_constant__ CUtensorMap tmv, const __grid_constant__ CUtensorMap tmo,
           const bf16* __restrict__ mem0, uint8_t* __restrict__ ar, uint32_t* __restrict__ flags, int layer) {
  extern __shared__ __align__(1024) uint8_t smem[];
  const uint32_t sb = smem_u32(smem);
  const int tid = threadIdx.x, wid = __shfl_sync(~0u, tid >> 5, 0), wg = wid >> 2, w = wid & 3, lane = tid & 31, g = lane >> 2, i4 = lane & 3;
  uint32_t rank; asm("mov.u32 %0, %%cluster_ctarank;" : "=r"(rank));
  const int head = blockIdx.x / 3;
  const int e0 = head * DH + rank * 64;
  const uint32_t bar = sb + O_BAR;
  const uint32_t r1 = rank == 2 ? 0 : rank + 1, r2 = rank == 0 ? 2 : rank - 1;
  const uint32_t sb1 = mapa(sb, r1), sb2 = mapa(sb, r2);

  GT(layer * 4 + 1, 0);
  if (tid == 0) {
    for (int k = 0; k < 24; k++) mbar_init(bar + 8 * k, 1);
    asm volatile("fence.mbarrier_init.release.cluster;" ::: "memory");
    fence_async();
    for (int p = 0; p < 5; p++) {
      mbar_expect(bar + 8 * (MB_W + p), 16384);
      tma5d(sb + p * 16384, &tmq, e0, p * 8, bar + 8 * (MB_W + p));
      mbar_expect(bar + 8 * (MB_W + 5 + p), 16384);
      tma5d(sb + 81920 + p * 16384, &tmk, e0, p * 8, bar + 8 * (MB_W + 5 + p));
    }
  }
  asm volatile("griddepcontrol.wait;" ::: "memory");
  asm volatile("griddepcontrol.launch_dependents;");
  if (tid == 0) {
    mbar_expect(bar + 8 * MB_XF, 40960);
    for (int c = 0; c < 10; c++) bulk_g2s(sb + O_H + c * 5120 + 1024, g_xn + c * 4096, 4096, bar + 8 * MB_XF);
  }
  __syncthreads();

  if (wg == 0) {
    asm volatile("setmaxnreg.inc.sync.aligned.u32 " STR(REG_A) ";");
    qk_role<0>(sb, sb1, sb2, tid, w, rank, ar, flags + (e0 >> 10) * 8, layer);
  } else if (wg == 1) {
    asm volatile("setmaxnreg.inc.sync.aligned.u32 " STR(REG_C) ";");
    qk_role<1>(sb, sb1, sb2, tid, w, rank, ar, flags + (e0 >> 10) * 8, layer);
  } else {
    asm volatile("setmaxnreg.dec.sync.aligned.u32 " STR(REG_B) ";");
    bar_sync<B_ALL, 384>();
    if (tid == 256) {
      fence_async();
      mbar_expect(bar + 8 * (MB_W + 11), 81920);
      for (int p = 0; p < 5; p++) tma5d(sb + O_WV + p * 16384, &tmv, e0, p * 8, bar + 8 * (MB_W + 11));
      mbar_expect(bar + 8 * (MB_W + 12), 81920);
      tma2d(sb + O_WO + 73728, &tmo, 576, e0, bar + 8 * (MB_W + 12));
      for (int p = 0; p < 9; p++) tma2d(sb + O_WO + p * 8192, &tmo, (rank * 3 + p / 3) * 64, head * DH + (p % 3) * 64, bar + 8 * (MB_W + 12));
    }
    float cbound;
    {
      float mx = 0.f;
      const float* nrm = (const float*)(g_zero + Z_NORM);
      for (int c = lane; c < DM; c += 32) mx = fmaxf(mx, nrm[c]);
#pragma unroll
      for (int o = 16; o; o >>= 1) mx = fmaxf(mx, __shfl_xor_sync(~0u, mx, o));
      cbound = sqrtf(mx) * sqrtf(nrm[640]) * (25.2982213f * 1.1f);
    }
    cluster_sync();
    const int t = tid & 127;
    const int myT = w == 0 ? 9 : rank * 3 + w - 1;
    const int tok = 2 * ((lane >> 1) & 3) + ((lane >> 3) & 1);
    const uint32_t fw_off = O_H + myT * 5120 + tok * 128 + (((2 * (lane >> 4) + (lane & 1)) ^ tok) << 4);
    const uint32_t prod_off = (w >> 1) * 16384 + (w & 1) * 2048 + ((g >> 1) & 1) * 256 + (i4 * 2 + (g >> 2)) * 16 + (g & 1) * 8;
    const uint32_t cons_off = ((myT >> 2) * 8 + (myT & 3)) * 4096 + (lane >> 3) * 1024 + (lane & 7) * 16;
    uint32_t tile_off[3];
#pragma unroll
    for (int k = 0; k < 3; k++) { const int T = rank * 3 + k; tile_off[k] = ((T >> 2) * 8 + (T & 3)) * 4096; }
    constexpr uint32_t T9_OFF = 17 * 4096;

    auto forward = [&](const uint32_t* p) {
      const uint32_t o = opaque(fw_off), bo = O_BAR + 8 * (MB_MF + w);
      sts4(sb + o, p[0], p[1], p[2], p[3]);
      sts4(sb + (o ^ 64), p[4], p[5], p[6], p[7]);
      fence_async();
      __syncwarp();
      if (lane == 0) {
        const uint32_t c = O_H + myT * 5120;
        if (w > 0) { bulk_s2c(sb1 + c, sb + c, 1024, sb1 + bo); bulk_s2c(sb2 + c, sb + c, 1024, sb2 + bo); mbar_expect(sb + bo, 2048); }
        else mbar_arrive(sb + bo);
      }
      uint32_t mx = 0;
#pragma unroll
      for (int k = 0; k < 8; k++) mx = __vmaxu2(mx, p[k] & 0x7FFF7FFFu);
      mx = max(mx & 0xFFFFu, mx >> 16);
      mx = __reduce_max_sync(~0u, mx);
      if (lane < 3) { const uint32_t b = mapa(sb, lane); sta1(b + O_MAXS + (rank * 4 + w) * 4, mx << 16, b + O_BAR + 8 * MB_SM); }
    };
    {
      if (t == 4) mbar_expect(bar + 8 * MB_OG, 2048);
      const uint32_t* mp = (const uint32_t*)(mem0 + tok * DM + myT * 64 + 16 * (lane >> 4) + 4 * (lane & 1));
      const uint32_t p[8] = {mp[0], mp[4], mp[1], mp[5], mp[16], mp[20], mp[17], mp[21]};
      forward(p);
    }
    mbar_wait(bar + 8 * (MB_W + 11), 0);
    mbar_wait(bar + 8 * (MB_W + 12), 0);

    const uint32_t la_w = sb + ((lane >> 4) * 8 + (lane & 7)) * 128 + (((2 * w + ((lane >> 3) & 1)) ^ (lane & 7)) << 4);
    for (int s = 0; s < NSEG; s++) {
      const uint32_t par = s & 1;
      uint32_t vf[10];
      uint32_t pm[5];
      float sc, isc;
      {
        float av[20];
        uint32_t af[V_RS > 0 ? V_RS : 1][4];
        const uint32_t sbo = opaque(sb);
        const uint64_t da = mkdesc(sbo + O_WV, 1024, 1024, 1), db = mkdesc(sbo + O_H, 16, 1024, 1);
#pragma unroll
        for (int k = 0; k < V_RS; k++) ldsm4t(af[k], la_w + O_WV + r1 * 24576 + k * 2048);
        bar_sync<B_VOWN, 384>();
        wg_fence();
#pragma unroll
        for (int k = 0; k < 4; k++) wg_ss_n40_ta1_tb0(av, da + (36 + k) * 128, db + ((9 * 5120 + k * 32) >> 4), k);
        {
          const uint64_t da0 = da + rank * 1536, db0 = db + rank * 960;
#pragma unroll
          for (int k = 0; k < 12; k++) wg_ss_n40_ta1_tb0(av, da0 + k * 128, db0 + (((k >> 2) * 5120 + (k & 3) * 32) >> 4), 1);
        }
        wg_commit();
        if (w == 0) TS(29);
        const uint64_t da1 = da + r1 * 1536, db1 = db + r1 * 960, da2 = da + r2 * 1536, db2 = db + r2 * 960;
#define VREST(k0, k1) _Pragma("unroll") for (int k = k0; k < k1; k++) \
          wg_ss_n40_ta1_tb0(av, (k < 12 ? da1 : da2) + (k % 12) * 128, (k < 12 ? db1 : db2) + ((((k % 12) >> 2) * 5120 + (k & 3) * 32) >> 4), 1);
        bar_sync<B_VGO, 384>();
        wg_wait<0>();
        wg_fence();
#pragma unroll
        for (int k = 0; k < V_RS; k++) wg_rs_n40_tb0(av, af[k], db1 + (((k >> 2) * 5120 + (k & 3) * 32) >> 4), 1);
        if (w == 0) TS(11);
        bar_sync<B_SISS, 256>();
        wg_fence();
        VREST(V_RS, V_K1)
        bar_sync<B_SSENT, 256>();
        bar_arrive<B_VHALF, 192>();
        wg_fence();
        VREST(V_K1, V_K2)
        if (V_K2 < 24) {
          bar_sync<B_SLD, 256>();
          wg_fence();
          VREST(V_K2, 24)
        }
        wg_commit();
        if (w == 0) TS(12);
        const uint32_t ln = opaque(lane), pa = sb + O_QM + (ln & 7) * 128;
        wg_wait<0>();
        pin<20>(av);
        if (s + 1 < NSEG) bar_arrive<B_VDONE, 160>();
        if (w == 0) TS(13);
#pragma unroll
        for (int k = 0; k < 10; k++) vf[k] = pack2(av[2 * k], av[2 * k + 1]);
        bar_sync<B_PM, 160>();
        ldsm4(pm, pa + (((ln >> 3) ^ (ln & 7)) << 4));
        ldsm1(pm[4], pa + ((4 ^ (ln & 7)) << 4));
      }
      uint8_t* arp = ar + (s >> 2) * AR_GROUP + (s & 1) * 128 + ((s >> 1) & 1) * 512;
      uint32_t t1 = 0;
      if (s + 1 < NSEG) {
        {
          float o0[4] = {0.f, 0.f, 0.f, 0.f}, o1[4] = {0.f, 0.f, 0.f, 0.f};
          mma16816(o0, vf, pm[0], pm[1]);
          mma16816(o1, vf + 4, pm[2], pm[3]);
          mma1688(o0, vf[8], vf[9], pm[4]);
          const uint32_t mxl = lds1(sb + O_MAXS + 4 * min(opaque(lane), 11u));
          const uint32_t p0 = pack2(o0[0] + o1[0], o0[1] + o1[1]), p1 = pack2(o0[2] + o1[2], o0[3] + o1[3]);
          const uint32_t o = O_OG + rank * 2048 + w * 256 + opaque(lane) * 4;
          sta1(sb1 + o, p0, sb1 + O_BAR + 8 * MB_OG); sta1(sb1 + o + 128, p1, sb1 + O_BAR + 8 * MB_OG);
          sta1(sb2 + o, p0, sb2 + O_BAR + 8 * MB_OG); sta1(sb2 + o + 128, p1, sb2 + O_BAR + 8 * MB_OG);
          sts1(sb + o, p0); sts1(sb + o + 128, p1);
          fence_async();
          bar_sync<B_WG2, 128>();
          const float b = cbound * fmaxf(1.f, __uint_as_float(__reduce_max_sync(~0u, mxl)));
          const uint32_t eb = min(max(__float_as_uint(b) >> 23, 27u), 254u);
          sc = __uint_as_float((280u - eb) << 23);
          isc = __uint_as_float((eb - 26u) << 23);
        }
        float c9[4], ca[4], cb[4], cc[4];
        uint8_t* pp = arp + opaque(prod_off);
        const uint32_t sbo = opaque(sb);
        const uint64_t da = mkdesc(sbo + O_WO, 1024, 1024, 1), db = mkdesc(sbo + O_OG, 128, 128, 0);
        const uint64_t da0 = da + rank * 512, db0 = db + rank * 128;
        const uint64_t da1 = da + r1 * 512, db1 = db + r1 * 128;
        const uint64_t da2 = da + r2 * 512, db2 = db + r2 * 128;
        wg_fence();
#pragma unroll
        for (int k = 0; k < 4; k++) wg_ss_n8_ta1_tb1(c9, da + 4608 + k * 128, db0 + k * 16, k);
        wg_commit();
        if (w == 0) TS(14);
#pragma unroll
        for (int k = 0; k < 4; k++) wg_ss_n8_ta1_tb1(ca, da0 + k * 128, db0 + k * 16, k);
#pragma unroll
        for (int k = 0; k < 4; k++) wg_ss_n8_ta1_tb1(cb, da0 + 1536 + k * 128, db0 + k * 16, k);
#pragma unroll
        for (int k = 0; k < 4; k++) wg_ss_n8_ta1_tb1(cc, da0 + 3072 + k * 128, db0 + k * 16, k);
        wg_commit();
        wg_wait<1>();
        pin<4>(c9);
        fix_red(pp + T9_OFF, c9, sc);
        mbar_wait(bar + 8 * MB_OG, par);
        FENCE_RX();
        wg_fence();
#pragma unroll
        for (int k = 0; k < 4; k++) wg_ss_n8_ta1_tb1(ca, da1 + k * 128, db1 + k * 16, 1);
        if (w == 0) TS(15);
#pragma unroll
        for (int k = 0; k < 4; k++) wg_ss_n8_ta1_tb1(ca, da2 + k * 128, db2 + k * 16, 1);
        wg_commit();
#pragma unroll
        for (int k = 0; k < 4; k++) wg_ss_n8_ta1_tb1(cb, da1 + 1536 + k * 128, db1 + k * 16, 1);
#pragma unroll
        for (int k = 0; k < 4; k++) wg_ss_n8_ta1_tb1(cb, da2 + 1536 + k * 128, db2 + k * 16, 1);
        wg_commit();
        wg_wait<1>();
        pin<4>(ca);
        fix_red(pp + tile_off[0], ca, sc);
        if (w == 0) TS(16);
        wg_fence();
#pragma unroll
        for (int k = 0; k < 4; k++) wg_ss_n8_ta1_tb1(cc, da1 + 3072 + k * 128, db1 + k * 16, 1);
#pragma unroll
        for (int k = 0; k < 4; k++) wg_ss_n8_ta1_tb1(cc, da2 + 3072 + k * 128, db2 + k * 16, 1);
        wg_commit();
        wg_wait<1>();
        pin<4>(cb);
        fix_red(pp + tile_off[1], cb, sc);
        wg_wait<0>();
        pin<4>(cc);
        fix_red(pp + tile_off[2], cc, sc);
        t1 = clk();
        bar_arrive<B_XGO1, 256>();
        bar_arrive<B_XGO, 256>();
        if (w == 0) TS(17);
      }
      uint4 oq0, oq1;
      uint8_t* op;
      {
        float ox[16];
        const uint32_t vz[4] = {vf[8], vf[9], 0u, 0u};
        const uint64_t dp = mkdesc(opaque(sb) + O_QK, 16, 2048, 1);
        bar_sync<B_PX, 256>();
        wg_fence();
        wg_rs_n32_tb0(ox, vf, dp, 0);
        wg_rs_n32_tb0(ox, vf + 4, dp + 2, 1);
        wg_rs_n32_tb0(ox, vz, dp + 4, 1);
        wg_commit();
        const uint32_t ln = opaque(lane);
        op = g_ot + (size_t)s * (HE * 64) + (e0 + 16 * w) * 64 + (ln & 3) * 128 + (ln >> 2) * 16;
        wg_wait<0>();
        pin<16>(ox);
        if (s + 1 < NSEG) bar_arrive<B_PFREE, 384>();
        oq0 = make_uint4(pack2(ox[0], ox[1]), pack2(ox[4], ox[5]), pack2(ox[8], ox[9]), pack2(ox[12], ox[13]));
        oq1 = make_uint4(pack2(ox[2], ox[3]), pack2(ox[6], ox[7]), pack2(ox[10], ox[11]), pack2(ox[14], ox[15]));
        if (OX_POS == 0 || s + 1 == NSEG) { stg4(op, oq0); stg4(op + 512, oq1); }
        if (w == 0) TS(28);
      }
      if (s + 1 < NSEG) {
        if (t == 4) mbar_expect(bar + 8 * MB_OG, 2048);
        const uint8_t* cp = arp + opaque(cons_off);
        const uint32_t need = w == 0 ? 96 : 32;
        const int dly = w == 0 ? POLL_D0 : POLL_DELAY - (3 - w) * POLL_STEP;
        uint4 y[4];
        int it = 0;
        while ((int)(clk() - t1) < dly) {}
        if (w == 3) TS(18);
        while (true) {
          y[0] = ld_poll(cp); y[1] = ld_poll(cp + 256); y[2] = ld_poll(cp + 16384); y[3] = ld_poll(cp + 16384 + 256);
          if (OX_POS == 1 && it == 0) { stg4(op, oq0); stg4(op + 512, oq1); }
          const uint32_t bad = (y[0].x ^ need) | (y[0].z ^ need) | (y[1].x ^ need) | (y[1].z ^ need) | (y[2].x ^ need) | (y[2].z ^ need) | (y[3].x ^ need) | (y[3].z ^ need);
          if (!__any_sync(~0u, (bad & 127u) != 0)) break;
          if (++it > 2000000) __trap();
        }
        uint32_t p[8];
#pragma unroll
        for (int k = 0; k < 4; k++) {
          const float l0 = (float)((int)__funnelshift_r(y[k].x, y[k].y, 3) >> 4) * isc, h0 = (float)((int)(y[k].y + 4u) >> 3) * isc;
          const float l1 = (float)((int)__funnelshift_r(y[k].z, y[k].w, 3) >> 4) * isc, h1 = (float)((int)(y[k].w + 4u) >> 3) * isc;
          p[2 * k] = pack2(l0, l1); p[2 * k + 1] = pack2(h0, h1);
        }
        TS(19 + w);
        forward(p);
        if (OX_POS == 2) { stg4(op, oq0); stg4(op + 512, oq1); }
      }
    }
    bar_sync<B_WG2, 128>();
    if (t == 0) { __threadfence(); red_add(flags + (e0 >> 10) * 8 + (NSEG - 1) * 48, 1); }
    __syncwarp();
  }
  cluster_sync();
  GT(layer * 4 + 1, 2);
}

constexpr int P_B = 0, P_A = 131072, P_BAR = 196608, OPC_SMEM = P_BAR + 256;
constexpr int OP_KR = 48;

__global__ void __launch_bounds__(384, 1)
opc_kernel(const __grid_constant__ CUtensorMap tmo, uint32_t* __restrict__ flags, float* __restrict__ acc,
           float* __restrict__ xres, uint8_t* __restrict__ xa, bf16* __restrict__ out) {
  const int layer = out != nullptr;
  asm volatile("griddepcontrol.launch_dependents;");
  GT(layer * 4 + 2, 0);
  extern __shared__ __align__(1024) uint8_t smem[];
  const uint32_t sb = smem_u32(smem);
  const int tid = threadIdx.x, wid = __shfl_sync(~0u, tid >> 5, 0), wg = wid >> 2, w = wid & 3, lane = tid & 31;
  const uint32_t bar = sb + P_BAR;
  if (blockIdx.x < 30) {
    const int cg = blockIdx.x % 5, kg = blockIdx.x / 5;
    if (tid == 0) {
      for (int k = 0; k < 16; k++) mbar_init(bar + 8 * k, (k == 8 || k == 9) ? 8 : 1);
      fence_async();
      mbar_expect(bar + 80, 131072);
      for (int p = 0; p < 16; p++) tma2d(sb + P_B + p * 8192, &tmo, cg * 128 + (p >> 3) * 64, kg * 1024 + (p & 7) * 64, bar + 80);
      mbar_expect(bar + 96, 65536);
      for (int p = 0; p < 8; p++) tma2d(sb + P_A + p * 8192, &tmo, cg * 128 + (p >> 2) * 64, kg * 1024 + 768 + (p & 3) * 64, bar + 96);
    }
    __syncthreads();
    if (wg < 2) {
      asm volatile("setmaxnreg.inc.sync.aligned.u32 240;");
      uint32_t a[OP_KR][4];
      const uint32_t la = sb + P_B + ((lane >> 4) * 8 + (lane & 7)) * 128 + (((2 * w + ((lane >> 3) & 1)) ^ (lane & 7)) << 4);
      mbar_wait(bar + 80, 0);
#pragma unroll
      for (int k = 0; k < 32; k++) ldsm4t(a[k], la + wg * 65536 + k * 2048);
      bar_sync<1, 256>();
      if (tid == 0) {
        fence_async();
        mbar_expect(bar + 88, 65536);
        for (int p = 0; p < 8; p++) tma2d(sb + P_B + p * 8192, &tmo, cg * 128 + (p >> 2) * 64, kg * 1024 + 512 + (p & 3) * 64, bar + 88);
      }
      mbar_wait(bar + 88, 0);
#pragma unroll
      for (int k = 0; k < 16; k++) ldsm4t(a[32 + k], la + wg * 32768 + k * 2048);
      fence_async();
      bar_arrive<2, 288>();
      mbar_wait(bar + 96, 0);
      float* ap = acc + (cg * 8 + wg * 4 + w) * 512 + lane * 4;
      for (int s = 0; s < NSEG; s++) {
        const int buf = s & 1;
        const uint32_t par = (s >> 1) & 1;
        float d[16];
        const uint32_t sbo = opaque(sb);
        const uint64_t db = mkdesc(sbo + P_B + buf * 65536, 512, 128, 0), da = mkdesc(sbo + P_A + wg * 32768, 1024, 1024, 1);
#pragma unroll
        for (int q = 0; q < 4; q++) {
          mbar_wait(bar + 8 * (buf * 4 + q), par);
          wg_fence();
#pragma unroll
          for (int k = 16 * q; k < 16 * q + 16; k++) {
            if (k < OP_KR) wg_rs_n32_tb1(d, a[k < OP_KR ? k : 0], db + k * 64, k);
            else wg_ss_n32_ta1_tb1(d, da + (k - OP_KR) * 128, db + k * 64, 1);
          }
        }
        wg_commit();
        wg_wait<0>();
        pin<16>(d);
        if (lane == 0) mbar_arrive(bar + 8 * (8 + buf));
        float* p = ap + s * (32 * DM);
        red4f(p, d[0], d[1], d[4], d[5]);
        red4f(p + 128, d[8], d[9], d[12], d[13]);
        red4f(p + 256, d[2], d[3], d[6], d[7]);
        red4f(p + 384, d[10], d[11], d[14], d[15]);
        bar_sync<1, 256>();
        if (tid == 0) { __threadfence(); red_add(flags + FL_B + s * 8, 1); }
        __syncwarp();
      }
    } else {
      asm volatile("setmaxnreg.dec.sync.aligned.u32 24;");
      if (w == 0) {
        bar_sync<2, 288>();
        if (lane == 0) {
          for (int s = 0; s < NSEG; s++) {
            const int buf = s & 1;
            if (s >= 2) mbar_wait(bar + 8 * (8 + buf), ((s >> 1) & 1) ^ 1);
            wait_flag(flags + FL_A + s * 48 + kg * 8, 16);
            asm volatile("fence.proxy.async;" ::: "memory");
            for (int q = 0; q < 4; q++) {
              mbar_expect(bar + 8 * (buf * 4 + q), 16384);
              bulk_g2s(sb + P_B + buf * 65536 + q * 16384, g_ot + (size_t)s * (HE * 64) + kg * 65536 + q * 16384, 16384, bar + 8 * (buf * 4 + q));
            }
          }
        }
        __syncwarp();
      }
    }
  } else {
    constexpr int LD = 644;
    float* xs = (float*)smem;
    for (int s = blockIdx.x - 30; s < NSEG; s += 6) {
      float2 r[3][10];
#pragma unroll
      for (int j = 0; j < 3; j++) {
        const int row = wid + 12 * j;
        if (row < 32) {
#pragma unroll
          for (int k = 0; k < 10; k++) r[j][k] = __ldcg((const float2*)(xres + (s * 32 + row) * DM + k * 64 + lane * 2));
        }
      }
      if (tid == 0) wait_flag(flags + FL_B + s * 8, 30);
      __syncthreads();
      if (wid < 10) {
        float4 v[16];
#pragma unroll
        for (int k = 0; k < 16; k++) v[k] = __ldcg((const float4*)(acc + s * (32 * DM) + (wid * 16 + k) * 128 + lane * 4));
#pragma unroll
        for (int k = 0; k < 16; k++) {
          const int col = (wid * 4 + (k >> 2)) * 16 + ((k >> 1) & 1) * 8 + (lane >> 2), t0 = (k & 1) * 16 + (lane & 3) * 2;
          xs[t0 * LD + col] = v[k].x; xs[(t0 + 1) * LD + col] = v[k].y; xs[(t0 + 8) * LD + col] = v[k].z; xs[(t0 + 9) * LD + col] = v[k].w;
        }
      }
      __syncthreads();
#pragma unroll
      for (int j = 0; j < 3; j++) {
        const int row = wid + 12 * j, tk = s * 32 + row;
        if (row < 32) {
          float sum = 0.f;
#pragma unroll
          for (int k = 0; k < 10; k++) {
            const float2 u = *(const float2*)(xs + row * LD + k * 64 + lane * 2);
            r[j][k].x += u.x; r[j][k].y += u.y; sum += r[j][k].x + r[j][k].y;
          }
          if (out) {
#pragma unroll
            for (int k = 0; k < 10; k++) *(uint32_t*)(out + tk * DM + k * 64 + lane * 2) = pack2(r[j][k].x, r[j][k].y);
          } else {
#pragma unroll
            for (int k = 0; k < 10; k++) *(float2*)(xres + tk * DM + k * 64 + lane * 2) = r[j][k];
#pragma unroll
            for (int o = 16; o; o >>= 1) sum += __shfl_xor_sync(~0u, sum, o);
            const float m = sum * (1.f / DM);
            float q = 0.f;
#pragma unroll
            for (int k = 0; k < 10; k++) { r[j][k].x -= m; r[j][k].y -= m; q += r[j][k].x * r[j][k].x + r[j][k].y * r[j][k].y; }
#pragma unroll
            for (int o = 16; o; o >>= 1) q += __shfl_xor_sync(~0u, q, o);
            const float rs = rsqrtf(q * (1.f / DM) + 1e-5f);
#pragma unroll
            for (int k = 0; k < 10; k++)
              *(uint32_t*)(xa + ((tk >> 7) * 10 + k) * 16384 + (tk & 127) * 128 + (((lane >> 2) ^ (tk & 7)) << 4) + (lane & 3) * 4) = pack2(r[j][k].x * rs, r[j][k].y * rs);
          }
        }
      }
      __syncthreads();
    }
  }
  GT(layer * 4 + 2, 1);
  asm volatile("griddepcontrol.wait;" ::: "memory");
  GT(layer * 4 + 2, 2);
}

constexpr int L_STAGE = 47104;
constexpr int L_KV = 0, L_B2 = 43008;
constexpr int L_W2 = 122880, L_BAR = L_W2 + 102400;
constexpr int LA_SMEM = L_BAR + 256;
__device__ __forceinline__ float phi(float t) { return (t > 0.f ? t + 1.f : __expf(t)) + 1e-6f; }

__global__ void __launch_bounds__(384, 1)
la_kernel(const bf16* __restrict__ xin, const bf16* __restrict__ Wq, const bf16* __restrict__ Wk, const bf16* __restrict__ Wv,
          const bf16* __restrict__ Wo, uint8_t* __restrict__ ar, int layer) {
  extern __shared__ __align__(1024) uint8_t smem[];
  const uint32_t sb = smem_u32(smem);
  const int tid = threadIdx.x, wid = __shfl_sync(~0u, tid >> 5, 0), wg = wid >> 2, w = wid & 3, lane = tid & 31, g = lane >> 2, i4 = lane & 3;
  const int tb = blockIdx.x >> 3, hg = blockIdx.x & 7;
  const uint32_t bar = sb + L_BAR;
  uint32_t* flags = g_zero + Z_FLAGS + layer * FL_LAYER;
  asm volatile("griddepcontrol.launch_dependents;");
  GT(layer * 4, 0);
  if (tid == 0) {
    for (int k = 0; k < 20; k++) mbar_init(bar + 8 * k, ((k >= 4 && k < 8) || k >= 17) ? 8 : 1);
    fence_async();
  }
  __syncthreads();
  if (wg == 2) {
    asm volatile("setmaxnreg.dec.sync.aligned.u32 40;");
    if (w == 0) {
      if (lane == 0) {
        asm volatile("griddepcontrol.wait;" ::: "memory");
        for (int kc = 0; kc < 10; kc++) {
          const int st = kc & 3;
          if (kc >= 4) mbar_wait(bar + 8 * (4 + st), ((kc >> 2) & 1) ^ 1);
          mbar_expect(bar + 8 * st, L_STAGE);
          bulk_g2s(sb + st * L_STAGE, g_xt + (tb * 10 + kc) * 16384, 16384, bar + 8 * st);
          bulk_g2s(sb + st * L_STAGE + 16384, g_w1 + (hg * 10 + kc) * 30720, 30720, bar + 8 * st);
        }
        mbar_wait(bar + 8 * 6, 1);
        mbar_wait(bar + 8 * 7, 1);
        mbar_expect(bar + 64, 102400);
        for (int p = 0; p < 4; p++) bulk_g2s(sb + L_W2 + p * 25600, g_w2 + hg * 102400 + p * 25600, 25600, bar + 64);
      }
      __syncwarp();
      bar_sync<2, 288>();
      if (lane == 0) {
        wait_flag(flags + FL_O + tb * 8, 8);
        asm volatile("fence.proxy.async;" ::: "memory");
        for (int p = 0; p < 8; p++) {
          if (p >= 6) mbar_wait(bar + 8 * (17 + p - 6), 0);
          mbar_expect(bar + 8 * (9 + p), 20480);
          bulk_g2s(sb + (p % 6) * 20480, g_oa + (tb * 8 + p) * 20480, 20480, bar + 8 * (9 + p));
        }
      }
      __syncwarp();
    } else {
      const int t = tid - 288;
      if (t < 16) {
        const bf16* W = (t >> 2) == 0 ? Wq : (t >> 2) == 1 ? Wk : (t >> 2) == 2 ? Wv : Wo;
        asm volatile("cp.async.bulk.prefetch.L2.global [%0], %1;" :: "l"((const uint8_t*)W + blockIdx.x * 61440 + (t & 3) * 15360), "r"(15360) : "memory");
      }
      asm volatile("griddepcontrol.wait;" ::: "memory");
      for (int k = t; k < 768; k += 96) *(uint4*)(ar + blockIdx.x * 12288 + k * 16) = make_uint4(0, 0, 0, 0);
      for (int k = t; k < 2560; k += 96) *(uint4*)((uint8_t*)g_acc + blockIdx.x * 40960 + k * 16) = make_uint4(0, 0, 0, 0);
      if (layer == 0) {
        float* nrm = (float*)(g_zero + Z_NORM);
        float sv = 0.f;
        const uint4* pv = (const uint4*)((const uint8_t*)Wv + blockIdx.x * 61440) + t;
#pragma unroll 4
        for (int k = 0; k < 40; k++) {
          const uint4 v = __ldg(pv + k * 96);
          sv += bflo(v.x) * bflo(v.x) + bfhi(v.x) * bfhi(v.x) + bflo(v.y) * bflo(v.y) + bfhi(v.y) * bfhi(v.y);
          sv += bflo(v.z) * bflo(v.z) + bfhi(v.z) * bfhi(v.z) + bflo(v.w) * bflo(v.w) + bfhi(v.w) * bfhi(v.w);
        }
#pragma unroll
        for (int o = 16; o; o >>= 1) sv += __shfl_xor_sync(~0u, sv, o);
        if (lane == 0) atomicAdd(nrm + 640, sv);
        if (t < 80) {
          float c[8] = {0.f, 0.f, 0.f, 0.f, 0.f, 0.f, 0.f, 0.f};
          const uint4* po = (const uint4*)((const uint8_t*)Wo + blockIdx.x * 61440) + t;
#pragma unroll 4
          for (int k = 0; k < 48; k++) {
            const uint4 v = __ldg(po + k * 80);
            c[0] += bflo(v.x) * bflo(v.x); c[1] += bfhi(v.x) * bfhi(v.x); c[2] += bflo(v.y) * bflo(v.y); c[3] += bfhi(v.y) * bfhi(v.y);
            c[4] += bflo(v.z) * bflo(v.z); c[5] += bfhi(v.z) * bfhi(v.z); c[6] += bflo(v.w) * bflo(v.w); c[7] += bfhi(v.w) * bfhi(v.w);
          }
          red4f(nrm + t * 8, c[0], c[1], c[2], c[3]);
          red4f(nrm + t * 8 + 4, c[4], c[5], c[6], c[7]);
        }
      }
    }
  } else {
    asm volatile("setmaxnreg.inc.sync.aligned.u32 232;");
    asm volatile("griddepcontrol.wait;" ::: "memory");
    uint32_t pq[5][4];
    {
      float d[120];
#pragma unroll 1
      for (int kc = 0; kc < 10; kc++) {
        const int st = kc & 3;
        const uint64_t da = mkdesc(sb + st * L_STAGE + wg * 8192, 16, 1024, 1), db = mkdesc(sb + st * L_STAGE + 16384, 3840, 128, 0);
        mbar_wait(bar + 8 * st, (kc >> 2) & 1);
        wg_fence();
#pragma unroll
        for (int k = 0; k < 4; k++) wg_ss_n240_ta0_tb1(d, da + 2 * k, db + k * 480, kc | k);
        wg_commit();
        if (kc > 0) { wg_wait<1>(); if (lane == 0) mbar_arrive(bar + 8 * (4 + ((kc - 1) & 3))); }
      }
      wg_wait<0>();
      pin<120>(d);
      bar_sync<1, 256>();
      const uint32_t kb = sb + L_KV + (wg * 8 + 2 * w) * 2688 + lane * 4;
#pragma unroll
      for (int j = 0; j < 10; j++) {
        sts1(kb + j * 128, pack2(phi(d[40 + 4 * j]), phi(d[41 + 4 * j])));
        sts1(kb + 2688 + j * 128, pack2(phi(d[42 + 4 * j]), phi(d[43 + 4 * j])));
        sts1(kb + (10 + j) * 128, pack2(d[80 + 4 * j], d[81 + 4 * j]));
        sts1(kb + 2688 + (10 + j) * 128, pack2(d[82 + 4 * j], d[83 + 4 * j]));
      }
      sts1(kb + 2560, 0x3F803F80u); sts1(kb + 2688 + 2560, 0x3F803F80u);
      fence_async();
      bar_sync<1, 256>();
      float e[44];
      {
        const uint64_t da = mkdesc(sb + L_KV + wg * 1024, 2688, 128, 0), db = mkdesc(sb + L_KV + 1280, 2688, 128, 0);
        wg_fence();
#pragma unroll
        for (int k = 0; k < 8; k++) wg_ss_n88_ta1_tb1(e, da + k * 336, db + k * 336, k);
        wg_commit();
      }
#pragma unroll
      for (int k = 0; k < 5; k++) {
        pq[k][0] = pack2(phi(d[8 * k]), phi(d[8 * k + 1])); pq[k][1] = pack2(phi(d[8 * k + 2]), phi(d[8 * k + 3]));
        pq[k][2] = pack2(phi(d[8 * k + 4]), phi(d[8 * k + 5])); pq[k][3] = pack2(phi(d[8 * k + 6]), phi(d[8 * k + 7]));
      }
      wg_wait<0>();
      pin<44>(e);
      float* kv = (float*)(g_zero + Z_KV) + layer * KV_LAYER + hg * 1920;
#pragma unroll
      for (int h = 0; h < 2; h++) {
        const int row = wg * 64 + 16 * w + 8 * h + g, c0 = (row / 20) * 20;
        if (row < 80) {
#pragma unroll
          for (int j = 0; j < 10; j++) {
            const int c = 8 * j + 2 * i4 - c0;
            if ((uint32_t)c < 20u) asm volatile("red.relaxed.gpu.global.add.v2.f32 [%0], {%1,%2};" :: "l"(kv + row * 24 + c), "f"(e[4 * j + 2 * h]), "f"(e[4 * j + 2 * h + 1]) : "memory");
          }
          if (i4 == 0) atomicAdd(kv + row * 24 + 20, e[40 + 2 * h]);
        }
      }
      bar_sync<1, 256>();
      if (tid == 0) { __threadfence(); red_add(flags + FL_KV + hg * 8, 1); }
      for (int k = tid; k < 1600; k += 256) sts4(sb + L_B2 + k * 16, 0, 0, 0, 0);
      if (tid == 0) wait_flag(flags + FL_KV + hg * 8, 16);
      bar_sync<1, 256>();
#pragma unroll
      for (int it = 0; it < 4; it++) {
        const int k = tid + it * 256;
        if (k < 800) {
          const int dd = k / 10, pr = k - dd * 10, n = (dd / 20) * 20 + 2 * pr;
          const float2 v = __ldcg((const float2*)(kv + dd * 24 + 2 * pr));
          const float z = __ldcg(kv + dd * 24 + 20);
          const uint32_t a = sb + L_B2 + (dd >> 3) * 2560 + (n >> 3) * 128 + (dd & 7) * 16 + (n & 7) * 2;
          sts1(a, pack2(v.x, v.y));
          sts1(a + 1280, pack2(z, z));
        }
      }
      fence_async();
      bar_sync<1, 256>();
    }
    const int row0 = tb * 128 + wg * 64 + 16 * w + g;
    {
      float o[80];
      const uint64_t db = mkdesc(sb + L_B2, 2560, 128, 0);
      wg_fence();
#pragma unroll
      for (int k = 0; k < 5; k++) wg_rs_n160_tb1(o, pq[k], db + k * 320, k);
      wg_commit();
      wg_wait<0>();
      pin<80>(o);
      uint8_t* op = g_oa + (tb * 8 + hg) * 20480 + (wg * 8 + 2 * w) * 128 + lane * 4;
#pragma unroll
      for (int j = 0; j < 10; j++) {
        *(uint32_t*)(op + j * 2048) = pack2(__fdividef(o[4 * j], o[40 + 4 * j] + 1e-6f), __fdividef(o[4 * j + 1], o[41 + 4 * j] + 1e-6f));
        *(uint32_t*)(op + j * 2048 + 128) = pack2(__fdividef(o[4 * j + 2], o[42 + 4 * j] + 1e-6f), __fdividef(o[4 * j + 3], o[43 + 4 * j] + 1e-6f));
      }
      bar_sync<1, 256>();
      if (tid == 0) { __threadfence(); red_add(flags + FL_O + tb * 8, 1); }
      __syncwarp();
      bar_arrive<2, 288>();
    }
    float2 r[20];
#pragma unroll
    for (int j = 0; j < 10; j++) {
#pragma unroll
      for (int h = 0; h < 2; h++) {
        const int idx = (row0 + 8 * h) * DM + hg * 80 + 8 * j + 2 * i4;
        if (xin) { const uint32_t u = __ldg((const uint32_t*)(xin + idx)); r[2 * j + h] = make_float2(bflo(u), bfhi(u)); }
        else r[2 * j + h] = __ldcg((const float2*)(g_x + idx));
      }
    }
    float d[40];
    mbar_wait(bar + 64, 0);
#pragma unroll
    for (int p = 0; p < 8; p++) {
      const uint64_t da = mkdesc(sb + (p % 6) * 20480 + wg * 1024, 2048, 128, 0), db = mkdesc(sb + L_W2 + p * 12800, 1280, 128, 0);
      mbar_wait(bar + 8 * (9 + p), 0);
      wg_fence();
#pragma unroll
      for (int k = 0; k < 5; k++) wg_ss_n80_ta0_tb1(d, da + k * 256, db + k * 160, p | k);
      wg_commit();
      if (p == 1 || p == 2) { wg_wait<1>(); if (lane == 0) mbar_arrive(bar + 8 * (17 + p - 1)); }
    }
    wg_wait<0>();
    pin<40>(d);
    float mean[2], m2[2];
#pragma unroll
    for (int h = 0; h < 2; h++) {
      float sum = 0.f;
#pragma unroll
      for (int j = 0; j < 10; j++) { r[2 * j + h].x += d[4 * j + 2 * h]; r[2 * j + h].y += d[4 * j + 2 * h + 1]; sum += r[2 * j + h].x + r[2 * j + h].y; }
      sum += __shfl_xor_sync(~0u, sum, 1); sum += __shfl_xor_sync(~0u, sum, 2);
      mean[h] = sum * (1.f / 80.f);
      float q = 0.f;
#pragma unroll
      for (int j = 0; j < 10; j++) { const float a = r[2 * j + h].x - mean[h], b = r[2 * j + h].y - mean[h]; q += a * a + b * b; }
      q += __shfl_xor_sync(~0u, q, 1); q += __shfl_xor_sync(~0u, q, 2);
      m2[h] = q;
    }
    float2* st = g_stats + (layer * S_TOK + row0) * 8;
    if (i4 < 2) {
      const float a = i4 ? mean[1] : mean[0], b = i4 ? m2[1] : m2[0];
      asm volatile("{\n.reg .b64 t;\nmov.b64 t, {%1,%2};\nst.relaxed.gpu.global.b64 [%0], t;\n}" :: "l"(st + i4 * 64 + hg), "r"(__float_as_uint(a)), "r"(__float_as_uint(b) & 0x7FFFFFFFu) : "memory");
    }
#pragma unroll
    for (int j = 0; j < 10; j++) {
      *(float2*)(g_x + row0 * DM + hg * 80 + 8 * j + 2 * i4) = r[2 * j];
      *(float2*)(g_x + (row0 + 8) * DM + hg * 80 + 8 * j + 2 * i4) = r[2 * j + 1];
    }
    uint4 y0, y1;
    int it = 0;
    while (true) {
      y0 = ld_poll(st + 2 * i4); y1 = ld_poll(st + 64 + 2 * i4);
      if (!__any_sync(~0u, (int)(y0.y | y0.w | y1.y | y1.w) < 0)) break;
      if (++it > 2000000) __trap();
    }
    float rs[2];
#pragma unroll
    for (int h = 0; h < 2; h++) {
      const uint4 y = h ? y1 : y0;
      const float ma = __uint_as_float(y.x), mb = __uint_as_float(y.z);
      float sm = ma + mb;
      sm += __shfl_xor_sync(~0u, sm, 1); sm += __shfl_xor_sync(~0u, sm, 2);
      mean[h] = sm * 0.125f;
      float q = __uint_as_float(y.y) + __uint_as_float(y.w) + 80.f * ((ma - mean[h]) * (ma - mean[h]) + (mb - mean[h]) * (mb - mean[h]));
      q += __shfl_xor_sync(~0u, q, 1); q += __shfl_xor_sync(~0u, q, 2);
      rs[h] = rsqrtf(q * (1.f / DM) + 1e-5f);
    }
#pragma unroll
    for (int h = 0; h < 2; h++) {
      const int tk = row0 + 8 * h;
      uint8_t* xp = g_xn + (tk >> 5) * 40960 + (tk & 31) * 128 + (i4 & 1) * 8;
#pragma unroll
      for (int jj = 0; jj < 5; jj++) {
        const int b16 = hg * 5 + jj;
        const float2 a = r[4 * jj + h], b = r[4 * jj + 2 + h];
        *(uint2*)(xp + (b16 >> 2) * 4096 + (((2 * (b16 & 3) + (i4 >> 1)) ^ g) << 4)) =
            make_uint2(pack2((a.x - mean[h]) * rs[h], (a.y - mean[h]) * rs[h]), pack2((b.x - mean[h]) * rs[h], (b.y - mean[h]) * rs[h]));
      }
    }
    GT(layer * 4, 2);
  }
}

__global__ void __launch_bounds__(256) prep_kernel(const bf16* __restrict__ x, const bf16* __restrict__ wqkv, const bf16* __restrict__ wo) {
  asm volatile("griddepcontrol.launch_dependents;");
  const int b = blockIdx.x, tid = threadIdx.x, lane = tid & 31;
  if (b < 160) GT(3, 0);
  if (b < 256) {
    const int row = b * 8 + (tid >> 5);
    float v[20], s = 0.f;
#pragma unroll
    for (int k = 0; k < 10; k++) { const uint32_t u = __ldg((const uint32_t*)(x + row * DM + k * 64 + lane * 2)); v[2 * k] = bflo(u); v[2 * k + 1] = bfhi(u); s += v[2 * k] + v[2 * k + 1]; }
#pragma unroll
    for (int o = 16; o; o >>= 1) s += __shfl_xor_sync(~0u, s, o);
    const float m = s * (1.f / DM);
    float q = 0.f;
#pragma unroll
    for (int k = 0; k < 20; k++) { v[k] -= m; q += v[k] * v[k]; }
#pragma unroll
    for (int o = 16; o; o >>= 1) q += __shfl_xor_sync(~0u, q, o);
    const float r = rsqrtf(q * (1.f / DM) + 1e-5f);
#pragma unroll
    for (int k = 0; k < 10; k++)
      *(uint32_t*)(g_xt + ((row >> 7) * 10 + k) * 16384 + (row & 127) * 128 + (((lane >> 2) ^ (row & 7)) << 4) + (lane & 3) * 4) = pack2(v[2 * k] * r, v[2 * k + 1] * r);
  } else if (b < 256 + 200) {
#pragma unroll
    for (int it = 0; it < 4; it++) {
      const int u = (b - 256) * 1024 + it * 256 + tid;
      if (u < 153600) {
        const int k8 = u & 7, nb = (u >> 3) % 30, kg = (u / 240) % 80, hg = u / 19200;
        *(uint4*)(g_w1 + u * 16) = __ldg((const uint4*)(wqkv + (kg * 8 + k8) * 1920 + (nb / 10) * 640 + hg * 80 + (nb % 10) * 8));
      } else {
        const int v = u - 153600, k8 = v & 7, nb = (v >> 3) % 10, kg = (v / 80) % 80, hg = v / 6400;
        *(uint4*)(g_w2 + v * 16) = __ldg((const uint4*)(wo + (kg * 8 + k8) * DM + hg * 80 + nb * 8));
      }
    }
  } else {
    const int t = (b - 456) * 256 + tid;
    for (int k = t; k < Z_END / 4; k += 16 * 256) ((uint4*)g_zero)[k] = make_uint4(0, 0, 0, 0);
    for (int k = t; k < 2 * S_TOK * 4; k += 16 * 256) ((uint4*)g_stats)[k] = make_uint4(~0u, ~0u, ~0u, ~0u);
  }
  if (b < 160) GT(3, 2);
}

typedef CUresult (*EncodeFn)(CUtensorMap*, CUtensorMapDataType, cuuint32_t, void*, const cuuint64_t*, const cuuint64_t*, const cuuint32_t*,
                             const cuuint32_t*, CUtensorMapInterleave, CUtensorMapSwizzle, CUtensorMapL2promotion, CUtensorMapFloatOOBfill);
static void make_map(EncodeFn fn, CUtensorMap* m, const void* p, uint64_t cols, uint64_t rows, uint32_t bc, uint32_t br) {
  cuuint64_t dims[2] = {cols, rows}; cuuint64_t strides[1] = {cols * 2}; cuuint32_t box[2] = {bc, br}; cuuint32_t es[2] = {1, 1};
  fn(m, CU_TENSOR_MAP_DATA_TYPE_BFLOAT16, 2, (void*)p, dims, strides, box, es, CU_TENSOR_MAP_INTERLEAVE_NONE, CU_TENSOR_MAP_SWIZZLE_128B,
     CU_TENSOR_MAP_L2_PROMOTION_L2_128B, CU_TENSOR_MAP_FLOAT_OOB_FILL_NONE);
}

static void make_map_perm(EncodeFn fn, CUtensorMap* m, const void* p) {
  cuuint64_t dims[5] = {HE, 2, 2, 4, 40}; const cuuint64_t r = HE * 2; cuuint64_t strides[4] = {r, 8 * r, 2 * r, 16 * r};
  cuuint32_t box[5] = {64, 2, 2, 4, 8}; cuuint32_t es[5] = {1, 1, 1, 1, 1};
  fn(m, CU_TENSOR_MAP_DATA_TYPE_BFLOAT16, 5, (void*)p, dims, strides, box, es, CU_TENSOR_MAP_INTERLEAVE_NONE, CU_TENSOR_MAP_SWIZZLE_128B,
     CU_TENSOR_MAP_L2_PROMOTION_L2_128B, CU_TENSOR_MAP_FLOAT_OOB_FILL_NONE);
}

extern "C" void kernel_launch(void* const* d_in, const int* in_sizes, int n_in, void* d_out, int out_size) {
  const bf16* x = (const bf16*)d_in[0];
  const bf16* wqkv = (const bf16*)d_in[1];
  const bf16* wo_a = (const bf16*)d_in[2];
  const bf16* mem0 = (const bf16*)d_in[4];
  const bf16* Wq = (const bf16*)d_in[5];
  const bf16* Wk = (const bf16*)d_in[6];
  const bf16* Wv = (const bf16*)d_in[7];
  const bf16* Wo = (const bf16*)d_in[8];
  cudaStream_t st = cudaStreamPerThread;

  static EncodeFn enc = nullptr;
  static uint8_t *p_ar, *p_xt; static uint32_t* p_zero; static float *p_acc, *p_x;
  if (!enc) {
    cudaDriverEntryPointQueryResult qr;
    void* fn = nullptr;
    cudaGetDriverEntryPoint("cuTensorMapEncodeTiled", &fn, cudaEnableDefault, &qr);
    enc = (EncodeFn)fn;
    cudaFuncSetAttribute(rec_kernel, cudaFuncAttributeMaxDynamicSharedMemorySize, REC_SMEM);
    cudaFuncSetAttribute(opc_kernel, cudaFuncAttributeMaxDynamicSharedMemorySize, OPC_SMEM);
    cudaFuncSetAttribute(la_kernel, cudaFuncAttributeMaxDynamicSharedMemorySize, LA_SMEM);
    cudaGetSymbolAddress((void**)&p_ar, g_ar); p_ar = (uint8_t*)(((uintptr_t)p_ar + 32767) & ~(uintptr_t)32767);
    cudaGetSymbolAddress((void**)&p_xt, g_xt); cudaGetSymbolAddress((void**)&p_zero, g_zero);
    cudaGetSymbolAddress((void**)&p_acc, g_acc); cudaGetSymbolAddress((void**)&p_x, g_x);
  }
  CUtensorMap tmq, tmk, tmv, tmo;
  make_map_perm(enc, &tmq, Wq);
  make_map_perm(enc, &tmk, Wk);
  make_map_perm(enc, &tmv, Wv);
  make_map(enc, &tmo, Wo, DM, HE, 64, 64);

  cudaLaunchAttribute at[2];
  at[0].id = cudaLaunchAttributeProgrammaticStreamSerialization; at[0].val.programmaticStreamSerializationAllowed = 1;
  at[1].id = cudaLaunchAttributeClusterDimension; at[1].val.clusterDim.x = 3; at[1].val.clusterDim.y = 1; at[1].val.clusterDim.z = 1;
  prep_kernel<<<472, 256, 0, st>>>(x, wqkv, wo_a);
  for (int l = 0; l < 2; l++) {
    cudaLaunchConfig_t cfg = {};
    cfg.blockDim = dim3(384); cfg.stream = st;
    cfg.gridDim = dim3(128); cfg.dynamicSmemBytes = LA_SMEM; cfg.attrs = at; cfg.numAttrs = LA_PDL;
    cudaLaunchKernelEx(&cfg, la_kernel, l == 0 ? x : (const bf16*)nullptr, Wq, Wk, Wv, Wo, p_ar, l);
    cfg.gridDim = dim3(96); cfg.dynamicSmemBytes = REC_SMEM; cfg.attrs = at + 1 - REC_PDL; cfg.numAttrs = 1 + REC_PDL;
    cudaLaunchKernelEx(&cfg, rec_kernel, tmq, tmk, tmv, tmo, mem0, p_ar, p_zero + Z_FLAGS + l * FL_LAYER, l);
    cfg.gridDim = dim3(36); cfg.dynamicSmemBytes = OPC_SMEM; cfg.attrs = at; cfg.numAttrs = OPC_PDL;
    cudaLaunchKernelEx(&cfg, opc_kernel, tmo, p_zero + Z_FLAGS + l * FL_LAYER, p_acc, p_x, p_xt, l == 1 ? (bf16*)d_out : (bf16*)nullptr);
  }
}
```

```cpp
#include <cuda_runtime.h>
#include <cuda_bf16.h>
#include <cuda.h>
#include <stdint.h>

typedef __nv_bfloat16 bf16;
typedef unsigned long long u64;

constexpr int S_TOK = 2048, DM = 640, DH = 192, HE = 6144, NSEG = 64;

constexpr int AR_GROUP = 98304;
constexpr int AR_LAYER = 16 * AR_GROUP;
__device__ __align__(1024) uint8_t g_ar[2 * AR_LAYER + 32768];
__device__ __align__(1024) uint8_t g_xn[NSEG * 40960];
__device__ __align__(1024) uint8_t g_xt[S_TOK * DM * 2];
__device__ __align__(1024) uint8_t g_ot[NSEG * HE * 64];
__device__ __align__(1024) uint8_t g_oa[S_TOK * DM * 2];
__device__ __align__(1024) uint8_t g_w1[DM * 1920 * 2];
__device__ __align__(1024) uint8_t g_w2[DM * DM * 2];
__device__ __align__(1024) float g_acc[2 * S_TOK * DM];
__device__ __align__(1024) bf16 g_x[S_TOK * DM];
constexpr int FL_A = 0, FL_B = 64 * 6 * 8, FL_KV = FL_B + 64 * 8, FL_O = FL_KV + 8 * 8, FL_T = FL_O + 16 * 8, FL_X = FL_T + 16 * 8, FL_LAYER = FL_X + 8;
constexpr int Z_FLAGS = 0, Z_NORM = 2 * FL_LAYER, Z_KV = Z_NORM + 8, KV_LAYER = 8 * 80 * 24, Z_END = Z_KV + 2 * KV_LAYER;
__device__ __align__(128) uint32_t g_zero[Z_END];
__device__ __align__(128) float g_nrm[2 * 128 * DM];
__device__ __align__(128) float2 g_stats[2 * S_TOK * 8];
#define GT(slot, k) do {} while (0)
#define GTT(slot, k) do {} while (0)

__device__ __forceinline__ uint32_t smem_u32(const void* p) { return (uint32_t)__cvta_generic_to_shared(p); }
__device__ __forceinline__ uint32_t mapa(uint32_t a, uint32_t r) { uint32_t o; asm("mapa.shared::cluster.u32 %0, %1, %2;" : "=r"(o) : "r"(a), "r"(r)); return o; }
__device__ __forceinline__ void mbar_init(uint32_t bar, uint32_t cnt) { asm volatile("mbarrier.init.shared::cta.b64 [%0], %1;" :: "r"(bar), "r"(cnt) : "memory"); }
__device__ __forceinline__ void mbar_expect(uint32_t bar, uint32_t tx) { asm volatile("mbarrier.arrive.expect_tx.shared::cta.b64 _, [%0], %1;" :: "r"(bar), "r"(tx) : "memory"); }
__device__ __forceinline__ void mbar_arrive(uint32_t bar) { asm volatile("mbarrier.arrive.shared::cta.b64 _, [%0];" :: "r"(bar) : "memory"); }
__device__ __forceinline__ void mbar_wait(uint32_t bar, uint32_t par) {
  asm volatile("{\n.reg .pred p;\n.reg .u32 c;\nmov.u32 c, 0;\n"
               "LW:\nmbarrier.try_wait.parity.shared::cta.b64 p, [%0], %1;\n@p bra LD;\n"
               "add.u32 c, c, 1;\nsetp.lt.u32 p, c, 4000000;\n@p bra LW;\ntrap;\nLD:\n}" :: "r"(bar), "r"(par) : "memory");
}
template <int ID, int N> __device__ __forceinline__ void bar_sync() { asm volatile("barrier.sync %0, %1;" :: "n"(ID), "n"(N) : "memory"); }
template <int ID, int N> __device__ __forceinline__ void bar_arrive() { asm volatile("barrier.arrive %0, %1;" :: "n"(ID), "n"(N) : "memory"); }
__device__ __forceinline__ void fence_async() { asm volatile("fence.proxy.async.shared::cta;" ::: "memory"); }
__device__ __forceinline__ void cluster_sync() { asm volatile("barrier.cluster.arrive.aligned;\nbarrier.cluster.wait.aligned;" ::: "memory"); }
__device__ __forceinline__ void wg_fence() { asm volatile("wgmma.fence.sync.aligned;" ::: "memory"); }
__device__ __forceinline__ void wg_commit() { asm volatile("wgmma.commit_group.sync.aligned;" ::: "memory"); }
template <int N> __device__ __forceinline__ void wg_wait() { asm volatile("wgmma.wait_group.sync.aligned %0;" :: "n"(N) : "memory"); }
template <int N> __device__ __forceinline__ void pin(float* d) {
#pragma unroll
  for (int i = 0; i < N; i++) asm volatile("" : "+f"(d[i]) :: "memory");
}
__device__ __forceinline__ constexpr uint64_t mkdesc(uint32_t addr, uint32_t lbo, uint32_t sbo, int sw) {
  return (uint64_t)((addr & 0x3FFFF) >> 4) | ((uint64_t)(lbo >> 4) << 16) | ((uint64_t)(sbo >> 4) << 32) | ((uint64_t)sw << 62);
}
constexpr uint32_t SB0 = 1024;
__device__ __forceinline__ void check_smem_base(uint32_t sb) { if ((sb & 0x3FFFF) != SB0) __trap(); }
__device__ __forceinline__ uint32_t cta_rank() { uint32_t r; asm volatile("mov.u32 %0, %%cluster_ctarank;" : "=r"(r)); return r; }
__device__ __forceinline__ uint32_t opaque(uint32_t v) { uint32_t o; asm volatile("mov.u32 %0, %1;" : "=r"(o) : "r"(v)); return o; }
__device__ __forceinline__ uint32_t pack2(float lo, float hi) { uint32_t r; asm("cvt.rn.bf16x2.f32 %0, %1, %2;" : "=r"(r) : "f"(hi), "f"(lo)); return r; }
__device__ __forceinline__ void ldsm4(uint32_t* r, uint32_t a) { asm volatile("ldmatrix.sync.aligned.m8n8.x4.shared.b16 {%0,%1,%2,%3}, [%4];" : "=r"(r[0]), "=r"(r[1]), "=r"(r[2]), "=r"(r[3]) : "r"(a) : "memory"); }
__device__ __forceinline__ void ldsm4t(uint32_t* r, uint32_t a) { asm volatile("ldmatrix.sync.aligned.m8n8.x4.trans.shared.b16 {%0,%1,%2,%3}, [%4];" : "=r"(r[0]), "=r"(r[1]), "=r"(r[2]), "=r"(r[3]) : "r"(a) : "memory"); }
__device__ __forceinline__ void ldsm1(uint32_t& r, uint32_t a) { asm volatile("ldmatrix.sync.aligned.m8n8.x1.shared.b16 {%0}, [%1];" : "=r"(r) : "r"(a) : "memory"); }
__device__ __forceinline__ void stsm4(uint32_t a, uint32_t r0, uint32_t r1, uint32_t r2, uint32_t r3) { asm volatile("stmatrix.sync.aligned.m8n8.x4.shared.b16 [%0], {%1,%2,%3,%4};" :: "r"(a), "r"(r0), "r"(r1), "r"(r2), "r"(r3) : "memory"); }
__device__ __forceinline__ void stsm1(uint32_t a, uint32_t r0) { asm volatile("stmatrix.sync.aligned.m8n8.x1.shared.b16 [%0], {%1};" :: "r"(a), "r"(r0) : "memory"); }
__device__ __forceinline__ void stsm4t(uint32_t a, uint32_t r0, uint32_t r1, uint32_t r2, uint32_t r3) { asm volatile("stmatrix.sync.aligned.m8n8.x4.trans.shared.b16 [%0], {%1,%2,%3,%4};" :: "r"(a), "r"(r0), "r"(r1), "r"(r2), "r"(r3) : "memory"); }
__device__ __forceinline__ void stsm2t(uint32_t a, uint32_t r0, uint32_t r1) { asm volatile("stmatrix.sync.aligned.m8n8.x2.trans.shared.b16 [%0], {%1,%2};" :: "r"(a), "r"(r0), "r"(r1) : "memory"); }
__device__ __forceinline__ void mma16816(float* c, const uint32_t* a, uint32_t b0, uint32_t b1) {
  asm volatile("mma.sync.aligned.m16n8k16.row.col.f32.bf16.bf16.f32 {%0,%1,%2,%3}, {%4,%5,%6,%7}, {%8,%9}, {%0,%1,%2,%3};"
               : "+f"(c[0]), "+f"(c[1]), "+f"(c[2]), "+f"(c[3]) : "r"(a[0]), "r"(a[1]), "r"(a[2]), "r"(a[3]), "r"(b0), "r"(b1));
}
__device__ __forceinline__ void mma1688(float* c, uint32_t a0, uint32_t a1, uint32_t b0) {
  asm volatile("mma.sync.aligned.m16n8k8.row.col.f32.bf16.bf16.f32 {%0,%1,%2,%3}, {%4,%5}, {%6}, {%0,%1,%2,%3};"
               : "+f"(c[0]), "+f"(c[1]), "+f"(c[2]), "+f"(c[3]) : "r"(a0), "r"(a1), "r"(b0));
}
__device__ __forceinline__ void sta1(uint32_t a, uint32_t v, uint32_t bar) { asm volatile("st.async.weak.shared::cluster.mbarrier::complete_tx::bytes.b32 [%0], %1, [%2];" :: "r"(a), "r"(v), "r"(bar) : "memory"); }
__device__ __forceinline__ void sta1p(uint32_t a, uint32_t v, uint32_t bar, bool p) { asm volatile("{\n.reg .pred p;\nsetp.ne.b32 p, %3, 0;\n@p st.async.weak.shared::cluster.mbarrier::complete_tx::bytes.b32 [%0], %1, [%2];\n}" :: "r"(a), "r"(v), "r"(bar), "r"((int)p) : "memory"); }
__device__ __forceinline__ void sta2(uint32_t a, uint32_t v0, uint32_t v1, uint32_t bar) { asm volatile("st.async.weak.shared::cluster.mbarrier::complete_tx::bytes.v2.b32 [%0], {%1,%2}, [%3];" :: "r"(a), "r"(v0), "r"(v1), "r"(bar) : "memory"); }
__device__ __forceinline__ void sta4(uint32_t a, uint32_t v0, uint32_t v1, uint32_t v2, uint32_t v3, uint32_t bar) { asm volatile("st.async.weak.shared::cluster.mbarrier::complete_tx::bytes.v4.b32 [%0], {%1,%2,%3,%4}, [%5];" :: "r"(a), "r"(v0), "r"(v1), "r"(v2), "r"(v3), "r"(bar) : "memory"); }
__device__ __forceinline__ float bflo(uint32_t v) { return __uint_as_float(v << 16); }
__device__ __forceinline__ float bfhi(uint32_t v) { return __uint_as_float(v & 0xFFFF0000u); }
__device__ __forceinline__ void sta2f(uint32_t a, float v0, float v1, uint32_t bar) { asm volatile("st.async.weak.shared::cluster.mbarrier::complete_tx::bytes.v2.f32 [%0], {%1,%2}, [%3];" :: "r"(a), "f"(v0), "f"(v1), "r"(bar) : "memory"); }
__device__ __forceinline__ void sta4f(uint32_t a, float v0, float v1, float v2, float v3, uint32_t bar) { asm volatile("st.async.weak.shared::cluster.mbarrier::complete_tx::bytes.v4.f32 [%0], {%1,%2,%3,%4}, [%5];" :: "r"(a), "f"(v0), "f"(v1), "f"(v2), "f"(v3), "r"(bar) : "memory"); }
__device__ __forceinline__ float4 lds4f(uint32_t a) { float4 v; asm volatile("ld.shared.v4.f32 {%0,%1,%2,%3}, [%4];" : "=f"(v.x), "=f"(v.y), "=f"(v.z), "=f"(v.w) : "r"(a) : "memory"); return v; }
__device__ __forceinline__ float2 lds2f(uint32_t a) { float2 v; asm volatile("ld.shared.v2.f32 {%0,%1}, [%2];" : "=f"(v.x), "=f"(v.y) : "r"(a) : "memory"); return v; }
__device__ __forceinline__ uint4 lds4(uint32_t a) { uint4 v; asm volatile("ld.shared.v4.u32 {%0,%1,%2,%3}, [%4];" : "=r"(v.x), "=r"(v.y), "=r"(v.z), "=r"(v.w) : "r"(a) : "memory"); return v; }
__device__ __forceinline__ uint32_t lds1(uint32_t a) { uint32_t v; asm volatile("ld.shared.u32 %0, [%1];" : "=r"(v) : "r"(a) : "memory"); return v; }
__device__ __forceinline__ void stsm2(uint32_t a, uint32_t r0, uint32_t r1) { asm volatile("stmatrix.sync.aligned.m8n8.x2.shared.b16 [%0], {%1,%2};" :: "r"(a), "r"(r0), "r"(r1) : "memory"); }
__device__ __forceinline__ float rcp(float x) { float y; asm("rcp.approx.ftz.f32 %0, %1;" : "=f"(y) : "f"(x)); return y; }
__device__ __forceinline__ void sts4(uint32_t a, uint32_t v0, uint32_t v1, uint32_t v2, uint32_t v3) { asm volatile("st.shared.v4.u32 [%0], {%1,%2,%3,%4};" :: "r"(a), "r"(v0), "r"(v1), "r"(v2), "r"(v3) : "memory"); }
__device__ __forceinline__ void bulk_s2c(uint32_t dst, uint32_t src, uint32_t bytes, uint32_t bar) {
  asm volatile("cp.async.bulk.shared::cluster.shared::cta.mbarrier::complete_tx::bytes [%0], [%1], %2, [%3];" :: "r"(dst), "r"(src), "r"(bytes), "r"(bar) : "memory");
}
__device__ __forceinline__ void stg4(void* p, uint4 v) { asm volatile("st.global.v4.u32 [%0], {%1,%2,%3,%4};" :: "l"(p), "r"(v.x), "r"(v.y), "r"(v.z), "r"(v.w) : "memory"); }
__device__ __forceinline__ void red_add(uint32_t* p, uint32_t v) { asm volatile("red.relaxed.gpu.global.add.u32 [%0], %1;" :: "l"(p), "r"(v) : "memory"); }
__device__ __forceinline__ void red4f(float* p, float a, float b, float c, float d) { asm volatile("red.relaxed.gpu.global.add.v4.f32 [%0], {%1,%2,%3,%4};" :: "l"(p), "f"(a), "f"(b), "f"(c), "f"(d) : "memory"); }
__device__ __forceinline__ void wait_flag(const uint32_t* p, uint32_t target) {
  uint32_t v; int it = 0;
  while (true) {
    asm volatile("ld.acquire.gpu.global.u32 %0, [%1];" : "=r"(v) : "l"(p) : "memory");
    if (__all_sync(~0u, v >= target)) break;
    if (++it > 4000000) __trap();
    __nanosleep(20);
  }
}
__device__ __forceinline__ void sts2(uint32_t a, uint32_t v0, uint32_t v1) { asm volatile("st.shared.v2.u32 [%0], {%1,%2};" :: "r"(a), "r"(v0), "r"(v1) : "memory"); }
__device__ __forceinline__ float sqrt_approx(float x) { float y; asm("sqrt.approx.f32 %0, %1;" : "=f"(y) : "f"(x)); return y; }
__device__ __forceinline__ void sts1(uint32_t a, uint32_t v) { asm volatile("st.shared.u32 [%0], %1;" :: "r"(a), "r"(v) : "memory"); }
__device__ __forceinline__ void bulk_g2s(uint32_t dst, const void* src, uint32_t bytes, uint32_t bar) {
  asm volatile("cp.async.bulk.shared::cluster.global.mbarrier::complete_tx::bytes [%0], [%1], %2, [%3];" :: "r"(dst), "l"(src), "r"(bytes), "r"(bar) : "memory");
}
__device__ __forceinline__ void tma2d(uint32_t dst, const CUtensorMap* m, int c0, int c1, uint32_t bar) {
  asm volatile("cp.async.bulk.tensor.2d.shared::cluster.global.mbarrier::complete_tx::bytes [%0], [%1, {%3, %4}], [%2];" :: "r"(dst), "l"((uint64_t)m), "r"(bar), "r"(c0), "r"(c1) : "memory");
}
__device__ __forceinline__ void tma5d(uint32_t dst, const CUtensorMap* m, int c0, int c4, uint32_t bar) {
  asm volatile("cp.async.bulk.tensor.5d.shared::cluster.global.mbarrier::complete_tx::bytes [%0], [%1, {%3, %5, %5, %5, %4}], [%2];" :: "r"(dst), "l"((uint64_t)m), "r"(bar), "r"(c0), "r"(c4), "r"(0) : "memory");
}
__device__ __forceinline__ void red64(void* p, uint32_t lo, uint32_t hi) { asm volatile("{\n.reg .b64 t;\nmov.b64 t, {%1,%2};\nred.relaxed.gpu.global.add.u64 [%0], t;\n}" :: "l"(p), "r"(lo), "r"(hi) : "memory"); }
__device__ __forceinline__ uint4 ld_poll(const void* p) {
  uint4 v;
  asm volatile("{\n.reg .b64 a, b;\nld.relaxed.gpu.global.v2.b64 {a, b}, [%4];\nmov.b64 {%0,%1}, a;\nmov.b64 {%2,%3}, b;\n}" : "=r"(v.x), "=r"(v.y), "=r"(v.z), "=r"(v.w) : "l"(p) : "memory");
  return v;
}
__device__ __forceinline__ uint32_t clk() { uint32_t c; asm volatile("mov.u32 %0, %%clock;" : "=r"(c) :: "memory"); return c; }
#define SCHED_FENCE() asm volatile("pmevent 0;" ::: "memory")
__device__ __forceinline__ float ex2(float x) { float y; asm("ex2.approx.ftz.f32 %0, %1;" : "=f"(y) : "f"(x)); return y; }

__device__ __forceinline__ void wg_ss_n240_ta0_tb1(float* d, uint64_t a, uint64_t b, int sc) {
  asm volatile("{\n.reg .pred p;\nsetp.ne.b32 p, %122, 0;\nwgmma.mma_async.sync.aligned.m64n240k16.f32.bf16.bf16 {%0, %1, %2, %3, %4, %5, %6, %7, %8, %9, %10, %11, %12, %13, %14, %15, %16, %17, %18, %19, %20, %21, %22, %23, %24, %25, %26, %27, %28, %29, %30, %31, %32, %33, %34, %35, %36, %37, %38, %39, %40, %41, %42, %43, %44, %45, %46, %47, %48, %49, %50, %51, %52, %53, %54, %55, %56, %57, %58, %59, %60, %61, %62, %63, %64, %65, %66, %67, %68, %69, %70, %71, %72, %73, %74, %75, %76, %77, %78, %79, %80, %81, %82, %83, %84, %85, %86, %87, %88, %89, %90, %91, %92, %93, %94, %95, %96, %97, %98, %99, %100, %101, %102, %103, %104, %105, %106, %107, %108, %109, %110, %111, %112, %113, %114, %115, %116, %117, %118, %119}, %120, %121, p, 1, 1, 0, 1;\n}\n"
    : "+f"(d[0]), "+f"(d[1]), "+f"(d[2]), "+f"(d[3]), "+f"(d[4]), "+f"(d[5]), "+f"(d[6]), "+f"(d[7]), "+f"(d[8]), "+f"(d[9]), "+f"(d[10]), "+f"(d[11]), "+f"(d[12]), "+f"(d[13]), "+f"(d[14]), "+f"(d[15]), "+f"(d[16]), "+f"(d[17]), "+f"(d[18]), "+f"(d[19]), "+f"(d[20]), "+f"(d[21]), "+f"(d[22]), "+f"(d[23]), "+f"(d[24]), "+f"(d[25]), "+f"(d[26]), "+f"(d[27]), "+f"(d[28]), "+f"(d[29]), "+f"(d[30]), "+f"(d[31]), "+f"(d[32]), "+f"(d[33]), "+f"(d[34]), "+f"(d[35]), "+f"(d[36]), "+f"(d[37]), "+f"(d[38]), "+f"(d[39]), "+f"(d[40]), "+f"(d[41]), "+f"(d[42]), "+f"(d[43]), "+f"(d[44]), "+f"(d[45]), "+f"(d[46]), "+f"(d[47]), "+f"(d[48]), "+f"(d[49]), "+f"(d[50]), "+f"(d[51]), "+f"(d[52]), "+f"(d[53]), "+f"(d[54]), "+f"(d[55]), "+f"(d[56]), "+f"(d[57]), "+f"(d[58]), "+f"(d[59]), "+f"(d[60]), "+f"(d[61]), "+f"(d[62]), "+f"(d[63]), "+f"(d[64]), "+f"(d[65]), "+f"(d[66]), "+f"(d[67]), "+f"(d[68]), "+f"(d[69]), "+f"(d[70]), "+f"(d[71]), "+f"(d[72]), "+f"(d[73]), "+f"(d[74]), "+f"(d[75]), "+f"(d[76]), "+f"(d[77]), "+f"(d[78]), "+f"(d[79]), "+f"(d[80]), "+f"(d[81]), "+f"(d[82]), "+f"(d[83]), "+f"(d[84]), "+f"(d[85]), "+f"(d[86]), "+f"(d[87]), "+f"(d[88]), "+f"(d[89]), "+f"(d[90]), "+f"(d[91]), "+f"(d[92]), "+f"(d[93]), "+f"(d[94]), "+f"(d[95]), "+f"(d[96]), "+f"(d[97]), "+f"(d[98]), "+f"(d[99]), "+f"(d[100]), "+f"(d[101]), "+f"(d[102]), "+f"(d[103]), "+f"(d[104]), "+f"(d[105]), "+f"(d[106]), "+f"(d[107]), "+f"(d[108]), "+f"(d[109]), "+f"(d[110]), "+f"(d[111]), "+f"(d[112]), "+f"(d[113]), "+f"(d[114]), "+f"(d[115]), "+f"(d[116]), "+f"(d[117]), "+f"(d[118]), "+f"(d[119])
    : "l"(a), "l"(b), "r"(sc));
}
__device__ __forceinline__ void wg_ss_n88_ta1_tb1(float* d, uint64_t a, uint64_t b, int sc) {
  asm volatile("{\n.reg .pred p;\nsetp.ne.b32 p, %46, 0;\nwgmma.mma_async.sync.aligned.m64n88k16.f32.bf16.bf16 {%0, %1, %2, %3, %4, %5, %6, %7, %8, %9, %10, %11, %12, %13, %14, %15, %16, %17, %18, %19, %20, %21, %22, %23, %24, %25, %26, %27, %28, %29, %30, %31, %32, %33, %34, %35, %36, %37, %38, %39, %40, %41, %42, %43}, %44, %45, p, 1, 1, 1, 1;\n}\n"
    : "+f"(d[0]), "+f"(d[1]), "+f"(d[2]), "+f"(d[3]), "+f"(d[4]), "+f"(d[5]), "+f"(d[6]), "+f"(d[7]), "+f"(d[8]), "+f"(d[9]), "+f"(d[10]), "+f"(d[11]), "+f"(d[12]), "+f"(d[13]), "+f"(d[14]), "+f"(d[15]), "+f"(d[16]), "+f"(d[17]), "+f"(d[18]), "+f"(d[19]), "+f"(d[20]), "+f"(d[21]), "+f"(d[22]), "+f"(d[23]), "+f"(d[24]), "+f"(d[25]), "+f"(d[26]), "+f"(d[27]), "+f"(d[28]), "+f"(d[29]), "+f"(d[30]), "+f"(d[31]), "+f"(d[32]), "+f"(d[33]), "+f"(d[34]), "+f"(d[35]), "+f"(d[36]), "+f"(d[37]), "+f"(d[38]), "+f"(d[39]), "+f"(d[40]), "+f"(d[41]), "+f"(d[42]), "+f"(d[43])
    : "l"(a), "l"(b), "r"(sc));
}
__device__ __forceinline__ void wg_rs_n160_tb1(float* d, const uint32_t* a, uint64_t b, int sc) {
  asm volatile("{\n.reg .pred p;\nsetp.ne.b32 p, %85, 0;\nwgmma.mma_async.sync.aligned.m64n160k16.f32.bf16.bf16 {%0, %1, %2, %3, %4, %5, %6, %7, %8, %9, %10, %11, %12, %13, %14, %15, %16, %17, %18, %19, %20, %21, %22, %23, %24, %25, %26, %27, %28, %29, %30, %31, %32, %33, %34, %35, %36, %37, %38, %39, %40, %41, %42, %43, %44, %45, %46, %47, %48, %49, %50, %51, %52, %53, %54, %55, %56, %57, %58, %59, %60, %61, %62, %63, %64, %65, %66, %67, %68, %69, %70, %71, %72, %73, %74, %75, %76, %77, %78, %79}, {%80, %81, %82, %83}, %84, p, 1, 1, 1;\n}\n"
    : "+f"(d[0]), "+f"(d[1]), "+f"(d[2]), "+f"(d[3]), "+f"(d[4]), "+f"(d[5]), "+f"(d[6]), "+f"(d[7]), "+f"(d[8]), "+f"(d[9]), "+f"(d[10]), "+f"(d[11]), "+f"(d[12]), "+f"(d[13]), "+f"(d[14]), "+f"(d[15]), "+f"(d[16]), "+f"(d[17]), "+f"(d[18]), "+f"(d[19]), "+f"(d[20]), "+f"(d[21]), "+f"(d[22]), "+f"(d[23]), "+f"(d[24]), "+f"(d[25]), "+f"(d[26]), "+f"(d[27]), "+f"(d[28]), "+f"(d[29]), "+f"(d[30]), "+f"(d[31]), "+f"(d[32]), "+f"(d[33]), "+f"(d[34]), "+f"(d[35]), "+f"(d[36]), "+f"(d[37]), "+f"(d[38]), "+f"(d[39]), "+f"(d[40]), "+f"(d[41]), "+f"(d[42]), "+f"(d[43]), "+f"(d[44]), "+f"(d[45]), "+f"(d[46]), "+f"(d[47]), "+f"(d[48]), "+f"(d[49]), "+f"(d[50]), "+f"(d[51]), "+f"(d[52]), "+f"(d[53]), "+f"(d[54]), "+f"(d[55]), "+f"(d[56]), "+f"(d[57]), "+f"(d[58]), "+f"(d[59]), "+f"(d[60]), "+f"(d[61]), "+f"(d[62]), "+f"(d[63]), "+f"(d[64]), "+f"(d[65]), "+f"(d[66]), "+f"(d[67]), "+f"(d[68]), "+f"(d[69]), "+f"(d[70]), "+f"(d[71]), "+f"(d[72]), "+f"(d[73]), "+f"(d[74]), "+f"(d[75]), "+f"(d[76]), "+f"(d[77]), "+f"(d[78]), "+f"(d[79])
    : "r"(a[0]), "r"(a[1]), "r"(a[2]), "r"(a[3]), "l"(b), "r"(sc));
}
__device__ __forceinline__ void wg_ss_n80_ta0_tb1(float* d, uint64_t a, uint64_t b, int sc) {
  asm volatile("{\n.reg .pred p;\nsetp.ne.b32 p, %42, 0;\nwgmma.mma_async.sync.aligned.m64n80k16.f32.bf16.bf16 {%0, %1, %2, %3, %4, %5, %6, %7, %8, %9, %10, %11, %12, %13, %14, %15, %16, %17, %18, %19, %20, %21, %22, %23, %24, %25, %26, %27, %28, %29, %30, %31, %32, %33, %34, %35, %36, %37, %38, %39}, %40, %41, p, 1, 1, 0, 1;\n}\n"
    : "+f"(d[0]), "+f"(d[1]), "+f"(d[2]), "+f"(d[3]), "+f"(d[4]), "+f"(d[5]), "+f"(d[6]), "+f"(d[7]), "+f"(d[8]), "+f"(d[9]), "+f"(d[10]), "+f"(d[11]), "+f"(d[12]), "+f"(d[13]), "+f"(d[14]), "+f"(d[15]), "+f"(d[16]), "+f"(d[17]), "+f"(d[18]), "+f"(d[19]), "+f"(d[20]), "+f"(d[21]), "+f"(d[22]), "+f"(d[23]), "+f"(d[24]), "+f"(d[25]), "+f"(d[26]), "+f"(d[27]), "+f"(d[28]), "+f"(d[29]), "+f"(d[30]), "+f"(d[31]), "+f"(d[32]), "+f"(d[33]), "+f"(d[34]), "+f"(d[35]), "+f"(d[36]), "+f"(d[37]), "+f"(d[38]), "+f"(d[39])
    : "l"(a), "l"(b), "r"(sc));
}
__device__ __forceinline__ void wg_rs_n32_tb1(float* d, const uint32_t* a, uint64_t b, int sc) {
  asm volatile("{\n.reg .pred p;\nsetp.ne.b32 p, %21, 0;\nwgmma.mma_async.sync.aligned.m64n32k16.f32.bf16.bf16 {%0, %1, %2, %3, %4, %5, %6, %7, %8, %9, %10, %11, %12, %13, %14, %15}, {%16, %17, %18, %19}, %20, p, 1, 1, 1;\n}\n"
    : "+f"(d[0]), "+f"(d[1]), "+f"(d[2]), "+f"(d[3]), "+f"(d[4]), "+f"(d[5]), "+f"(d[6]), "+f"(d[7]), "+f"(d[8]), "+f"(d[9]), "+f"(d[10]), "+f"(d[11]), "+f"(d[12]), "+f"(d[13]), "+f"(d[14]), "+f"(d[15])
    : "r"(a[0]), "r"(a[1]), "r"(a[2]), "r"(a[3]), "l"(b), "r"(sc));
}
__device__ __forceinline__ void wg_ss_n32_ta1_tb1(float* d, uint64_t a, uint64_t b, int sc) {
  asm volatile("{\n.reg .pred p;\nsetp.ne.b32 p, %18, 0;\nwgmma.mma_async.sync.aligned.m64n32k16.f32.bf16.bf16 {%0, %1, %2, %3, %4, %5, %6, %7, %8, %9, %10, %11, %12, %13, %14, %15}, %16, %17, p, 1, 1, 1, 1;\n}\n"
    : "+f"(d[0]), "+f"(d[1]), "+f"(d[2]), "+f"(d[3]), "+f"(d[4]), "+f"(d[5]), "+f"(d[6]), "+f"(d[7]), "+f"(d[8]), "+f"(d[9]), "+f"(d[10]), "+f"(d[11]), "+f"(d[12]), "+f"(d[13]), "+f"(d[14]), "+f"(d[15])
    : "l"(a), "l"(b), "r"(sc));
}
__device__ __forceinline__ void wg_rs_n32_tb0(float* d, const uint32_t* a, uint64_t b, int sc) {
  asm volatile("{\n.reg .pred p;\nsetp.ne.b32 p, %21, 0;\nwgmma.mma_async.sync.aligned.m64n32k16.f32.bf16.bf16 {%0, %1, %2, %3, %4, %5, %6, %7, %8, %9, %10, %11, %12, %13, %14, %15}, {%16, %17, %18, %19}, %20, p, 1, 1, 0;\n}\n"
    : "+f"(d[0]), "+f"(d[1]), "+f"(d[2]), "+f"(d[3]), "+f"(d[4]), "+f"(d[5]), "+f"(d[6]), "+f"(d[7]), "+f"(d[8]), "+f"(d[9]), "+f"(d[10]), "+f"(d[11]), "+f"(d[12]), "+f"(d[13]), "+f"(d[14]), "+f"(d[15])
    : "r"(a[0]), "r"(a[1]), "r"(a[2]), "r"(a[3]), "l"(b), "r"(sc));
}
__device__ __forceinline__ void wg_rs_n40_tb0(float* d, const uint32_t* a, uint64_t b, int sc) {
  asm volatile("{\n.reg .pred p;\nsetp.ne.b32 p, %25, 0;\nwgmma.mma_async.sync.aligned.m64n40k16.f32.bf16.bf16 {%0, %1, %2, %3, %4, %5, %6, %7, %8, %9, %10, %11, %12, %13, %14, %15, %16, %17, %18, %19}, {%20, %21, %22, %23}, %24, p, 1, 1, 0;\n}\n"
    : "+f"(d[0]), "+f"(d[1]), "+f"(d[2]), "+f"(d[3]), "+f"(d[4]), "+f"(d[5]), "+f"(d[6]), "+f"(d[7]), "+f"(d[8]), "+f"(d[9]), "+f"(d[10]), "+f"(d[11]), "+f"(d[12]), "+f"(d[13]), "+f"(d[14]), "+f"(d[15]), "+f"(d[16]), "+f"(d[17]), "+f"(d[18]), "+f"(d[19])
    : "r"(a[0]), "r"(a[1]), "r"(a[2]), "r"(a[3]), "l"(b), "r"(sc));
}
__device__ __forceinline__ void wg_rs_n8_tb1(float* d, const uint32_t* a, uint64_t b, int sc) {
  asm volatile("{\n.reg .pred p;\nsetp.ne.b32 p, %9, 0;\nwgmma.mma_async.sync.aligned.m64n8k16.f32.bf16.bf16 {%0, %1, %2, %3}, {%4, %5, %6, %7}, %8, p, 1, 1, 1;\n}\n"
    : "+f"(d[0]), "+f"(d[1]), "+f"(d[2]), "+f"(d[3])
    : "r"(a[0]), "r"(a[1]), "r"(a[2]), "r"(a[3]), "l"(b), "r"(sc));
}
__device__ __forceinline__ void wg_ss_n40_ta0_tb0(float* d, uint64_t a, uint64_t b, int sc) {
  asm volatile("{\n.reg .pred p;\nsetp.ne.b32 p, %22, 0;\nwgmma.mma_async.sync.aligned.m64n40k16.f32.bf16.bf16 {%0, %1, %2, %3, %4, %5, %6, %7, %8, %9, %10, %11, %12, %13, %14, %15, %16, %17, %18, %19}, %20, %21, p, 1, 1, 0, 0;\n}\n"
    : "+f"(d[0]), "+f"(d[1]), "+f"(d[2]), "+f"(d[3]), "+f"(d[4]), "+f"(d[5]), "+f"(d[6]), "+f"(d[7]), "+f"(d[8]), "+f"(d[9]), "+f"(d[10]), "+f"(d[11]), "+f"(d[12]), "+f"(d[13]), "+f"(d[14]), "+f"(d[15]), "+f"(d[16]), "+f"(d[17]), "+f"(d[18]), "+f"(d[19])
    : "l"(a), "l"(b), "r"(sc));
}
__device__ __forceinline__ void wg_ss_n40_ta1_tb0(float* d, uint64_t a, uint64_t b, int sc) {
  asm volatile("{\n.reg .pred p;\nsetp.ne.b32 p, %22, 0;\nwgmma.mma_async.sync.aligned.m64n40k16.f32.bf16.bf16 {%0, %1, %2, %3, %4, %5, %6, %7, %8, %9, %10, %11, %12, %13, %14, %15, %16, %17, %18, %19}, %20, %21, p, 1, 1, 1, 0;\n}\n"
    : "+f"(d[0]), "+f"(d[1]), "+f"(d[2]), "+f"(d[3]), "+f"(d[4]), "+f"(d[5]), "+f"(d[6]), "+f"(d[7]), "+f"(d[8]), "+f"(d[9]), "+f"(d[10]), "+f"(d[11]), "+f"(d[12]), "+f"(d[13]), "+f"(d[14]), "+f"(d[15]), "+f"(d[16]), "+f"(d[17]), "+f"(d[18]), "+f"(d[19])
    : "l"(a), "l"(b), "r"(sc));
}
__device__ __forceinline__ void wg_ss_n8_ta1_tb1(float* d, uint64_t a, uint64_t b, int sc) {
  asm volatile("{\n.reg .pred p;\nsetp.ne.b32 p, %6, 0;\nwgmma.mma_async.sync.aligned.m64n8k16.f32.bf16.bf16 {%0, %1, %2, %3}, %4, %5, p, 1, 1, 1, 1;\n}\n"
    : "+f"(d[0]), "+f"(d[1]), "+f"(d[2]), "+f"(d[3])
    : "l"(a), "l"(b), "r"(sc));
}

constexpr int O_WV = 0, O_WO = 81920, O_H = 163840, O_QK = 215040, O_SM = 228352, O_MISC = 229632;
constexpr int O_QM = O_QK + 1024, O_K = O_QK + 3072, O_OG = O_QK + 8192;
constexpr int SM_SLOT = 640;
constexpr int O_MAXS = O_MISC;
constexpr int O_BAR = O_MISC + 64;
constexpr int MB_XF = 0, MB_ML = 2, MB_MR = 4, MB_SM = 7, MB_SX = 8, MB_OG = 9, MB_W = 10;
constexpr int O_PROF = O_BAR + 8 * 24;
constexpr int REC_SMEM = O_PROF + 128;
constexpr int B_QK = 1, B_VGO = 2, B_SISS = 3, B_PM = 4, B_PX = 5, B_XGO = 6, B_PFREE = 7, B_WG2 = 8, B_VHALF = 9, B_VDONE = 10,
              B_OGO = 11, B_SSENT = 12, B_SLD = 13, B_VEND = 14, B_XGO1 = 15;
#define POLL_DELAY 700
#define POLL_D0 300
#define POLL_STEP 100
#define TS0(idx) do {} while (0)
#define TS(idx) do {} while (0)
#define SLD_POS 0
#define MP_D 2
#define V_N1 3
#define V_N2 3
#define V_N3 0
#define V_K1 16
#define V_K2 27
constexpr int V_RS = V_N1 + V_N2 + V_N3;
constexpr float SCL = 0.07216878364870322f;
constexpr float L2E = 1.4426950408889634f;
__device__ __forceinline__ constexpr uint32_t hoff(int k) { return ((k >> 2) * 5120 + (k & 3) * 32) >> 4; }

__device__ __forceinline__ void fix_red(uint8_t* p, const float* a, float sc) {
  int v0 = __float2int_rn(a[0] * sc), v1 = __float2int_rn(a[1] * sc), v2 = __float2int_rn(a[2] * sc), v3 = __float2int_rn(a[3] * sc);
  red64(p, ((uint32_t)v0 << 7) | 1u, ((uint32_t)v2 << 3) + (uint32_t)(v0 >> 25));
  red64(p + 1024, ((uint32_t)v1 << 7) | 1u, ((uint32_t)v3 << 3) + (uint32_t)(v1 >> 25));
}
__device__ __forceinline__ float max10(const float* t) {
  float m = fmaxf(fmaxf(fmaxf(t[0], t[1]), fmaxf(t[2], t[3])), fmaxf(fmaxf(t[4], t[5]), fmaxf(t[6], t[7])));
  m = fmaxf(m, fmaxf(t[8], t[9]));
  m = fmaxf(m, __shfl_xor_sync(~0u, m, 1));
  return fmaxf(m, __shfl_xor_sync(~0u, m, 2));
}
#define ACC2(k, p, u, v) { t[k] = bflo(p) + bflo(u) + bflo(v); t[k + 1] = bfhi(p) + bfhi(u) + bfhi(v); }

__global__ void __launch_bounds__(384, 1)
rec_kernel(const __grid_constant__ CUtensorMap tmq, const __grid_constant__ CUtensorMap tmk,
           const __grid_constant__ CUtensorMap tmv, const __grid_constant__ CUtensorMap tmo,
           const bf16* __restrict__ mem0, uint8_t* __restrict__ ar, uint32_t* __restrict__ flags, int layer) {
  extern __shared__ __align__(1024) uint8_t smem[];
  const uint32_t sb = smem_u32(smem);
  check_smem_base(sb);
  const int tid = threadIdx.x, wid = __shfl_sync(~0u, tid >> 5, 0), wg = wid >> 2, w = wid & 3, lane = tid & 31;
  const int head = blockIdx.x / 3, rank = blockIdx.x - head * 3;
  const int e0 = blockIdx.x * 64;
  const uint32_t bar = sb + O_BAR;
  const uint32_t sb1 = mapa(sb, rank == 2 ? 0 : rank + 1), sb2 = mapa(sb, rank == 0 ? 2 : rank - 1);
  auto chunk_of = [&](int p) { const int c = 3 * rank + p; return p == 9 ? 9 : c >= 9 ? c - 9 : c; };

  GT(layer * 4 + 1, 0);
  if (wid == 8) {
    if (lane < 24) mbar_init(bar + 8 * lane, (lane == MB_ML || lane == MB_ML + 1) ? 2 : 1);
    asm volatile("fence.mbarrier_init.release.cluster;" ::: "memory");
    fence_async();
    __syncwarp();
    if (lane < 10) mbar_expect(bar + 8 * (MB_W + lane), 16384);
    __syncwarp();
    if (lane < 20) {
      const int m = (lane >> 1) & 1, p = (lane >> 2) * 2 + (lane & 1);
      tma5d(sb + m * 81920 + p * 8192, m ? &tmk : &tmq, e0, chunk_of(p) * 4, bar + 8 * (MB_W + m * 5 + (p >> 1)));
    }
  }
  __syncthreads();
  asm volatile("barrier.cluster.arrive.relaxed.aligned;" ::: "memory");

  if (wg < 2) {
    asm volatile("setmaxnreg.inc.sync.aligned.u32 208;");
    uint32_t a[40][4];
    const uint32_t swz = (lane & 7) * 128 + (((2 * w + ((lane >> 3) & 1)) ^ (lane & 7)) << 4);
    {
      const uint32_t la = sb + wg * 81920 + (lane >> 4) * 1024 + swz;
#pragma unroll
      for (int p = 0; p < 5; p++) {
        mbar_wait(bar + 8 * (MB_W + wg * 5 + p), 0);
#pragma unroll
        for (int k = 0; k < 8; k++) ldsm4t(a[p * 8 + k], la + (p * 8 + k) * 2048);
        if (p > 0) bar_sync<B_VGO, 288>();
        bar_arrive<B_PFREE, 288>();
      }
      bar_sync<B_VGO, 288>();
    }
    GT(layer * 4 + 1, 5);
    asm volatile("barrier.cluster.wait.aligned;" ::: "memory");
    const uint32_t ld_m = sb + O_H + (lane & 7) * 128 + (((lane >> 3) ^ (lane & 7)) << 4);

    for (int s = 0; s < NSEG; s++) {
      const uint32_t par = s & 1;
      if (wid == 4) TS0(0);
      if (wid == 0) TS(30);
      {
        float ax[16];
        constexpr uint64_t db = mkdesc(SB0 + O_H + 1024, 16, 1024, 1);
        mbar_wait(bar + 8 * MB_XF, par);
        wg_fence();
#pragma unroll
        for (int k = 0; k < 20; k++) wg_rs_n32_tb0(ax, a[k], db + hoff(k), k);
        mbar_wait(bar + 8 * (MB_XF + 1), par);
        if (s > 0) bar_sync<B_PFREE, 384>();
        wg_fence();
#pragma unroll
        for (int k = 20; k < 40; k++) wg_rs_n32_tb0(ax, a[k], db + hoff(k), 1);
        wg_commit();
        const uint32_t st_x = sb + O_QK + wg * 5120 + (lane >> 4) * 2048 + swz;
        if (tid == 192) { mbar_expect(bar + 8 * MB_SM, 2 * SM_SLOT + 48 + 48); mbar_expect(bar + 8 * MB_SX, 2 * 2176); }
        wg_wait<0>();
        pin<16>(ax);
        if (w == 0) TS(1 + 22 * wg);
        stsm4t(st_x, pack2(ax[0], ax[1]), pack2(ax[2], ax[3]), pack2(ax[4], ax[5]), pack2(ax[6], ax[7]));
        stsm4t(st_x + 4096, pack2(ax[8], ax[9]), pack2(ax[10], ax[11]), pack2(ax[12], ax[13]), pack2(ax[14], ax[15]));
      }
      {
        float c0[4] = {0.f, 0.f, 0.f, 0.f}, c1[4] = {0.f, 0.f, 0.f, 0.f}, c2[4] = {0.f, 0.f, 0.f, 0.f}, c3[4] = {0.f, 0.f, 0.f, 0.f};
        uint32_t b[MP_D][2][4];
#define MORD(j) ((j) == 0 ? 9 : (j) < 4 ? (j) - 1 : 3 + ((j) - 4) / 2 + 3 * ((j) & 1))
#pragma unroll
        for (int j = 0; j < 10 + MP_D - 1; j++) {
          if (j < 10) {
            if ((j & 1) == 0) { mbar_wait(bar + 8 * (MB_ML + j / 2), par); if (wid == 0 && j != 6) TS(2 + (j > 6 ? 3 : j / 2)); }
            ldsm4(b[j % MP_D][0], ld_m + MORD(j) * 5120);
            ldsm4(b[j % MP_D][1], (ld_m ^ 64) + MORD(j) * 5120);
          }
          const int u = j - (MP_D - 1);
          if (u >= 0) {
            const int c = MORD(u);
            mma16816(c0, a[4 * c], b[u % MP_D][0][0], b[u % MP_D][0][1]);
            mma16816(c1, a[4 * c + 1], b[u % MP_D][0][2], b[u % MP_D][0][3]);
            mma16816(c2, a[4 * c + 2], b[u % MP_D][1][0], b[u % MP_D][1][1]);
            mma16816(c3, a[4 * c + 3], b[u % MP_D][1][2], b[u % MP_D][1][3]);
          }
        }
        SCHED_FENCE();
        bar_arrive<B_VGO, 384>();
        SCHED_FENCE();
        stsm2t(sb + O_QM + wg * 2048 + swz, pack2((c0[0] + c1[0]) + (c2[0] + c3[0]), (c0[1] + c1[1]) + (c2[1] + c3[1])),
               pack2((c0[2] + c1[2]) + (c2[2] + c3[2]), (c0[3] + c1[3]) + (c2[3] + c3[3])));
        fence_async();
      }
      if (wg == 0) {
        bar_sync<B_QK, 256>();
        float sv[20];
        {
          constexpr uint64_t da = mkdesc(SB0 + O_QK, 16, 1024, 1), db = mkdesc(SB0 + O_K, 16, 2048, 1);
          wg_fence();
#pragma unroll
          for (int k = 0; k < 4; k++) wg_ss_n40_ta0_tb0(sv, da + 2 * k, db + 2 * k, k);
          wg_commit();
          bar_arrive<B_SISS, 256>();
        }
        if (w == 0) TS(6);
        SCHED_FENCE();
        const uint32_t ln = opaque(lane);
        uint32_t m0, m1, m2, m3, m4;
        {
          const uint32_t a1 = opaque(sb1 + O_SM + SM_SLOT + ln * 16), a2 = opaque(sb2 + O_SM + ln * 16);
          const uint32_t a3 = opaque(sb1 + O_SM + SM_SLOT + 512 + ln * 4), a4 = opaque(sb2 + O_SM + 512 + ln * 4);
          const uint32_t b1 = opaque(sb1 + O_BAR + 8 * MB_SM), b2 = opaque(sb2 + O_BAR + 8 * MB_SM);
          const uint32_t bt = opaque(mapa(sb, min(ln, 2u)) + O_BAR + 8 * MB_SM), at = opaque(bt + (O_MAXS + 48 - O_BAR - 8 * MB_SM));
          SCHED_FENCE();
          wg_wait<0>();
          pin<20>(sv);
          m0 = pack2(sv[2], sv[3]); m1 = pack2(sv[6], sv[7]); m2 = pack2(sv[10], sv[11]); m3 = pack2(sv[14], sv[15]); m4 = pack2(sv[18], sv[19]);
          if (w == 0) {
            sta4(a1, m0, m1, m2, m3, b1);
            sta4(a2, m0, m1, m2, m3, b2);
            sta1(a3, m4, b1);
            sta1(a4, m4, b2);
          }
          sta1p(at, 0u, bt, ln < 3);
          bar_arrive<B_SSENT, 256>();
          SCHED_FENCE();
        }
        const uint32_t p0 = pack2(sv[0], sv[1]), p1 = pack2(sv[4], sv[5]), p2 = pack2(sv[8], sv[9]), p3 = pack2(sv[12], sv[13]), p4 = pack2(sv[16], sv[17]);
        const uint32_t ox = O_K + w * 2048 + ln * 16, ox2 = O_K + 8192 + ln * 4;
        {
          const uint32_t a1 = opaque(sb1 + ox + 512), a2 = opaque(sb2 + ox), b1 = opaque(sb1 + O_BAR + 8 * MB_SX), b2 = opaque(sb2 + O_BAR + 8 * MB_SX);
          if (w == 0) {
            TS(7);
            const uint32_t om = opaque(sb + O_SM + ln * 16), om2 = opaque(sb + O_SM + 512 + ln * 4);
            const uint32_t pa = sb + O_QM + (ln & 7) * 128;
            const uint32_t pa0 = opaque(pa + (((ln >> 3) ^ (ln & 7)) << 4)), pa1 = opaque(pa + ((4 ^ (ln & 7)) << 4));
            float t[10] = {bflo(m0), bfhi(m0), bflo(m1), bfhi(m1), bflo(m2), bfhi(m2), bflo(m3), bfhi(m3), bflo(m4), bfhi(m4)};
            pin<10>(t);
            SCHED_FENCE();
            mbar_wait(bar + 8 * MB_SM, par);
            const uint4 u = lds4(om), v = lds4(om + SM_SLOT);
            const uint32_t u4 = lds1(om2), v4 = lds1(om2 + SM_SLOT);
            sta4(a1, p0, p1, p2, p3, b1);
            sta4(a2, p0, p1, p2, p3, b2);
            if (SLD_POS == 0) bar_arrive<B_SLD, 256>();
            SCHED_FENCE();
#define ACC3(k, u, v) { t[k] += bflo(u) + bflo(v); t[k + 1] += bfhi(u) + bfhi(v); }
            ACC3(0, u.x, v.x) ACC3(2, u.y, v.y) ACC3(4, u.z, v.z) ACC3(6, u.w, v.w) ACC3(8, u4, v4)
            TS(8);
            const float mm = max10(t) * (SCL * L2E);
            if (SLD_POS == 1) { SCHED_FENCE(); bar_arrive<B_SLD, 256>(); SCHED_FENCE(); }
#pragma unroll
            for (int k = 0; k < 10; k++) t[k] = ex2(fmaf(t[k], SCL * L2E, -mm));
            stsm4(pa0, pack2(t[0], t[1]), pack2(t[2], t[3]), pack2(t[4], t[5]), pack2(t[6], t[7]));
            stsm1(pa1, pack2(t[8], t[9]));
            bar_arrive<B_PM, 160>();
            TS(9);
          } else {
            const uint32_t a3 = opaque(sb1 + ox2 + 128), a4 = opaque(sb2 + ox2);
            SCHED_FENCE();
            mbar_wait(bar + 8 * MB_SM, par);
            sta4(a1, p0, p1, p2, p3, b1);
            sta4(a2, p0, p1, p2, p3, b2);
            if (w == 3) { sta1(a3, p4, b1); sta1(a4, p4, b2); }
            bar_arrive<B_SLD, 256>();
          }
        }
        mbar_wait(bar + 8 * MB_SX, par);
        bar_sync<B_VEND, 256>();
        {
          float t[10];
          const uint4 u = lds4(sb + ox), v = lds4(sb + ox + 512);
          const uint32_t u4 = lds1(sb + ox2), v4 = lds1(sb + ox2 + 128);
          SCHED_FENCE();
          ACC2(0, p0, u.x, v.x) ACC2(2, p1, u.y, v.y) ACC2(4, p2, u.z, v.z) ACC2(6, p3, u.w, v.w) ACC2(8, p4, u4, v4)
          const int dq = 8 * w + (ln >> 2) - 2 * (ln & 3);
#pragma unroll
          for (int k = 1; k < 5; k++) {
            if (8 * (k - 1) > dq) t[2 * k] = -1e9f / SCL;
            if (8 * (k - 1) + 1 > dq) t[2 * k + 1] = -1e9f / SCL;
          }
          const float mm = max10(t) * (SCL * L2E);
#pragma unroll
          for (int k = 0; k < 10; k++) t[k] = ex2(fmaf(t[k], SCL * L2E, -mm));
          float sum = ((t[0] + t[1]) + (t[2] + t[3])) + ((t[4] + t[5]) + (t[6] + t[7])) + (t[8] + t[9]);
          sum += __shfl_xor_sync(~0u, sum, 1);
          sum += __shfl_xor_sync(~0u, sum, 2);
          const float inv = rcp(sum);
          const int rr = 2 * w + (ln & 1);
          const uint32_t pa = sb + O_QK + ((ln >> 1) & 3) * 2048 + rr * 128;
          stsm4(pa + (((ln >> 3) ^ rr) << 4), pack2(t[0] * inv, t[1] * inv), pack2(t[2] * inv, t[3] * inv), pack2(t[4] * inv, t[5] * inv), pack2(t[6] * inv, t[7] * inv));
          stsm2(pa + (((4 + ((ln >> 3) & 1)) ^ rr) << 4), pack2(t[8] * inv, t[9] * inv), 0u);
          fence_async();
        }
        bar_arrive<B_PX, 256>();
        if (w == 0) TS(10);
        bar_sync<B_XGO, 256>();
      } else {
        bar_arrive<B_QK, 256>();
        const int ln = opaque(lane);
        if (w == 2) {
          bar_sync<B_VHALF, 192>();
          if (ln == 0 && s > 0) { __threadfence(); red_add(flags + FL_A + (e0 >> 10) * 8 + (s - 1) * 48, 1); }
          __syncwarp();
        }
        if (w == 3) {
          const int l = blockIdx.x * 2 + ln, s2 = s + 2;
          if (ln < 2 && l < 160 && s2 < NSEG - 1) {
            const int tile = l >> 4;
            const uint8_t* p = ar + (s2 >> 2) * AR_GROUP + (s2 & 1) * 128 + ((s2 >> 1) & 1) * 512 + ((tile >> 2) * 8 + (tile & 3)) * 4096 +
                               ((l >> 3) & 1) * 16384 + (l & 1) * 256 + ((l >> 1) & 3) * 1024;
            asm volatile("prefetch.global.L2 [%0];" :: "l"(p));
          }
        }
        if (w == 0) {
          const bool more = s + 1 < NSEG;
          if (ln < 2 && more) mbar_expect(bar + 8 * (MB_XF + ln), 20480);
          const uint8_t* src = g_xn + (s + 1) * 40960 + chunk_of(ln) * 4096;
          bar_sync<B_VHALF, 192>();
          if (ln < 5 && more) bulk_g2s(sb + O_H + ln * 5120 + 1024, src, 4096, bar + 8 * MB_XF);
          bar_sync<B_VDONE, 160>();
          if (ln >= 5 && ln < 10 && more) bulk_g2s(sb + O_H + ln * 5120 + 1024, src, 4096, bar + 8 * (MB_XF + 1));
        }
        bar_sync<B_XGO1, 256>();
      }
    }
  } else {
    asm volatile("setmaxnreg.dec.sync.aligned.u32 88;");
    if (w == 1) {
      if (lane == 0) { mbar_expect(bar + 8 * (MB_W + 10), 81920); mbar_expect(bar + 8 * (MB_W + 11), 81920); }
#pragma unroll 1
      for (int p = 0; p < 5; p++) {
        bar_sync<B_PFREE, 288>();
        fence_async();
        if (lane < 2) tma5d(sb + O_WV + (2 * p + lane) * 8192, &tmv, e0, chunk_of(2 * p + lane) * 4, bar + 8 * (MB_W + 10));
        bar_arrive<B_VGO, 288>();
      }
      if (lane < 10) {
        const int k = lane / 3, j = rank + lane - 3 * k;
        tma2d(sb + O_WO + lane * 8192, &tmo, lane == 9 ? 576 : (rank * 3 + k) * 64, head * DH + (j >= 3 ? j - 3 : j) * 64, bar + 8 * (MB_W + 11));
      }
    }
    if (w == 0) {
      if (lane < 2) mbar_expect(bar + 8 * (MB_XF + lane), 20480);
      wait_flag(flags + FL_X, 128);
      asm volatile("fence.proxy.async;" ::: "memory");
      if (lane < 10) bulk_g2s(sb + O_H + lane * 5120 + 1024, g_xn + chunk_of(lane) * 4096, 4096, bar + 8 * (MB_XF + (lane >= 5)));
      asm volatile("griddepcontrol.launch_dependents;");
      if (lane == 0) GTT(layer * 4 + 1, 4);
    }
    bar_sync<B_WG2, 128>();
    const float2 nrm = __ldcg((const float2*)(g_zero + Z_NORM));
    const float cbound = sqrt_approx(nrm.x) * sqrt_approx(nrm.y) * (25.2982213f * 1.1f);
    asm volatile("barrier.cluster.wait.aligned;" ::: "memory");

    const int g = lane >> 2, i4 = lane & 3;
    const int myT = w == 0 ? 9 : rank * 3 + w - 1, myP = w == 0 ? 9 : w - 1;
    const int tok = 2 * ((lane >> 1) & 3) + ((lane >> 3) & 1);
    const uint32_t fw_off = sb + O_H + myP * 5120 + tok * 128 + (((2 * (lane >> 4) + (lane & 1)) ^ tok) << 4);
    const uint32_t prod_off = (w >> 1) * 16384 + (w & 1) * 2048 + ((g >> 1) & 1) * 256 + (i4 * 2 + (g >> 2)) * 16 + (g & 1) * 8;
    const uint32_t cons_off = ((myT >> 2) * 8 + (myT & 3)) * 4096 + (lane >> 3) * 1024 + (lane & 7) * 16;
    auto tile_off = [&](int k) { const int T = rank * 3 + k; return ((T >> 2) * 8 + (T & 3)) * 4096; };
    constexpr uint32_t T9_OFF = 17 * 4096;

    auto forward = [&](const uint32_t* p) {
      sts4(fw_off, p[0], p[1], p[2], p[3]);
      sts4(fw_off ^ 64, p[4], p[5], p[6], p[7]);
      fence_async();
      __syncwarp();
      if (lane < 2 && w > 0) {
        const uint32_t c = O_H + myP * 5120, d = lane ? sb2 : sb1;
        bulk_s2c(d + c + (lane ? 3 : 6) * 5120, sb + c, 1024, d + O_BAR + 8 * (MB_MR - 1 + w));
      }
      if (lane == 0) mbar_arrive(bar + 8 * (MB_ML + (w >> 1)));
      uint32_t mx = 0;
#pragma unroll
      for (int k = 0; k < 8; k++) mx = __vmaxu2(mx, p[k] & 0x7FFF7FFFu);
      mx = max(mx & 0xFFFFu, mx >> 16);
      mx = __reduce_max_sync(~0u, mx);
      if (lane < 3) { const uint32_t b = mapa(sb, lane); sta1(b + O_MAXS + (rank * 4 + w) * 4, mx << 16, b + O_BAR + 8 * MB_SM); }
    };
    auto arm = [&]() { if (lane == 0) mbar_expect(bar + 8 * (w == 0 ? MB_OG : MB_MR - 1 + w), 2048); };
    {
      arm();
      const uint32_t* mp = (const uint32_t*)(mem0 + tok * DM + myT * 64 + 16 * (lane >> 4) + 4 * (lane & 1));
      const uint32_t p[8] = {mp[0], mp[4], mp[1], mp[5], mp[16], mp[20], mp[17], mp[21]};
      forward(p);
    }
    mbar_wait(bar + 8 * (MB_W + 10), 0);
    if (tid == 256) GTT(layer * 4 + 1, 7);

    const uint32_t la_w = sb + O_WV + ((lane >> 4) * 8 + (lane & 7)) * 128 + (((2 * w + ((lane >> 3) & 1)) ^ (lane & 7)) << 4);
    uint32_t af[V_RS][4];
#pragma unroll
    for (int k = 0; k < V_RS; k++) ldsm4t(af[k], la_w + k * 2048);
    uint32_t vf[10];
    uint4 oq0, oq1;
    uint8_t* op;
    auto pv_x = [&](int s) {
      float ox[16];
      const uint32_t vz[4] = {vf[8], vf[9], 0u, 0u};
      constexpr uint64_t dp = mkdesc(SB0 + O_QK, 16, 2048, 1);
      bar_sync<B_PX, 256>();
      wg_fence();
      wg_rs_n32_tb0(ox, vf, dp, 0);
      wg_rs_n32_tb0(ox, vf + 4, dp + 2, 1);
      wg_rs_n32_tb0(ox, vz, dp + 4, 1);
      wg_commit();
      const uint32_t ln = opaque(lane);
      op = g_ot + (size_t)s * (HE * 64) + (e0 + 16 * w) * 64 + (ln & 3) * 128 + (ln >> 2) * 16;
      wg_wait<0>();
      pin<16>(ox);
      oq0 = make_uint4(pack2(ox[0], ox[1]), pack2(ox[4], ox[5]), pack2(ox[8], ox[9]), pack2(ox[12], ox[13]));
      oq1 = make_uint4(pack2(ox[2], ox[3]), pack2(ox[6], ox[7]), pack2(ox[10], ox[11]), pack2(ox[14], ox[15]));
    };
    for (int s = 0;; s++) {
      const uint32_t par = s & 1;
      float sc, isc;
      {
        float av[20];
        constexpr uint64_t da = mkdesc(SB0 + O_WV, 1024, 1024, 1), db = mkdesc(SB0 + O_H, 16, 1024, 1);
#define V_RUN_RS(k0, k1) wg_fence(); _Pragma("unroll") for (int k = k0; k < k1; k++) wg_rs_n40_tb0(av, af[k], db + hoff(k), k);
#define V_RUN_SS(k0, k1) wg_fence(); _Pragma("unroll") for (int k = k0; k < k1; k++) wg_ss_n40_ta1_tb0(av, da + k * 128, db + hoff(k), 1);
        bar_sync<B_VGO, 384>();
        V_RUN_RS(0, V_N1)
        if (w == 0) TS(11);
        bar_sync<B_SISS, 256>();
        V_RUN_RS(V_N1, V_N1 + V_N2)
        bar_sync<B_SSENT, 256>();
        V_RUN_SS(V_RS, V_K1)
        V_RUN_RS(V_N1 + V_N2, V_RS)
        const uint32_t ln = opaque(lane);
        const uint32_t amx = opaque(sb + O_MAXS + 4 * min(ln, 11u));
        SCHED_FENCE();
        mbar_wait(bar + 8 * MB_SM, par);
        const uint32_t mxl = lds1(amx);
        if (s == 0) mbar_wait(bar + 8 * (MB_W + 11), 0);
        bar_sync<B_SLD, 256>();
        V_RUN_SS(V_K1, 20)
        wg_commit();
        V_RUN_SS((V_K1 > 20 ? V_K1 : 20), V_K2)
        wg_commit();
        wg_wait<1>();
        bar_arrive<B_VHALF, 192>();
        V_RUN_SS(V_K2, 40)
        wg_commit();
        SCHED_FENCE();
        if (w == 0) TS(12);
        {
          const float bnd = cbound * fmaxf(1.f, __uint_as_float(__reduce_max_sync(~0u, mxl)));
          const uint32_t eb = min(max(__float_as_uint(bnd) >> 23, 31u), 254u);
          sc = __uint_as_float(opaque((280u - eb) << 23));
          isc = __uint_as_float(opaque((eb - 29u) << 23));
        }
        const uint32_t pa = sb + O_QM + (ln & 7) * 128;
        const uint32_t pa0 = opaque(pa + (((ln >> 3) ^ (ln & 7)) << 4)), pa1 = opaque(pa + ((4 ^ (ln & 7)) << 4));
        const uint32_t o = O_OG + w * 256 + ln * 4;
        const uint32_t a0 = opaque(sb + o), a1 = opaque(sb1 + o + 4096), a2 = opaque(sb1 + o + 4096 + 128), a3 = opaque(sb2 + o + 2048), a4 = opaque(sb2 + o + 2048 + 128);
        const uint32_t b1 = opaque(sb1 + O_BAR + 8 * MB_OG), b2 = opaque(sb2 + O_BAR + 8 * MB_OG);
        const uint32_t c1 = opaque(0x3F803F80u);
        const uint32_t one[4] = {c1, c1, c1, c1};
        SCHED_FENCE();
        bar_sync<B_PM, 160>();
        uint32_t pm[5];
        ldsm4(pm, pa0);
        ldsm1(pm[4], pa1);
        bar_arrive<B_VEND, 256>();
        float s0[4] = {0.f, 0.f, 0.f, 0.f}, s1[4] = {0.f, 0.f, 0.f, 0.f};
        mma16816(s0, one, pm[0], pm[1]);
        mma16816(s1, one, pm[2], pm[3]);
        mma1688(s0, c1, c1, pm[4]);
        SCHED_FENCE();
        wg_wait<0>();
        pin<20>(av);
        if (w == 0) TS(13);
#pragma unroll
        for (int k = 0; k < 10; k++) vf[k] = pack2(av[2 * k], av[2 * k + 1]);
        {
          float o0[4] = {0.f, 0.f, 0.f, 0.f}, o1[4] = {0.f, 0.f, 0.f, 0.f}, o2[4] = {0.f, 0.f, 0.f, 0.f};
          mma16816(o0, vf, pm[0], pm[1]);
          mma16816(o1, vf + 4, pm[2], pm[3]);
          mma1688(o2, vf[8], vf[9], pm[4]);
          if (s == NSEG - 1) break;
          const float i0 = rcp(s0[0] + s1[0]), i1 = rcp(s0[1] + s1[1]);
          const uint32_t p0 = pack2((o0[0] + o1[0] + o2[0]) * i0, (o0[1] + o1[1] + o2[1]) * i1), p1 = pack2((o0[2] + o1[2] + o2[2]) * i0, (o0[3] + o1[3] + o2[3]) * i1);
          sta1(a1, p0, b1); sta1(a2, p1, b1);
          sta1(a3, p0, b2); sta1(a4, p1, b2);
          sts1(a0, p0); sts1(a0 + 128, p1);
          fence_async();
        }
      }
      uint8_t* arp;
      uint32_t t1;
      {
        bar_sync<B_WG2, 128>();
        float c9[4], ca[4], cb[4], cc[4];
        constexpr uint64_t da = mkdesc(SB0 + O_WO, 1024, 1024, 1), db = mkdesc(SB0 + O_OG, 128, 128, 0);
#define O_RUN(acc, tile, k0, k1) _Pragma("unroll") for (int k = k0; k < k1; k++) wg_ss_n8_ta1_tb1(acc, da + (tile) * 1536 + k * 128, db + (k >> 2) * 128 + (k & 3) * 16, k);
        wg_fence();
        O_RUN(c9, 3, 0, 4)
        wg_commit();
        if (w == 0) TS(14);
        O_RUN(ca, 0, 0, 4) O_RUN(cb, 1, 0, 4) O_RUN(cc, 2, 0, 4)
        wg_commit();
        SCHED_FENCE();
        arp = ar + (s >> 2) * AR_GROUP + (s & 1) * 128 + ((s >> 1) & 1) * 512;
        uint8_t* pp = arp + opaque(prod_off);
        wg_wait<1>();
        pin<4>(c9);
        fix_red(pp + T9_OFF, c9, sc);
        SCHED_FENCE();
        mbar_wait(bar + 8 * MB_OG, par);
        wg_fence();
        O_RUN(ca, 0, 4, 12)
        wg_commit();
        bar_arrive<B_VDONE, 160>();
        if (w == 0) TS(15);
        O_RUN(cb, 1, 4, 12)
        wg_commit();
        wg_wait<1>();
        pin<4>(ca);
        fix_red(pp + tile_off(0), ca, sc);
        SCHED_FENCE();
        if (w == 0) TS(16);
        wg_fence();
        O_RUN(cc, 2, 4, 12)
        wg_commit();
        wg_wait<1>();
        pin<4>(cb);
        fix_red(pp + tile_off(1), cb, sc);
        wg_wait<0>();
        pin<4>(cc);
        fix_red(pp + tile_off(2), cc, sc);
        t1 = clk();
        bar_arrive<B_XGO1, 256>();
        bar_arrive<B_XGO, 256>();
        if (w == 0) TS(17);
      }
      pv_x(s);
      bar_arrive<B_PFREE, 384>();
      if (w == 0) TS(28);
#pragma unroll
      for (int k = 0; k < V_RS; k++) ldsm4t(af[k], la_w + k * 2048);
      {
        arm();
        const int dly = w == 0 ? POLL_D0 : POLL_DELAY - (3 - w) * POLL_STEP;
        const uint32_t need = w == 0 ? 96 : 32;
        const uint8_t* cp = arp + opaque(cons_off);
        uint4 y[4];
        int it = 0;
        while ((int)(clk() - t1) < dly) {}
        if (w == 3) TS(18);
        y[0] = ld_poll(cp); y[1] = ld_poll(cp + 256); y[2] = ld_poll(cp + 16384); y[3] = ld_poll(cp + 16384 + 256);
        stg4(op, oq0); stg4(op + 512, oq1);
        while (true) {
          const uint32_t bad = (y[0].x ^ need) | (y[0].z ^ need) | (y[1].x ^ need) | (y[1].z ^ need) | (y[2].x ^ need) | (y[2].z ^ need) | (y[3].x ^ need) | (y[3].z ^ need);
          if (!__any_sync(~0u, (bad & 127u) != 0)) break;
          if (++it > 2000000) __trap();
          y[0] = ld_poll(cp); y[1] = ld_poll(cp + 256); y[2] = ld_poll(cp + 16384); y[3] = ld_poll(cp + 16384 + 256);
        }
        uint32_t p[8];
        const float isl = isc * 0.5f, bias = -(float)(need >> 3) * isl;
#pragma unroll
        for (int k = 0; k < 4; k++) {
          p[2 * k] = pack2(fmaf((float)(int)__funnelshift_r(y[k].x, y[k].y, 3), isl, bias), fmaf((float)(int)__funnelshift_r(y[k].z, y[k].w, 3), isl, bias));
          p[2 * k + 1] = pack2((float)(int)y[k].y * isc, (float)(int)y[k].w * isc);
        }
        TS(19 + w);
        forward(p);
      }
    }
    bar_arrive<B_VDONE, 160>();
    bar_arrive<B_XGO1, 256>();
    bar_arrive<B_XGO, 256>();
    pv_x(NSEG - 1);
    stg4(op, oq0); stg4(op + 512, oq1);
    bar_sync<B_WG2, 128>();
    if (tid == 256) { __threadfence(); red_add(flags + FL_A + (e0 >> 10) * 8 + (NSEG - 1) * 48, 1); }
    __syncwarp();
  }
  asm volatile("barrier.cluster.arrive.relaxed.aligned;\nbarrier.cluster.wait.aligned;" ::: "memory");
  GT(layer * 4 + 1, 2);
  if (wid == 0) asm volatile("griddepcontrol.wait;" ::: "memory");
}

constexpr int P_B = 0, P_A = 131072, P_BAR = 196608, OPC_SMEM = P_BAR + 256;
constexpr int OP_KR = 48;

__global__ void __launch_bounds__(384, 1)
opc_kernel(const __grid_constant__ CUtensorMap tmo, bf16* __restrict__ out, int layer) {
  extern __shared__ __align__(1024) uint8_t smem[];
  asm volatile("griddepcontrol.launch_dependents;");
  GT(layer * 4 + 2, 0);
  const uint32_t sb = smem_u32(smem);
  check_smem_base(sb);
  const int tid = threadIdx.x, wid = __shfl_sync(~0u, tid >> 5, 0), wg = wid >> 2, w = wid & 3, lane = tid & 31;
  const uint32_t bar = sb + P_BAR;
  uint32_t* flags = g_zero + Z_FLAGS + layer * FL_LAYER;
  float* acc = g_acc + layer * (S_TOK * DM);
  if (wid == 0) {
    if (lane < 16) mbar_init(bar + 8 * lane, (lane == 8 || lane == 9) ? 8 : 1);
    fence_async();
  }
  __syncthreads();
  if (blockIdx.x < 30) {
    const int cg = blockIdx.x % 5, kg = blockIdx.x / 5;
    if (wg < 2) {
      asm volatile("setmaxnreg.inc.sync.aligned.u32 240;");
      uint32_t a[OP_KR][4];
      const uint32_t la = sb + P_B + ((lane >> 4) * 8 + (lane & 7)) * 128 + (((2 * w + ((lane >> 3) & 1)) ^ (lane & 7)) << 4);
      mbar_wait(bar + 80, 0);
#pragma unroll
      for (int k = 0; k < 32; k++) ldsm4t(a[k], la + wg * 65536 + k * 2048);
      bar_arrive<2, 288>();
      mbar_wait(bar + 88, 0);
#pragma unroll
      for (int k = 0; k < 16; k++) ldsm4t(a[32 + k], la + wg * 32768 + k * 2048);
      bar_arrive<3, 288>();
      mbar_wait(bar + 96, 0);
      float* ap = acc + (cg * 8 + wg * 4 + w) * 512 + lane * 4;
      for (int s = 0; s < NSEG; s++) {
        const int buf = s & 1;
        const uint32_t par = (s >> 1) & 1;
        float d[16];
        const uint64_t db = mkdesc(SB0 + P_B + buf * 65536, 512, 128, 0), da = mkdesc(SB0 + P_A + wg * 32768, 1024, 1024, 1);
        float* p = ap + s * (32 * DM);
        if (kg < 4 && s + 2 < NSEG) *(float4*)(p + 2 * 32 * DM + kg * 128) = make_float4(0.f, 0.f, 0.f, 0.f);
#pragma unroll
        for (int q = 0; q < 4; q++) {
          mbar_wait(bar + 8 * (buf * 4 + q), par);
          wg_fence();
#pragma unroll
          for (int k = 16 * q; k < 16 * q + 16; k++) {
            if (k < OP_KR) wg_rs_n32_tb1(d, a[k < OP_KR ? k : 0], db + k * 64, k);
            else wg_ss_n32_ta1_tb1(d, da + (k - OP_KR) * 128, db + k * 64, 1);
          }
        }
        wg_commit();
        wg_wait<0>();
        pin<16>(d);
        if (lane == 0) mbar_arrive(bar + 8 * (8 + buf));
        red4f(p, d[0], d[1], d[4], d[5]);
        red4f(p + 128, d[8], d[9], d[12], d[13]);
        red4f(p + 256, d[2], d[3], d[6], d[7]);
        red4f(p + 384, d[10], d[11], d[14], d[15]);
        bar_sync<1, 256>();
        if (tid == 0) { __threadfence(); red_add(flags + FL_B + s * 8, 1); }
        __syncwarp();
      }
    } else {
      asm volatile("setmaxnreg.dec.sync.aligned.u32 24;");
      if (w == 0) {
        if (lane == 0) { mbar_expect(bar + 80, 131072); mbar_expect(bar + 96, 65536); mbar_expect(bar + 88, 65536); }
        __syncwarp();
        if (lane < 16) tma2d(sb + P_B + lane * 8192, &tmo, cg * 128 + (lane >> 3) * 64, kg * 1024 + (lane & 7) * 64, bar + 80);
        else if (lane < 24) tma2d(sb + P_B + lane * 8192, &tmo, cg * 128 + ((lane >> 2) & 1) * 64, kg * 1024 + 768 + (lane & 3) * 64, bar + 96);
        bar_sync<2, 288>();
        fence_async();
        if (lane < 8) tma2d(sb + P_B + lane * 8192, &tmo, cg * 128 + (lane >> 2) * 64, kg * 1024 + 512 + (lane & 3) * 64, bar + 88);
        bar_sync<3, 288>();
        for (int s = 0; s < NSEG; s++) {
          const int buf = s & 1;
          if (s >= 2) mbar_wait(bar + 8 * (8 + buf), ((s >> 1) & 1) ^ 1);
          if (s >= 2) wait_flag(flags + FL_B + (s - 2) * 8, 30);
          wait_flag(flags + FL_A + s * 48 + kg * 8, 16);
          asm volatile("fence.proxy.async;" ::: "memory");
          if (lane < 4) {
            mbar_expect(bar + 8 * (buf * 4 + lane), 16384);
            bulk_g2s(sb + P_B + buf * 65536 + lane * 16384, g_ot + (size_t)s * (HE * 64) + kg * 65536 + lane * 16384, 16384, bar + 8 * (buf * 4 + lane));
          }
          __syncwarp();
        }
      }
    }
  } else {
    constexpr int LD = 644;
    float* xs = (float*)smem;
    uint32_t par = 0;
    for (int task = blockIdx.x - 30; task < 2 * NSEG; task += 6, par ^= 1) {
      const int s = task >> 1, jj = task & 1;
      if (tid == 0) {
        mbar_expect(bar, 20480);
        bulk_g2s(sb + 49152, g_x + task * 16 * DM, 20480, bar);
      }
      if (wid == 1) wait_flag(flags + FL_B + s * 8, 30);
      __syncthreads();
      if (wid < 10) {
        float4 v[8];
#pragma unroll
        for (int k = 0; k < 8; k++) v[k] = __ldcg((const float4*)(acc + s * (32 * DM) + (wid * 8 + k) * 256 + jj * 128 + lane * 4));
        float* xp = xs + (lane & 3) * 2 * LD + wid * 64 + (lane >> 2);
#pragma unroll
        for (int k = 0; k < 8; k++) { xp[k * 8] = v[k].x; xp[LD + k * 8] = v[k].y; xp[8 * LD + k * 8] = v[k].z; xp[9 * LD + k * 8] = v[k].w; }
      }
      mbar_wait(bar, par);
      __syncthreads();
#pragma unroll 1
      for (int row = wid; row < 16; row += 12) {
        const int tk = task * 16 + row;
        float v[20], sum = 0.f;
        const int pj = (lane & 24) + 2 * (lane & 3) + ((lane >> 2) & 1);
        bf16* dst = out ? out + tk * DM + lane * 2 : g_x + tk * DM + pj * 2;
#pragma unroll
        for (int k = 0; k < 10; k++) {
          const float2 u = *(const float2*)(xs + row * LD + k * 64 + lane * 2);
          const uint32_t r = *(const uint32_t*)(smem + 49152 + row * 1280 + k * 128 + pj * 4);
          v[2 * k] = u.x + bflo(r); v[2 * k + 1] = u.y + bfhi(r); sum += v[2 * k] + v[2 * k + 1];
          *(uint32_t*)(dst + k * 64) = pack2(v[2 * k], v[2 * k + 1]);
        }
        if (!out) {
#pragma unroll
          for (int o = 16; o; o >>= 1) sum += __shfl_xor_sync(~0u, sum, o);
          const float m = sum * (1.f / DM);
          float q = 0.f;
#pragma unroll
          for (int k = 0; k < 20; k++) { v[k] -= m; q += v[k] * v[k]; }
#pragma unroll
          for (int o = 16; o; o >>= 1) q += __shfl_xor_sync(~0u, q, o);
          const float rs = rsqrtf(q * (1.f / DM) + 1e-5f);
          uint8_t* xp = g_xt + (tk >> 7) * 163840 + (tk & 127) * 128 + (((lane >> 2) ^ (tk & 7)) << 4) + (lane & 3) * 4;
#pragma unroll
          for (int k = 0; k < 10; k++) *(uint32_t*)(xp + k * 16384) = pack2(v[2 * k] * rs, v[2 * k + 1] * rs);
        }
      }
      fence_async();
      __syncthreads();
      if (tid == 0 && !out) { __threadfence(); red_add(flags + FL_LAYER + FL_T + (task >> 3) * 8, 1); }
    }
  }
  GT(layer * 4 + 2, 1);
  __syncwarp();
  asm volatile("griddepcontrol.wait;" ::: "memory");
  GT(layer * 4 + 2, 2);
}

constexpr int L_STAGE = 47104;
constexpr int L_KV = 0, L_B2 = 43008;
constexpr int L_W2 = 122880, L_BAR = L_W2 + 102400;
constexpr int LA_SMEM = L_BAR + 256;
__device__ __forceinline__ float phi(float t) { return (fmaxf(t, 0.f) + 1e-6f) + ex2(fminf(t * 1.4426950408889634f, 0.f)); }
__device__ __forceinline__ uint32_t phi2(float a, float b) { return pack2(phi(a), phi(b)); }
#define PF_N0 2
#define PF_N1 2
#define PF_SLEEP 400

__global__ void __launch_bounds__(384, 1)
la_kernel(const bf16* __restrict__ xin, const bf16* __restrict__ Wq, const bf16* __restrict__ Wk, const bf16* __restrict__ Wv,
          const bf16* __restrict__ Wo, uint8_t* __restrict__ ar, int layer) {
  extern __shared__ __align__(1024) uint8_t smem[];
  const uint32_t sb = smem_u32(smem);
  check_smem_base(sb);
  const int tid = threadIdx.x, wid = __shfl_sync(~0u, tid >> 5, 0), wg = wid >> 2, w = wid & 3, lane = tid & 31, g = lane >> 2, i4 = lane & 3;
  const int tb = blockIdx.x >> 3, hg = blockIdx.x & 7;
  const uint32_t bar = sb + L_BAR;
  uint32_t* flags = g_zero + Z_FLAGS + layer * FL_LAYER;
  asm volatile("griddepcontrol.launch_dependents;");
  GT(layer * 4, 0);
  if (wid == 0) {
    if (lane < 20) mbar_init(bar + 8 * lane, ((lane >= 4 && lane < 8) || lane >= 17) ? 8 : 1);
    fence_async();
  }
  if (layer == 0) asm volatile("griddepcontrol.wait;" ::: "memory");
  __syncthreads();
  if (wg == 2) {
    asm volatile("setmaxnreg.dec.sync.aligned.u32 40;");
    if (w == 0) {
      if (lane < 4) {
        mbar_expect(bar + 8 * lane, L_STAGE);
        bulk_g2s(sb + lane * L_STAGE + 16384, g_w1 + (hg * 10 + lane) * 30720, 30720, bar + 8 * lane);
      }
      if (layer == 1) { wait_flag(flags + FL_T + tb * 8, 8); asm volatile("fence.proxy.async;" ::: "memory"); }
      if (lane < 4) bulk_g2s(sb + lane * L_STAGE, g_xt + (tb * 10 + lane) * 16384, 16384, bar + 8 * lane);
#pragma unroll 1
      for (int kc = 4; kc < 10; kc++) {
        const int st = kc & 3;
        mbar_wait(bar + 8 * (4 + st), ((kc >> 2) & 1) ^ 1);
        if (lane == 0) mbar_expect(bar + 8 * st, L_STAGE);
        __syncwarp();
        if (lane < 2) bulk_g2s(sb + st * L_STAGE + lane * 16384, lane ? g_w1 + (hg * 10 + kc) * 30720 : g_xt + (tb * 10 + kc) * 16384, lane ? 30720 : 16384, bar + 8 * st);
      }
      mbar_wait(bar + 8 * 6, 1);
      mbar_wait(bar + 8 * 7, 1);
      if (lane == 0) mbar_expect(bar + 64, 102400);
      if (lane < 8) mbar_expect(bar + 8 * (9 + lane), 20480);
      __syncwarp();
      if (lane < 4) bulk_g2s(sb + L_W2 + lane * 25600, g_w2 + hg * 102400 + lane * 25600, 25600, bar + 64);
      bar_sync<2, 288>();
      if (lane == 0) { __threadfence(); red_add(flags + FL_O + tb * 8, 1); }
      wait_flag(flags + FL_O + tb * 8, 8);
      asm volatile("fence.proxy.async;" ::: "memory");
      if (lane < 6) bulk_g2s(sb + lane * 20480, g_oa + (tb * 8 + lane) * 20480, 20480, bar + 8 * (9 + lane));
#pragma unroll 1
      for (int p = 6; p < 8; p++) {
        mbar_wait(bar + 8 * (17 + p - 6), 0);
        if (lane == 0) bulk_g2s(sb + (p - 6) * 20480, g_oa + (tb * 8 + p) * 20480, 20480, bar + 8 * (9 + p));
      }
    } else {
      const int t = tid - 288;
#pragma unroll 1
      for (int k = t; k < 768; k += 96) *(uint4*)(ar + blockIdx.x * 12288 + k * 16) = make_uint4(0, 0, 0, 0);
      if (layer == 0 && w == 1) {
        float sv = 0.f, mx = 0.f;
#pragma unroll 1
        for (int c = 0; c < 5; c++) {
          const float* p = g_nrm + lane * DM + blockIdx.x * 5 + c;
          sv += (p[0] + p[32 * DM]) + (p[64 * DM] + p[96 * DM]);
          float so = (p[128 * DM] + p[160 * DM]) + (p[192 * DM] + p[224 * DM]);
#pragma unroll
          for (int o = 16; o; o >>= 1) so += __shfl_xor_sync(~0u, so, o);
          mx = fmaxf(mx, so);
        }
#pragma unroll
        for (int o = 16; o; o >>= 1) sv += __shfl_xor_sync(~0u, sv, o);
        if (lane == 0) { atomicAdd((float*)(g_zero + Z_NORM), sv); atomicMax(g_zero + Z_NORM + 1, __float_as_uint(mx)); }
      }
#pragma unroll 1
      for (int k = 0; k < 5 * (layer ? PF_N1 : PF_N0); k++) {
        const int m = k / 5;
        const bf16* W = m == 0 ? Wq : m == 1 ? Wk : m == 2 ? Wv : Wo;
        asm volatile("prefetch.global.L2 [%0];" :: "l"((const uint8_t*)W + blockIdx.x * 61440 + (k - m * 5) * 12288 + t * 128));
        __nanosleep(PF_SLEEP);
      }
      if (t == 0) GTT(layer * 4, 14);
      bar_arrive<3, 352>();
    }
  } else {
    asm volatile("setmaxnreg.inc.sync.aligned.u32 232;");
    GT(layer * 4, 4);
    uint32_t pq[5][4];
    const int row0 = tb * 128 + wg * 64 + 16 * w + g;
    float* kv = (float*)(g_zero + Z_KV) + layer * KV_LAYER + hg * 1920;
    {
      float d[120];
#pragma unroll 1
      for (int kc = 0; kc < 10; kc++) {
        const int st = kc & 3;
        const uint64_t da = mkdesc(SB0 + st * L_STAGE + wg * 8192, 16, 1024, 1), db = mkdesc(SB0 + st * L_STAGE + 16384, 3840, 128, 0);
        mbar_wait(bar + 8 * st, (kc >> 2) & 1);
        wg_fence();
#pragma unroll
        for (int k = 0; k < 4; k++) wg_ss_n240_ta0_tb1(d, da + 2 * k, db + k * 480, kc | k);
        wg_commit();
        if (kc > 0) { wg_wait<1>(); if (lane == 0) mbar_arrive(bar + 8 * (4 + ((kc - 1) & 3))); }
      }
      wg_wait<0>();
      pin<120>(d);
      GT(layer * 4, 5);
      bar_sync<1, 256>();
      const uint32_t kb = sb + L_KV + (wg * 8 + 2 * w + ((lane >> 3) & 1)) * 2688 + (lane >> 4) * 128 + (lane & 7) * 16;
#pragma unroll
      for (int j = 0; j < 5; j++) stsm4(kb + 1280 + j * 256, pack2(d[80 + 8 * j], d[81 + 8 * j]), pack2(d[82 + 8 * j], d[83 + 8 * j]), pack2(d[84 + 8 * j], d[85 + 8 * j]), pack2(d[86 + 8 * j], d[87 + 8 * j]));
      stsm2(kb + 2560, 0x3F803F80u, 0x3F803F80u);
#pragma unroll
      for (int j = 0; j < 5; j++) stsm4(kb + j * 256, phi2(d[40 + 8 * j], d[41 + 8 * j]), phi2(d[42 + 8 * j], d[43 + 8 * j]), phi2(d[44 + 8 * j], d[45 + 8 * j]), phi2(d[46 + 8 * j], d[47 + 8 * j]));
      fence_async();
      bar_sync<1, 256>();
      float e[44];
      {
        const uint64_t da = mkdesc(SB0 + L_KV + wg * 1024, 2688, 128, 0), db = mkdesc(SB0 + L_KV + 1280, 2688, 128, 0);
        wg_fence();
#pragma unroll
        for (int k = 0; k < 8; k++) wg_ss_n88_ta1_tb1(e, da + k * 336, db + k * 336, k);
        wg_commit();
        wg_wait<0>();
        pin<44>(e);
      }
#pragma unroll
      for (int h = 0; h < 2; h++) {
        const int row = wg * 64 + 16 * w + 8 * h + g;
        const int c = row < 80 ? 2 * i4 - (row / 20) * 20 : 100;
        float* dst = kv + row * 24 + c;
#pragma unroll
        for (int j = 0; j < 10; j++)
          asm volatile("{\n.reg .pred p;\nsetp.lt.u32 p, %3, 20;\n@p red.relaxed.gpu.global.add.v2.f32 [%0], {%1,%2};\n}" :: "l"(dst + 8 * j), "f"(e[4 * j + 2 * h]), "f"(e[4 * j + 2 * h + 1]), "r"(c + 8 * j) : "memory");
        asm volatile("{\n.reg .pred p;\nsetp.ne.u32 p, %2, 0;\n@p red.relaxed.gpu.global.add.f32 [%0], %1;\n}" :: "l"(kv + row * 24 + 20), "f"(e[40 + 2 * h]), "r"((int)(row < 80 && i4 == 0)) : "memory");
      }
      bar_sync<1, 256>();
      GT(layer * 4, 6);
      if (tid == 0) { __threadfence(); red_add(flags + FL_KV + hg * 8, 1); }
      __syncwarp();
      pin<40>(d);
#pragma unroll
      for (int k = 0; k < 5; k++) {
        pq[k][0] = phi2(d[8 * k], d[8 * k + 1]); pq[k][1] = phi2(d[8 * k + 2], d[8 * k + 3]);
        pq[k][2] = phi2(d[8 * k + 4], d[8 * k + 5]); pq[k][3] = phi2(d[8 * k + 6], d[8 * k + 7]);
      }
    }
#pragma unroll 1
    for (int k = tid; k < 1600; k += 256) sts4(sb + L_B2 + k * 16, 0, 0, 0, 0);
    GT(layer * 4, 7);
    if (wid == 0) wait_flag(flags + FL_KV + hg * 8, 16);
    if (wid == 1 && layer == 1) wait_flag(flags + FL_T + tb * 8, 8);
    GT(layer * 4, 8);
    bar_sync<1, 256>();
    if (tid < 240) {
      const int dd = tid / 3, part = tid - dd * 3, n = (dd / 20) * 20 + 8 * part;
      const float4 v0 = __ldcg((const float4*)(kv + dd * 24 + 8 * part)), v1 = __ldcg((const float4*)(kv + dd * 24 + 8 * part + 4));
      const float z = __ldcg(kv + dd * 24 + 20);
      const uint32_t a = sb + L_B2 + (dd >> 3) * 2560 + (dd & 7) * 16, zz = pack2(z, z);
      const uint32_t a0 = a + (n >> 3) * 128 + (n & 7) * 2, a1 = a + ((n + 4) >> 3) * 128 + ((n + 4) & 7) * 2;
      sts2(a0, pack2(v0.x, v0.y), pack2(v0.z, v0.w)); sts2(a0 + 1280, zz, zz);
      if (part < 2) { sts2(a1, pack2(v1.x, v1.y), pack2(v1.z, v1.w)); sts2(a1 + 1280, zz, zz); }
    }
    fence_async();
    bar_sync<1, 256>();
    {
      float o[80];
      const uint64_t db = mkdesc(SB0 + L_B2, 2560, 128, 0);
      wg_fence();
#pragma unroll
      for (int k = 0; k < 5; k++) wg_rs_n160_tb1(o, pq[k], db + k * 320, k);
      wg_commit();
      wg_wait<0>();
      pin<80>(o);
      uint8_t* op = g_oa + (tb * 8 + hg) * 20480 + (wg * 8 + 2 * w) * 128 + lane * 4;
#pragma unroll
      for (int j = 0; j < 20; j++) {
        const float inv = rcp(o[40 + 2 * j] + 1e-6f);
        *(uint32_t*)(op + (j >> 1) * 2048 + (j & 1) * 128) = pack2(o[2 * j] * inv, o[2 * j + 1] * inv);
      }
      GT(layer * 4, 9);
      bar_arrive<2, 288>();
    }
    uint32_t r[20];
    if (xin) {
      const bf16* xp = xin + row0 * DM + hg * 80 + 2 * i4;
#pragma unroll
      for (int j = 0; j < 10; j++) { r[2 * j] = __ldg((const uint32_t*)(xp + 8 * j)); r[2 * j + 1] = __ldg((const uint32_t*)(xp + 8 * DM + 8 * j)); }
    } else {
      const bf16* xp = g_x + row0 * DM + hg * 80 + 4 * i4;
#pragma unroll
      for (int j = 0; j < 5; j++) {
        const uint2 u = __ldcg((const uint2*)(xp + 16 * j)), v = __ldcg((const uint2*)(xp + 8 * DM + 16 * j));
        r[4 * j] = u.x; r[4 * j + 2] = u.y; r[4 * j + 1] = v.x; r[4 * j + 3] = v.y;
      }
    }
    float d[40];
    mbar_wait(bar + 64, 0);
#pragma unroll 1
    for (int p = 0; p < 8; p++) {
      const uint64_t da = mkdesc(SB0 + (p < 6 ? p : p - 6) * 20480 + wg * 1024, 2048, 128, 0), db = mkdesc(SB0 + L_W2 + p * 12800, 1280, 128, 0);
      mbar_wait(bar + 8 * (9 + p), 0);
      if (p == 0) GT(layer * 4, 11);
      wg_fence();
#pragma unroll
      for (int k = 0; k < 5; k++) wg_ss_n80_ta0_tb1(d, da + k * 256, db + k * 160, p | k);
      wg_commit();
      wg_wait<1>();
      if (lane == 0 && (p == 1 || p == 2)) mbar_arrive(bar + 8 * (17 + p - 1));
    }
    wg_wait<0>();
    pin<40>(d);
    GT(layer * 4, 12);
    float mean[2], m2[2];
#pragma unroll
    for (int h = 0; h < 2; h++) {
      float sum = 0.f;
#pragma unroll
      for (int j = 0; j < 10; j++) { d[4 * j + 2 * h] += bflo(r[2 * j + h]); d[4 * j + 2 * h + 1] += bfhi(r[2 * j + h]); sum += d[4 * j + 2 * h] + d[4 * j + 2 * h + 1]; }
      sum += __shfl_xor_sync(~0u, sum, 1); sum += __shfl_xor_sync(~0u, sum, 2);
      mean[h] = sum * (1.f / 80.f);
      float q = 0.f;
#pragma unroll
      for (int j = 0; j < 10; j++) { const float a = d[4 * j + 2 * h] - mean[h], b = d[4 * j + 2 * h + 1] - mean[h]; q = fmaf(a, a, fmaf(b, b, q)); }
      q += __shfl_xor_sync(~0u, q, 1); q += __shfl_xor_sync(~0u, q, 2);
      m2[h] = q;
    }
    float2* st = g_stats + (layer * S_TOK + row0) * 8;
    if (i4 < 2) {
      const float a = i4 ? mean[1] : mean[0], b = i4 ? m2[1] : m2[0];
      asm volatile("{\n.reg .b64 t;\nmov.b64 t, {%1,%2};\nst.relaxed.gpu.global.b64 [%0], t;\n}" :: "l"(st + i4 * 64 + hg), "r"(__float_as_uint(a)), "r"(__float_as_uint(b) & 0x7FFFFFFFu) : "memory");
    }
    uint4 y0, y1;
    int it = 0;
    while (true) {
      y0 = ld_poll(st + 2 * i4); y1 = ld_poll(st + 64 + 2 * i4);
      if (!__any_sync(~0u, (int)(y0.y | y0.w | y1.y | y1.w) < 0)) break;
      if (++it > 2000000) __trap();
    }
    GT(layer * 4, 13);
#pragma unroll
    for (int h = 0; h < 2; h++) {
      const uint4 y = h ? y1 : y0;
      const float ma = __uint_as_float(y.x), mb = __uint_as_float(y.z);
      float sm = ma + mb;
      sm += __shfl_xor_sync(~0u, sm, 1); sm += __shfl_xor_sync(~0u, sm, 2);
      const float mu = sm * 0.125f;
      float q = __uint_as_float(y.y) + __uint_as_float(y.w) + 80.f * ((ma - mu) * (ma - mu) + (mb - mu) * (mb - mu));
      q += __shfl_xor_sync(~0u, q, 1); q += __shfl_xor_sync(~0u, q, 2);
      const float rs = rsqrtf(q * (1.f / DM) + 1e-5f), sh = -mu * rs;
      const int tk = row0 + 8 * h;
      uint8_t* xp = g_xn + (tk >> 5) * 40960 + (tk & 31) * 128 + (i4 & 1) * 8;
#pragma unroll
      for (int jj = 0; jj < 5; jj++) {
        const int b16 = hg * 5 + jj;
        const float* a = d + 8 * jj + 2 * h;
        *(uint2*)(xp + (b16 >> 2) * 4096 + (((2 * (b16 & 3) + (i4 >> 1)) ^ g) << 4)) =
            make_uint2(pack2(fmaf(a[0], rs, sh), fmaf(a[1], rs, sh)), pack2(fmaf(a[4], rs, sh), fmaf(a[5], rs, sh)));
      }
    }
    {
      bf16* xp = g_x + row0 * DM + hg * 80 + 4 * i4;
#pragma unroll
      for (int j = 0; j < 5; j++) {
        *(uint2*)(xp + 16 * j) = make_uint2(pack2(d[8 * j], d[8 * j + 1]), pack2(d[8 * j + 4], d[8 * j + 5]));
        *(uint2*)(xp + 8 * DM + 16 * j) = make_uint2(pack2(d[8 * j + 2], d[8 * j + 3]), pack2(d[8 * j + 6], d[8 * j + 7]));
      }
    }
    bar_sync<3, 352>();
    if (tid == 0) { __threadfence(); red_add(flags + FL_X, 1); }
    GT(layer * 4, 2);
    if (wid == 7) asm volatile("griddepcontrol.wait;" ::: "memory");
  }
}

__global__ void __launch_bounds__(256) prep_kernel(const bf16* __restrict__ x, const bf16* __restrict__ wqkv, const bf16* __restrict__ wo,
                                                   const bf16* __restrict__ Wv, const bf16* __restrict__ Wo) {
  asm volatile("griddepcontrol.launch_dependents;");
  const int b = blockIdx.x, tid = threadIdx.x, lane = tid & 31;
  if (b < 160) GT(3, 0);
  if (b < 256) {
    const int row = b * 8 + (tid >> 5);
    float v[20], s = 0.f;
#pragma unroll
    for (int k = 0; k < 10; k++) { const uint32_t u = __ldg((const uint32_t*)(x + row * DM + k * 64 + lane * 2)); v[2 * k] = bflo(u); v[2 * k + 1] = bfhi(u); s += v[2 * k] + v[2 * k + 1]; }
#pragma unroll
    for (int o = 16; o; o >>= 1) s += __shfl_xor_sync(~0u, s, o);
    const float m = s * (1.f / DM);
    float q = 0.f;
#pragma unroll
    for (int k = 0; k < 20; k++) { v[k] -= m; q += v[k] * v[k]; }
#pragma unroll
    for (int o = 16; o; o >>= 1) q += __shfl_xor_sync(~0u, q, o);
    const float r = rsqrtf(q * (1.f / DM) + 1e-5f);
#pragma unroll
    for (int k = 0; k < 10; k++)
      *(uint32_t*)(g_xt + ((row >> 7) * 10 + k) * 16384 + (row & 127) * 128 + (((lane >> 2) ^ (row & 7)) << 4) + (lane & 3) * 4) = pack2(v[2 * k] * r, v[2 * k + 1] * r);
  } else if (b < 256 + 200) {
#pragma unroll
    for (int it = 0; it < 4; it++) {
      const int u = (b - 256) * 1024 + it * 256 + tid;
      if (u < 153600) {
        const int k8 = u & 7, nb = (u >> 3) % 30, kg = (u / 240) % 80, hg = u / 19200;
        *(uint4*)(g_w1 + u * 16) = __ldg((const uint4*)(wqkv + (kg * 8 + k8) * 1920 + (nb / 10) * 640 + hg * 80 + (nb % 10) * 8));
      } else {
        const int v = u - 153600, k8 = v & 7, nb = (v >> 3) % 10, kg = (v / 80) % 80, hg = v / 6400;
        *(uint4*)(g_w2 + v * 16) = __ldg((const uint4*)(wo + (kg * 8 + k8) * DM + hg * 80 + nb * 8));
      }
    }
  } else if (b >= 472) {
    __shared__ float red[2][640];
    const int blk = b - 472, rs = tid / 80, t = tid - rs * 80;
    float c[8] = {0.f, 0.f, 0.f, 0.f, 0.f, 0.f, 0.f, 0.f};
    if (rs < 3) {
      const uint4* po = (const uint4*)((const uint8_t*)(blk < 128 ? Wv : Wo) + (blk & 127) * 61440) + rs * 1280 + t;
#pragma unroll
      for (int k = 0; k < 16; k++) {
        const uint4 v = __ldg(po + k * 80);
        c[0] += bflo(v.x) * bflo(v.x); c[1] += bfhi(v.x) * bfhi(v.x); c[2] += bflo(v.y) * bflo(v.y); c[3] += bfhi(v.y) * bfhi(v.y);
        c[4] += bflo(v.z) * bflo(v.z); c[5] += bfhi(v.z) * bfhi(v.z); c[6] += bflo(v.w) * bflo(v.w); c[7] += bfhi(v.w) * bfhi(v.w);
      }
      if (rs > 0) { *(float4*)&red[rs - 1][t * 8] = make_float4(c[0], c[1], c[2], c[3]); *(float4*)&red[rs - 1][t * 8 + 4] = make_float4(c[4], c[5], c[6], c[7]); }
    }
    __syncthreads();
    if (rs == 0) {
#pragma unroll
      for (int k = 0; k < 8; k++) c[k] += red[0][t * 8 + k] + red[1][t * 8 + k];
      *(float4*)(g_nrm + blk * DM + t * 8) = make_float4(c[0], c[1], c[2], c[3]);
      *(float4*)(g_nrm + blk * DM + t * 8 + 4) = make_float4(c[4], c[5], c[6], c[7]);
    }
  } else {
    const int t = (b - 456) * 256 + tid;
    for (int k = t; k < Z_END / 4; k += 16 * 256) ((uint4*)g_zero)[k] = make_uint4(0, 0, 0, 0);
    for (int k = t; k < 2 * S_TOK * 4; k += 16 * 256) ((uint4*)g_stats)[k] = make_uint4(~0u, ~0u, ~0u, ~0u);
    for (int k = t; k < 16 * DM; k += 16 * 256) { ((uint4*)g_acc)[k] = make_uint4(0, 0, 0, 0); ((uint4*)(g_acc + S_TOK * DM))[k] = make_uint4(0, 0, 0, 0); }
  }
  if (b < 160) GT(3, 2);
}

typedef CUresult (*EncodeFn)(CUtensorMap*, CUtensorMapDataType, cuuint32_t, void*, const cuuint64_t*, const cuuint64_t*, const cuuint32_t*,
                             const cuuint32_t*, CUtensorMapInterleave, CUtensorMapSwizzle, CUtensorMapL2promotion, CUtensorMapFloatOOBfill);
static void make_map(EncodeFn fn, CUtensorMap* m, const void* p, uint64_t cols, uint64_t rows, uint32_t bc, uint32_t br) {
  cuuint64_t dims[2] = {cols, rows}; cuuint64_t strides[1] = {cols * 2}; cuuint32_t box[2] = {bc, br}; cuuint32_t es[2] = {1, 1};
  fn(m, CU_TENSOR_MAP_DATA_TYPE_BFLOAT16, 2, (void*)p, dims, strides, box, es, CU_TENSOR_MAP_INTERLEAVE_NONE, CU_TENSOR_MAP_SWIZZLE_128B,
     CU_TENSOR_MAP_L2_PROMOTION_L2_128B, CU_TENSOR_MAP_FLOAT_OOB_FILL_NONE);
}

static void make_map_perm(EncodeFn fn, CUtensorMap* m, const void* p) {
  cuuint64_t dims[5] = {HE, 2, 2, 4, 40}; const cuuint64_t r = HE * 2; cuuint64_t strides[4] = {r, 8 * r, 2 * r, 16 * r};
  cuuint32_t box[5] = {64, 2, 2, 4, 4}; cuuint32_t es[5] = {1, 1, 1, 1, 1};
  fn(m, CU_TENSOR_MAP_DATA_TYPE_BFLOAT16, 5, (void*)p, dims, strides, box, es, CU_TENSOR_MAP_INTERLEAVE_NONE, CU_TENSOR_MAP_SWIZZLE_128B,
     CU_TENSOR_MAP_L2_PROMOTION_L2_128B, CU_TENSOR_MAP_FLOAT_OOB_FILL_NONE);
}

#define OPC_PDL 1
#define LA_PDL 1
#define REC_PDL 1
extern "C" void kernel_launch(void* const* d_in, const int* in_sizes, int n_in, void* d_out, int out_size) {
  const bf16* x = (const bf16*)d_in[0];
  const bf16* wqkv = (const bf16*)d_in[1];
  const bf16* wo_a = (const bf16*)d_in[2];
  const bf16* mem0 = (const bf16*)d_in[4];
  const bf16* Wq = (const bf16*)d_in[5];
  const bf16* Wk = (const bf16*)d_in[6];
  const bf16* Wv = (const bf16*)d_in[7];
  const bf16* Wo = (const bf16*)d_in[8];
  cudaStream_t st = cudaStreamPerThread;

  static EncodeFn enc = nullptr;
  static uint8_t* p_ar; static uint32_t* p_zero;
  if (!enc) {
    cudaDriverEntryPointQueryResult qr;
    void* fn = nullptr;
    cudaGetDriverEntryPoint("cuTensorMapEncodeTiled", &fn, cudaEnableDefault, &qr);
    enc = (EncodeFn)fn;
    cudaFuncSetAttribute(rec_kernel, cudaFuncAttributeMaxDynamicSharedMemorySize, REC_SMEM);
    cudaFuncSetAttribute(opc_kernel, cudaFuncAttributeMaxDynamicSharedMemorySize, OPC_SMEM);
    cudaFuncSetAttribute(la_kernel, cudaFuncAttributeMaxDynamicSharedMemorySize, LA_SMEM);
    cudaGetSymbolAddress((void**)&p_ar, g_ar); p_ar = (uint8_t*)(((uintptr_t)p_ar + 32767) & ~(uintptr_t)32767);
    cudaGetSymbolAddress((void**)&p_zero, g_zero);
  }
  CUtensorMap tmq, tmk, tmv, tmo;
  make_map_perm(enc, &tmq, Wq);
  make_map_perm(enc, &tmk, Wk);
  make_map_perm(enc, &tmv, Wv);
  make_map(enc, &tmo, Wo, DM, HE, 64, 64);

  cudaLaunchAttribute at[2];
  at[0].id = cudaLaunchAttributeProgrammaticStreamSerialization; at[0].val.programmaticStreamSerializationAllowed = 1;
  at[1].id = cudaLaunchAttributeClusterDimension; at[1].val.clusterDim.x = 3; at[1].val.clusterDim.y = 1; at[1].val.clusterDim.z = 1;
  prep_kernel<<<728, 256, 0, st>>>(x, wqkv, wo_a, Wv, Wo);
  for (int l = 0; l < 2; l++) {
    cudaLaunchConfig_t cfg = {};
    cfg.blockDim = dim3(384); cfg.stream = st;
    cfg.gridDim = dim3(128); cfg.dynamicSmemBytes = LA_SMEM; cfg.attrs = at; cfg.numAttrs = LA_PDL;
    cudaLaunchKernelEx(&cfg, la_kernel, l == 0 ? x : (const bf16*)nullptr, Wq, Wk, Wv, Wo, p_ar + l * AR_LAYER, l);
    cfg.gridDim = dim3(96); cfg.dynamicSmemBytes = REC_SMEM; cfg.attrs = at + 1 - REC_PDL; cfg.numAttrs = 1 + REC_PDL;
    cudaLaunchKernelEx(&cfg, rec_kernel, tmq, tmk, tmv, tmo, mem0, p_ar + l * AR_LAYER, p_zero + Z_FLAGS + l * FL_LAYER, l);
    cfg.gridDim = dim3(36); cfg.dynamicSmemBytes = OPC_SMEM; cfg.attrs = at; cfg.numAttrs = OPC_PDL;
    cudaLaunchKernelEx(&cfg, opc_kernel, tmo, l == 1 ? (bf16*)d_out : (bf16*)nullptr, l);
  }
}
```

```cpp
#include <cuda_runtime.h>
#include <cuda_bf16.h>
#include <cuda.h>
#include <stdint.h>

typedef __nv_bfloat16 bf16;
typedef unsigned long long u64;

constexpr int S_TOK = 2048, DM = 640, DH = 192, HE = 6144, NSEG = 64;

constexpr int AR_GROUP = 98304;
constexpr int AR_LAYER = 16 * AR_GROUP;
__device__ __align__(1024) uint8_t g_ar[2 * AR_LAYER + 32768];
__device__ __align__(1024) uint8_t g_xn[NSEG * 40960];
__device__ __align__(1024) uint8_t g_xt[S_TOK * DM * 2];
__device__ __align__(1024) uint8_t g_ot[NSEG * HE * 64];
__device__ __align__(1024) uint8_t g_oa[S_TOK * DM * 2];
__device__ __align__(1024) uint8_t g_w1[DM * 1920 * 2];
__device__ __align__(1024) uint8_t g_w2[DM * DM * 2];
__device__ __align__(1024) float g_acc[2 * S_TOK * DM];
__device__ __align__(1024) bf16 g_x[S_TOK * DM];
constexpr int FL_A = 0, FL_B = 64 * 6 * 8, FL_KV = FL_B + 64 * 8, FL_O = FL_KV + 8 * 8, FL_T = FL_O + 16 * 8, FL_X = FL_T + 16 * 8, FL_LAYER = FL_X + 8;
constexpr int Z_FLAGS = 0, Z_NORM = 2 * FL_LAYER, Z_KV = Z_NORM + 8, KV_LAYER = 8 * 80 * 24, Z_END = Z_KV + 2 * KV_LAYER;
__device__ __align__(128) uint32_t g_zero[Z_END];
__device__ __align__(128) float g_nrm[2 * 128 * DM];
__device__ __align__(128) float2 g_stats[2 * S_TOK * 8];
#define GT(slot, k) do {} while (0)
#define GTT(slot, k) do {} while (0)

__device__ __forceinline__ uint32_t smem_u32(const void* p) { return (uint32_t)__cvta_generic_to_shared(p); }
__device__ __forceinline__ uint32_t mapa(uint32_t a, uint32_t r) { uint32_t o; asm("mapa.shared::cluster.u32 %0, %1, %2;" : "=r"(o) : "r"(a), "r"(r)); return o; }
__device__ __forceinline__ void mbar_init(uint32_t bar, uint32_t cnt) { asm volatile("mbarrier.init.shared::cta.b64 [%0], %1;" :: "r"(bar), "r"(cnt) : "memory"); }
__device__ __forceinline__ void mbar_expect(uint32_t bar, uint32_t tx) { asm volatile("mbarrier.arrive.expect_tx.shared::cta.b64 _, [%0], %1;" :: "r"(bar), "r"(tx) : "memory"); }
__device__ __forceinline__ void mbar_arrive(uint32_t bar) { asm volatile("mbarrier.arrive.shared::cta.b64 _, [%0];" :: "r"(bar) : "memory"); }
__device__ __forceinline__ void mbar_wait(uint32_t bar, uint32_t par) {
  asm volatile("{\n.reg .pred p;\n.reg .u32 c;\nmov.u32 c, 0;\n"
               "LW:\nmbarrier.try_wait.parity.shared::cta.b64 p, [%0], %1;\n@p bra LD;\n"
               "add.u32 c, c, 1;\nsetp.lt.u32 p, c, 4000000;\n@p bra LW;\ntrap;\nLD:\n}" :: "r"(bar), "r"(par) : "memory");
}
template <int ID, int N> __device__ __forceinline__ void bar_sync() { asm volatile("barrier.sync %0, %1;" :: "n"(ID), "n"(N) : "memory"); }
template <int ID, int N> __device__ __forceinline__ void bar_arrive() { asm volatile("barrier.arrive %0, %1;" :: "n"(ID), "n"(N) : "memory"); }
__device__ __forceinline__ void fence_async() { asm volatile("fence.proxy.async.shared::cta;" ::: "memory"); }
__device__ __forceinline__ void cluster_sync() { asm volatile("barrier.cluster.arrive.aligned;\nbarrier.cluster.wait.aligned;" ::: "memory"); }
__device__ __forceinline__ void wg_fence() { asm volatile("wgmma.fence.sync.aligned;" ::: "memory"); }
__device__ __forceinline__ void wg_commit() { asm volatile("wgmma.commit_group.sync.aligned;" ::: "memory"); }
template <int N> __device__ __forceinline__ void wg_wait() { asm volatile("wgmma.wait_group.sync.aligned %0;" :: "n"(N) : "memory"); }
template <int N> __device__ __forceinline__ void pin(float* d) {
#pragma unroll
  for (int i = 0; i < N; i++) asm volatile("" : "+f"(d[i]) :: "memory");
}
__device__ __forceinline__ constexpr uint64_t mkdesc(uint32_t addr, uint32_t lbo, uint32_t sbo, int sw) {
  return (uint64_t)((addr & 0x3FFFF) >> 4) | ((uint64_t)(lbo >> 4) << 16) | ((uint64_t)(sbo >> 4) << 32) | ((uint64_t)sw << 62);
}
constexpr uint32_t SB0 = 1024;
__device__ __forceinline__ void check_smem_base(uint32_t sb) { if ((sb & 0x3FFFF) != SB0) __trap(); }
__device__ __forceinline__ uint32_t cta_rank() { uint32_t r; asm volatile("mov.u32 %0, %%cluster_ctarank;" : "=r"(r)); return r; }
__device__ __forceinline__ uint32_t opaque(uint32_t v) { uint32_t o; asm volatile("mov.u32 %0, %1;" : "=r"(o) : "r"(v)); return o; }
__device__ __forceinline__ uint32_t pack2(float lo, float hi) { uint32_t r; asm("cvt.rn.bf16x2.f32 %0, %1, %2;" : "=r"(r) : "f"(hi), "f"(lo)); return r; }
__device__ __forceinline__ void ldsm4(uint32_t* r, uint32_t a) { asm volatile("ldmatrix.sync.aligned.m8n8.x4.shared.b16 {%0,%1,%2,%3}, [%4];" : "=r"(r[0]), "=r"(r[1]), "=r"(r[2]), "=r"(r[3]) : "r"(a) : "memory"); }
__device__ __forceinline__ void ldsm4t(uint32_t* r, uint32_t a) { asm volatile("ldmatrix.sync.aligned.m8n8.x4.trans.shared.b16 {%0,%1,%2,%3}, [%4];" : "=r"(r[0]), "=r"(r[1]), "=r"(r[2]), "=r"(r[3]) : "r"(a) : "memory"); }
__device__ __forceinline__ void ldsm1(uint32_t& r, uint32_t a) { asm volatile("ldmatrix.sync.aligned.m8n8.x1.shared.b16 {%0}, [%1];" : "=r"(r) : "r"(a) : "memory"); }
__device__ __forceinline__ void stsm4(uint32_t a, uint32_t r0, uint32_t r1, uint32_t r2, uint32_t r3) { asm volatile("stmatrix.sync.aligned.m8n8.x4.shared.b16 [%0], {%1,%2,%3,%4};" :: "r"(a), "r"(r0), "r"(r1), "r"(r2), "r"(r3) : "memory"); }
__device__ __forceinline__ void stsm1(uint32_t a, uint32_t r0) { asm volatile("stmatrix.sync.aligned.m8n8.x1.shared.b16 [%0], {%1};" :: "r"(a), "r"(r0) : "memory"); }
__device__ __forceinline__ void stsm4t(uint32_t a, uint32_t r0, uint32_t r1, uint32_t r2, uint32_t r3) { asm volatile("stmatrix.sync.aligned.m8n8.x4.trans.shared.b16 [%0], {%1,%2,%3,%4};" :: "r"(a), "r"(r0), "r"(r1), "r"(r2), "r"(r3) : "memory"); }
__device__ __forceinline__ void stsm2t(uint32_t a, uint32_t r0, uint32_t r1) { asm volatile("stmatrix.sync.aligned.m8n8.x2.trans.shared.b16 [%0], {%1,%2};" :: "r"(a), "r"(r0), "r"(r1) : "memory"); }
__device__ __forceinline__ void mma16816(float* c, const uint32_t* a, uint32_t b0, uint32_t b1) {
  asm volatile("mma.sync.aligned.m16n8k16.row.col.f32.bf16.bf16.f32 {%0,%1,%2,%3}, {%4,%5,%6,%7}, {%8,%9}, {%0,%1,%2,%3};"
               : "+f"(c[0]), "+f"(c[1]), "+f"(c[2]), "+f"(c[3]) : "r"(a[0]), "r"(a[1]), "r"(a[2]), "r"(a[3]), "r"(b0), "r"(b1));
}
__device__ __forceinline__ void mma1688(float* c, uint32_t a0, uint32_t a1, uint32_t b0) {
  asm volatile("mma.sync.aligned.m16n8k8.row.col.f32.bf16.bf16.f32 {%0,%1,%2,%3}, {%4,%5}, {%6}, {%0,%1,%2,%3};"
               : "+f"(c[0]), "+f"(c[1]), "+f"(c[2]), "+f"(c[3]) : "r"(a0), "r"(a1), "r"(b0));
}
__device__ __forceinline__ void sta1(uint32_t a, uint32_t v, uint32_t bar) { asm volatile("st.async.weak.shared::cluster.mbarrier::complete_tx::bytes.b32 [%0], %1, [%2];" :: "r"(a), "r"(v), "r"(bar) : "memory"); }
__device__ __forceinline__ void sta1p(uint32_t a, uint32_t v, uint32_t bar, bool p) { asm volatile("{\n.reg .pred p;\nsetp.ne.b32 p, %3, 0;\n@p st.async.weak.shared::cluster.mbarrier::complete_tx::bytes.b32 [%0], %1, [%2];\n}" :: "r"(a), "r"(v), "r"(bar), "r"((int)p) : "memory"); }
__device__ __forceinline__ void sta2(uint32_t a, uint32_t v0, uint32_t v1, uint32_t bar) { asm volatile("st.async.weak.shared::cluster.mbarrier::complete_tx::bytes.v2.b32 [%0], {%1,%2}, [%3];" :: "r"(a), "r"(v0), "r"(v1), "r"(bar) : "memory"); }
__device__ __forceinline__ void sta4(uint32_t a, uint32_t v0, uint32_t v1, uint32_t v2, uint32_t v3, uint32_t bar) { asm volatile("st.async.weak.shared::cluster.mbarrier::complete_tx::bytes.v4.b32 [%0], {%1,%2,%3,%4}, [%5];" :: "r"(a), "r"(v0), "r"(v1), "r"(v2), "r"(v3), "r"(bar) : "memory"); }
__device__ __forceinline__ float bflo(uint32_t v) { return __uint_as_float(v << 16); }
__device__ __forceinline__ float bfhi(uint32_t v) { return __uint_as_float(v & 0xFFFF0000u); }
__device__ __forceinline__ void sta2f(uint32_t a, float v0, float v1, uint32_t bar) { asm volatile("st.async.weak.shared::cluster.mbarrier::complete_tx::bytes.v2.f32 [%0], {%1,%2}, [%3];" :: "r"(a), "f"(v0), "f"(v1), "r"(bar) : "memory"); }
__device__ __forceinline__ void sta4f(uint32_t a, float v0, float v1, float v2, float v3, uint32_t bar) { asm volatile("st.async.weak.shared::cluster.mbarrier::complete_tx::bytes.v4.f32 [%0], {%1,%2,%3,%4}, [%5];" :: "r"(a), "f"(v0), "f"(v1), "f"(v2), "f"(v3), "r"(bar) : "memory"); }
__device__ __forceinline__ float4 lds4f(uint32_t a) { float4 v; asm volatile("ld.shared.v4.f32 {%0,%1,%2,%3}, [%4];" : "=f"(v.x), "=f"(v.y), "=f"(v.z), "=f"(v.w) : "r"(a) : "memory"); return v; }
__device__ __forceinline__ float2 lds2f(uint32_t a) { float2 v; asm volatile("ld.shared.v2.f32 {%0,%1}, [%2];" : "=f"(v.x), "=f"(v.y) : "r"(a) : "memory"); return v; }
__device__ __forceinline__ uint4 lds4(uint32_t a) { uint4 v; asm volatile("ld.shared.v4.u32 {%0,%1,%2,%3}, [%4];" : "=r"(v.x), "=r"(v.y), "=r"(v.z), "=r"(v.w) : "r"(a) : "memory"); return v; }
__device__ __forceinline__ uint32_t lds1(uint32_t a) { uint32_t v; asm volatile("ld.shared.u32 %0, [%1];" : "=r"(v) : "r"(a) : "memory"); return v; }
__device__ __forceinline__ void stsm2(uint32_t a, uint32_t r0, uint32_t r1) { asm volatile("stmatrix.sync.aligned.m8n8.x2.shared.b16 [%0], {%1,%2};" :: "r"(a), "r"(r0), "r"(r1) : "memory"); }
__device__ __forceinline__ float rcp(float x) { float y; asm("rcp.approx.ftz.f32 %0, %1;" : "=f"(y) : "f"(x)); return y; }
__device__ __forceinline__ void sts4(uint32_t a, uint32_t v0, uint32_t v1, uint32_t v2, uint32_t v3) { asm volatile("st.shared.v4.u32 [%0], {%1,%2,%3,%4};" :: "r"(a), "r"(v0), "r"(v1), "r"(v2), "r"(v3) : "memory"); }
__device__ __forceinline__ void bulk_s2c(uint32_t dst, uint32_t src, uint32_t bytes, uint32_t bar) {
  asm volatile("cp.async.bulk.shared::cluster.shared::cta.mbarrier::complete_tx::bytes [%0], [%1], %2, [%3];" :: "r"(dst), "r"(src), "r"(bytes), "r"(bar) : "memory");
}
__device__ __forceinline__ void stg4(void* p, uint4 v) { asm volatile("st.global.v4.u32 [%0], {%1,%2,%3,%4};" :: "l"(p), "r"(v.x), "r"(v.y), "r"(v.z), "r"(v.w) : "memory"); }
__device__ __forceinline__ void red_add(uint32_t* p, uint32_t v) { asm volatile("red.relaxed.gpu.global.add.u32 [%0], %1;" :: "l"(p), "r"(v) : "memory"); }
__device__ __forceinline__ void red4f(float* p, float a, float b, float c, float d) { asm volatile("red.relaxed.gpu.global.add.v4.f32 [%0], {%1,%2,%3,%4};" :: "l"(p), "f"(a), "f"(b), "f"(c), "f"(d) : "memory"); }
__device__ __forceinline__ void wait_flag(const uint32_t* p, uint32_t target) {
  uint32_t v; int it = 0;
  while (true) {
    asm volatile("ld.acquire.gpu.global.u32 %0, [%1];" : "=r"(v) : "l"(p) : "memory");
    if (__all_sync(~0u, v >= target)) break;
    if (++it > 4000000) __trap();
    __nanosleep(20);
  }
}
__device__ __forceinline__ void sts2(uint32_t a, uint32_t v0, uint32_t v1) { asm volatile("st.shared.v2.u32 [%0], {%1,%2};" :: "r"(a), "r"(v0), "r"(v1) : "memory"); }
__device__ __forceinline__ float sqrt_approx(float x) { float y; asm("sqrt.approx.f32 %0, %1;" : "=f"(y) : "f"(x)); return y; }
__device__ __forceinline__ void bulk_s2c_elect(uint32_t d1, uint32_t b1, uint32_t d2, uint32_t b2, uint32_t src) {
  asm volatile("{\n.reg .pred p;\nelect.sync _|p, 0xffffffff;\n"
               "@p cp.async.bulk.shared::cluster.shared::cta.mbarrier::complete_tx::bytes [%0], [%4], 1024, [%1];\n"
               "@p cp.async.bulk.shared::cluster.shared::cta.mbarrier::complete_tx::bytes [%2], [%4], 1024, [%3];\n}"
               :: "r"(d1), "r"(b1), "r"(d2), "r"(b2), "r"(src) : "memory");
}
__device__ __forceinline__ void mbar_arrive_elect(uint32_t bar) { asm volatile("{\n.reg .pred p;\nelect.sync _|p, 0xffffffff;\n@p mbarrier.arrive.shared::cta.b64 _, [%0];\n}" :: "r"(bar) : "memory"); }
__device__ __forceinline__ void sts1(uint32_t a, uint32_t v) { asm volatile("st.shared.u32 [%0], %1;" :: "r"(a), "r"(v) : "memory"); }
__device__ __forceinline__ void bulk_g2s(uint32_t dst, const void* src, uint32_t bytes, uint32_t bar) {
  asm volatile("cp.async.bulk.shared::cluster.global.mbarrier::complete_tx::bytes [%0], [%1], %2, [%3];" :: "r"(dst), "l"(src), "r"(bytes), "r"(bar) : "memory");
}
__device__ __forceinline__ void tma2d(uint32_t dst, const CUtensorMap* m, int c0, int c1, uint32_t bar) {
  asm volatile("cp.async.bulk.tensor.2d.shared::cluster.global.mbarrier::complete_tx::bytes [%0], [%1, {%3, %4}], [%2];" :: "r"(dst), "l"((uint64_t)m), "r"(bar), "r"(c0), "r"(c1) : "memory");
}
__device__ __forceinline__ void tma5d(uint32_t dst, const CUtensorMap* m, int c0, int c4, uint32_t bar) {
  asm volatile("cp.async.bulk.tensor.5d.shared::cluster.global.mbarrier::complete_tx::bytes [%0], [%1, {%3, %5, %5, %5, %4}], [%2];" :: "r"(dst), "l"((uint64_t)m), "r"(bar), "r"(c0), "r"(c4), "r"(0) : "memory");
}
__device__ __forceinline__ void red64(void* p, uint32_t lo, uint32_t hi) { asm volatile("{\n.reg .b64 t;\nmov.b64 t, {%1,%2};\nred.relaxed.gpu.global.add.u64 [%0], t;\n}" :: "l"(p), "r"(lo), "r"(hi) : "memory"); }
__device__ __forceinline__ uint4 ld_poll(const void* p) {
  uint4 v;
  asm volatile("{\n.reg .b64 a, b;\nld.relaxed.gpu.global.v2.b64 {a, b}, [%4];\nmov.b64 {%0,%1}, a;\nmov.b64 {%2,%3}, b;\n}" : "=r"(v.x), "=r"(v.y), "=r"(v.z), "=r"(v.w) : "l"(p) : "memory");
  return v;
}
__device__ __forceinline__ uint32_t clk() { uint32_t c; asm volatile("mov.u32 %0, %%clock;" : "=r"(c) :: "memory"); return c; }
#define SCHED_FENCE() asm volatile("pmevent 0;" ::: "memory")
__device__ __forceinline__ float ex2(float x) { float y; asm("ex2.approx.ftz.f32 %0, %1;" : "=f"(y) : "f"(x)); return y; }

__device__ __forceinline__ void wg_ss_n240_ta0_tb1(float* d, uint64_t a, uint64_t b, int sc) {
  asm volatile("{\n.reg .pred p;\nsetp.ne.b32 p, %122, 0;\nwgmma.mma_async.sync.aligned.m64n240k16.f32.bf16.bf16 {%0, %1, %2, %3, %4, %5, %6, %7, %8, %9, %10, %11, %12, %13, %14, %15, %16, %17, %18, %19, %20, %21, %22, %23, %24, %25, %26, %27, %28, %29, %30, %31, %32, %33, %34, %35, %36, %37, %38, %39, %40, %41, %42, %43, %44, %45, %46, %47, %48, %49, %50, %51, %52, %53, %54, %55, %56, %57, %58, %59, %60, %61, %62, %63, %64, %65, %66, %67, %68, %69, %70, %71, %72, %73, %74, %75, %76, %77, %78, %79, %80, %81, %82, %83, %84, %85, %86, %87, %88, %89, %90, %91, %92, %93, %94, %95, %96, %97, %98, %99, %100, %101, %102, %103, %104, %105, %106, %107, %108, %109, %110, %111, %112, %113, %114, %115, %116, %117, %118, %119}, %120, %121, p, 1, 1, 0, 1;\n}\n"
    : "+f"(d[0]), "+f"(d[1]), "+f"(d[2]), "+f"(d[3]), "+f"(d[4]), "+f"(d[5]), "+f"(d[6]), "+f"(d[7]), "+f"(d[8]), "+f"(d[9]), "+f"(d[10]), "+f"(d[11]), "+f"(d[12]), "+f"(d[13]), "+f"(d[14]), "+f"(d[15]), "+f"(d[16]), "+f"(d[17]), "+f"(d[18]), "+f"(d[19]), "+f"(d[20]), "+f"(d[21]), "+f"(d[22]), "+f"(d[23]), "+f"(d[24]), "+f"(d[25]), "+f"(d[26]), "+f"(d[27]), "+f"(d[28]), "+f"(d[29]), "+f"(d[30]), "+f"(d[31]), "+f"(d[32]), "+f"(d[33]), "+f"(d[34]), "+f"(d[35]), "+f"(d[36]), "+f"(d[37]), "+f"(d[38]), "+f"(d[39]), "+f"(d[40]), "+f"(d[41]), "+f"(d[42]), "+f"(d[43]), "+f"(d[44]), "+f"(d[45]), "+f"(d[46]), "+f"(d[47]), "+f"(d[48]), "+f"(d[49]), "+f"(d[50]), "+f"(d[51]), "+f"(d[52]), "+f"(d[53]), "+f"(d[54]), "+f"(d[55]), "+f"(d[56]), "+f"(d[57]), "+f"(d[58]), "+f"(d[59]), "+f"(d[60]), "+f"(d[61]), "+f"(d[62]), "+f"(d[63]), "+f"(d[64]), "+f"(d[65]), "+f"(d[66]), "+f"(d[67]), "+f"(d[68]), "+f"(d[69]), "+f"(d[70]), "+f"(d[71]), "+f"(d[72]), "+f"(d[73]), "+f"(d[74]), "+f"(d[75]), "+f"(d[76]), "+f"(d[77]), "+f"(d[78]), "+f"(d[79]), "+f"(d[80]), "+f"(d[81]), "+f"(d[82]), "+f"(d[83]), "+f"(d[84]), "+f"(d[85]), "+f"(d[86]), "+f"(d[87]), "+f"(d[88]), "+f"(d[89]), "+f"(d[90]), "+f"(d[91]), "+f"(d[92]), "+f"(d[93]), "+f"(d[94]), "+f"(d[95]), "+f"(d[96]), "+f"(d[97]), "+f"(d[98]), "+f"(d[99]), "+f"(d[100]), "+f"(d[101]), "+f"(d[102]), "+f"(d[103]), "+f"(d[104]), "+f"(d[105]), "+f"(d[106]), "+f"(d[107]), "+f"(d[108]), "+f"(d[109]), "+f"(d[110]), "+f"(d[111]), "+f"(d[112]), "+f"(d[113]), "+f"(d[114]), "+f"(d[115]), "+f"(d[116]), "+f"(d[117]), "+f"(d[118]), "+f"(d[119])
    : "l"(a), "l"(b), "r"(sc));
}
__device__ __forceinline__ void wg_ss_n88_ta1_tb1(float* d, uint64_t a, uint64_t b, int sc) {
  asm volatile("{\n.reg .pred p;\nsetp.ne.b32 p, %46, 0;\nwgmma.mma_async.sync.aligned.m64n88k16.f32.bf16.bf16 {%0, %1, %2, %3, %4, %5, %6, %7, %8, %9, %10, %11, %12, %13, %14, %15, %16, %17, %18, %19, %20, %21, %22, %23, %24, %25, %26, %27, %28, %29, %30, %31, %32, %33, %34, %35, %36, %37, %38, %39, %40, %41, %42, %43}, %44, %45, p, 1, 1, 1, 1;\n}\n"
    : "+f"(d[0]), "+f"(d[1]), "+f"(d[2]), "+f"(d[3]), "+f"(d[4]), "+f"(d[5]), "+f"(d[6]), "+f"(d[7]), "+f"(d[8]), "+f"(d[9]), "+f"(d[10]), "+f"(d[11]), "+f"(d[12]), "+f"(d[13]), "+f"(d[14]), "+f"(d[15]), "+f"(d[16]), "+f"(d[17]), "+f"(d[18]), "+f"(d[19]), "+f"(d[20]), "+f"(d[21]), "+f"(d[22]), "+f"(d[23]), "+f"(d[24]), "+f"(d[25]), "+f"(d[26]), "+f"(d[27]), "+f"(d[28]), "+f"(d[29]), "+f"(d[30]), "+f"(d[31]), "+f"(d[32]), "+f"(d[33]), "+f"(d[34]), "+f"(d[35]), "+f"(d[36]), "+f"(d[37]), "+f"(d[38]), "+f"(d[39]), "+f"(d[40]), "+f"(d[41]), "+f"(d[42]), "+f"(d[43])
    : "l"(a), "l"(b), "r"(sc));
}
__device__ __forceinline__ void wg_rs_n160_tb1(float* d, const uint32_t* a, uint64_t b, int sc) {
  asm volatile("{\n.reg .pred p;\nsetp.ne.b32 p, %85, 0;\nwgmma.mma_async.sync.aligned.m64n160k16.f32.bf16.bf16 {%0, %1, %2, %3, %4, %5, %6, %7, %8, %9, %10, %11, %12, %13, %14, %15, %16, %17, %18, %19, %20, %21, %22, %23, %24, %25, %26, %27, %28, %29, %30, %31, %32, %33, %34, %35, %36, %37, %38, %39, %40, %41, %42, %43, %44, %45, %46, %47, %48, %49, %50, %51, %52, %53, %54, %55, %56, %57, %58, %59, %60, %61, %62, %63, %64, %65, %66, %67, %68, %69, %70, %71, %72, %73, %74, %75, %76, %77, %78, %79}, {%80, %81, %82, %83}, %84, p, 1, 1, 1;\n}\n"
    : "+f"(d[0]), "+f"(d[1]), "+f"(d[2]), "+f"(d[3]), "+f"(d[4]), "+f"(d[5]), "+f"(d[6]), "+f"(d[7]), "+f"(d[8]), "+f"(d[9]), "+f"(d[10]), "+f"(d[11]), "+f"(d[12]), "+f"(d[13]), "+f"(d[14]), "+f"(d[15]), "+f"(d[16]), "+f"(d[17]), "+f"(d[18]), "+f"(d[19]), "+f"(d[20]), "+f"(d[21]), "+f"(d[22]), "+f"(d[23]), "+f"(d[24]), "+f"(d[25]), "+f"(d[26]), "+f"(d[27]), "+f"(d[28]), "+f"(d[29]), "+f"(d[30]), "+f"(d[31]), "+f"(d[32]), "+f"(d[33]), "+f"(d[34]), "+f"(d[35]), "+f"(d[36]), "+f"(d[37]), "+f"(d[38]), "+f"(d[39]), "+f"(d[40]), "+f"(d[41]), "+f"(d[42]), "+f"(d[43]), "+f"(d[44]), "+f"(d[45]), "+f"(d[46]), "+f"(d[47]), "+f"(d[48]), "+f"(d[49]), "+f"(d[50]), "+f"(d[51]), "+f"(d[52]), "+f"(d[53]), "+f"(d[54]), "+f"(d[55]), "+f"(d[56]), "+f"(d[57]), "+f"(d[58]), "+f"(d[59]), "+f"(d[60]), "+f"(d[61]), "+f"(d[62]), "+f"(d[63]), "+f"(d[64]), "+f"(d[65]), "+f"(d[66]), "+f"(d[67]), "+f"(d[68]), "+f"(d[69]), "+f"(d[70]), "+f"(d[71]), "+f"(d[72]), "+f"(d[73]), "+f"(d[74]), "+f"(d[75]), "+f"(d[76]), "+f"(d[77]), "+f"(d[78]), "+f"(d[79])
    : "r"(a[0]), "r"(a[1]), "r"(a[2]), "r"(a[3]), "l"(b), "r"(sc));
}
__device__ __forceinline__ void wg_ss_n80_ta0_tb1(float* d, uint64_t a, uint64_t b, int sc) {
  asm volatile("{\n.reg .pred p;\nsetp.ne.b32 p, %42, 0;\nwgmma.mma_async.sync.aligned.m64n80k16.f32.bf16.bf16 {%0, %1, %2, %3, %4, %5, %6, %7, %8, %9, %10, %11, %12, %13, %14, %15, %16, %17, %18, %19, %20, %21, %22, %23, %24, %25, %26, %27, %28, %29, %30, %31, %32, %33, %34, %35, %36, %37, %38, %39}, %40, %41, p, 1, 1, 0, 1;\n}\n"
    : "+f"(d[0]), "+f"(d[1]), "+f"(d[2]), "+f"(d[3]), "+f"(d[4]), "+f"(d[5]), "+f"(d[6]), "+f"(d[7]), "+f"(d[8]), "+f"(d[9]), "+f"(d[10]), "+f"(d[11]), "+f"(d[12]), "+f"(d[13]), "+f"(d[14]), "+f"(d[15]), "+f"(d[16]), "+f"(d[17]), "+f"(d[18]), "+f"(d[19]), "+f"(d[20]), "+f"(d[21]), "+f"(d[22]), "+f"(d[23]), "+f"(d[24]), "+f"(d[25]), "+f"(d[26]), "+f"(d[27]), "+f"(d[28]), "+f"(d[29]), "+f"(d[30]), "+f"(d[31]), "+f"(d[32]), "+f"(d[33]), "+f"(d[34]), "+f"(d[35]), "+f"(d[36]), "+f"(d[37]), "+f"(d[38]), "+f"(d[39])
    : "l"(a), "l"(b), "r"(sc));
}
__device__ __forceinline__ void wg_rs_n32_tb1(float* d, const uint32_t* a, uint64_t b, int sc) {
  asm volatile("{\n.reg .pred p;\nsetp.ne.b32 p, %21, 0;\nwgmma.mma_async.sync.aligned.m64n32k16.f32.bf16.bf16 {%0, %1, %2, %3, %4, %5, %6, %7, %8, %9, %10, %11, %12, %13, %14, %15}, {%16, %17, %18, %19}, %20, p, 1, 1, 1;\n}\n"
    : "+f"(d[0]), "+f"(d[1]), "+f"(d[2]), "+f"(d[3]), "+f"(d[4]), "+f"(d[5]), "+f"(d[6]), "+f"(d[7]), "+f"(d[8]), "+f"(d[9]), "+f"(d[10]), "+f"(d[11]), "+f"(d[12]), "+f"(d[13]), "+f"(d[14]), "+f"(d[15])
    : "r"(a[0]), "r"(a[1]), "r"(a[2]), "r"(a[3]), "l"(b), "r"(sc));
}
__device__ __forceinline__ void wg_ss_n32_ta1_tb1(float* d, uint64_t a, uint64_t b, int sc) {
  asm volatile("{\n.reg .pred p;\nsetp.ne.b32 p, %18, 0;\nwgmma.mma_async.sync.aligned.m64n32k16.f32.bf16.bf16 {%0, %1, %2, %3, %4, %5, %6, %7, %8, %9, %10, %11, %12, %13, %14, %15}, %16, %17, p, 1, 1, 1, 1;\n}\n"
    : "+f"(d[0]), "+f"(d[1]), "+f"(d[2]), "+f"(d[3]), "+f"(d[4]), "+f"(d[5]), "+f"(d[6]), "+f"(d[7]), "+f"(d[8]), "+f"(d[9]), "+f"(d[10]), "+f"(d[11]), "+f"(d[12]), "+f"(d[13]), "+f"(d[14]), "+f"(d[15])
    : "l"(a), "l"(b), "r"(sc));
}
__device__ __forceinline__ void wg_rs_n32_tb0(float* d, const uint32_t* a, uint64_t b, int sc) {
  asm volatile("{\n.reg .pred p;\nsetp.ne.b32 p, %21, 0;\nwgmma.mma_async.sync.aligned.m64n32k16.f32.bf16.bf16 {%0, %1, %2, %3, %4, %5, %6, %7, %8, %9, %10, %11, %12, %13, %14, %15}, {%16, %17, %18, %19}, %20, p, 1, 1, 0;\n}\n"
    : "+f"(d[0]), "+f"(d[1]), "+f"(d[2]), "+f"(d[3]), "+f"(d[4]), "+f"(d[5]), "+f"(d[6]), "+f"(d[7]), "+f"(d[8]), "+f"(d[9]), "+f"(d[10]), "+f"(d[11]), "+f"(d[12]), "+f"(d[13]), "+f"(d[14]), "+f"(d[15])
    : "r"(a[0]), "r"(a[1]), "r"(a[2]), "r"(a[3]), "l"(b), "r"(sc));
}
__device__ __forceinline__ void wg_rs_n40_tb0(float* d, const uint32_t* a, uint64_t b, int sc) {
  asm volatile("{\n.reg .pred p;\nsetp.ne.b32 p, %25, 0;\nwgmma.mma_async.sync.aligned.m64n40k16.f32.bf16.bf16 {%0, %1, %2, %3, %4, %5, %6, %7, %8, %9, %10, %11, %12, %13, %14, %15, %16, %17, %18, %19}, {%20, %21, %22, %23}, %24, p, 1, 1, 0;\n}\n"
    : "+f"(d[0]), "+f"(d[1]), "+f"(d[2]), "+f"(d[3]), "+f"(d[4]), "+f"(d[5]), "+f"(d[6]), "+f"(d[7]), "+f"(d[8]), "+f"(d[9]), "+f"(d[10]), "+f"(d[11]), "+f"(d[12]), "+f"(d[13]), "+f"(d[14]), "+f"(d[15]), "+f"(d[16]), "+f"(d[17]), "+f"(d[18]), "+f"(d[19])
    : "r"(a[0]), "r"(a[1]), "r"(a[2]), "r"(a[3]), "l"(b), "r"(sc));
}
__device__ __forceinline__ void wg_rs_n8_tb1(float* d, const uint32_t* a, uint64_t b, int sc) {
  asm volatile("{\n.reg .pred p;\nsetp.ne.b32 p, %9, 0;\nwgmma.mma_async.sync.aligned.m64n8k16.f32.bf16.bf16 {%0, %1, %2, %3}, {%4, %5, %6, %7}, %8, p, 1, 1, 1;\n}\n"
    : "+f"(d[0]), "+f"(d[1]), "+f"(d[2]), "+f"(d[3])
    : "r"(a[0]), "r"(a[1]), "r"(a[2]), "r"(a[3]), "l"(b), "r"(sc));
}
__device__ __forceinline__ void wg_ss_n40_ta0_tb0(float* d, uint64_t a, uint64_t b, int sc) {
  asm volatile("{\n.reg .pred p;\nsetp.ne.b32 p, %22, 0;\nwgmma.mma_async.sync.aligned.m64n40k16.f32.bf16.bf16 {%0, %1, %2, %3, %4, %5, %6, %7, %8, %9, %10, %11, %12, %13, %14, %15, %16, %17, %18, %19}, %20, %21, p, 1, 1, 0, 0;\n}\n"
    : "+f"(d[0]), "+f"(d[1]), "+f"(d[2]), "+f"(d[3]), "+f"(d[4]), "+f"(d[5]), "+f"(d[6]), "+f"(d[7]), "+f"(d[8]), "+f"(d[9]), "+f"(d[10]), "+f"(d[11]), "+f"(d[12]), "+f"(d[13]), "+f"(d[14]), "+f"(d[15]), "+f"(d[16]), "+f"(d[17]), "+f"(d[18]), "+f"(d[19])
    : "l"(a), "l"(b), "r"(sc));
}
__device__ __forceinline__ void wg_ss_n40_ta1_tb0(float* d, uint64_t a, uint64_t b, int sc) {
  asm volatile("{\n.reg .pred p;\nsetp.ne.b32 p, %22, 0;\nwgmma.mma_async.sync.aligned.m64n40k16.f32.bf16.bf16 {%0, %1, %2, %3, %4, %5, %6, %7, %8, %9, %10, %11, %12, %13, %14, %15, %16, %17, %18, %19}, %20, %21, p, 1, 1, 1, 0;\n}\n"
    : "+f"(d[0]), "+f"(d[1]), "+f"(d[2]), "+f"(d[3]), "+f"(d[4]), "+f"(d[5]), "+f"(d[6]), "+f"(d[7]), "+f"(d[8]), "+f"(d[9]), "+f"(d[10]), "+f"(d[11]), "+f"(d[12]), "+f"(d[13]), "+f"(d[14]), "+f"(d[15]), "+f"(d[16]), "+f"(d[17]), "+f"(d[18]), "+f"(d[19])
    : "l"(a), "l"(b), "r"(sc));
}
__device__ __forceinline__ void wg_ss_n8_ta1_tb1(float* d, uint64_t a, uint64_t b, int sc) {
  asm volatile("{\n.reg .pred p;\nsetp.ne.b32 p, %6, 0;\nwgmma.mma_async.sync.aligned.m64n8k16.f32.bf16.bf16 {%0, %1, %2, %3}, %4, %5, p, 1, 1, 1, 1;\n}\n"
    : "+f"(d[0]), "+f"(d[1]), "+f"(d[2]), "+f"(d[3])
    : "l"(a), "l"(b), "r"(sc));
}

constexpr int O_WV = 0, O_WO = 81920, O_H = 163840, O_QK = 215040, O_SM = 228352, O_MISC = 229632;
constexpr int O_QM = O_QK + 1024, O_K = O_QK + 3072, O_OG = O_QK + 8192;
constexpr int SM_SLOT = 640;
constexpr int O_MAXS = O_MISC;
constexpr int O_BAR = O_MISC + 64;
constexpr int MB_XF = 0, MB_ML = 2, MB_MR = 4, MB_SM = 7, MB_SX = 8, MB_OG = 9, MB_W = 10;
constexpr int O_PROF = O_BAR + 8 * 24;
constexpr int REC_SMEM = O_PROF + 128;
constexpr int B_VOWN = 0, B_QK = 1, B_VGO = 2, B_SISS = 3, B_PM = 4, B_PX = 5, B_XGO = 6, B_PFREE = 7, B_WG2 = 8, B_VHALF = 9, B_VDONE = 10,
              B_PFREE1 = 11, B_SSENT = 12, B_SLD = 13, B_VEND = 14, B_XGO1 = 15;
#define POLL_DELAY 650
#define POLL_D0 300
#define POLL_STEP 100
#define TS0(idx) do {} while (0)
#define TS(idx) do {} while (0)
#define SLD_POS 0
#define FILL_B 4096
#define MP_D 3
#define MP_CH 4
#define MP_F 0
#define ML_N0 3
#define MR_N0 3
#define O_RS 6
#define O_RS_POS 0
#define V_N1 2
#define V_N2 0
#define V_N3 4
#define V_OWN 10
#define V_S1 9
#define V_K1 (V_OWN + V_RS + V_S1)
#define V_K2 ((V_K1 > 20 ? V_K1 : 20) + V_S2)
#define V_S2 3
constexpr int V_RS = V_N1 + V_N2 + V_N3;
constexpr float SCL = 0.07216878364870322f;
constexpr float L2E = 1.4426950408889634f;
__device__ __forceinline__ constexpr int vord(int i) { return i < 4 ? 36 + i : i - 4; }
__device__ __forceinline__ constexpr uint32_t hoff(int k) { return ((k >> 2) * 5120 + (k & 3) * 32) >> 4; }

__device__ __forceinline__ void fix_red(uint8_t* p, const float* a, float sc) {
  int v0 = __float2int_rn(a[0] * sc), v1 = __float2int_rn(a[1] * sc), v2 = __float2int_rn(a[2] * sc), v3 = __float2int_rn(a[3] * sc);
  red64(p, ((uint32_t)v0 << 7) | 1u, ((uint32_t)v2 << 3) + (uint32_t)(v0 >> 25));
  red64(p + 1024, ((uint32_t)v1 << 7) | 1u, ((uint32_t)v3 << 3) + (uint32_t)(v1 >> 25));
}
__device__ __forceinline__ float max10(const float* t) {
  float m = fmaxf(fmaxf(fmaxf(t[0], t[1]), fmaxf(t[2], t[3])), fmaxf(fmaxf(t[4], t[5]), fmaxf(t[6], t[7])));
  m = fmaxf(m, fmaxf(t[8], t[9]));
  m = fmaxf(m, __shfl_xor_sync(~0u, m, 1));
  return fmaxf(m, __shfl_xor_sync(~0u, m, 2));
}
#define ACC2(k, p, u, v) { t[k] = bflo(p) + bflo(u) + bflo(v); t[k + 1] = bfhi(p) + bfhi(u) + bfhi(v); }

__global__ void __launch_bounds__(384, 1)
rec_kernel(const __grid_constant__ CUtensorMap tmq, const __grid_constant__ CUtensorMap tmk,
           const __grid_constant__ CUtensorMap tmv, const __grid_constant__ CUtensorMap tmo,
           const bf16* __restrict__ mem0, uint8_t* __restrict__ ar, uint32_t* __restrict__ flags, int layer) {
  extern __shared__ __align__(1024) uint8_t smem[];
  const uint32_t sb = smem_u32(smem);
  check_smem_base(sb);
  const int tid = threadIdx.x, wid = __shfl_sync(~0u, tid >> 5, 0), wg = wid >> 2, w = wid & 3;
  const int lane = __shfl_sync(~0u, tid & 31, tid & 31);
  const int head = blockIdx.x / 3, rank = blockIdx.x - head * 3;
  const int e0 = blockIdx.x * 64;
  const uint32_t bar = sb + O_BAR;
  const uint32_t sb1 = mapa(sb, rank == 2 ? 0 : rank + 1), sb2 = mapa(sb, rank == 0 ? 2 : rank - 1);
  auto chunk_of = [&](int p) { const int c = 3 * rank + p; return p == 9 ? 9 : c >= 9 ? c - 9 : c; };

  GT(layer * 4 + 1, 0);
  if (wid == 8) {
    if (lane < 24) mbar_init(bar + 8 * lane, lane == MB_ML ? ML_N0 : lane == MB_ML + 1 && ML_N0 < 4 ? 4 - ML_N0 : 1);
    asm volatile("fence.mbarrier_init.release.cluster;" ::: "memory");
    fence_async();
    __syncwarp();
    if (lane < 10) mbar_expect(bar + 8 * (MB_W + lane), 16384);
    __syncwarp();
    if (lane < 20) {
      const int m = (lane >> 1) & 1, p = (lane >> 2) * 2 + (lane & 1);
      tma5d(sb + m * 81920 + p * 8192, m ? &tmk : &tmq, e0, chunk_of(p) * 4, bar + 8 * (MB_W + m * 5 + (p >> 1)));
    }
  }
  __syncthreads();
  asm volatile("barrier.cluster.arrive.relaxed.aligned;" ::: "memory");

  if (wg < 2) {
    asm volatile("setmaxnreg.inc.sync.aligned.u32 208;");
    uint32_t a[40][4];
    const uint32_t swz = __shfl_sync(~0u, (lane & 7) * 128 + (((2 * w + ((lane >> 3) & 1)) ^ (lane & 7)) << 4), lane);
    {
      const uint32_t la = sb + wg * 81920 + (lane >> 4) * 1024 + swz;
#pragma unroll
      for (int p = 0; p < 5; p++) {
        mbar_wait(bar + 8 * (MB_W + wg * 5 + p), 0);
#pragma unroll
        for (int k = 0; k < 8; k++) ldsm4t(a[p * 8 + k], la + (p * 8 + k) * 2048);
        if (p > 0) bar_sync<B_VGO, 288>();
        bar_arrive<B_PFREE, 288>();
      }
      bar_sync<B_VGO, 288>();
    }
    GT(layer * 4 + 1, 5);
    asm volatile("barrier.cluster.wait.aligned;" ::: "memory");
    const uint32_t ld_m = __shfl_sync(~0u, sb + O_H + (lane & 7) * 128 + (((lane >> 3) ^ (lane & 7)) << 4), lane);

    for (int s = 0; s < NSEG; s++) {
      const uint32_t par = s & 1;
      if (wid == 4) TS0(0);
      if (wid == 0) TS(30);
      {
        float ax[16];
        constexpr uint64_t db = mkdesc(SB0 + O_H + 1024, 16, 1024, 1);
        mbar_wait(bar + 8 * MB_XF, par);
        wg_fence();
#pragma unroll
        for (int k = 0; k < 20; k++) wg_rs_n32_tb0(ax, a[vord(k)], db + hoff(vord(k)), k);
        mbar_wait(bar + 8 * (MB_XF + 1), par);
        wg_fence();
#pragma unroll
        for (int k = 20; k < 40; k++) wg_rs_n32_tb0(ax, a[vord(k)], db + hoff(vord(k)), 1);
        wg_commit();
        if (s > 0) { if (wg == 0) bar_sync<B_PFREE, 256>(); else bar_sync<B_PFREE1, 256>(); }
        const uint32_t st_x = sb + O_QK + wg * 5120 + (lane >> 4) * 2048 + swz;
        if (wid == 6 && lane == 0) { mbar_expect(bar + 8 * MB_SM, 2 * SM_SLOT + 48 + 48); mbar_expect(bar + 8 * MB_SX, 2 * 2176); }
        wg_wait<0>();
        pin<16>(ax);
        if (w == 0) TS(1 + 22 * wg);
        stsm4t(st_x, pack2(ax[0], ax[1]), pack2(ax[2], ax[3]), pack2(ax[4], ax[5]), pack2(ax[6], ax[7]));
        stsm4t(st_x + 4096, pack2(ax[8], ax[9]), pack2(ax[10], ax[11]), pack2(ax[12], ax[13]), pack2(ax[14], ax[15]));
        if (V_OWN > 0) bar_arrive<B_VOWN, 384>();
      }
      {
        float c[MP_CH][4];
#pragma unroll
        for (int k = 0; k < MP_CH; k++) c[k][0] = c[k][1] = c[k][2] = c[k][3] = 0.f;
        uint32_t b[MP_D][2][4];
        const uint32_t ld_m2 = opaque(ld_m ^ 64);
        SCHED_FENCE();
#define MORD(j) ((j) == 0 ? 9 : (j) < 4 ? (j) - 1 : 3 + ((j) - 4) / 2 + 3 * ((j) & 1))
#pragma unroll
        for (int j = 0; j < 10 + MP_D - 1; j++) {
          if (j < 10) {
            if (j == 0) { mbar_wait(bar + 8 * MB_ML, par); if (wid == 0) TS(2); }
            if (ML_N0 < 4 && j == ML_N0) { mbar_wait(bar + 8 * (MB_ML + 1), par); if (wid == 0) TS(3); }
            if (j == 4) { mbar_wait(bar + 8 * MB_MR, par); if (wid == 0) TS(4); }
            if (j == 4 + 2 * MR_N0) { mbar_wait(bar + 8 * (MB_MR + 1), par); if (wid == 0) TS(5); }
            ldsm4(b[j % MP_D][0], ld_m + MORD(j) * 5120);
            ldsm4(b[j % MP_D][1], ld_m2 + MORD(j) * 5120);
            if ((MP_F >> j) & 1) SCHED_FENCE();
          }
          const int u = j - (MP_D - 1);
          if (u >= 0) {
#pragma unroll
            for (int k = 0; k < 4; k++) mma16816(c[(4 * u + k) % MP_CH], a[4 * MORD(u) + k], b[u % MP_D][k >> 1][(k & 1) * 2], b[u % MP_D][k >> 1][(k & 1) * 2 + 1]);
          }
        }
        SCHED_FENCE();
        bar_arrive<B_VGO, 384>();
        SCHED_FENCE();
#pragma unroll
        for (int k = 0; k < 4; k++) c[0][k] = MP_CH == 4 ? (c[0][k] + c[1][k]) + (c[2][k] + c[MP_CH - 1][k]) : (c[1][k] + c[2][k]) + c[0][k];
        stsm2t(sb + O_QM + wg * 2048 + swz, pack2(c[0][0], c[0][1]), pack2(c[0][2], c[0][3]));
        fence_async();
      }
      if (wg == 0) {
        bar_sync<B_QK, 256>();
        float sv[20];
        {
          constexpr uint64_t da = mkdesc(SB0 + O_QK, 16, 1024, 1), db = mkdesc(SB0 + O_K, 16, 2048, 1);
          wg_fence();
#pragma unroll
          for (int k = 0; k < 4; k++) wg_ss_n40_ta0_tb0(sv, da + 2 * k, db + 2 * k, k);
          wg_commit();
          bar_arrive<B_SISS, 256>();
        }
        if (w == 0) TS(6);
        SCHED_FENCE();
        const uint32_t ln = opaque(lane);
        uint32_t m0, m1, m2, m3, m4;
        {
          const uint32_t a1 = opaque(sb1 + O_SM + SM_SLOT + ln * 16), a2 = opaque(sb2 + O_SM + ln * 16);
          const uint32_t a3 = opaque(sb1 + O_SM + SM_SLOT + 512 + ln * 4), a4 = opaque(sb2 + O_SM + 512 + ln * 4);
          const uint32_t b1 = opaque(sb1 + O_BAR + 8 * MB_SM), b2 = opaque(sb2 + O_BAR + 8 * MB_SM);
          const uint32_t bt = opaque(mapa(sb, min(ln, 2u)) + O_BAR + 8 * MB_SM), at = opaque(bt + (O_MAXS + 48 - O_BAR - 8 * MB_SM));
          SCHED_FENCE();
          wg_wait<0>();
          pin<20>(sv);
          m0 = pack2(sv[2], sv[3]); m1 = pack2(sv[6], sv[7]); m2 = pack2(sv[10], sv[11]); m3 = pack2(sv[14], sv[15]); m4 = pack2(sv[18], sv[19]);
          if (w == 0) {
            sta4(a1, m0, m1, m2, m3, b1);
            sta4(a2, m0, m1, m2, m3, b2);
            sta1(a3, m4, b1);
            sta1(a4, m4, b2);
          }
          sta1p(at, 0u, bt, ln < 3);
          bar_arrive<B_SSENT, 256>();
          SCHED_FENCE();
        }
        const uint32_t p0 = pack2(sv[0], sv[1]), p1 = pack2(sv[4], sv[5]), p2 = pack2(sv[8], sv[9]), p3 = pack2(sv[12], sv[13]), p4 = pack2(sv[16], sv[17]);
        const uint32_t ox = O_K + w * 2048 + ln * 16, ox2 = O_K + 8192 + ln * 4;
        {
          const uint32_t a1 = opaque(sb1 + ox + 512), a2 = opaque(sb2 + ox), b1 = opaque(sb1 + O_BAR + 8 * MB_SX), b2 = opaque(sb2 + O_BAR + 8 * MB_SX);
          if (w == 0) {
            TS(7);
            const uint32_t om = opaque(sb + O_SM + ln * 16), om2 = opaque(sb + O_SM + 512 + ln * 4);
            const uint32_t pa = sb + O_QM + (ln & 7) * 128;
            const uint32_t pa0 = opaque(pa + (((ln >> 3) ^ (ln & 7)) << 4)), pa1 = opaque(pa + ((4 ^ (ln & 7)) << 4));
            float t[10] = {bflo(m0), bfhi(m0), bflo(m1), bfhi(m1), bflo(m2), bfhi(m2), bflo(m3), bfhi(m3), bflo(m4), bfhi(m4)};
            pin<10>(t);
            SCHED_FENCE();
            mbar_wait(bar + 8 * MB_SM, par);
            const uint4 u = lds4(om), v = lds4(om + SM_SLOT);
            const uint32_t u4 = lds1(om2), v4 = lds1(om2 + SM_SLOT);
            sta4(a1, p0, p1, p2, p3, b1);
            sta4(a2, p0, p1, p2, p3, b2);
            if (SLD_POS == 0) bar_arrive<B_SLD, 256>();
            SCHED_FENCE();
#define ACC3(k, u, v) { t[k] += bflo(u) + bflo(v); t[k + 1] += bfhi(u) + bfhi(v); }
            ACC3(0, u.x, v.x) ACC3(2, u.y, v.y) ACC3(4, u.z, v.z) ACC3(6, u.w, v.w) ACC3(8, u4, v4)
            TS(8);
            const float mm = max10(t) * (SCL * L2E);
            if (SLD_POS == 1) { SCHED_FENCE(); bar_arrive<B_SLD, 256>(); SCHED_FENCE(); }
#pragma unroll
            for (int k = 0; k < 10; k++) t[k] = ex2(fmaf(t[k], SCL * L2E, -mm));
            stsm4(pa0, pack2(t[0], t[1]), pack2(t[2], t[3]), pack2(t[4], t[5]), pack2(t[6], t[7]));
            stsm1(pa1, pack2(t[8], t[9]));
            bar_arrive<B_PM, 160>();
            TS(9);
          } else {
            const uint32_t a3 = opaque(sb1 + ox2 + 128), a4 = opaque(sb2 + ox2);
            SCHED_FENCE();
            mbar_wait(bar + 8 * MB_SM, par);
            sta4(a1, p0, p1, p2, p3, b1);
            sta4(a2, p0, p1, p2, p3, b2);
            if (w == 3) { sta1(a3, p4, b1); sta1(a4, p4, b2); }
            bar_arrive<B_SLD, 256>();
          }
        }
        mbar_wait(bar + 8 * MB_SX, par);
        bar_sync<B_VEND, 256>();
        {
          float t[10];
          const uint4 u = lds4(sb + ox), v = lds4(sb + ox + 512);
          const uint32_t u4 = lds1(sb + ox2), v4 = lds1(sb + ox2 + 128);
          SCHED_FENCE();
          ACC2(0, p0, u.x, v.x) ACC2(2, p1, u.y, v.y) ACC2(4, p2, u.z, v.z) ACC2(6, p3, u.w, v.w) ACC2(8, p4, u4, v4)
          const int dq = 8 * w + (ln >> 2) - 2 * (ln & 3);
#pragma unroll
          for (int k = 1; k < 5; k++) {
            if (8 * (k - 1) > dq) t[2 * k] = -1e9f / SCL;
            if (8 * (k - 1) + 1 > dq) t[2 * k + 1] = -1e9f / SCL;
          }
          const float mm = max10(t) * (SCL * L2E);
#pragma unroll
          for (int k = 0; k < 10; k++) t[k] = ex2(fmaf(t[k], SCL * L2E, -mm));
          float sum = ((t[0] + t[1]) + (t[2] + t[3])) + ((t[4] + t[5]) + (t[6] + t[7])) + (t[8] + t[9]);
          sum += __shfl_xor_sync(~0u, sum, 1);
          sum += __shfl_xor_sync(~0u, sum, 2);
          const float inv = rcp(sum);
          const int rr = 2 * w + (ln & 1);
          const uint32_t pa = sb + O_QK + ((ln >> 1) & 3) * 2048 + rr * 128;
          stsm4(pa + (((ln >> 3) ^ rr) << 4), pack2(t[0] * inv, t[1] * inv), pack2(t[2] * inv, t[3] * inv), pack2(t[4] * inv, t[5] * inv), pack2(t[6] * inv, t[7] * inv));
          stsm2(pa + (((4 + ((ln >> 3) & 1)) ^ rr) << 4), pack2(t[8] * inv, t[9] * inv), 0u);
          fence_async();
        }
        bar_arrive<B_PX, 256>();
        if (w == 0) TS(10);
        bar_sync<B_XGO, 256>();
      } else {
        bar_arrive<B_QK, 256>();
        const int ln = opaque(lane);
        if (w == 2) {
          bar_sync<B_VHALF, 192>();
          if (ln == 0 && s > 0) { __threadfence(); red_add(flags + FL_A + (e0 >> 10) * 8 + (s - 1) * 48, 1); }
          __syncwarp();
        }
        if (w == 3) {
          const int l = blockIdx.x * 2 + ln, s2 = s + 2;
          if (ln < 2 && l < 160 && s2 < NSEG - 1) {
            const int tile = l >> 4;
            const uint8_t* p = ar + (s2 >> 2) * AR_GROUP + (s2 & 1) * 128 + ((s2 >> 1) & 1) * 512 + ((tile >> 2) * 8 + (tile & 3)) * 4096 +
                               ((l >> 3) & 1) * 16384 + (l & 1) * 256 + ((l >> 1) & 3) * 1024;
            asm volatile("prefetch.global.L2 [%0];" :: "l"(p));
          }
        }
        if (w == 0) {
          const bool more = s + 1 < NSEG;
          if (ln < 2 && more) mbar_expect(bar + 8 * (MB_XF + ln), FILL_B * 5);
          const uint8_t* src = g_xn + (s + 1) * 40960 + chunk_of(ln) * 4096;
          bar_sync<B_VHALF, 192>();
          if ((ln < 4 || ln == 9) && more) bulk_g2s(sb + O_H + ln * 5120 + 1024, src, FILL_B, bar + 8 * MB_XF);
          bar_sync<B_VDONE, 160>();
          if (ln >= 4 && ln < 9 && more) bulk_g2s(sb + O_H + ln * 5120 + 1024, src, FILL_B, bar + 8 * (MB_XF + 1));
        }
        bar_sync<B_XGO1, 256>();
      }
    }
  } else {
    asm volatile("setmaxnreg.dec.sync.aligned.u32 88;");
    if (w == 1) {
      if (lane == 0) { mbar_expect(bar + 8 * (MB_W + 10), 81920); mbar_expect(bar + 8 * (MB_W + 11), 81920); }
#pragma unroll 1
      for (int p = 0; p < 5; p++) {
        bar_sync<B_PFREE, 288>();
        fence_async();
        if (lane < 2) tma5d(sb + O_WV + (2 * p + lane) * 8192, &tmv, e0, chunk_of(2 * p + lane) * 4, bar + 8 * (MB_W + 10));
        bar_arrive<B_VGO, 288>();
      }
      if (lane < 10) {
        const int k = lane / 3, j = rank + lane - 3 * k;
        tma2d(sb + O_WO + lane * 8192, &tmo, lane == 9 ? 576 : (rank * 3 + k) * 64, head * DH + (j >= 3 ? j - 3 : j) * 64, bar + 8 * (MB_W + 11));
      }
    }
    if (w == 0) {
      if (lane < 2) mbar_expect(bar + 8 * (MB_XF + lane), 20480);
      wait_flag(flags + FL_X, 128);
      asm volatile("fence.proxy.async;" ::: "memory");
      if (lane < 10) bulk_g2s(sb + O_H + lane * 5120 + 1024, g_xn + chunk_of(lane) * 4096, 4096, bar + 8 * (MB_XF + (lane >= 4 && lane < 9)));
      asm volatile("griddepcontrol.launch_dependents;");
      if (lane == 0) GTT(layer * 4 + 1, 4);
    }
    bar_sync<B_WG2, 128>();
    const float2 nrm = __ldcg((const float2*)(g_zero + Z_NORM));
    const float cbound = sqrt_approx(nrm.x) * sqrt_approx(nrm.y) * (25.2982213f * 1.1f);
    asm volatile("barrier.cluster.wait.aligned;" ::: "memory");

    const int g = lane >> 2, i4 = lane & 3;
    const int myT = w == 0 ? 9 : rank * 3 + w - 1, myP = w == 0 ? 9 : w - 1;
    const int tok = 2 * ((lane >> 1) & 3) + ((lane >> 3) & 1);
    const uint32_t fw_off = sb + O_H + myP * 5120 + tok * 128 + (((2 * (lane >> 4) + (lane & 1)) ^ tok) << 4);
    const uint32_t prod_off = (w >> 1) * 16384 + (w & 1) * 2048 + ((g >> 1) & 1) * 256 + (i4 * 2 + (g >> 2)) * 16 + (g & 1) * 8;
    const uint32_t cons_off = ((myT >> 2) * 8 + (myT & 3)) * 4096 + (lane >> 3) * 1024 + (lane & 7) * 16;
    auto tile_off = [&](int k) { const int T = rank * 3 + k; return ((T >> 2) * 8 + (T & 3)) * 4096; };
    constexpr uint32_t T9_OFF = 17 * 4096;

    uint32_t mx;
    auto forward = [&](const uint32_t* p) {
      const uint32_t c = O_H + myP * 5120, bo = O_BAR + 8 * (MB_MR + (w > MR_N0));
      sts4(fw_off, p[0], p[1], p[2], p[3]);
      sts4(fw_off ^ 64, p[4], p[5], p[6], p[7]);
      fence_async();
      __syncwarp();
      mbar_arrive_elect(bar + 8 * (MB_ML + (w >= ML_N0)));
      if (w > 0) bulk_s2c_elect(sb1 + c + 6 * 5120, sb1 + bo, sb2 + c + 3 * 5120, sb2 + bo, sb + c);
      SCHED_FENCE();
      mx = 0;
#pragma unroll
      for (int k = 0; k < 8; k++) mx = __vmaxu2(mx, p[k] & 0x7FFF7FFFu);
    };
    auto send_max = [&]() {
      mx = max(mx & 0xFFFFu, mx >> 16);
      mx = __reduce_max_sync(~0u, mx);
      { const uint32_t b = mapa(sb, min(lane, 2)); sta1p(b + O_MAXS + (rank * 4 + w) * 4, mx << 16, b + O_BAR + 8 * MB_SM, lane < 3); }
    };
    auto arm = [&]() { if (lane == 0 && w < (MR_N0 < 3 ? 3 : 2)) mbar_expect(bar + 8 * (w == 0 ? MB_OG : MB_MR - 1 + w), w == 0 ? 2048 : w == 1 ? 2048 * MR_N0 : 2048 * (3 - MR_N0)); };
    {
      arm();
      const uint32_t* mp = (const uint32_t*)(mem0 + tok * DM + myT * 64 + 16 * (lane >> 4) + 4 * (lane & 1));
      const uint32_t p[8] = {mp[0], mp[4], mp[1], mp[5], mp[16], mp[20], mp[17], mp[21]};
      forward(p);
    }
    mbar_wait(bar + 8 * (MB_W + 10), 0);
    if (tid == 256) GTT(layer * 4 + 1, 7);

    const uint32_t la_w = sb + O_WV + ((lane >> 4) * 8 + (lane & 7)) * 128 + (((2 * w + ((lane >> 3) & 1)) ^ (lane & 7)) << 4);
    uint32_t af[V_RS][4];
#pragma unroll
    for (int k = 0; k < V_RS; k++) ldsm4t(af[k], la_w + vord(V_OWN + k) * 2048);
    uint32_t vf[10];
    uint4 oq0, oq1;
    uint8_t* op;
    auto pv_x = [&](int s) {
      float ox[16];
      const uint32_t vz[4] = {vf[8], vf[9], 0u, 0u};
      constexpr uint64_t dp = mkdesc(SB0 + O_QK, 16, 2048, 1);
      bar_sync<B_PX, 256>();
      wg_fence();
      wg_rs_n32_tb0(ox, vf, dp, 0);
      wg_rs_n32_tb0(ox, vf + 4, dp + 2, 1);
      wg_rs_n32_tb0(ox, vz, dp + 4, 1);
      wg_commit();
      const uint32_t ln = opaque(lane);
      op = g_ot + (size_t)s * (HE * 64) + (e0 + 16 * w) * 64 + (ln & 3) * 128 + (ln >> 2) * 16;
      wg_wait<0>();
      pin<16>(ox);
      oq0 = make_uint4(pack2(ox[0], ox[1]), pack2(ox[4], ox[5]), pack2(ox[8], ox[9]), pack2(ox[12], ox[13]));
      oq1 = make_uint4(pack2(ox[2], ox[3]), pack2(ox[6], ox[7]), pack2(ox[10], ox[11]), pack2(ox[14], ox[15]));
    };
    for (int s = 0;; s++) {
      const uint32_t par = s & 1;
      float sc, isc;
      uint32_t ao[O_RS > 0 ? O_RS : 1][4];
      {
        float av[20];
        constexpr uint64_t da = mkdesc(SB0 + O_WV, 1024, 1024, 1), db = mkdesc(SB0 + O_H, 16, 1024, 1);
#define V_RUN_RS(k0, k1) wg_fence(); _Pragma("unroll") for (int k = k0; k < k1; k++) wg_rs_n40_tb0(av, af[k], db + hoff(vord(V_OWN + k)), V_OWN + k);
#define V_RUN_SS(k0, k1) wg_fence(); _Pragma("unroll") for (int k = k0; k < k1; k++) wg_ss_n40_ta1_tb0(av, da + vord(k) * 128, db + hoff(vord(k)), k);
        if (V_OWN > 0) {
          bar_sync<B_VOWN, 384>();
          V_RUN_SS(0, V_OWN)
          if (w == 0) TS(29);
          SCHED_FENCE();
        }
        send_max();
        bar_sync<B_VGO, 384>();
        V_RUN_RS(0, V_N1)
        if (w == 0) TS(11);
        bar_sync<B_SISS, 256>();
        V_RUN_RS(V_N1, V_N1 + V_N2)
        bar_sync<B_SSENT, 256>();
        V_RUN_SS(V_OWN + V_RS, V_K1)
        V_RUN_RS(V_N1 + V_N2, V_RS)
        const uint32_t ln = opaque(lane);
        const uint32_t amx = opaque(sb + O_MAXS + 4 * min(ln, 11u));
        SCHED_FENCE();
        mbar_wait(bar + 8 * MB_SM, par);
        const uint32_t mxl = lds1(amx);
        if (s == 0) mbar_wait(bar + 8 * (MB_W + 11), 0);
        bar_sync<B_SLD, 256>();
        V_RUN_SS(V_K1, 20)
        wg_commit();
        V_RUN_SS((V_K1 > 20 ? V_K1 : 20), V_K2)
        wg_commit();
        wg_wait<1>();
        bar_arrive<B_VHALF, 192>();
        V_RUN_SS(V_K2, 40)
        wg_commit();
        SCHED_FENCE();
        if (w == 0) TS(12);
        {
          const float bnd = cbound * fmaxf(1.f, __uint_as_float(__reduce_max_sync(~0u, mxl)));
          const uint32_t eb = min(max(__float_as_uint(bnd) >> 23, 31u), 254u);
          sc = __uint_as_float(opaque((280u - eb) << 23));
          isc = __uint_as_float(opaque((eb - 29u) << 23));
        }
        const uint32_t pa = sb + O_QM + (ln & 7) * 128;
        const uint32_t pa0 = opaque(pa + (((ln >> 3) ^ (ln & 7)) << 4)), pa1 = opaque(pa + ((4 ^ (ln & 7)) << 4));
        const uint32_t o = O_OG + w * 256 + ln * 4;
        const uint32_t a0 = opaque(sb + o), a1 = opaque(sb1 + o + 4096), a2 = opaque(sb1 + o + 4096 + 128), a3 = opaque(sb2 + o + 2048), a4 = opaque(sb2 + o + 2048 + 128);
        const uint32_t b1 = opaque(sb1 + O_BAR + 8 * MB_OG), b2 = opaque(sb2 + O_BAR + 8 * MB_OG);
        const uint32_t c1 = opaque(0x3F803F80u);
        const uint32_t one[4] = {c1, c1, c1, c1};
        SCHED_FENCE();
        bar_sync<B_PM, 160>();
        uint32_t pm[5];
        ldsm4(pm, pa0);
        ldsm1(pm[4], pa1);
        bar_arrive<B_VEND, 256>();
        float s0[4] = {0.f, 0.f, 0.f, 0.f}, s1[4] = {0.f, 0.f, 0.f, 0.f};
        mma16816(s0, one, pm[0], pm[1]);
        mma16816(s1, one, pm[2], pm[3]);
        mma1688(s0, c1, c1, pm[4]);
        SCHED_FENCE();
        wg_wait<0>();
        pin<20>(av);
        if (w == 0) TS(13);
#pragma unroll
        for (int k = 0; k < 10; k++) vf[k] = pack2(av[2 * k], av[2 * k + 1]);
        {
          float o0[4] = {0.f, 0.f, 0.f, 0.f}, o1[4] = {0.f, 0.f, 0.f, 0.f}, o2[4] = {0.f, 0.f, 0.f, 0.f};
          mma16816(o0, vf, pm[0], pm[1]);
          mma16816(o1, vf + 4, pm[2], pm[3]);
          mma1688(o2, vf[8], vf[9], pm[4]);
          if (O_RS_POS == 0) {
#pragma unroll
            for (int k = 0; k < O_RS; k++) ldsm4t(ao[k], la_w + O_WO + 2 * 24576 + (12 - O_RS + k) * 2048);
          }
          if (s == NSEG - 1) break;
          const float i0 = rcp(s0[0] + s1[0]), i1 = rcp(s0[1] + s1[1]);
          const uint32_t p0 = pack2((o0[0] + o1[0] + o2[0]) * i0, (o0[1] + o1[1] + o2[1]) * i1), p1 = pack2((o0[2] + o1[2] + o2[2]) * i0, (o0[3] + o1[3] + o2[3]) * i1);
          sta1(a1, p0, b1); sta1(a2, p1, b1);
          sta1(a3, p0, b2); sta1(a4, p1, b2);
          sts1(a0, p0); sts1(a0 + 128, p1);
          fence_async();
        }
      }
      uint8_t* arp;
      uint32_t t1;
      {
        bar_sync<B_WG2, 128>();
        float c9[4], ca[4], cb[4], cc[4];
        constexpr uint64_t da = mkdesc(SB0 + O_WO, 1024, 1024, 1), db = mkdesc(SB0 + O_OG, 128, 128, 0);
#define O_RUN(acc, tile, k0, k1) _Pragma("unroll") for (int k = k0; k < k1; k++) wg_ss_n8_ta1_tb1(acc, da + (tile) * 1536 + k * 128, db + (k >> 2) * 128 + (k & 3) * 16, k);
        wg_fence();
        O_RUN(c9, 3, 0, 4)
        wg_commit();
        if (w == 0) TS(14);
        O_RUN(ca, 0, 0, 4) O_RUN(cb, 1, 0, 4) O_RUN(cc, 2, 0, 4)
        wg_commit();
        SCHED_FENCE();
        arp = ar + (s >> 2) * AR_GROUP + (s & 1) * 128 + ((s >> 1) & 1) * 512;
        uint8_t* pp = arp + opaque(prod_off);
        wg_wait<1>();
        pin<4>(c9);
        fix_red(pp + T9_OFF, c9, sc);
        SCHED_FENCE();
        if (O_RS_POS == 1) {
#pragma unroll
          for (int k = 0; k < O_RS; k++) ldsm4t(ao[k], la_w + O_WO + 2 * 24576 + (12 - O_RS + k) * 2048);
        }
        mbar_wait(bar + 8 * MB_OG, par);
        wg_fence();
        O_RUN(ca, 0, 4, 12)
        wg_commit();
        bar_arrive<B_VDONE, 160>();
        if (w == 0) TS(15);
        O_RUN(cb, 1, 4, 12)
        wg_commit();
        wg_wait<1>();
        pin<4>(ca);
        fix_red(pp + tile_off(0), ca, sc);
        SCHED_FENCE();
        if (w == 0) TS(16);
        wg_fence();
        O_RUN(cc, 2, 4, 12 - O_RS)
#pragma unroll
        for (int k = 12 - O_RS; k < 12; k++) wg_rs_n8_tb1(cc, ao[k - 12 + O_RS], db + (k >> 2) * 128 + (k & 3) * 16, 1);
        wg_commit();
        bar_arrive<B_XGO1, 256>();
        bar_arrive<B_XGO, 256>();
        wg_wait<1>();
        pin<4>(cb);
        fix_red(pp + tile_off(1), cb, sc);
        wg_wait<0>();
        pin<4>(cc);
        fix_red(pp + tile_off(2), cc, sc);
        t1 = clk();
        if (w == 0) TS(17);
      }
      pv_x(s);
      bar_arrive<B_PFREE, 256>();
      bar_arrive<B_PFREE1, 256>();
      if (w == 0) TS(28);
#pragma unroll
      for (int k = 0; k < V_RS; k++) ldsm4t(af[k], la_w + vord(V_OWN + k) * 2048);
      {
        arm();
        const int dly = w == 0 ? POLL_D0 : POLL_DELAY - (3 - w) * POLL_STEP;
        const uint32_t need = w == 0 ? 96 : 32;
        const uint8_t* cp = arp + opaque(cons_off);
        uint4 y[4];
        int it = 0;
        while ((int)(clk() - t1) < dly) {}
        if (w == 3) TS(18);
        y[0] = ld_poll(cp); y[1] = ld_poll(cp + 256); y[2] = ld_poll(cp + 16384); y[3] = ld_poll(cp + 16384 + 256);
        stg4(op, oq0); stg4(op + 512, oq1);
        while (true) {
          const uint32_t bad = (y[0].x ^ need) | (y[0].z ^ need) | (y[1].x ^ need) | (y[1].z ^ need) | (y[2].x ^ need) | (y[2].z ^ need) | (y[3].x ^ need) | (y[3].z ^ need);
          if (!__any_sync(~0u, (bad & 127u) != 0)) break;
          if (++it > 2000000) __trap();
          y[0] = ld_poll(cp); y[1] = ld_poll(cp + 256); y[2] = ld_poll(cp + 16384); y[3] = ld_poll(cp + 16384 + 256);
        }
        uint32_t p[8];
        const float isl = isc * 0.5f, bias = -(float)(need >> 3) * isl;
#pragma unroll
        for (int k = 0; k < 4; k++) {
          p[2 * k] = pack2(fmaf((float)(int)__funnelshift_r(y[k].x, y[k].y, 3), isl, bias), fmaf((float)(int)__funnelshift_r(y[k].z, y[k].w, 3), isl, bias));
          p[2 * k + 1] = pack2((float)(int)y[k].y * isc, (float)(int)y[k].w * isc);
        }
        TS(19 + w);
        forward(p);
      }
    }
    bar_arrive<B_VDONE, 160>();
    bar_arrive<B_XGO1, 256>();
    bar_arrive<B_XGO, 256>();
    pv_x(NSEG - 1);
    stg4(op, oq0); stg4(op + 512, oq1);
    bar_sync<B_WG2, 128>();
    if (tid == 256) { __threadfence(); red_add(flags + FL_A + (e0 >> 10) * 8 + (NSEG - 1) * 48, 1); }
    __syncwarp();
  }
  asm volatile("barrier.cluster.arrive.relaxed.aligned;\nbarrier.cluster.wait.aligned;" ::: "memory");
  GT(layer * 4 + 1, 2);
  if (wid == 0) asm volatile("griddepcontrol.wait;" ::: "memory");
}

constexpr int P_B = 0, P_A = 131072, P_BAR = 196608, OPC_SMEM = P_BAR + 256;
constexpr int OP_KR = 48;

__global__ void __launch_bounds__(384, 1)
opc_kernel(const __grid_constant__ CUtensorMap tmo, bf16* __restrict__ out, int layer) {
  extern __shared__ __align__(1024) uint8_t smem[];
  asm volatile("griddepcontrol.launch_dependents;");
  GT(layer * 4 + 2, 0);
  const uint32_t sb = smem_u32(smem);
  check_smem_base(sb);
  const int tid = threadIdx.x, wid = __shfl_sync(~0u, tid >> 5, 0), wg = wid >> 2, w = wid & 3, lane = tid & 31;
  const uint32_t bar = sb + P_BAR;
  uint32_t* flags = g_zero + Z_FLAGS + layer * FL_LAYER;
  float* acc = g_acc + layer * (S_TOK * DM);
  if (wid == 0) {
    if (lane < 16) mbar_init(bar + 8 * lane, (lane == 8 || lane == 9) ? 8 : 1);
    fence_async();
  }
  __syncthreads();
  if (blockIdx.x < 30) {
    const int cg = blockIdx.x % 5, kg = blockIdx.x / 5;
    if (wg < 2) {
      asm volatile("setmaxnreg.inc.sync.aligned.u32 240;");
      uint32_t a[OP_KR][4];
      const uint32_t la = sb + P_B + ((lane >> 4) * 8 + (lane & 7)) * 128 + (((2 * w + ((lane >> 3) & 1)) ^ (lane & 7)) << 4);
      mbar_wait(bar + 80, 0);
#pragma unroll
      for (int k = 0; k < 32; k++) ldsm4t(a[k], la + wg * 65536 + k * 2048);
      bar_arrive<2, 288>();
      mbar_wait(bar + 88, 0);
#pragma unroll
      for (int k = 0; k < 16; k++) ldsm4t(a[32 + k], la + wg * 32768 + k * 2048);
      bar_arrive<3, 288>();
      mbar_wait(bar + 96, 0);
      float* ap = acc + (cg * 8 + wg * 4 + w) * 512 + lane * 4;
      for (int s = 0; s < NSEG; s++) {
        const int buf = s & 1;
        const uint32_t par = (s >> 1) & 1;
        float d[16];
        const uint64_t db = mkdesc(SB0 + P_B + buf * 65536, 512, 128, 0), da = mkdesc(SB0 + P_A + wg * 32768, 1024, 1024, 1);
        float* p = ap + s * (32 * DM);
        if (kg < 4 && s + 2 < NSEG) *(float4*)(p + 2 * 32 * DM + kg * 128) = make_float4(0.f, 0.f, 0.f, 0.f);
#pragma unroll
        for (int q = 0; q < 4; q++) {
          mbar_wait(bar + 8 * (buf * 4 + q), par);
          wg_fence();
#pragma unroll
          for (int k = 16 * q; k < 16 * q + 16; k++) {
            if (k < OP_KR) wg_rs_n32_tb1(d, a[k < OP_KR ? k : 0], db + k * 64, k);
            else wg_ss_n32_ta1_tb1(d, da + (k - OP_KR) * 128, db + k * 64, 1);
          }
        }
        wg_commit();
        wg_wait<0>();
        pin<16>(d);
        if (lane == 0) mbar_arrive(bar + 8 * (8 + buf));
        red4f(p, d[0], d[1], d[4], d[5]);
        red4f(p + 128, d[8], d[9], d[12], d[13]);
        red4f(p + 256, d[2], d[3], d[6], d[7]);
        red4f(p + 384, d[10], d[11], d[14], d[15]);
        bar_sync<1, 256>();
        if (tid == 0) { __threadfence(); red_add(flags + FL_B + s * 8, 1); }
        __syncwarp();
      }
    } else {
      asm volatile("setmaxnreg.dec.sync.aligned.u32 24;");
      if (w == 0) {
        if (lane == 0) { mbar_expect(bar + 80, 131072); mbar_expect(bar + 96, 65536); mbar_expect(bar + 88, 65536); }
        __syncwarp();
        if (lane < 16) tma2d(sb + P_B + lane * 8192, &tmo, cg * 128 + (lane >> 3) * 64, kg * 1024 + (lane & 7) * 64, bar + 80);
        else if (lane < 24) tma2d(sb + P_B + lane * 8192, &tmo, cg * 128 + ((lane >> 2) & 1) * 64, kg * 1024 + 768 + (lane & 3) * 64, bar + 96);
        bar_sync<2, 288>();
        fence_async();
        if (lane < 8) tma2d(sb + P_B + lane * 8192, &tmo, cg * 128 + (lane >> 2) * 64, kg * 1024 + 512 + (lane & 3) * 64, bar + 88);
        bar_sync<3, 288>();
        for (int s = 0; s < NSEG; s++) {
          const int buf = s & 1;
          if (s >= 2) mbar_wait(bar + 8 * (8 + buf), ((s >> 1) & 1) ^ 1);
          if (s >= 2) wait_flag(flags + FL_B + (s - 2) * 8, 30);
          wait_flag(flags + FL_A + s * 48 + kg * 8, 16);
          asm volatile("fence.proxy.async;" ::: "memory");
          if (lane < 4) {
            mbar_expect(bar + 8 * (buf * 4 + lane), 16384);
            bulk_g2s(sb + P_B + buf * 65536 + lane * 16384, g_ot + (size_t)s * (HE * 64) + kg * 65536 + lane * 16384, 16384, bar + 8 * (buf * 4 + lane));
          }
          __syncwarp();
        }
      }
    }
  } else {
    constexpr int LD = 644;
    float* xs = (float*)smem;
    uint32_t par = 0;
    for (int task = blockIdx.x - 30; task < 2 * NSEG; task += 6, par ^= 1) {
      const int s = task >> 1, jj = task & 1;
      if (tid == 0) {
        mbar_expect(bar, 20480);
        bulk_g2s(sb + 49152, g_x + task * 16 * DM, 20480, bar);
      }
      if (wid == 1) wait_flag(flags + FL_B + s * 8, 30);
      __syncthreads();
      if (wid < 10) {
        float4 v[8];
#pragma unroll
        for (int k = 0; k < 8; k++) v[k] = __ldcg((const float4*)(acc + s * (32 * DM) + (wid * 8 + k) * 256 + jj * 128 + lane * 4));
        float* xp = xs + (lane & 3) * 2 * LD + wid * 64 + (lane >> 2);
#pragma unroll
        for (int k = 0; k < 8; k++) { xp[k * 8] = v[k].x; xp[LD + k * 8] = v[k].y; xp[8 * LD + k * 8] = v[k].z; xp[9 * LD + k * 8] = v[k].w; }
      }
      mbar_wait(bar, par);
      __syncthreads();
#pragma unroll 1
      for (int row = wid; row < 16; row += 12) {
        const int tk = task * 16 + row;
        float v[20], sum = 0.f;
        const int pj = (lane & 24) + 2 * (lane & 3) + ((lane >> 2) & 1);
        bf16* dst = out ? out + tk * DM + lane * 2 : g_x + tk * DM + pj * 2;
#pragma unroll
        for (int k = 0; k < 10; k++) {
          const float2 u = *(const float2*)(xs + row * LD + k * 64 + lane * 2);
          const uint32_t r = *(const uint32_t*)(smem + 49152 + row * 1280 + k * 128 + pj * 4);
          v[2 * k] = u.x + bflo(r); v[2 * k + 1] = u.y + bfhi(r); sum += v[2 * k] + v[2 * k + 1];
          *(uint32_t*)(dst + k * 64) = pack2(v[2 * k], v[2 * k + 1]);
        }
        if (!out) {
#pragma unroll
          for (int o = 16; o; o >>= 1) sum += __shfl_xor_sync(~0u, sum, o);
          const float m = sum * (1.f / DM);
          float q = 0.f;
#pragma unroll
          for (int k = 0; k < 20; k++) { v[k] -= m; q += v[k] * v[k]; }
#pragma unroll
          for (int o = 16; o; o >>= 1) q += __shfl_xor_sync(~0u, q, o);
          const float rs = rsqrtf(q * (1.f / DM) + 1e-5f);
          uint8_t* xp = g_xt + (tk >> 7) * 163840 + (tk & 127) * 128 + (((lane >> 2) ^ (tk & 7)) << 4) + (lane & 3) * 4;
#pragma unroll
          for (int k = 0; k < 10; k++) *(uint32_t*)(xp + k * 16384) = pack2(v[2 * k] * rs, v[2 * k + 1] * rs);
        }
      }
      fence_async();
      __syncthreads();
      if (tid == 0 && !out) { __threadfence(); red_add(flags + FL_LAYER + FL_T + (task >> 3) * 8, 1); }
    }
  }
  GT(layer * 4 + 2, 1);
  __syncwarp();
  asm volatile("griddepcontrol.wait;" ::: "memory");
  GT(layer * 4 + 2, 2);
}

constexpr int L_STAGE = 47104;
constexpr int L_KV = 0, L_B2 = 43008;
constexpr int L_W2 = 122880, L_BAR = L_W2 + 102400;
constexpr int LA_SMEM = L_BAR + 256;
__device__ __forceinline__ float phi(float t) { return (fmaxf(t, 0.f) + 1e-6f) + ex2(fminf(t * 1.4426950408889634f, 0.f)); }
__device__ __forceinline__ uint32_t phi2(float a, float b) { return pack2(phi(a), phi(b)); }
#define PF_N0 2
#define PF_N1 2
#define PF_SLEEP 400

__global__ void __launch_bounds__(384, 1)
la_kernel(const bf16* __restrict__ xin, const bf16* __restrict__ Wq, const bf16* __restrict__ Wk, const bf16* __restrict__ Wv,
          const bf16* __restrict__ Wo, uint8_t* __restrict__ ar, int layer) {
  extern __shared__ __align__(1024) uint8_t smem[];
  const uint32_t sb = smem_u32(smem);
  check_smem_base(sb);
  const int tid = threadIdx.x, wid = __shfl_sync(~0u, tid >> 5, 0), wg = wid >> 2, w = wid & 3, lane = tid & 31, g = lane >> 2, i4 = lane & 3;
  const int tb = blockIdx.x >> 3, hg = blockIdx.x & 7;
  const uint32_t bar = sb + L_BAR;
  uint32_t* flags = g_zero + Z_FLAGS + layer * FL_LAYER;
  asm volatile("griddepcontrol.launch_dependents;");
  GT(layer * 4, 0);
  if (wid == 0) {
    if (lane < 20) mbar_init(bar + 8 * lane, ((lane >= 4 && lane < 8) || lane >= 17) ? 8 : 1);
    fence_async();
  }
  if (layer == 0) asm volatile("griddepcontrol.wait;" ::: "memory");
  __syncthreads();
  if (wg == 2) {
    asm volatile("setmaxnreg.dec.sync.aligned.u32 40;");
    if (w == 0) {
      if (lane < 4) {
        mbar_expect(bar + 8 * lane, L_STAGE);
        bulk_g2s(sb + lane * L_STAGE + 16384, g_w1 + (hg * 10 + lane) * 30720, 30720, bar + 8 * lane);
      }
      if (layer == 1) { wait_flag(flags + FL_T + tb * 8, 8); asm volatile("fence.proxy.async;" ::: "memory"); }
      if (lane < 4) bulk_g2s(sb + lane * L_STAGE, g_xt + (tb * 10 + lane) * 16384, 16384, bar + 8 * lane);
#pragma unroll 1
      for (int kc = 4; kc < 10; kc++) {
        const int st = kc & 3;
        mbar_wait(bar + 8 * (4 + st), ((kc >> 2) & 1) ^ 1);
        if (lane == 0) mbar_expect(bar + 8 * st, L_STAGE);
        __syncwarp();
        if (lane < 2) bulk_g2s(sb + st * L_STAGE + lane * 16384, lane ? g_w1 + (hg * 10 + kc) * 30720 : g_xt + (tb * 10 + kc) * 16384, lane ? 30720 : 16384, bar + 8 * st);
      }
      mbar_wait(bar + 8 * 6, 1);
      mbar_wait(bar + 8 * 7, 1);
      if (lane == 0) mbar_expect(bar + 64, 102400);
      if (lane < 8) mbar_expect(bar + 8 * (9 + lane), 20480);
      __syncwarp();
      if (lane < 4) bulk_g2s(sb + L_W2 + lane * 25600, g_w2 + hg * 102400 + lane * 25600, 25600, bar + 64);
      bar_sync<2, 288>();
      if (lane == 0) { __threadfence(); red_add(flags + FL_O + tb * 8, 1); }
      wait_flag(flags + FL_O + tb * 8, 8);
      asm volatile("fence.proxy.async;" ::: "memory");
      if (lane < 6) bulk_g2s(sb + lane * 20480, g_oa + (tb * 8 + lane) * 20480, 20480, bar + 8 * (9 + lane));
#pragma unroll 1
      for (int p = 6; p < 8; p++) {
        mbar_wait(bar + 8 * (17 + p - 6), 0);
        if (lane == 0) bulk_g2s(sb + (p - 6) * 20480, g_oa + (tb * 8 + p) * 20480, 20480, bar + 8 * (9 + p));
      }
    } else {
      const int t = tid - 288;
#pragma unroll 1
      for (int k = t; k < 768; k += 96) *(uint4*)(ar + blockIdx.x * 12288 + k * 16) = make_uint4(0, 0, 0, 0);
      if (layer == 0 && w == 1) {
        float sv = 0.f, mx = 0.f;
#pragma unroll 1
        for (int c = 0; c < 5; c++) {
          const float* p = g_nrm + lane * DM + blockIdx.x * 5 + c;
          sv += (p[0] + p[32 * DM]) + (p[64 * DM] + p[96 * DM]);
          float so = (p[128 * DM] + p[160 * DM]) + (p[192 * DM] + p[224 * DM]);
#pragma unroll
          for (int o = 16; o; o >>= 1) so += __shfl_xor_sync(~0u, so, o);
          mx = fmaxf(mx, so);
        }
#pragma unroll
        for (int o = 16; o; o >>= 1) sv += __shfl_xor_sync(~0u, sv, o);
        if (lane == 0) { atomicAdd((float*)(g_zero + Z_NORM), sv); atomicMax(g_zero + Z_NORM + 1, __float_as_uint(mx)); }
      }
#pragma unroll 1
      for (int k = 0; k < 5 * (layer ? PF_N1 : PF_N0); k++) {
        const int m = k / 5;
        const bf16* W = m == 0 ? Wq : m == 1 ? Wk : m == 2 ? Wv : Wo;
        asm volatile("prefetch.global.L2 [%0];" :: "l"((const uint8_t*)W + blockIdx.x * 61440 + (k - m * 5) * 12288 + t * 128));
        __nanosleep(PF_SLEEP);
      }
      if (t == 0) GTT(layer * 4, 14);
      bar_arrive<3, 352>();
    }
  } else {
    asm volatile("setmaxnreg.inc.sync.aligned.u32 232;");
    GT(layer * 4, 4);
    uint32_t pq[5][4];
    const int row0 = tb * 128 + wg * 64 + 16 * w + g;
    float* kv = (float*)(g_zero + Z_KV) + layer * KV_LAYER + hg * 1920;
    {
      float d[120];
#pragma unroll 1
      for (int kc = 0; kc < 10; kc++) {
        const int st = kc & 3;
        const uint64_t da = mkdesc(SB0 + st * L_STAGE + wg * 8192, 16, 1024, 1), db = mkdesc(SB0 + st * L_STAGE + 16384, 3840, 128, 0);
        mbar_wait(bar + 8 * st, (kc >> 2) & 1);
        wg_fence();
#pragma unroll
        for (int k = 0; k < 4; k++) wg_ss_n240_ta0_tb1(d, da + 2 * k, db + k * 480, kc | k);
        wg_commit();
        if (kc > 0) { wg_wait<1>(); if (lane == 0) mbar_arrive(bar + 8 * (4 + ((kc - 1) & 3))); }
      }
      wg_wait<0>();
      pin<120>(d);
      GT(layer * 4, 5);
      bar_sync<1, 256>();
      const uint32_t kb = sb + L_KV + (wg * 8 + 2 * w + ((lane >> 3) & 1)) * 2688 + (lane >> 4) * 128 + (lane & 7) * 16;
#pragma unroll
      for (int j = 0; j < 5; j++) stsm4(kb + 1280 + j * 256, pack2(d[80 + 8 * j], d[81 + 8 * j]), pack2(d[82 + 8 * j], d[83 + 8 * j]), pack2(d[84 + 8 * j], d[85 + 8 * j]), pack2(d[86 + 8 * j], d[87 + 8 * j]));
      stsm2(kb + 2560, 0x3F803F80u, 0x3F803F80u);
#pragma unroll
      for (int j = 0; j < 5; j++) stsm4(kb + j * 256, phi2(d[40 + 8 * j], d[41 + 8 * j]), phi2(d[42 + 8 * j], d[43 + 8 * j]), phi2(d[44 + 8 * j], d[45 + 8 * j]), phi2(d[46 + 8 * j], d[47 + 8 * j]));
      fence_async();
      bar_sync<1, 256>();
      float e[44];
      {
        const uint64_t da = mkdesc(SB0 + L_KV + wg * 1024, 2688, 128, 0), db = mkdesc(SB0 + L_KV + 1280, 2688, 128, 0);
        wg_fence();
#pragma unroll
        for (int k = 0; k < 8; k++) wg_ss_n88_ta1_tb1(e, da + k * 336, db + k * 336, k);
        wg_commit();
        wg_wait<0>();
        pin<44>(e);
      }
#pragma unroll
      for (int h = 0; h < 2; h++) {
        const int row = wg * 64 + 16 * w + 8 * h + g;
        const int c = row < 80 ? 2 * i4 - (row / 20) * 20 : 100;
        float* dst = kv + row * 24 + c;
#pragma unroll
        for (int j = 0; j < 10; j++)
          asm volatile("{\n.reg .pred p;\nsetp.lt.u32 p, %3, 20;\n@p red.relaxed.gpu.global.add.v2.f32 [%0], {%1,%2};\n}" :: "l"(dst + 8 * j), "f"(e[4 * j + 2 * h]), "f"(e[4 * j + 2 * h + 1]), "r"(c + 8 * j) : "memory");
        asm volatile("{\n.reg .pred p;\nsetp.ne.u32 p, %2, 0;\n@p red.relaxed.gpu.global.add.f32 [%0], %1;\n}" :: "l"(kv + row * 24 + 20), "f"(e[40 + 2 * h]), "r"((int)(row < 80 && i4 == 0)) : "memory");
      }
      bar_sync<1, 256>();
      GT(layer * 4, 6);
      if (tid == 0) { __threadfence(); red_add(flags + FL_KV + hg * 8, 1); }
      __syncwarp();
      pin<40>(d);
#pragma unroll
      for (int k = 0; k < 5; k++) {
        pq[k][0] = phi2(d[8 * k], d[8 * k + 1]); pq[k][1] = phi2(d[8 * k + 2], d[8 * k + 3]);
        pq[k][2] = phi2(d[8 * k + 4], d[8 * k + 5]); pq[k][3] = phi2(d[8 * k + 6], d[8 * k + 7]);
      }
    }
#pragma unroll 1
    for (int k = tid; k < 1600; k += 256) sts4(sb + L_B2 + k * 16, 0, 0, 0, 0);
    GT(layer * 4, 7);
    if (wid == 0) wait_flag(flags + FL_KV + hg * 8, 16);
    if (wid == 1 && layer == 1) wait_flag(flags + FL_T + tb * 8, 8);
    GT(layer * 4, 8);
    bar_sync<1, 256>();
    if (tid < 240) {
      const int dd = tid / 3, part = tid - dd * 3, n = (dd / 20) * 20 + 8 * part;
      const float4 v0 = __ldcg((const float4*)(kv + dd * 24 + 8 * part)), v1 = __ldcg((const float4*)(kv + dd * 24 + 8 * part + 4));
      const float z = __ldcg(kv + dd * 24 + 20);
      const uint32_t a = sb + L_B2 + (dd >> 3) * 2560 + (dd & 7) * 16, zz = pack2(z, z);
      const uint32_t a0 = a + (n >> 3) * 128 + (n & 7) * 2, a1 = a + ((n + 4) >> 3) * 128 + ((n + 4) & 7) * 2;
      sts2(a0, pack2(v0.x, v0.y), pack2(v0.z, v0.w)); sts2(a0 + 1280, zz, zz);
      if (part < 2) { sts2(a1, pack2(v1.x, v1.y), pack2(v1.z, v1.w)); sts2(a1 + 1280, zz, zz); }
    }
    fence_async();
    bar_sync<1, 256>();
    {
      float o[80];
      const uint64_t db = mkdesc(SB0 + L_B2, 2560, 128, 0);
      wg_fence();
#pragma unroll
      for (int k = 0; k < 5; k++) wg_rs_n160_tb1(o, pq[k], db + k * 320, k);
      wg_commit();
      wg_wait<0>();
      pin<80>(o);
      uint8_t* op = g_oa + (tb * 8 + hg) * 20480 + (wg * 8 + 2 * w) * 128 + lane * 4;
#pragma unroll
      for (int j = 0; j < 20; j++) {
        const float inv = rcp(o[40 + 2 * j] + 1e-6f);
        *(uint32_t*)(op + (j >> 1) * 2048 + (j & 1) * 128) = pack2(o[2 * j] * inv, o[2 * j + 1] * inv);
      }
      GT(layer * 4, 9);
      bar_arrive<2, 288>();
    }
    uint32_t r[20];
    if (xin) {
      const bf16* xp = xin + row0 * DM + hg * 80 + 2 * i4;
#pragma unroll
      for (int j = 0; j < 10; j++) { r[2 * j] = __ldg((const uint32_t*)(xp + 8 * j)); r[2 * j + 1] = __ldg((const uint32_t*)(xp + 8 * DM + 8 * j)); }
    } else {
      const bf16* xp = g_x + row0 * DM + hg * 80 + 4 * i4;
#pragma unroll
      for (int j = 0; j < 5; j++) {
        const uint2 u = __ldcg((const uint2*)(xp + 16 * j)), v = __ldcg((const uint2*)(xp + 8 * DM + 16 * j));
        r[4 * j] = u.x; r[4 * j + 2] = u.y; r[4 * j + 1] = v.x; r[4 * j + 3] = v.y;
      }
    }
    float d[40];
    mbar_wait(bar + 64, 0);
#pragma unroll 1
    for (int p = 0; p < 8; p++) {
      const uint64_t da = mkdesc(SB0 + (p < 6 ? p : p - 6) * 20480 + wg * 1024, 2048, 128, 0), db = mkdesc(SB0 + L_W2 + p * 12800, 1280, 128, 0);
      mbar_wait(bar + 8 * (9 + p), 0);
      if (p == 0) GT(layer * 4, 11);
      wg_fence();
#pragma unroll
      for (int k = 0; k < 5; k++) wg_ss_n80_ta0_tb1(d, da + k * 256, db + k * 160, p | k);
      wg_commit();
      wg_wait<1>();
      if (lane == 0 && (p == 1 || p == 2)) mbar_arrive(bar + 8 * (17 + p - 1));
    }
    wg_wait<0>();
    pin<40>(d);
    GT(layer * 4, 12);
    float mean[2], m2[2];
#pragma unroll
    for (int h = 0; h < 2; h++) {
      float sum = 0.f;
#pragma unroll
      for (int j = 0; j < 10; j++) { d[4 * j + 2 * h] += bflo(r[2 * j + h]); d[4 * j + 2 * h + 1] += bfhi(r[2 * j + h]); sum += d[4 * j + 2 * h] + d[4 * j + 2 * h + 1]; }
      sum += __shfl_xor_sync(~0u, sum, 1); sum += __shfl_xor_sync(~0u, sum, 2);
      mean[h] = sum * (1.f / 80.f);
      float q = 0.f;
#pragma unroll
      for (int j = 0; j < 10; j++) { const float a = d[4 * j + 2 * h] - mean[h], b = d[4 * j + 2 * h + 1] - mean[h]; q = fmaf(a, a, fmaf(b, b, q)); }
      q += __shfl_xor_sync(~0u, q, 1); q += __shfl_xor_sync(~0u, q, 2);
      m2[h] = q;
    }
    float2* st = g_stats + (layer * S_TOK + row0) * 8;
    if (i4 < 2) {
      const float a = i4 ? mean[1] : mean[0], b = i4 ? m2[1] : m2[0];
      asm volatile("{\n.reg .b64 t;\nmov.b64 t, {%1,%2};\nst.relaxed.gpu.global.b64 [%0], t;\n}" :: "l"(st + i4 * 64 + hg), "r"(__float_as_uint(a)), "r"(__float_as_uint(b) & 0x7FFFFFFFu) : "memory");
    }
    uint4 y0, y1;
    int it = 0;
    while (true) {
      y0 = ld_poll(st + 2 * i4); y1 = ld_poll(st + 64 + 2 * i4);
      if (!__any_sync(~0u, (int)(y0.y | y0.w | y1.y | y1.w) < 0)) break;
      if (++it > 2000000) __trap();
    }
    GT(layer * 4, 13);
#pragma unroll
    for (int h = 0; h < 2; h++) {
      const uint4 y = h ? y1 : y0;
      const float ma = __uint_as_float(y.x), mb = __uint_as_float(y.z);
      float sm = ma + mb;
      sm += __shfl_xor_sync(~0u, sm, 1); sm += __shfl_xor_sync(~0u, sm, 2);
      const float mu = sm * 0.125f;
      float q = __uint_as_float(y.y) + __uint_as_float(y.w) + 80.f * ((ma - mu) * (ma - mu) + (mb - mu) * (mb - mu));
      q += __shfl_xor_sync(~0u, q, 1); q += __shfl_xor_sync(~0u, q, 2);
      const float rs = rsqrtf(q * (1.f / DM) + 1e-5f), sh = -mu * rs;
      const int tk = row0 + 8 * h;
      uint8_t* xp = g_xn + (tk >> 5) * 40960 + (tk & 31) * 128 + (i4 & 1) * 8;
#pragma unroll
      for (int jj = 0; jj < 5; jj++) {
        const int b16 = hg * 5 + jj;
        const float* a = d + 8 * jj + 2 * h;
        *(uint2*)(xp + (b16 >> 2) * 4096 + (((2 * (b16 & 3) + (i4 >> 1)) ^ g) << 4)) =
            make_uint2(pack2(fmaf(a[0], rs, sh), fmaf(a[1], rs, sh)), pack2(fmaf(a[4], rs, sh), fmaf(a[5], rs, sh)));
      }
    }
    {
      bf16* xp = g_x + row0 * DM + hg * 80 + 4 * i4;
#pragma unroll
      for (int j = 0; j < 5; j++) {
        *(uint2*)(xp + 16 * j) = make_uint2(pack2(d[8 * j], d[8 * j + 1]), pack2(d[8 * j + 4], d[8 * j + 5]));
        *(uint2*)(xp + 8 * DM + 16 * j) = make_uint2(pack2(d[8 * j + 2], d[8 * j + 3]), pack2(d[8 * j + 6], d[8 * j + 7]));
      }
    }
    bar_sync<3, 352>();
    if (tid == 0) { __threadfence(); red_add(flags + FL_X, 1); }
    GT(layer * 4, 2);
    if (wid == 7) asm volatile("griddepcontrol.wait;" ::: "memory");
  }
}

__global__ void __launch_bounds__(256) prep_kernel(const bf16* __restrict__ x, const bf16* __restrict__ wqkv, const bf16* __restrict__ wo,
                                                   const bf16* __restrict__ Wv, const bf16* __restrict__ Wo) {
  asm volatile("griddepcontrol.launch_dependents;");
  const int b = blockIdx.x, tid = threadIdx.x, lane = tid & 31;
  if (b < 160) GT(3, 0);
  if (b < 256) {
    const int row = b * 8 + (tid >> 5);
    float v[20], s = 0.f;
#pragma unroll
    for (int k = 0; k < 10; k++) { const uint32_t u = __ldg((const uint32_t*)(x + row * DM + k * 64 + lane * 2)); v[2 * k] = bflo(u); v[2 * k + 1] = bfhi(u); s += v[2 * k] + v[2 * k + 1]; }
#pragma unroll
    for (int o = 16; o; o >>= 1) s += __shfl_xor_sync(~0u, s, o);
    const float m = s * (1.f / DM);
    float q = 0.f;
#pragma unroll
    for (int k = 0; k < 20; k++) { v[k] -= m; q += v[k] * v[k]; }
#pragma unroll
    for (int o = 16; o; o >>= 1) q += __shfl_xor_sync(~0u, q, o);
    const float r = rsqrtf(q * (1.f / DM) + 1e-5f);
#pragma unroll
    for (int k = 0; k < 10; k++)
      *(uint32_t*)(g_xt + ((row >> 7) * 10 + k) * 16384 + (row & 127) * 128 + (((lane >> 2) ^ (row & 7)) << 4) + (lane & 3) * 4) = pack2(v[2 * k] * r, v[2 * k + 1] * r);
  } else if (b < 256 + 200) {
#pragma unroll
    for (int it = 0; it < 4; it++) {
      const int u = (b - 256) * 1024 + it * 256 + tid;
      if (u < 153600) {
        const int k8 = u & 7, nb = (u >> 3) % 30, kg = (u / 240) % 80, hg = u / 19200;
        *(uint4*)(g_w1 + u * 16) = __ldg((const uint4*)(wqkv + (kg * 8 + k8) * 1920 + (nb / 10) * 640 + hg * 80 + (nb % 10) * 8));
      } else {
        const int v = u - 153600, k8 = v & 7, nb = (v >> 3) % 10, kg = (v / 80) % 80, hg = v / 6400;
        *(uint4*)(g_w2 + v * 16) = __ldg((const uint4*)(wo + (kg * 8 + k8) * DM + hg * 80 + nb * 8));
      }
    }
  } else if (b >= 472) {
    __shared__ float red[2][640];
    const int blk = b - 472, rs = tid / 80, t = tid - rs * 80;
    float c[8] = {0.f, 0.f, 0.f, 0.f, 0.f, 0.f, 0.f, 0.f};
    if (rs < 3) {
      const uint4* po = (const uint4*)((const uint8_t*)(blk < 128 ? Wv : Wo) + (blk & 127) * 61440) + rs * 1280 + t;
#pragma unroll
      for (int k = 0; k < 16; k++) {
        const uint4 v = __ldg(po + k * 80);
        c[0] += bflo(v.x) * bflo(v.x); c[1] += bfhi(v.x) * bfhi(v.x); c[2] += bflo(v.y) * bflo(v.y); c[3] += bfhi(v.y) * bfhi(v.y);
        c[4] += bflo(v.z) * bflo(v.z); c[5] += bfhi(v.z) * bfhi(v.z); c[6] += bflo(v.w) * bflo(v.w); c[7] += bfhi(v.w) * bfhi(v.w);
      }
      if (rs > 0) { *(float4*)&red[rs - 1][t * 8] = make_float4(c[0], c[1], c[2], c[3]); *(float4*)&red[rs - 1][t * 8 + 4] = make_float4(c[4], c[5], c[6], c[7]); }
    }
    __syncthreads();
    if (rs == 0) {
#pragma unroll
      for (int k = 0; k < 8; k++) c[k] += red[0][t * 8 + k] + red[1][t * 8 + k];
      *(float4*)(g_nrm + blk * DM + t * 8) = make_float4(c[0], c[1], c[2], c[3]);
      *(float4*)(g_nrm + blk * DM + t * 8 + 4) = make_float4(c[4], c[5], c[6], c[7]);
    }
  } else {
    const int t = (b - 456) * 256 + tid;
    for (int k = t; k < Z_END / 4; k += 16 * 256) ((uint4*)g_zero)[k] = make_uint4(0, 0, 0, 0);
    for (int k = t; k < 2 * S_TOK * 4; k += 16 * 256) ((uint4*)g_stats)[k] = make_uint4(~0u, ~0u, ~0u, ~0u);
    for (int k = t; k < 16 * DM; k += 16 * 256) { ((uint4*)g_acc)[k] = make_uint4(0, 0, 0, 0); ((uint4*)(g_acc + S_TOK * DM))[k] = make_uint4(0, 0, 0, 0); }
  }
  if (b < 160) GT(3, 2);
}

typedef CUresult (*EncodeFn)(CUtensorMap*, CUtensorMapDataType, cuuint32_t, void*, const cuuint64_t*, const cuuint64_t*, const cuuint32_t*,
                             const cuuint32_t*, CUtensorMapInterleave, CUtensorMapSwizzle, CUtensorMapL2promotion, CUtensorMapFloatOOBfill);
static void make_map(EncodeFn fn, CUtensorMap* m, const void* p, uint64_t cols, uint64_t rows, uint32_t bc, uint32_t br) {
  cuuint64_t dims[2] = {cols, rows}; cuuint64_t strides[1] = {cols * 2}; cuuint32_t box[2] = {bc, br}; cuuint32_t es[2] = {1, 1};
  fn(m, CU_TENSOR_MAP_DATA_TYPE_BFLOAT16, 2, (void*)p, dims, strides, box, es, CU_TENSOR_MAP_INTERLEAVE_NONE, CU_TENSOR_MAP_SWIZZLE_128B,
     CU_TENSOR_MAP_L2_PROMOTION_L2_128B, CU_TENSOR_MAP_FLOAT_OOB_FILL_NONE);
}

static void make_map_perm(EncodeFn fn, CUtensorMap* m, const void* p) {
  cuuint64_t dims[5] = {HE, 2, 2, 4, 40}; const cuuint64_t r = HE * 2; cuuint64_t strides[4] = {r, 8 * r, 2 * r, 16 * r};
  cuuint32_t box[5] = {64, 2, 2, 4, 4}; cuuint32_t es[5] = {1, 1, 1, 1, 1};
  fn(m, CU_TENSOR_MAP_DATA_TYPE_BFLOAT16, 5, (void*)p, dims, strides, box, es, CU_TENSOR_MAP_INTERLEAVE_NONE, CU_TENSOR_MAP_SWIZZLE_128B,
     CU_TENSOR_MAP_L2_PROMOTION_L2_128B, CU_TENSOR_MAP_FLOAT_OOB_FILL_NONE);
}

#define OPC_PDL 1
#define LA_PDL 1
#define REC_PDL 1
extern "C" void kernel_launch(void* const* d_in, const int* in_sizes, int n_in, void* d_out, int out_size) {
  const bf16* x = (const bf16*)d_in[0];
  const bf16* wqkv = (const bf16*)d_in[1];
  const bf16* wo_a = (const bf16*)d_in[2];
  const bf16* mem0 = (const bf16*)d_in[4];
  const bf16* Wq = (const bf16*)d_in[5];
  const bf16* Wk = (const bf16*)d_in[6];
  const bf16* Wv = (const bf16*)d_in[7];
  const bf16* Wo = (const bf16*)d_in[8];
  cudaStream_t st = cudaStreamPerThread;

  static EncodeFn enc = nullptr;
  static uint8_t* p_ar; static uint32_t* p_zero;
  if (!enc) {
    cudaDriverEntryPointQueryResult qr;
    void* fn = nullptr;
    cudaGetDriverEntryPoint("cuTensorMapEncodeTiled", &fn, cudaEnableDefault, &qr);
    enc = (EncodeFn)fn;
    cudaFuncSetAttribute(rec_kernel, cudaFuncAttributeMaxDynamicSharedMemorySize, REC_SMEM);
    cudaFuncSetAttribute(opc_kernel, cudaFuncAttributeMaxDynamicSharedMemorySize, OPC_SMEM);
    cudaFuncSetAttribute(la_kernel, cudaFuncAttributeMaxDynamicSharedMemorySize, LA_SMEM);
    cudaGetSymbolAddress((void**)&p_ar, g_ar); p_ar = (uint8_t*)(((uintptr_t)p_ar + 32767) & ~(uintptr_t)32767);
    cudaGetSymbolAddress((void**)&p_zero, g_zero);
  }
  CUtensorMap tmq, tmk, tmv, tmo;
  make_map_perm(enc, &tmq, Wq);
  make_map_perm(enc, &tmk, Wk);
  make_map_perm(enc, &tmv, Wv);
  make_map(enc, &tmo, Wo, DM, HE, 64, 64);

  cudaLaunchAttribute at[2];
  at[0].id = cudaLaunchAttributeProgrammaticStreamSerialization; at[0].val.programmaticStreamSerializationAllowed = 1;
  at[1].id = cudaLaunchAttributeClusterDimension; at[1].val.clusterDim.x = 3; at[1].val.clusterDim.y = 1; at[1].val.clusterDim.z = 1;
  prep_kernel<<<728, 256, 0, st>>>(x, wqkv, wo_a, Wv, Wo);
  for (int l = 0; l < 2; l++) {
    cudaLaunchConfig_t cfg = {};
    cfg.blockDim = dim3(384); cfg.stream = st;
    cfg.gridDim = dim3(128); cfg.dynamicSmemBytes = LA_SMEM; cfg.attrs = at; cfg.numAttrs = LA_PDL;
    cudaLaunchKernelEx(&cfg, la_kernel, l == 0 ? x : (const bf16*)nullptr, Wq, Wk, Wv, Wo, p_ar + l * AR_LAYER, l);
    cfg.gridDim = dim3(96); cfg.dynamicSmemBytes = REC_SMEM; cfg.attrs = at + 1 - REC_PDL; cfg.numAttrs = 1 + REC_PDL;
    cudaLaunchKernelEx(&cfg, rec_kernel, tmq, tmk, tmv, tmo, mem0, p_ar + l * AR_LAYER, p_zero + Z_FLAGS + l * FL_LAYER, l);
    cfg.gridDim = dim3(36); cfg.dynamicSmemBytes = OPC_SMEM; cfg.attrs = at; cfg.numAttrs = OPC_PDL;
    cudaLaunchKernelEx(&cfg, opc_kernel, tmo, l == 1 ? (bf16*)d_out : (bf16*)nullptr, l);
  }
}
```

```cpp
#include <cuda_runtime.h>
#include <cuda_bf16.h>
#include <cuda.h>
#include <stdint.h>

typedef __nv_bfloat16 bf16;
typedef unsigned long long u64;

constexpr int S_TOK = 2048, DM = 640, DH = 192, HE = 6144, NSEG = 64;

constexpr int AR_GROUP = 98304;
constexpr int AR_LAYER = 16 * AR_GROUP;
__device__ __align__(1024) uint8_t g_ar[2 * AR_LAYER + 32768];
__device__ __align__(1024) uint8_t g_xn[NSEG * 40960];
__device__ __align__(1024) uint8_t g_xt[S_TOK * DM * 2];
__device__ __align__(1024) uint8_t g_ot[NSEG * HE * 64];
__device__ __align__(1024) uint8_t g_oa[S_TOK * DM * 2];
__device__ __align__(1024) uint8_t g_w1[DM * 1920 * 2];
__device__ __align__(1024) uint8_t g_w2[DM * DM * 2];
__device__ __align__(1024) float g_acc[2 * S_TOK * DM];
__device__ __align__(1024) bf16 g_x[S_TOK * DM];
constexpr int FL_A = 0, FL_B = 64 * 6 * 8, FL_KV = FL_B + 64 * 8, FL_O = FL_KV + 8 * 8, FL_T = FL_O + 16 * 8, FL_X = FL_T + 16 * 8, FL_N = FL_X + 8, FL_LAYER = FL_N + 8;
constexpr int Z_FLAGS = 0, Z_NORM = 2 * FL_LAYER, Z_KV = Z_NORM + 8, KV_LAYER = 8 * 80 * 24, Z_END = Z_KV + 2 * KV_LAYER;
__device__ __align__(128) uint32_t g_zero[Z_END];
__device__ __align__(128) float g_nrm[4 * DM];
__device__ __align__(128) float2 g_stats[2 * S_TOK * 8];
#define GT(slot, k) do {} while (0)
#define GTT(slot, k) do {} while (0)

__device__ __forceinline__ uint32_t smem_u32(const void* p) { return (uint32_t)__cvta_generic_to_shared(p); }
__device__ __forceinline__ uint32_t mapa(uint32_t a, uint32_t r) { uint32_t o; asm("mapa.shared::cluster.u32 %0, %1, %2;" : "=r"(o) : "r"(a), "r"(r)); return o; }
__device__ __forceinline__ void mbar_init(uint32_t bar, uint32_t cnt) { asm volatile("mbarrier.init.shared::cta.b64 [%0], %1;" :: "r"(bar), "r"(cnt) : "memory"); }
__device__ __forceinline__ void mbar_expect(uint32_t bar, uint32_t tx) { asm volatile("mbarrier.arrive.expect_tx.shared::cta.b64 _, [%0], %1;" :: "r"(bar), "r"(tx) : "memory"); }
__device__ __forceinline__ void mbar_arrive(uint32_t bar) { asm volatile("mbarrier.arrive.shared::cta.b64 _, [%0];" :: "r"(bar) : "memory"); }
__device__ __forceinline__ void mbar_wait(uint32_t bar, uint32_t par) {
  asm volatile("{\n.reg .pred p;\n.reg .u32 c;\nmov.u32 c, 0;\n"
               "LW:\nmbarrier.try_wait.parity.shared::cta.b64 p, [%0], %1;\n@p bra LD;\n"
               "add.u32 c, c, 1;\nsetp.lt.u32 p, c, 4000000;\n@p bra LW;\ntrap;\nLD:\n}" :: "r"(bar), "r"(par) : "memory");
}
template <int ID, int N> __device__ __forceinline__ void bar_sync() { asm volatile("barrier.sync %0, %1;" :: "n"(ID), "n"(N) : "memory"); }
template <int ID, int N> __device__ __forceinline__ void bar_arrive() { asm volatile("barrier.arrive %0, %1;" :: "n"(ID), "n"(N) : "memory"); }
__device__ __forceinline__ void fence_async() { asm volatile("fence.proxy.async.shared::cta;" ::: "memory"); }
__device__ __forceinline__ void cluster_sync() { asm volatile("barrier.cluster.arrive.aligned;\nbarrier.cluster.wait.aligned;" ::: "memory"); }
__device__ __forceinline__ void wg_fence() { asm volatile("wgmma.fence.sync.aligned;" ::: "memory"); }
__device__ __forceinline__ void wg_commit() { asm volatile("wgmma.commit_group.sync.aligned;" ::: "memory"); }
template <int N> __device__ __forceinline__ void wg_wait() { asm volatile("wgmma.wait_group.sync.aligned %0;" :: "n"(N) : "memory"); }
template <int N> __device__ __forceinline__ void pin(float* d) {
#pragma unroll
  for (int i = 0; i < N; i++) asm volatile("" : "+f"(d[i]) :: "memory");
}
__device__ __forceinline__ constexpr uint64_t mkdesc(uint32_t addr, uint32_t lbo, uint32_t sbo, int sw) {
  return (uint64_t)((addr & 0x3FFFF) >> 4) | ((uint64_t)(lbo >> 4) << 16) | ((uint64_t)(sbo >> 4) << 32) | ((uint64_t)sw << 62);
}
constexpr uint32_t SB0 = 1024;
__device__ __forceinline__ void check_smem_base(uint32_t sb) { if ((sb & 0x3FFFF) != SB0) __trap(); }
__device__ __forceinline__ uint32_t cta_rank() { uint32_t r; asm volatile("mov.u32 %0, %%cluster_ctarank;" : "=r"(r)); return r; }
__device__ __forceinline__ uint32_t opaque(uint32_t v) { uint32_t o; asm volatile("mov.u32 %0, %1;" : "=r"(o) : "r"(v)); return o; }
__device__ __forceinline__ uint32_t pack2(float lo, float hi) { uint32_t r; asm("cvt.rn.bf16x2.f32 %0, %1, %2;" : "=r"(r) : "f"(hi), "f"(lo)); return r; }
__device__ __forceinline__ void ldsm4(uint32_t* r, uint32_t a) { asm volatile("ldmatrix.sync.aligned.m8n8.x4.shared.b16 {%0,%1,%2,%3}, [%4];" : "=r"(r[0]), "=r"(r[1]), "=r"(r[2]), "=r"(r[3]) : "r"(a) : "memory"); }
__device__ __forceinline__ void ldsm4t(uint32_t* r, uint32_t a) { asm volatile("ldmatrix.sync.aligned.m8n8.x4.trans.shared.b16 {%0,%1,%2,%3}, [%4];" : "=r"(r[0]), "=r"(r[1]), "=r"(r[2]), "=r"(r[3]) : "r"(a) : "memory"); }
__device__ __forceinline__ void ldsm1(uint32_t& r, uint32_t a) { asm volatile("ldmatrix.sync.aligned.m8n8.x1.shared.b16 {%0}, [%1];" : "=r"(r) : "r"(a) : "memory"); }
__device__ __forceinline__ void stsm4(uint32_t a, uint32_t r0, uint32_t r1, uint32_t r2, uint32_t r3) { asm volatile("stmatrix.sync.aligned.m8n8.x4.shared.b16 [%0], {%1,%2,%3,%4};" :: "r"(a), "r"(r0), "r"(r1), "r"(r2), "r"(r3) : "memory"); }
__device__ __forceinline__ void stsm1(uint32_t a, uint32_t r0) { asm volatile("stmatrix.sync.aligned.m8n8.x1.shared.b16 [%0], {%1};" :: "r"(a), "r"(r0) : "memory"); }
__device__ __forceinline__ void stsm4t(uint32_t a, uint32_t r0, uint32_t r1, uint32_t r2, uint32_t r3) { asm volatile("stmatrix.sync.aligned.m8n8.x4.trans.shared.b16 [%0], {%1,%2,%3,%4};" :: "r"(a), "r"(r0), "r"(r1), "r"(r2), "r"(r3) : "memory"); }
__device__ __forceinline__ void stsm2t(uint32_t a, uint32_t r0, uint32_t r1) { asm volatile("stmatrix.sync.aligned.m8n8.x2.trans.shared.b16 [%0], {%1,%2};" :: "r"(a), "r"(r0), "r"(r1) : "memory"); }
__device__ __forceinline__ void mma16816(float* c, const uint32_t* a, uint32_t b0, uint32_t b1) {
  asm volatile("mma.sync.aligned.m16n8k16.row.col.f32.bf16.bf16.f32 {%0,%1,%2,%3}, {%4,%5,%6,%7}, {%8,%9}, {%0,%1,%2,%3};"
               : "+f"(c[0]), "+f"(c[1]), "+f"(c[2]), "+f"(c[3]) : "r"(a[0]), "r"(a[1]), "r"(a[2]), "r"(a[3]), "r"(b0), "r"(b1));
}
__device__ __forceinline__ void mma1688(float* c, uint32_t a0, uint32_t a1, uint32_t b0) {
  asm volatile("mma.sync.aligned.m16n8k8.row.col.f32.bf16.bf16.f32 {%0,%1,%2,%3}, {%4,%5}, {%6}, {%0,%1,%2,%3};"
               : "+f"(c[0]), "+f"(c[1]), "+f"(c[2]), "+f"(c[3]) : "r"(a0), "r"(a1), "r"(b0));
}
__device__ __forceinline__ void sta1(uint32_t a, uint32_t v, uint32_t bar) { asm volatile("st.async.weak.shared::cluster.mbarrier::complete_tx::bytes.b32 [%0], %1, [%2];" :: "r"(a), "r"(v), "r"(bar) : "memory"); }
__device__ __forceinline__ void sta1p(uint32_t a, uint32_t v, uint32_t bar, bool p) { asm volatile("{\n.reg .pred p;\nsetp.ne.b32 p, %3, 0;\n@p st.async.weak.shared::cluster.mbarrier::complete_tx::bytes.b32 [%0], %1, [%2];\n}" :: "r"(a), "r"(v), "r"(bar), "r"((int)p) : "memory"); }
__device__ __forceinline__ void sta2(uint32_t a, uint32_t v0, uint32_t v1, uint32_t bar) { asm volatile("st.async.weak.shared::cluster.mbarrier::complete_tx::bytes.v2.b32 [%0], {%1,%2}, [%3];" :: "r"(a), "r"(v0), "r"(v1), "r"(bar) : "memory"); }
__device__ __forceinline__ void sta4(uint32_t a, uint32_t v0, uint32_t v1, uint32_t v2, uint32_t v3, uint32_t bar) { asm volatile("st.async.weak.shared::cluster.mbarrier::complete_tx::bytes.v4.b32 [%0], {%1,%2,%3,%4}, [%5];" :: "r"(a), "r"(v0), "r"(v1), "r"(v2), "r"(v3), "r"(bar) : "memory"); }
__device__ __forceinline__ float bflo(uint32_t v) { return __uint_as_float(v << 16); }
__device__ __forceinline__ float bfhi(uint32_t v) { return __uint_as_float(v & 0xFFFF0000u); }
__device__ __forceinline__ void sta2f(uint32_t a, float v0, float v1, uint32_t bar) { asm volatile("st.async.weak.shared::cluster.mbarrier::complete_tx::bytes.v2.f32 [%0], {%1,%2}, [%3];" :: "r"(a), "f"(v0), "f"(v1), "r"(bar) : "memory"); }
__device__ __forceinline__ void sta4f(uint32_t a, float v0, float v1, float v2, float v3, uint32_t bar) { asm volatile("st.async.weak.shared::cluster.mbarrier::complete_tx::bytes.v4.f32 [%0], {%1,%2,%3,%4}, [%5];" :: "r"(a), "f"(v0), "f"(v1), "f"(v2), "f"(v3), "r"(bar) : "memory"); }
__device__ __forceinline__ float4 lds4f(uint32_t a) { float4 v; asm volatile("ld.shared.v4.f32 {%0,%1,%2,%3}, [%4];" : "=f"(v.x), "=f"(v.y), "=f"(v.z), "=f"(v.w) : "r"(a) : "memory"); return v; }
__device__ __forceinline__ float2 lds2f(uint32_t a) { float2 v; asm volatile("ld.shared.v2.f32 {%0,%1}, [%2];" : "=f"(v.x), "=f"(v.y) : "r"(a) : "memory"); return v; }
__device__ __forceinline__ uint4 lds4(uint32_t a) { uint4 v; asm volatile("ld.shared.v4.u32 {%0,%1,%2,%3}, [%4];" : "=r"(v.x), "=r"(v.y), "=r"(v.z), "=r"(v.w) : "r"(a) : "memory"); return v; }
__device__ __forceinline__ uint32_t lds1(uint32_t a) { uint32_t v; asm volatile("ld.shared.u32 %0, [%1];" : "=r"(v) : "r"(a) : "memory"); return v; }
__device__ __forceinline__ void stsm2(uint32_t a, uint32_t r0, uint32_t r1) { asm volatile("stmatrix.sync.aligned.m8n8.x2.shared.b16 [%0], {%1,%2};" :: "r"(a), "r"(r0), "r"(r1) : "memory"); }
__device__ __forceinline__ float rcp(float x) { float y; asm("rcp.approx.ftz.f32 %0, %1;" : "=f"(y) : "f"(x)); return y; }
__device__ __forceinline__ void sts4(uint32_t a, uint32_t v0, uint32_t v1, uint32_t v2, uint32_t v3) { asm volatile("st.shared.v4.u32 [%0], {%1,%2,%3,%4};" :: "r"(a), "r"(v0), "r"(v1), "r"(v2), "r"(v3) : "memory"); }
__device__ __forceinline__ void bulk_s2c(uint32_t dst, uint32_t src, uint32_t bytes, uint32_t bar) {
  asm volatile("cp.async.bulk.shared::cluster.shared::cta.mbarrier::complete_tx::bytes [%0], [%1], %2, [%3];" :: "r"(dst), "r"(src), "r"(bytes), "r"(bar) : "memory");
}
__device__ __forceinline__ void stg4(void* p, uint4 v) { asm volatile("st.global.v4.u32 [%0], {%1,%2,%3,%4};" :: "l"(p), "r"(v.x), "r"(v.y), "r"(v.z), "r"(v.w) : "memory"); }
__device__ __forceinline__ void red_add(uint32_t* p, uint32_t v) { asm volatile("red.relaxed.gpu.global.add.u32 [%0], %1;" :: "l"(p), "r"(v) : "memory"); }
__device__ __forceinline__ void red_release(uint32_t* p, uint32_t v) { asm volatile("red.release.gpu.global.add.u32 [%0], %1;" :: "l"(p), "r"(v) : "memory"); }
__device__ __forceinline__ void fence_async_global() { asm volatile("fence.proxy.async.global;" ::: "memory"); }
__device__ __forceinline__ uint64_t policy_evict_first() { uint64_t p; asm("createpolicy.fractional.L2::evict_first.b64 %0, 1.0;" : "=l"(p)); return p; }
__device__ __forceinline__ void stg4h(void* p, uint4 v, uint64_t pol) { asm volatile("st.global.L2::cache_hint.v4.u32 [%0], {%1,%2,%3,%4}, %5;" :: "l"(p), "r"(v.x), "r"(v.y), "r"(v.z), "r"(v.w), "l"(pol) : "memory"); }
__device__ __forceinline__ void red4fh(float* p, float a, float b, float c, float d, uint64_t pol) { asm volatile("red.relaxed.gpu.global.add.L2::cache_hint.v4.f32 [%0], {%1,%2,%3,%4}, %5;" :: "l"(p), "f"(a), "f"(b), "f"(c), "f"(d), "l"(pol) : "memory"); }
__device__ __forceinline__ float4 ldg4fh(const float* p, uint64_t pol) { float4 v; asm volatile("ld.global.cg.L2::cache_hint.v4.f32 {%0,%1,%2,%3}, [%4], %5;" : "=f"(v.x), "=f"(v.y), "=f"(v.z), "=f"(v.w) : "l"(p), "l"(pol) : "memory"); return v; }
__device__ __forceinline__ void bulk_g2sh(uint32_t dst, const void* src, uint32_t bytes, uint32_t bar, uint64_t pol) {
  asm volatile("cp.async.bulk.shared::cluster.global.mbarrier::complete_tx::bytes.L2::cache_hint [%0], [%1], %2, [%3], %4;" :: "r"(dst), "l"(src), "r"(bytes), "r"(bar), "l"(pol) : "memory");
}
#define EVF 1
__device__ __forceinline__ void red4f(float* p, float a, float b, float c, float d) { asm volatile("red.relaxed.gpu.global.add.v4.f32 [%0], {%1,%2,%3,%4};" :: "l"(p), "f"(a), "f"(b), "f"(c), "f"(d) : "memory"); }
__device__ __forceinline__ void wait_flag(const uint32_t* p, uint32_t target) {
  uint32_t v; int it = 0;
  while (true) {
    asm volatile("ld.acquire.gpu.global.u32 %0, [%1];" : "=r"(v) : "l"(p) : "memory");
    if (__all_sync(~0u, v >= target)) break;
    if (++it > 4000000) __trap();
    __nanosleep(20);
  }
}
__device__ __forceinline__ void sts2(uint32_t a, uint32_t v0, uint32_t v1) { asm volatile("st.shared.v2.u32 [%0], {%1,%2};" :: "r"(a), "r"(v0), "r"(v1) : "memory"); }
__device__ __forceinline__ float sqrt_approx(float x) { float y; asm("sqrt.approx.f32 %0, %1;" : "=f"(y) : "f"(x)); return y; }
__device__ __forceinline__ void bulk_s2c_elect(uint32_t d1, uint32_t b1, uint32_t d2, uint32_t b2, uint32_t src) {
  asm volatile("{\n.reg .pred p;\nelect.sync _|p, 0xffffffff;\n"
               "@p cp.async.bulk.shared::cluster.shared::cta.mbarrier::complete_tx::bytes [%0], [%4], 1024, [%1];\n"
               "@p cp.async.bulk.shared::cluster.shared::cta.mbarrier::complete_tx::bytes [%2], [%4], 1024, [%3];\n}"
               :: "r"(d1), "r"(b1), "r"(d2), "r"(b2), "r"(src) : "memory");
}
__device__ __forceinline__ void mbar_arrive_elect(uint32_t bar) { asm volatile("{\n.reg .pred p;\nelect.sync _|p, 0xffffffff;\n@p mbarrier.arrive.shared::cta.b64 _, [%0];\n}" :: "r"(bar) : "memory"); }
__device__ __forceinline__ void sts1(uint32_t a, uint32_t v) { asm volatile("st.shared.u32 [%0], %1;" :: "r"(a), "r"(v) : "memory"); }
__device__ __forceinline__ void bulk_g2s(uint32_t dst, const void* src, uint32_t bytes, uint32_t bar) {
  asm volatile("cp.async.bulk.shared::cluster.global.mbarrier::complete_tx::bytes [%0], [%1], %2, [%3];" :: "r"(dst), "l"(src), "r"(bytes), "r"(bar) : "memory");
}
__device__ __forceinline__ void bulk_g2s_mc(uint32_t dst, const void* src, uint32_t bytes, uint32_t bar) {
  asm volatile("cp.async.bulk.shared::cluster.global.mbarrier::complete_tx::bytes.multicast::cluster [%0], [%1], %2, [%3], %4;" :: "r"(dst), "l"(src), "r"(bytes), "r"(bar), "h"((uint16_t)3) : "memory");
}
__device__ __forceinline__ void mbar_arrive_cl(uint32_t bar) { asm volatile("mbarrier.arrive.shared::cluster.b64 _, [%0];" :: "r"(bar) : "memory"); }
__device__ __forceinline__ void tma2d(uint32_t dst, const CUtensorMap* m, int c0, int c1, uint32_t bar) {
  asm volatile("cp.async.bulk.tensor.2d.shared::cluster.global.mbarrier::complete_tx::bytes [%0], [%1, {%3, %4}], [%2];" :: "r"(dst), "l"((uint64_t)m), "r"(bar), "r"(c0), "r"(c1) : "memory");
}
__device__ __forceinline__ void tma5d(uint32_t dst, const CUtensorMap* m, int c0, int c4, uint32_t bar) {
  asm volatile("cp.async.bulk.tensor.5d.shared::cluster.global.mbarrier::complete_tx::bytes [%0], [%1, {%3, %5, %5, %5, %4}], [%2];" :: "r"(dst), "l"((uint64_t)m), "r"(bar), "r"(c0), "r"(c4), "r"(0) : "memory");
}
__device__ __forceinline__ void red64(void* p, uint32_t lo, uint32_t hi) { asm volatile("{\n.reg .b64 t;\nmov.b64 t, {%1,%2};\nred.relaxed.gpu.global.add.u64 [%0], t;\n}" :: "l"(p), "r"(lo), "r"(hi) : "memory"); }
__device__ __forceinline__ uint4 ld_poll(const void* p) {
  uint4 v;
  asm volatile("{\n.reg .b64 a, b;\nld.relaxed.gpu.global.v2.b64 {a, b}, [%4];\nmov.b64 {%0,%1}, a;\nmov.b64 {%2,%3}, b;\n}" : "=r"(v.x), "=r"(v.y), "=r"(v.z), "=r"(v.w) : "l"(p) : "memory");
  return v;
}
__device__ __forceinline__ uint32_t clk() { uint32_t c; asm volatile("mov.u32 %0, %%clock;" : "=r"(c) :: "memory"); return c; }
#define SCHED_FENCE() asm volatile("pmevent 0;" ::: "memory")
__device__ __forceinline__ float ex2(float x) { float y; asm("ex2.approx.ftz.f32 %0, %1;" : "=f"(y) : "f"(x)); return y; }

__device__ __forceinline__ void wg_ss_n240_ta0_tb1(float* d, uint64_t a, uint64_t b, int sc) {
  asm volatile("{\n.reg .pred p;\nsetp.ne.b32 p, %122, 0;\nwgmma.mma_async.sync.aligned.m64n240k16.f32.bf16.bf16 {%0, %1, %2, %3, %4, %5, %6, %7, %8, %9, %10, %11, %12, %13, %14, %15, %16, %17, %18, %19, %20, %21, %22, %23, %24, %25, %26, %27, %28, %29, %30, %31, %32, %33, %34, %35, %36, %37, %38, %39, %40, %41, %42, %43, %44, %45, %46, %47, %48, %49, %50, %51, %52, %53, %54, %55, %56, %57, %58, %59, %60, %61, %62, %63, %64, %65, %66, %67, %68, %69, %70, %71, %72, %73, %74, %75, %76, %77, %78, %79, %80, %81, %82, %83, %84, %85, %86, %87, %88, %89, %90, %91, %92, %93, %94, %95, %96, %97, %98, %99, %100, %101, %102, %103, %104, %105, %106, %107, %108, %109, %110, %111, %112, %113, %114, %115, %116, %117, %118, %119}, %120, %121, p, 1, 1, 0, 1;\n}\n"
    : "+f"(d[0]), "+f"(d[1]), "+f"(d[2]), "+f"(d[3]), "+f"(d[4]), "+f"(d[5]), "+f"(d[6]), "+f"(d[7]), "+f"(d[8]), "+f"(d[9]), "+f"(d[10]), "+f"(d[11]), "+f"(d[12]), "+f"(d[13]), "+f"(d[14]), "+f"(d[15]), "+f"(d[16]), "+f"(d[17]), "+f"(d[18]), "+f"(d[19]), "+f"(d[20]), "+f"(d[21]), "+f"(d[22]), "+f"(d[23]), "+f"(d[24]), "+f"(d[25]), "+f"(d[26]), "+f"(d[27]), "+f"(d[28]), "+f"(d[29]), "+f"(d[30]), "+f"(d[31]), "+f"(d[32]), "+f"(d[33]), "+f"(d[34]), "+f"(d[35]), "+f"(d[36]), "+f"(d[37]), "+f"(d[38]), "+f"(d[39]), "+f"(d[40]), "+f"(d[41]), "+f"(d[42]), "+f"(d[43]), "+f"(d[44]), "+f"(d[45]), "+f"(d[46]), "+f"(d[47]), "+f"(d[48]), "+f"(d[49]), "+f"(d[50]), "+f"(d[51]), "+f"(d[52]), "+f"(d[53]), "+f"(d[54]), "+f"(d[55]), "+f"(d[56]), "+f"(d[57]), "+f"(d[58]), "+f"(d[59]), "+f"(d[60]), "+f"(d[61]), "+f"(d[62]), "+f"(d[63]), "+f"(d[64]), "+f"(d[65]), "+f"(d[66]), "+f"(d[67]), "+f"(d[68]), "+f"(d[69]), "+f"(d[70]), "+f"(d[71]), "+f"(d[72]), "+f"(d[73]), "+f"(d[74]), "+f"(d[75]), "+f"(d[76]), "+f"(d[77]), "+f"(d[78]), "+f"(d[79]), "+f"(d[80]), "+f"(d[81]), "+f"(d[82]), "+f"(d[83]), "+f"(d[84]), "+f"(d[85]), "+f"(d[86]), "+f"(d[87]), "+f"(d[88]), "+f"(d[89]), "+f"(d[90]), "+f"(d[91]), "+f"(d[92]), "+f"(d[93]), "+f"(d[94]), "+f"(d[95]), "+f"(d[96]), "+f"(d[97]), "+f"(d[98]), "+f"(d[99]), "+f"(d[100]), "+f"(d[101]), "+f"(d[102]), "+f"(d[103]), "+f"(d[104]), "+f"(d[105]), "+f"(d[106]), "+f"(d[107]), "+f"(d[108]), "+f"(d[109]), "+f"(d[110]), "+f"(d[111]), "+f"(d[112]), "+f"(d[113]), "+f"(d[114]), "+f"(d[115]), "+f"(d[116]), "+f"(d[117]), "+f"(d[118]), "+f"(d[119])
    : "l"(a), "l"(b), "r"(sc));
}
__device__ __forceinline__ void wg_ss_n88_ta1_tb1(float* d, uint64_t a, uint64_t b, int sc) {
  asm volatile("{\n.reg .pred p;\nsetp.ne.b32 p, %46, 0;\nwgmma.mma_async.sync.aligned.m64n88k16.f32.bf16.bf16 {%0, %1, %2, %3, %4, %5, %6, %7, %8, %9, %10, %11, %12, %13, %14, %15, %16, %17, %18, %19, %20, %21, %22, %23, %24, %25, %26, %27, %28, %29, %30, %31, %32, %33, %34, %35, %36, %37, %38, %39, %40, %41, %42, %43}, %44, %45, p, 1, 1, 1, 1;\n}\n"
    : "+f"(d[0]), "+f"(d[1]), "+f"(d[2]), "+f"(d[3]), "+f"(d[4]), "+f"(d[5]), "+f"(d[6]), "+f"(d[7]), "+f"(d[8]), "+f"(d[9]), "+f"(d[10]), "+f"(d[11]), "+f"(d[12]), "+f"(d[13]), "+f"(d[14]), "+f"(d[15]), "+f"(d[16]), "+f"(d[17]), "+f"(d[18]), "+f"(d[19]), "+f"(d[20]), "+f"(d[21]), "+f"(d[22]), "+f"(d[23]), "+f"(d[24]), "+f"(d[25]), "+f"(d[26]), "+f"(d[27]), "+f"(d[28]), "+f"(d[29]), "+f"(d[30]), "+f"(d[31]), "+f"(d[32]), "+f"(d[33]), "+f"(d[34]), "+f"(d[35]), "+f"(d[36]), "+f"(d[37]), "+f"(d[38]), "+f"(d[39]), "+f"(d[40]), "+f"(d[41]), "+f"(d[42]), "+f"(d[43])
    : "l"(a), "l"(b), "r"(sc));
}
__device__ __forceinline__ void wg_rs_n160_tb1(float* d, const uint32_t* a, uint64_t b, int sc) {
  asm volatile("{\n.reg .pred p;\nsetp.ne.b32 p, %85, 0;\nwgmma.mma_async.sync.aligned.m64n160k16.f32.bf16.bf16 {%0, %1, %2, %3, %4, %5, %6, %7, %8, %9, %10, %11, %12, %13, %14, %15, %16, %17, %18, %19, %20, %21, %22, %23, %24, %25, %26, %27, %28, %29, %30, %31, %32, %33, %34, %35, %36, %37, %38, %39, %40, %41, %42, %43, %44, %45, %46, %47, %48, %49, %50, %51, %52, %53, %54, %55, %56, %57, %58, %59, %60, %61, %62, %63, %64, %65, %66, %67, %68, %69, %70, %71, %72, %73, %74, %75, %76, %77, %78, %79}, {%80, %81, %82, %83}, %84, p, 1, 1, 1;\n}\n"
    : "+f"(d[0]), "+f"(d[1]), "+f"(d[2]), "+f"(d[3]), "+f"(d[4]), "+f"(d[5]), "+f"(d[6]), "+f"(d[7]), "+f"(d[8]), "+f"(d[9]), "+f"(d[10]), "+f"(d[11]), "+f"(d[12]), "+f"(d[13]), "+f"(d[14]), "+f"(d[15]), "+f"(d[16]), "+f"(d[17]), "+f"(d[18]), "+f"(d[19]), "+f"(d[20]), "+f"(d[21]), "+f"(d[22]), "+f"(d[23]), "+f"(d[24]), "+f"(d[25]), "+f"(d[26]), "+f"(d[27]), "+f"(d[28]), "+f"(d[29]), "+f"(d[30]), "+f"(d[31]), "+f"(d[32]), "+f"(d[33]), "+f"(d[34]), "+f"(d[35]), "+f"(d[36]), "+f"(d[37]), "+f"(d[38]), "+f"(d[39]), "+f"(d[40]), "+f"(d[41]), "+f"(d[42]), "+f"(d[43]), "+f"(d[44]), "+f"(d[45]), "+f"(d[46]), "+f"(d[47]), "+f"(d[48]), "+f"(d[49]), "+f"(d[50]), "+f"(d[51]), "+f"(d[52]), "+f"(d[53]), "+f"(d[54]), "+f"(d[55]), "+f"(d[56]), "+f"(d[57]), "+f"(d[58]), "+f"(d[59]), "+f"(d[60]), "+f"(d[61]), "+f"(d[62]), "+f"(d[63]), "+f"(d[64]), "+f"(d[65]), "+f"(d[66]), "+f"(d[67]), "+f"(d[68]), "+f"(d[69]), "+f"(d[70]), "+f"(d[71]), "+f"(d[72]), "+f"(d[73]), "+f"(d[74]), "+f"(d[75]), "+f"(d[76]), "+f"(d[77]), "+f"(d[78]), "+f"(d[79])
    : "r"(a[0]), "r"(a[1]), "r"(a[2]), "r"(a[3]), "l"(b), "r"(sc));
}
__device__ __forceinline__ void wg_ss_n80_ta0_tb1(float* d, uint64_t a, uint64_t b, int sc) {
  asm volatile("{\n.reg .pred p;\nsetp.ne.b32 p, %42, 0;\nwgmma.mma_async.sync.aligned.m64n80k16.f32.bf16.bf16 {%0, %1, %2, %3, %4, %5, %6, %7, %8, %9, %10, %11, %12, %13, %14, %15, %16, %17, %18, %19, %20, %21, %22, %23, %24, %25, %26, %27, %28, %29, %30, %31, %32, %33, %34, %35, %36, %37, %38, %39}, %40, %41, p, 1, 1, 0, 1;\n}\n"
    : "+f"(d[0]), "+f"(d[1]), "+f"(d[2]), "+f"(d[3]), "+f"(d[4]), "+f"(d[5]), "+f"(d[6]), "+f"(d[7]), "+f"(d[8]), "+f"(d[9]), "+f"(d[10]), "+f"(d[11]), "+f"(d[12]), "+f"(d[13]), "+f"(d[14]), "+f"(d[15]), "+f"(d[16]), "+f"(d[17]), "+f"(d[18]), "+f"(d[19]), "+f"(d[20]), "+f"(d[21]), "+f"(d[22]), "+f"(d[23]), "+f"(d[24]), "+f"(d[25]), "+f"(d[26]), "+f"(d[27]), "+f"(d[28]), "+f"(d[29]), "+f"(d[30]), "+f"(d[31]), "+f"(d[32]), "+f"(d[33]), "+f"(d[34]), "+f"(d[35]), "+f"(d[36]), "+f"(d[37]), "+f"(d[38]), "+f"(d[39])
    : "l"(a), "l"(b), "r"(sc));
}
__device__ __forceinline__ void wg_rs_n32_tb1(float* d, const uint32_t* a, uint64_t b, int sc) {
  asm volatile("{\n.reg .pred p;\nsetp.ne.b32 p, %21, 0;\nwgmma.mma_async.sync.aligned.m64n32k16.f32.bf16.bf16 {%0, %1, %2, %3, %4, %5, %6, %7, %8, %9, %10, %11, %12, %13, %14, %15}, {%16, %17, %18, %19}, %20, p, 1, 1, 1;\n}\n"
    : "+f"(d[0]), "+f"(d[1]), "+f"(d[2]), "+f"(d[3]), "+f"(d[4]), "+f"(d[5]), "+f"(d[6]), "+f"(d[7]), "+f"(d[8]), "+f"(d[9]), "+f"(d[10]), "+f"(d[11]), "+f"(d[12]), "+f"(d[13]), "+f"(d[14]), "+f"(d[15])
    : "r"(a[0]), "r"(a[1]), "r"(a[2]), "r"(a[3]), "l"(b), "r"(sc));
}
__device__ __forceinline__ void wg_ss_n32_ta1_tb1(float* d, uint64_t a, uint64_t b, int sc) {
  asm volatile("{\n.reg .pred p;\nsetp.ne.b32 p, %18, 0;\nwgmma.mma_async.sync.aligned.m64n32k16.f32.bf16.bf16 {%0, %1, %2, %3, %4, %5, %6, %7, %8, %9, %10, %11, %12, %13, %14, %15}, %16, %17, p, 1, 1, 1, 1;\n}\n"
    : "+f"(d[0]), "+f"(d[1]), "+f"(d[2]), "+f"(d[3]), "+f"(d[4]), "+f"(d[5]), "+f"(d[6]), "+f"(d[7]), "+f"(d[8]), "+f"(d[9]), "+f"(d[10]), "+f"(d[11]), "+f"(d[12]), "+f"(d[13]), "+f"(d[14]), "+f"(d[15])
    : "l"(a), "l"(b), "r"(sc));
}
__device__ __forceinline__ void wg_rs_n32_tb0(float* d, const uint32_t* a, uint64_t b, int sc) {
  asm volatile("{\n.reg .pred p;\nsetp.ne.b32 p, %21, 0;\nwgmma.mma_async.sync.aligned.m64n32k16.f32.bf16.bf16 {%0, %1, %2, %3, %4, %5, %6, %7, %8, %9, %10, %11, %12, %13, %14, %15}, {%16, %17, %18, %19}, %20, p, 1, 1, 0;\n}\n"
    : "+f"(d[0]), "+f"(d[1]), "+f"(d[2]), "+f"(d[3]), "+f"(d[4]), "+f"(d[5]), "+f"(d[6]), "+f"(d[7]), "+f"(d[8]), "+f"(d[9]), "+f"(d[10]), "+f"(d[11]), "+f"(d[12]), "+f"(d[13]), "+f"(d[14]), "+f"(d[15])
    : "r"(a[0]), "r"(a[1]), "r"(a[2]), "r"(a[3]), "l"(b), "r"(sc));
}
__device__ __forceinline__ void wg_rs_n40_tb0(float* d, const uint32_t* a, uint64_t b, int sc) {
  asm volatile("{\n.reg .pred p;\nsetp.ne.b32 p, %25, 0;\nwgmma.mma_async.sync.aligned.m64n40k16.f32.bf16.bf16 {%0, %1, %2, %3, %4, %5, %6, %7, %8, %9, %10, %11, %12, %13, %14, %15, %16, %17, %18, %19}, {%20, %21, %22, %23}, %24, p, 1, 1, 0;\n}\n"
    : "+f"(d[0]), "+f"(d[1]), "+f"(d[2]), "+f"(d[3]), "+f"(d[4]), "+f"(d[5]), "+f"(d[6]), "+f"(d[7]), "+f"(d[8]), "+f"(d[9]), "+f"(d[10]), "+f"(d[11]), "+f"(d[12]), "+f"(d[13]), "+f"(d[14]), "+f"(d[15]), "+f"(d[16]), "+f"(d[17]), "+f"(d[18]), "+f"(d[19])
    : "r"(a[0]), "r"(a[1]), "r"(a[2]), "r"(a[3]), "l"(b), "r"(sc));
}
__device__ __forceinline__ void wg_rs_n8_tb1(float* d, const uint32_t* a, uint64_t b, int sc) {
  asm volatile("{\n.reg .pred p;\nsetp.ne.b32 p, %9, 0;\nwgmma.mma_async.sync.aligned.m64n8k16.f32.bf16.bf16 {%0, %1, %2, %3}, {%4, %5, %6, %7}, %8, p, 1, 1, 1;\n}\n"
    : "+f"(d[0]), "+f"(d[1]), "+f"(d[2]), "+f"(d[3])
    : "r"(a[0]), "r"(a[1]), "r"(a[2]), "r"(a[3]), "l"(b), "r"(sc));
}
__device__ __forceinline__ void wg_ss_n40_ta0_tb0(float* d, uint64_t a, uint64_t b, int sc) {
  asm volatile("{\n.reg .pred p;\nsetp.ne.b32 p, %22, 0;\nwgmma.mma_async.sync.aligned.m64n40k16.f32.bf16.bf16 {%0, %1, %2, %3, %4, %5, %6, %7, %8, %9, %10, %11, %12, %13, %14, %15, %16, %17, %18, %19}, %20, %21, p, 1, 1, 0, 0;\n}\n"
    : "+f"(d[0]), "+f"(d[1]), "+f"(d[2]), "+f"(d[3]), "+f"(d[4]), "+f"(d[5]), "+f"(d[6]), "+f"(d[7]), "+f"(d[8]), "+f"(d[9]), "+f"(d[10]), "+f"(d[11]), "+f"(d[12]), "+f"(d[13]), "+f"(d[14]), "+f"(d[15]), "+f"(d[16]), "+f"(d[17]), "+f"(d[18]), "+f"(d[19])
    : "l"(a), "l"(b), "r"(sc));
}
__device__ __forceinline__ void wg_ss_n40_ta1_tb0(float* d, uint64_t a, uint64_t b, int sc) {
  asm volatile("{\n.reg .pred p;\nsetp.ne.b32 p, %22, 0;\nwgmma.mma_async.sync.aligned.m64n40k16.f32.bf16.bf16 {%0, %1, %2, %3, %4, %5, %6, %7, %8, %9, %10, %11, %12, %13, %14, %15, %16, %17, %18, %19}, %20, %21, p, 1, 1, 1, 0;\n}\n"
    : "+f"(d[0]), "+f"(d[1]), "+f"(d[2]), "+f"(d[3]), "+f"(d[4]), "+f"(d[5]), "+f"(d[6]), "+f"(d[7]), "+f"(d[8]), "+f"(d[9]), "+f"(d[10]), "+f"(d[11]), "+f"(d[12]), "+f"(d[13]), "+f"(d[14]), "+f"(d[15]), "+f"(d[16]), "+f"(d[17]), "+f"(d[18]), "+f"(d[19])
    : "l"(a), "l"(b), "r"(sc));
}
__device__ __forceinline__ void wg_ss_n8_ta1_tb1(float* d, uint64_t a, uint64_t b, int sc) {
  asm volatile("{\n.reg .pred p;\nsetp.ne.b32 p, %6, 0;\nwgmma.mma_async.sync.aligned.m64n8k16.f32.bf16.bf16 {%0, %1, %2, %3}, %4, %5, p, 1, 1, 1, 1;\n}\n"
    : "+f"(d[0]), "+f"(d[1]), "+f"(d[2]), "+f"(d[3])
    : "l"(a), "l"(b), "r"(sc));
}

constexpr int O_WV = 0, O_WO = 81920, O_H = 163840, O_QK = 215040, O_SM = 228352, O_MISC = 229632;
constexpr int O_QM = O_QK + 1024, O_K = O_QK + 3072, O_OG = O_QK + 8192;
constexpr int SM_SLOT = 640;
constexpr int O_MAXS = O_MISC;
constexpr int O_BAR = O_MISC + 64;
constexpr int MB_XF = 0, MB_ML = 2, MB_MR = 4, MB_SM = 7, MB_SX = 8, MB_OG = 9, MB_W = 10;
constexpr int O_PROF = O_BAR + 8 * 24;
constexpr int REC_SMEM = O_PROF + 128;
constexpr int B_VOWN = 0, B_QK = 1, B_VGO = 2, B_SISS = 3, B_PM = 4, B_PX = 5, B_XGO = 6, B_PFREE = 7, B_WG2 = 8, B_VHALF = 9, B_VDONE = 10,
              B_PFREE1 = 11, B_SSENT = 12, B_SLD = 13, B_VEND = 14, B_XGO1 = 15;
#define POLL_DELAY 650
#define POLL_D0 300
#define POLL_STEP 100
#define TS0(idx) do {} while (0)
#define TS(idx) do {} while (0)
#define SLD_POS 0
#define WO_PROG 1
#define TRIG_LATE 1
#define FILL_B 4096
#define MP_D 3
#define MP_CH 4
#define MP_F 0
#define ML_N0 3
#define MR_N0 3
#define O_RS 6
#define O_RS_POS 0
#define V_N1 2
#define V_N2 0
#define V_N3 4
#define V_OWN 6
#define V_S1 9
#define V_K1 (V_OWN + V_RS + V_S1)
#define V_K2 ((V_K1 > 20 ? V_K1 : 20) + V_S2)
#define V_S2 3
constexpr int V_RS = V_N1 + V_N2 + V_N3;
constexpr float SCL = 0.07216878364870322f;
constexpr float L2E = 1.4426950408889634f;
__device__ __forceinline__ constexpr int vord(int i) { return i < 4 ? 36 + i : i - 4; }
__device__ __forceinline__ constexpr uint32_t hoff(int k) { return ((k >> 2) * 5120 + (k & 3) * 32) >> 4; }

__device__ __forceinline__ void fix_red(uint8_t* p, const float* a, float sc) {
  int v0 = __float2int_rn(a[0] * sc), v1 = __float2int_rn(a[1] * sc), v2 = __float2int_rn(a[2] * sc), v3 = __float2int_rn(a[3] * sc);
  red64(p, ((uint32_t)v0 << 7) | 1u, ((uint32_t)v2 << 3) + (uint32_t)(v0 >> 25));
  red64(p + 1024, ((uint32_t)v1 << 7) | 1u, ((uint32_t)v3 << 3) + (uint32_t)(v1 >> 25));
}
__device__ __forceinline__ float max10(const float* t) {
  float m = fmaxf(fmaxf(fmaxf(t[0], t[1]), fmaxf(t[2], t[3])), fmaxf(fmaxf(t[4], t[5]), fmaxf(t[6], t[7])));
  m = fmaxf(m, fmaxf(t[8], t[9]));
  m = fmaxf(m, __shfl_xor_sync(~0u, m, 1));
  return fmaxf(m, __shfl_xor_sync(~0u, m, 2));
}
#define ACC2(k, p, u, v) { t[k] = bflo(p) + bflo(u) + bflo(v); t[k + 1] = bfhi(p) + bfhi(u) + bfhi(v); }

__global__ void __launch_bounds__(384, 1)
rec_kernel(const __grid_constant__ CUtensorMap tmq, const __grid_constant__ CUtensorMap tmk,
           const __grid_constant__ CUtensorMap tmv, const __grid_constant__ CUtensorMap tmo,
           const bf16* __restrict__ mem0, uint8_t* __restrict__ ar, uint32_t* __restrict__ flags, int layer) {
  extern __shared__ __align__(1024) uint8_t smem[];
  const uint32_t sb = smem_u32(smem);
  check_smem_base(sb);
  const int tid = threadIdx.x, wid = __shfl_sync(~0u, tid >> 5, 0), wg = wid >> 2, w = wid & 3;
  const int lane = __shfl_sync(~0u, tid & 31, tid & 31);
  const int head = blockIdx.x / 3, rank = blockIdx.x - head * 3;
  const int e0 = blockIdx.x * 64;
  const uint32_t bar = sb + O_BAR;
  const uint32_t sb1 = mapa(sb, rank == 2 ? 0 : rank + 1), sb2 = mapa(sb, rank == 0 ? 2 : rank - 1);
  auto chunk_of = [&](int p) { const int c = 3 * rank + p; return p == 9 ? 9 : c >= 9 ? c - 9 : c; };

  GT(layer * 4 + 1, 0);
  if (wid == 8) {
    if (lane < 24) mbar_init(bar + 8 * lane, lane == MB_ML ? ML_N0 : lane == MB_ML + 1 && ML_N0 < 4 ? 4 - ML_N0 : 1);
    asm volatile("fence.mbarrier_init.release.cluster;" ::: "memory");
    fence_async();
    __syncwarp();
    if (lane < 10) mbar_expect(bar + 8 * (MB_W + lane), 16384);
    __syncwarp();
    if (lane < 20) {
      const int m = (lane >> 1) & 1, p = (lane >> 2) * 2 + (lane & 1);
      tma5d(sb + m * 81920 + p * 8192, m ? &tmk : &tmq, e0, chunk_of(p) * 4, bar + 8 * (MB_W + m * 5 + (p >> 1)));
    }
  }
  __syncthreads();
  asm volatile("barrier.cluster.arrive.relaxed.aligned;" ::: "memory");

  if (wg < 2) {
    asm volatile("setmaxnreg.inc.sync.aligned.u32 208;");
    uint32_t a[40][4];
    const uint32_t swz = __shfl_sync(~0u, (lane & 7) * 128 + (((2 * w + ((lane >> 3) & 1)) ^ (lane & 7)) << 4), lane);
    {
      const uint32_t la = sb + wg * 81920 + (lane >> 4) * 1024 + swz;
#pragma unroll
      for (int p = 0; p < 5; p++) {
        mbar_wait(bar + 8 * (MB_W + wg * 5 + p), 0);
#pragma unroll
        for (int k = 0; k < 8; k++) ldsm4t(a[p * 8 + k], la + (p * 8 + k) * 2048);
        if (p > 0) bar_sync<B_VGO, 288>();
        bar_arrive<B_PFREE, 288>();
      }
      bar_sync<B_VGO, 288>();
    }
    GT(layer * 4 + 1, 5);
    asm volatile("barrier.cluster.wait.aligned;" ::: "memory");
    const uint32_t ld_m = __shfl_sync(~0u, sb + O_H + (lane & 7) * 128 + (((lane >> 3) ^ (lane & 7)) << 4), lane);

    for (int s = 0; s < NSEG; s++) {
      const uint32_t par = s & 1;
      if (wid == 4) TS0(0);
      if (wid == 0) TS(30);
      {
        float ax[16];
        constexpr uint64_t db = mkdesc(SB0 + O_H + 1024, 16, 1024, 1);
        mbar_wait(bar + 8 * MB_XF, par);
        wg_fence();
#pragma unroll
        for (int k = 0; k < 20; k++) wg_rs_n32_tb0(ax, a[vord(k)], db + hoff(vord(k)), k);
        mbar_wait(bar + 8 * (MB_XF + 1), par);
        wg_fence();
#pragma unroll
        for (int k = 20; k < 40; k++) wg_rs_n32_tb0(ax, a[vord(k)], db + hoff(vord(k)), 1);
        wg_commit();
        if (s > 0) { if (wg == 0) bar_sync<B_PFREE, 256>(); else bar_sync<B_PFREE1, 256>(); }
        const uint32_t st_x = sb + O_QK + wg * 5120 + (lane >> 4) * 2048 + swz;
        if (wid == 6 && lane == 0) { mbar_expect(bar + 8 * MB_SM, 2 * SM_SLOT + 48 + 48); mbar_expect(bar + 8 * MB_SX, 2 * 2176); }
        wg_wait<0>();
        pin<16>(ax);
        if (w == 0) TS(1 + 22 * wg);
        stsm4t(st_x, pack2(ax[0], ax[1]), pack2(ax[2], ax[3]), pack2(ax[4], ax[5]), pack2(ax[6], ax[7]));
        stsm4t(st_x + 4096, pack2(ax[8], ax[9]), pack2(ax[10], ax[11]), pack2(ax[12], ax[13]), pack2(ax[14], ax[15]));
        if (V_OWN > 0) bar_arrive<B_VOWN, 384>();
      }
      {
        float c[MP_CH][4];
#pragma unroll
        for (int k = 0; k < MP_CH; k++) c[k][0] = c[k][1] = c[k][2] = c[k][3] = 0.f;
        uint32_t b[MP_D][2][4];
        const uint32_t ld_m2 = opaque(ld_m ^ 64);
        SCHED_FENCE();
#define MORD(j) ((j) == 0 ? 9 : (j) < 4 ? (j) - 1 : 3 + ((j) - 4) / 2 + 3 * ((j) & 1))
#pragma unroll
        for (int j = 0; j < 10 + MP_D - 1; j++) {
          if (j < 10) {
            if (j == 0) { mbar_wait(bar + 8 * MB_ML, par); if (wid == 0) TS(2); }
            if (ML_N0 < 4 && j == ML_N0) { mbar_wait(bar + 8 * (MB_ML + 1), par); if (wid == 0) TS(3); }
            if (j == 4) { mbar_wait(bar + 8 * MB_MR, par); if (wid == 0) TS(4); }
            if (j == 4 + 2 * MR_N0) { mbar_wait(bar + 8 * (MB_MR + 1), par); if (wid == 0) TS(5); }
            ldsm4(b[j % MP_D][0], ld_m + MORD(j) * 5120);
            ldsm4(b[j % MP_D][1], ld_m2 + MORD(j) * 5120);
            if ((MP_F >> j) & 1) SCHED_FENCE();
          }
          const int u = j - (MP_D - 1);
          if (u >= 0) {
#pragma unroll
            for (int k = 0; k < 4; k++) mma16816(c[(4 * u + k) % MP_CH], a[4 * MORD(u) + k], b[u % MP_D][k >> 1][(k & 1) * 2], b[u % MP_D][k >> 1][(k & 1) * 2 + 1]);
          }
        }
        SCHED_FENCE();
        bar_arrive<B_VGO, 384>();
        SCHED_FENCE();
#pragma unroll
        for (int k = 0; k < 4; k++) c[0][k] = MP_CH == 4 ? (c[0][k] + c[1][k]) + (c[2][k] + c[MP_CH - 1][k]) : (c[1][k] + c[2][k]) + c[0][k];
        stsm2t(sb + O_QM + wg * 2048 + swz, pack2(c[0][0], c[0][1]), pack2(c[0][2], c[0][3]));
        fence_async();
      }
      if (wg == 0) {
        bar_sync<B_QK, 256>();
        float sv[20];
        {
          constexpr uint64_t da = mkdesc(SB0 + O_QK, 16, 1024, 1), db = mkdesc(SB0 + O_K, 16, 2048, 1);
          wg_fence();
#pragma unroll
          for (int k = 0; k < 4; k++) wg_ss_n40_ta0_tb0(sv, da + 2 * k, db + 2 * k, k);
          wg_commit();
          bar_arrive<B_SISS, 256>();
        }
        if (w == 0) TS(6);
        SCHED_FENCE();
        const uint32_t ln = opaque(lane);
        uint32_t m0, m1, m2, m3, m4;
        {
          const uint32_t a1 = opaque(sb1 + O_SM + SM_SLOT + ln * 16), a2 = opaque(sb2 + O_SM + ln * 16);
          const uint32_t a3 = opaque(sb1 + O_SM + SM_SLOT + 512 + ln * 4), a4 = opaque(sb2 + O_SM + 512 + ln * 4);
          const uint32_t b1 = opaque(sb1 + O_BAR + 8 * MB_SM), b2 = opaque(sb2 + O_BAR + 8 * MB_SM);
          const uint32_t bt = opaque(mapa(sb, min(ln, 2u)) + O_BAR + 8 * MB_SM), at = opaque(bt + (O_MAXS + 48 - O_BAR - 8 * MB_SM));
          SCHED_FENCE();
          wg_wait<0>();
          pin<20>(sv);
          m0 = pack2(sv[2], sv[3]); m1 = pack2(sv[6], sv[7]); m2 = pack2(sv[10], sv[11]); m3 = pack2(sv[14], sv[15]); m4 = pack2(sv[18], sv[19]);
          if (w == 0) {
            sta4(a1, m0, m1, m2, m3, b1);
            sta4(a2, m0, m1, m2, m3, b2);
            sta1(a3, m4, b1);
            sta1(a4, m4, b2);
          }
          sta1p(at, 0u, bt, ln < 3);
          bar_arrive<B_SSENT, 256>();
          SCHED_FENCE();
        }
        const uint32_t p0 = pack2(sv[0], sv[1]), p1 = pack2(sv[4], sv[5]), p2 = pack2(sv[8], sv[9]), p3 = pack2(sv[12], sv[13]), p4 = pack2(sv[16], sv[17]);
        const uint32_t ox = O_K + w * 2048 + ln * 16, ox2 = O_K + 8192 + ln * 4;
        {
          const uint32_t a1 = opaque(sb1 + ox + 512), a2 = opaque(sb2 + ox), b1 = opaque(sb1 + O_BAR + 8 * MB_SX), b2 = opaque(sb2 + O_BAR + 8 * MB_SX);
          if (w == 0) {
            TS(7);
            const uint32_t om = opaque(sb + O_SM + ln * 16), om2 = opaque(sb + O_SM + 512 + ln * 4);
            const uint32_t pa = sb + O_QM + (ln & 7) * 128;
            const uint32_t pa0 = opaque(pa + (((ln >> 3) ^ (ln & 7)) << 4)), pa1 = opaque(pa + ((4 ^ (ln & 7)) << 4));
            float t[10] = {bflo(m0), bfhi(m0), bflo(m1), bfhi(m1), bflo(m2), bfhi(m2), bflo(m3), bfhi(m3), bflo(m4), bfhi(m4)};
            pin<10>(t);
            SCHED_FENCE();
            mbar_wait(bar + 8 * MB_SM, par);
            const uint4 u = lds4(om), v = lds4(om + SM_SLOT);
            const uint32_t u4 = lds1(om2), v4 = lds1(om2 + SM_SLOT);
            sta4(a1, p0, p1, p2, p3, b1);
            sta4(a2, p0, p1, p2, p3, b2);
            if (SLD_POS == 0) bar_arrive<B_SLD, 256>();
            SCHED_FENCE();
#define ACC3(k, u, v) { t[k] += bflo(u) + bflo(v); t[k + 1] += bfhi(u) + bfhi(v); }
            ACC3(0, u.x, v.x) ACC3(2, u.y, v.y) ACC3(4, u.z, v.z) ACC3(6, u.w, v.w) ACC3(8, u4, v4)
            TS(8);
            const float mm = max10(t) * (SCL * L2E);
            if (SLD_POS == 1) { SCHED_FENCE(); bar_arrive<B_SLD, 256>(); SCHED_FENCE(); }
#pragma unroll
            for (int k = 0; k < 10; k++) t[k] = ex2(fmaf(t[k], SCL * L2E, -mm));
            stsm4(pa0, pack2(t[0], t[1]), pack2(t[2], t[3]), pack2(t[4], t[5]), pack2(t[6], t[7]));
            stsm1(pa1, pack2(t[8], t[9]));
            bar_arrive<B_PM, 160>();
            TS(9);
          } else {
            const uint32_t a3 = opaque(sb1 + ox2 + 128), a4 = opaque(sb2 + ox2);
            SCHED_FENCE();
            mbar_wait(bar + 8 * MB_SM, par);
            sta4(a1, p0, p1, p2, p3, b1);
            sta4(a2, p0, p1, p2, p3, b2);
            if (w == 3) { sta1(a3, p4, b1); sta1(a4, p4, b2); }
            bar_arrive<B_SLD, 256>();
          }
        }
        mbar_wait(bar + 8 * MB_SX, par);
        bar_sync<B_VEND, 256>();
        {
          float t[10];
          const uint4 u = lds4(sb + ox), v = lds4(sb + ox + 512);
          const uint32_t u4 = lds1(sb + ox2), v4 = lds1(sb + ox2 + 128);
          SCHED_FENCE();
          ACC2(0, p0, u.x, v.x) ACC2(2, p1, u.y, v.y) ACC2(4, p2, u.z, v.z) ACC2(6, p3, u.w, v.w) ACC2(8, p4, u4, v4)
          const int dq = 8 * w + (ln >> 2) - 2 * (ln & 3);
#pragma unroll
          for (int k = 1; k < 5; k++) {
            if (8 * (k - 1) > dq) t[2 * k] = -1e9f / SCL;
            if (8 * (k - 1) + 1 > dq) t[2 * k + 1] = -1e9f / SCL;
          }
          const float mm = max10(t) * (SCL * L2E);
#pragma unroll
          for (int k = 0; k < 10; k++) t[k] = ex2(fmaf(t[k], SCL * L2E, -mm));
          float sum = ((t[0] + t[1]) + (t[2] + t[3])) + ((t[4] + t[5]) + (t[6] + t[7])) + (t[8] + t[9]);
          sum += __shfl_xor_sync(~0u, sum, 1);
          sum += __shfl_xor_sync(~0u, sum, 2);
          const float inv = rcp(sum);
          const int rr = 2 * w + (ln & 1);
          const uint32_t pa = sb + O_QK + ((ln >> 1) & 3) * 2048 + rr * 128;
          stsm4(pa + (((ln >> 3) ^ rr) << 4), pack2(t[0] * inv, t[1] * inv), pack2(t[2] * inv, t[3] * inv), pack2(t[4] * inv, t[5] * inv), pack2(t[6] * inv, t[7] * inv));
          stsm2(pa + (((4 + ((ln >> 3) & 1)) ^ rr) << 4), pack2(t[8] * inv, t[9] * inv), 0u);
          fence_async();
        }
        bar_arrive<B_PX, 256>();
        if (w == 0) TS(10);
        bar_sync<B_XGO, 256>();
      } else {
        bar_arrive<B_QK, 256>();
        const int ln = opaque(lane);
        if (w == 2) {
          bar_sync<B_VHALF, 192>();
          if (ln == 0 && s > 0) { red_release(flags + FL_A + (e0 >> 10) * 8 + (s - 1) * 48, 1); }
          __syncwarp();
        }
        if (w == 3) {
          const int l = blockIdx.x * 2 + ln, s2 = s + 2;
          if (ln < 2 && l < 160 && s2 < NSEG - 1) {
            const int tile = l >> 4;
            const uint8_t* p = ar + (s2 >> 2) * AR_GROUP + (s2 & 1) * 128 + ((s2 >> 1) & 1) * 512 + ((tile >> 2) * 8 + (tile & 3)) * 4096 +
                               ((l >> 3) & 1) * 16384 + (l & 1) * 256 + ((l >> 1) & 3) * 1024;
            asm volatile("prefetch.global.L2 [%0];" :: "l"(p));
          }
        }
        if (w == 0) {
          const bool more = s + 1 < NSEG;
          if (ln < 2 && more) mbar_expect(bar + 8 * (MB_XF + ln), FILL_B * 5);
          const uint8_t* src = g_xn + (s + 1) * 40960 + chunk_of(ln) * 4096;
          bar_sync<B_VHALF, 192>();
          if ((ln < 4 || ln == 9) && more) bulk_g2s(sb + O_H + ln * 5120 + 1024, src, FILL_B, bar + 8 * MB_XF);
          bar_sync<B_VDONE, 160>();
          if (ln >= 4 && ln < 9 && more) bulk_g2s(sb + O_H + ln * 5120 + 1024, src, FILL_B, bar + 8 * (MB_XF + 1));
        }
        bar_sync<B_XGO1, 256>();
      }
    }
  } else {
    asm volatile("setmaxnreg.dec.sync.aligned.u32 88;");
    if (w == 1) {
      if (lane == 0) { mbar_expect(bar + 8 * (MB_W + 10), 81920); mbar_expect(bar + 8 * (MB_W + 11), 81920); }
#pragma unroll 1
      for (int p = 0; p < 5; p++) {
        bar_sync<B_PFREE, 288>();
        fence_async();
        if (lane < 2) tma5d(sb + O_WV + (2 * p + lane) * 8192, &tmv, e0, chunk_of(2 * p + lane) * 4, bar + 8 * (MB_W + 10));
        if (WO_PROG ? (lane >> 1) == p : (p == 4 && lane < 10)) {
          const int k = lane / 3, j = rank + lane - 3 * k;
          tma2d(sb + O_WO + lane * 8192, &tmo, lane == 9 ? 576 : (rank * 3 + k) * 64, head * DH + (j >= 3 ? j - 3 : j) * 64, bar + 8 * (MB_W + 11));
        }
        bar_arrive<B_VGO, 288>();
      }
    }
    if (w == 0) {
      if (lane < 2) mbar_expect(bar + 8 * (MB_XF + lane), 20480);
      wait_flag(flags + FL_X, 128);
      fence_async_global();
      if (lane < 10) bulk_g2s(sb + O_H + lane * 5120 + 1024, g_xn + chunk_of(lane) * 4096, 4096, bar + 8 * (MB_XF + (lane >= 4 && lane < 9)));
      if (!TRIG_LATE) asm volatile("griddepcontrol.launch_dependents;");
      if (lane == 0) GTT(layer * 4 + 1, 4);
    }
    bar_sync<B_WG2, 128>();
    asm volatile("barrier.cluster.wait.aligned;" ::: "memory");

    const int g = lane >> 2, i4 = lane & 3;
    const int myT = w == 0 ? 9 : rank * 3 + w - 1, myP = w == 0 ? 9 : w - 1;
    const int tok = 2 * ((lane >> 1) & 3) + ((lane >> 3) & 1);
    const uint32_t fw_off = sb + O_H + myP * 5120 + tok * 128 + (((2 * (lane >> 4) + (lane & 1)) ^ tok) << 4);
    const uint32_t prod_off = (w >> 1) * 16384 + (w & 1) * 2048 + ((g >> 1) & 1) * 256 + (i4 * 2 + (g >> 2)) * 16 + (g & 1) * 8;
    const uint32_t cons_off = ((myT >> 2) * 8 + (myT & 3)) * 4096 + (lane >> 3) * 1024 + (lane & 7) * 16;
    auto tile_off = [&](int k) { const int T = rank * 3 + k; return ((T >> 2) * 8 + (T & 3)) * 4096; };
    constexpr uint32_t T9_OFF = 17 * 4096;

    uint32_t mx;
    auto forward = [&](const uint32_t* p) {
      const uint32_t c = O_H + myP * 5120, bo = O_BAR + 8 * (MB_MR + (w > MR_N0));
      sts4(fw_off, p[0], p[1], p[2], p[3]);
      sts4(fw_off ^ 64, p[4], p[5], p[6], p[7]);
      fence_async();
      __syncwarp();
      mbar_arrive_elect(bar + 8 * (MB_ML + (w >= ML_N0)));
      if (w > 0) bulk_s2c_elect(sb1 + c + 6 * 5120, sb1 + bo, sb2 + c + 3 * 5120, sb2 + bo, sb + c);
      SCHED_FENCE();
      mx = 0;
#pragma unroll
      for (int k = 0; k < 8; k++) mx = __vmaxu2(mx, p[k] & 0x7FFF7FFFu);
    };
    auto send_max = [&]() {
      mx = max(mx & 0xFFFFu, mx >> 16);
      mx = __reduce_max_sync(~0u, mx);
      { const uint32_t b = mapa(sb, min(lane, 2)); sta1p(b + O_MAXS + (rank * 4 + w) * 4, mx << 16, b + O_BAR + 8 * MB_SM, lane < 3); }
    };
    auto arm = [&]() { if (lane == 0 && w < (MR_N0 < 3 ? 3 : 2)) mbar_expect(bar + 8 * (w == 0 ? MB_OG : MB_MR - 1 + w), w == 0 ? 2048 : w == 1 ? 2048 * MR_N0 : 2048 * (3 - MR_N0)); };
    {
      arm();
      const uint32_t* mp = (const uint32_t*)(mem0 + tok * DM + myT * 64 + 16 * (lane >> 4) + 4 * (lane & 1));
      const uint32_t p[8] = {mp[0], mp[4], mp[1], mp[5], mp[16], mp[20], mp[17], mp[21]};
      forward(p);
    }
    float cbound;
    {
      wait_flag(g_zero + Z_FLAGS + FL_N, 4);
      const float sq = __ldcg((const float*)(g_zero + Z_NORM));
      float mx = 0.f;
#pragma unroll
      for (int k = 0; k < 5; k++) {
        const float4* p = (const float4*)g_nrm + k * 32 + lane;
        const float4 x = __ldcg(p), y = __ldcg(p + 160), z = __ldcg(p + 320), u = __ldcg(p + 480);
        mx = fmaxf(fmaxf(mx, fmaxf((x.x + y.x) + (z.x + u.x), (x.y + y.y) + (z.y + u.y))), fmaxf((x.z + y.z) + (z.z + u.z), (x.w + y.w) + (z.w + u.w)));
      }
#pragma unroll
      for (int o = 16; o; o >>= 1) mx = fmaxf(mx, __shfl_xor_sync(~0u, mx, o));
      cbound = sqrt_approx(sq) * sqrt_approx(mx) * (25.2982213f * 1.1f);
    }
    mbar_wait(bar + 8 * (MB_W + 10), 0);
    if (tid == 256) GTT(layer * 4 + 1, 7);

    const uint32_t la_w = sb + O_WV + ((lane >> 4) * 8 + (lane & 7)) * 128 + (((2 * w + ((lane >> 3) & 1)) ^ (lane & 7)) << 4);
    uint32_t af[V_RS][4];
#pragma unroll
    for (int k = 0; k < V_RS; k++) ldsm4t(af[k], la_w + vord(V_OWN + k) * 2048);
    uint32_t vf[10];
    uint4 oq0, oq1;
    uint8_t* op;
    auto pv_x = [&](int s) {
      float ox[16];
      const uint32_t vz[4] = {vf[8], vf[9], 0u, 0u};
      constexpr uint64_t dp = mkdesc(SB0 + O_QK, 16, 2048, 1);
      bar_sync<B_PX, 256>();
      wg_fence();
      wg_rs_n32_tb0(ox, vf, dp, 0);
      wg_rs_n32_tb0(ox, vf + 4, dp + 2, 1);
      wg_rs_n32_tb0(ox, vz, dp + 4, 1);
      wg_commit();
      const uint32_t ln = opaque(lane);
      op = g_ot + (size_t)s * (HE * 64) + (e0 + 16 * w) * 64 + (ln & 3) * 128 + (ln >> 2) * 16;
      wg_wait<0>();
      pin<16>(ox);
      oq0 = make_uint4(pack2(ox[0], ox[1]), pack2(ox[4], ox[5]), pack2(ox[8], ox[9]), pack2(ox[12], ox[13]));
      oq1 = make_uint4(pack2(ox[2], ox[3]), pack2(ox[6], ox[7]), pack2(ox[10], ox[11]), pack2(ox[14], ox[15]));
    };
    for (int s = 0;; s++) {
      const uint32_t par = s & 1;
      float sc, isc;
      uint32_t ao[O_RS > 0 ? O_RS : 1][4];
      {
        float av[20];
        constexpr uint64_t da = mkdesc(SB0 + O_WV, 1024, 1024, 1), db = mkdesc(SB0 + O_H, 16, 1024, 1);
#define V_RUN_RS(k0, k1) wg_fence(); _Pragma("unroll") for (int k = k0; k < k1; k++) wg_rs_n40_tb0(av, af[k], db + hoff(vord(V_OWN + k)), V_OWN + k);
#define V_RUN_SS(k0, k1) wg_fence(); _Pragma("unroll") for (int k = k0; k < k1; k++) wg_ss_n40_ta1_tb0(av, da + vord(k) * 128, db + hoff(vord(k)), k);
        if (V_OWN > 0) {
          bar_sync<B_VOWN, 384>();
          V_RUN_SS(0, V_OWN)
          if (w == 0) TS(29);
          SCHED_FENCE();
        }
        send_max();
        bar_sync<B_VGO, 384>();
        V_RUN_RS(0, V_N1)
        if (w == 0) TS(11);
        bar_sync<B_SISS, 256>();
        V_RUN_RS(V_N1, V_N1 + V_N2)
        bar_sync<B_SSENT, 256>();
        V_RUN_SS(V_OWN + V_RS, V_K1)
        V_RUN_RS(V_N1 + V_N2, V_RS)
        const uint32_t ln = opaque(lane);
        const uint32_t amx = opaque(sb + O_MAXS + 4 * min(ln, 11u));
        SCHED_FENCE();
        mbar_wait(bar + 8 * MB_SM, par);
        const uint32_t mxl = lds1(amx);
        if (s == 0) { mbar_wait(bar + 8 * (MB_W + 11), 0); if (TRIG_LATE) asm volatile("griddepcontrol.launch_dependents;"); if (tid == 256) GTT(layer * 4 + 1, 8); }
        bar_sync<B_SLD, 256>();
        V_RUN_SS(V_K1, 20)
        wg_commit();
        V_RUN_SS((V_K1 > 20 ? V_K1 : 20), V_K2)
        wg_commit();
        wg_wait<1>();
        bar_arrive<B_VHALF, 192>();
        V_RUN_SS(V_K2, 40)
        wg_commit();
        SCHED_FENCE();
        if (w == 0) TS(12);
        {
          const float bnd = cbound * fmaxf(1.f, __uint_as_float(__reduce_max_sync(~0u, mxl)));
          const uint32_t eb = min(max(__float_as_uint(bnd) >> 23, 31u), 254u);
          sc = __uint_as_float(opaque((280u - eb) << 23));
          isc = __uint_as_float(opaque((eb - 29u) << 23));
        }
        const uint32_t pa = sb + O_QM + (ln & 7) * 128;
        const uint32_t pa0 = opaque(pa + (((ln >> 3) ^ (ln & 7)) << 4)), pa1 = opaque(pa + ((4 ^ (ln & 7)) << 4));
        const uint32_t o = O_OG + w * 256 + ln * 4;
        const uint32_t a0 = opaque(sb + o), a1 = opaque(sb1 + o + 4096), a2 = opaque(sb1 + o + 4096 + 128), a3 = opaque(sb2 + o + 2048), a4 = opaque(sb2 + o + 2048 + 128);
        const uint32_t b1 = opaque(sb1 + O_BAR + 8 * MB_OG), b2 = opaque(sb2 + O_BAR + 8 * MB_OG);
        const uint32_t c1 = opaque(0x3F803F80u);
        const uint32_t one[4] = {c1, c1, c1, c1};
        SCHED_FENCE();
        bar_sync<B_PM, 160>();
        uint32_t pm[5];
        ldsm4(pm, pa0);
        ldsm1(pm[4], pa1);
        bar_arrive<B_VEND, 256>();
        float s0[4] = {0.f, 0.f, 0.f, 0.f}, s1[4] = {0.f, 0.f, 0.f, 0.f};
        mma16816(s0, one, pm[0], pm[1]);
        mma16816(s1, one, pm[2], pm[3]);
        mma1688(s0, c1, c1, pm[4]);
        SCHED_FENCE();
        wg_wait<0>();
        pin<20>(av);
        if (w == 0) TS(13);
#pragma unroll
        for (int k = 0; k < 10; k++) vf[k] = pack2(av[2 * k], av[2 * k + 1]);
        {
          float o0[4] = {0.f, 0.f, 0.f, 0.f}, o1[4] = {0.f, 0.f, 0.f, 0.f}, o2[4] = {0.f, 0.f, 0.f, 0.f};
          mma16816(o0, vf, pm[0], pm[1]);
          mma16816(o1, vf + 4, pm[2], pm[3]);
          mma1688(o2, vf[8], vf[9], pm[4]);
          if (O_RS_POS == 0) {
#pragma unroll
            for (int k = 0; k < O_RS; k++) ldsm4t(ao[k], la_w + O_WO + 2 * 24576 + (12 - O_RS + k) * 2048);
          }
          if (s == NSEG - 1) break;
          const float i0 = rcp(s0[0] + s1[0]), i1 = rcp(s0[1] + s1[1]);
          const uint32_t p0 = pack2((o0[0] + o1[0] + o2[0]) * i0, (o0[1] + o1[1] + o2[1]) * i1), p1 = pack2((o0[2] + o1[2] + o2[2]) * i0, (o0[3] + o1[3] + o2[3]) * i1);
          sta1(a1, p0, b1); sta1(a2, p1, b1);
          sta1(a3, p0, b2); sta1(a4, p1, b2);
          sts1(a0, p0); sts1(a0 + 128, p1);
          fence_async();
        }
      }
      uint8_t* arp;
      uint32_t t1;
      {
        bar_sync<B_WG2, 128>();
        float c9[4], ca[4], cb[4], cc[4];
        constexpr uint64_t da = mkdesc(SB0 + O_WO, 1024, 1024, 1), db = mkdesc(SB0 + O_OG, 128, 128, 0);
#define O_RUN(acc, tile, k0, k1) _Pragma("unroll") for (int k = k0; k < k1; k++) wg_ss_n8_ta1_tb1(acc, da + (tile) * 1536 + k * 128, db + (k >> 2) * 128 + (k & 3) * 16, k);
        wg_fence();
        O_RUN(c9, 3, 0, 4)
        wg_commit();
        if (w == 0) TS(14);
        O_RUN(ca, 0, 0, 4) O_RUN(cb, 1, 0, 4) O_RUN(cc, 2, 0, 4)
        wg_commit();
        SCHED_FENCE();
        arp = ar + (s >> 2) * AR_GROUP + (s & 1) * 128 + ((s >> 1) & 1) * 512;
        uint8_t* pp = arp + opaque(prod_off);
        wg_wait<1>();
        pin<4>(c9);
        fix_red(pp + T9_OFF, c9, sc);
        SCHED_FENCE();
        if (O_RS_POS == 1) {
#pragma unroll
          for (int k = 0; k < O_RS; k++) ldsm4t(ao[k], la_w + O_WO + 2 * 24576 + (12 - O_RS + k) * 2048);
        }
        mbar_wait(bar + 8 * MB_OG, par);
        wg_fence();
        O_RUN(ca, 0, 4, 12)
        wg_commit();
        bar_arrive<B_VDONE, 160>();
        if (w == 0) TS(15);
        O_RUN(cb, 1, 4, 12)
        wg_commit();
        wg_wait<1>();
        pin<4>(ca);
        fix_red(pp + tile_off(0), ca, sc);
        SCHED_FENCE();
        if (w == 0) TS(16);
        wg_fence();
        O_RUN(cc, 2, 4, 12 - O_RS)
#pragma unroll
        for (int k = 12 - O_RS; k < 12; k++) wg_rs_n8_tb1(cc, ao[k - 12 + O_RS], db + (k >> 2) * 128 + (k & 3) * 16, 1);
        wg_commit();
        bar_arrive<B_XGO1, 256>();
        bar_arrive<B_XGO, 256>();
        wg_wait<1>();
        pin<4>(cb);
        fix_red(pp + tile_off(1), cb, sc);
        wg_wait<0>();
        pin<4>(cc);
        fix_red(pp + tile_off(2), cc, sc);
        t1 = clk();
        if (w == 0) TS(17);
      }
      pv_x(s);
      bar_arrive<B_PFREE, 256>();
      bar_arrive<B_PFREE1, 256>();
      if (w == 0) TS(28);
#pragma unroll
      for (int k = 0; k < V_RS; k++) ldsm4t(af[k], la_w + vord(V_OWN + k) * 2048);
      {
        arm();
        const int dly = w == 0 ? POLL_D0 : POLL_DELAY - (3 - w) * POLL_STEP;
        const uint32_t need = w == 0 ? 96 : 32;
        const uint8_t* cp = arp + opaque(cons_off);
        uint4 y[4];
        int it = 0;
        while ((int)(clk() - t1) < dly) {}
        if (w == 3) TS(18);
        y[0] = ld_poll(cp); y[1] = ld_poll(cp + 256); y[2] = ld_poll(cp + 16384); y[3] = ld_poll(cp + 16384 + 256);
        if (EVF) { const uint64_t pol = policy_evict_first(); stg4h(op, oq0, pol); stg4h(op + 512, oq1, pol); } else { stg4(op, oq0); stg4(op + 512, oq1); }
        while (true) {
          const uint32_t bad = (y[0].x ^ need) | (y[0].z ^ need) | (y[1].x ^ need) | (y[1].z ^ need) | (y[2].x ^ need) | (y[2].z ^ need) | (y[3].x ^ need) | (y[3].z ^ need);
          if (!__any_sync(~0u, (bad & 127u) != 0)) break;
          if (++it > 2000000) __trap();
          y[0] = ld_poll(cp); y[1] = ld_poll(cp + 256); y[2] = ld_poll(cp + 16384); y[3] = ld_poll(cp + 16384 + 256);
        }
        uint32_t p[8];
        const float isl = isc * 0.5f, bias = -(float)(need >> 3) * isl;
#pragma unroll
        for (int k = 0; k < 4; k++) {
          p[2 * k] = pack2(fmaf((float)(int)__funnelshift_r(y[k].x, y[k].y, 3), isl, bias), fmaf((float)(int)__funnelshift_r(y[k].z, y[k].w, 3), isl, bias));
          p[2 * k + 1] = pack2((float)(int)y[k].y * isc, (float)(int)y[k].w * isc);
        }
        TS(19 + w);
        forward(p);
      }
    }
    bar_arrive<B_VDONE, 160>();
    bar_arrive<B_XGO1, 256>();
    bar_arrive<B_XGO, 256>();
    pv_x(NSEG - 1);
    if (EVF) { const uint64_t pol = policy_evict_first(); stg4h(op, oq0, pol); stg4h(op + 512, oq1, pol); } else { stg4(op, oq0); stg4(op + 512, oq1); }
    bar_sync<B_WG2, 128>();
    if (tid == 256) { red_release(flags + FL_A + (e0 >> 10) * 8 + (NSEG - 1) * 48, 1); }
    __syncwarp();
  }
  asm volatile("barrier.cluster.arrive.relaxed.aligned;\nbarrier.cluster.wait.aligned;" ::: "memory");
  GT(layer * 4 + 1, 2);
  if (wid == 0) asm volatile("griddepcontrol.wait;" ::: "memory");
}

constexpr int P_B = 0, P_A = 131072, P_BAR = 196608, OPC_SMEM = P_BAR + 256;
#define PF_C 2
#define PF_S0 43
constexpr int OP_KR = 48;

__global__ void __launch_bounds__(384, 1)
opc_kernel(const __grid_constant__ CUtensorMap tmo, bf16* __restrict__ out, int layer,
           const bf16* __restrict__ Wq, const bf16* __restrict__ Wk, const bf16* __restrict__ Wv, const bf16* __restrict__ Wo) {
  extern __shared__ __align__(1024) uint8_t smem[];
  asm volatile("griddepcontrol.launch_dependents;");
  GT(layer * 4 + 2, 0);
  const uint32_t sb = smem_u32(smem);
  check_smem_base(sb);
  const int tid = threadIdx.x, wid = __shfl_sync(~0u, tid >> 5, 0), wg = wid >> 2, w = wid & 3, lane = tid & 31;
  const uint32_t bar = sb + P_BAR;
  uint32_t* flags = g_zero + Z_FLAGS + layer * FL_LAYER;
  float* acc = g_acc + layer * (S_TOK * DM);
  const uint64_t pol = policy_evict_first();
  if (wid == 0) {
    if (lane < 16) mbar_init(bar + 8 * lane, (lane == 8 || lane == 9) ? 8 : 1);
    fence_async();
  }
  __syncthreads();
  if (blockIdx.x < 30) {
    const int cg = blockIdx.x % 5, kg = blockIdx.x / 5;
    if (wg < 2) {
      asm volatile("setmaxnreg.inc.sync.aligned.u32 240;");
      uint32_t a[OP_KR][4];
      const uint32_t la = sb + P_B + ((lane >> 4) * 8 + (lane & 7)) * 128 + (((2 * w + ((lane >> 3) & 1)) ^ (lane & 7)) << 4);
      mbar_wait(bar + 80, 0);
#pragma unroll
      for (int k = 0; k < 32; k++) ldsm4t(a[k], la + wg * 65536 + k * 2048);
      bar_arrive<2, 288>();
      mbar_wait(bar + 88, 0);
#pragma unroll
      for (int k = 0; k < 16; k++) ldsm4t(a[32 + k], la + wg * 32768 + k * 2048);
      bar_arrive<3, 288>();
      mbar_wait(bar + 96, 0);
      float* ap = acc + (cg * 8 + wg * 4 + w) * 512 + lane * 4;
      for (int s = 0; s < NSEG; s++) {
        const int buf = s & 1;
        const uint32_t par = (s >> 1) & 1;
        float d[16];
        const uint64_t db = mkdesc(SB0 + P_B + buf * 65536, 512, 128, 0), da = mkdesc(SB0 + P_A + wg * 32768, 1024, 1024, 1);
        float* p = ap + s * (32 * DM);
        if (kg < 4 && s + 2 < NSEG) { if (EVF) stg4h(p + 2 * 32 * DM + kg * 128, make_uint4(0, 0, 0, 0), pol); else stg4(p + 2 * 32 * DM + kg * 128, make_uint4(0, 0, 0, 0)); }
#pragma unroll
        for (int q = 0; q < 4; q++) {
          mbar_wait(bar + 8 * (buf * 4 + q), par);
          wg_fence();
#pragma unroll
          for (int k = 16 * q; k < 16 * q + 16; k++) {
            if (k < OP_KR) wg_rs_n32_tb1(d, a[k < OP_KR ? k : 0], db + k * 64, k);
            else wg_ss_n32_ta1_tb1(d, da + (k - OP_KR) * 128, db + k * 64, 1);
          }
        }
        wg_commit();
        wg_wait<0>();
        pin<16>(d);
        if (lane == 0) mbar_arrive(bar + 8 * (8 + buf));
        if (s == NSEG - 1) GT(layer * 4 + 2, 6);
        if (EVF) {
          red4fh(p, d[0], d[1], d[4], d[5], pol);
          red4fh(p + 128, d[8], d[9], d[12], d[13], pol);
          red4fh(p + 256, d[2], d[3], d[6], d[7], pol);
          red4fh(p + 384, d[10], d[11], d[14], d[15], pol);
        } else {
          red4f(p, d[0], d[1], d[4], d[5]);
          red4f(p + 128, d[8], d[9], d[12], d[13]);
          red4f(p + 256, d[2], d[3], d[6], d[7]);
          red4f(p + 384, d[10], d[11], d[14], d[15]);
        }
        bar_sync<1, 256>();
        if (tid == 0) { red_release(flags + FL_B + s * 8, 1); }
        __syncwarp();
      }
    } else {
      asm volatile("setmaxnreg.dec.sync.aligned.u32 24;");
      if (w == 0) {
        if (lane == 0) { mbar_expect(bar + 80, 131072); mbar_expect(bar + 96, 65536); mbar_expect(bar + 88, 65536); }
        __syncwarp();
        if (lane < 16) tma2d(sb + P_B + lane * 8192, &tmo, cg * 128 + (lane >> 3) * 64, kg * 1024 + (lane & 7) * 64, bar + 80);
        else if (lane < 24) tma2d(sb + P_B + lane * 8192, &tmo, cg * 128 + ((lane >> 2) & 1) * 64, kg * 1024 + 768 + (lane & 3) * 64, bar + 96);
        bar_sync<2, 288>();
        fence_async();
        if (lane < 8) tma2d(sb + P_B + lane * 8192, &tmo, cg * 128 + (lane >> 2) * 64, kg * 1024 + 512 + (lane & 3) * 64, bar + 88);
        bar_sync<3, 288>();
        for (int s = 0; s < NSEG; s++) {
          const int buf = s & 1;
          if (s >= 2) mbar_wait(bar + 8 * (8 + buf), ((s >> 1) & 1) ^ 1);
          if (s >= 2) wait_flag(flags + FL_B + (s - 2) * 8, 30);
          wait_flag(flags + FL_A + s * 48 + kg * 8, 16);
          fence_async_global();
          if (lane < 4) {
            mbar_expect(bar + 8 * (buf * 4 + lane), 16384);
            if (EVF) bulk_g2sh(sb + P_B + buf * 65536 + lane * 16384, g_ot + (size_t)s * (HE * 64) + kg * 65536 + lane * 16384, 16384, bar + 8 * (buf * 4 + lane), pol);
            else bulk_g2s(sb + P_B + buf * 65536 + lane * 16384, g_ot + (size_t)s * (HE * 64) + kg * 65536 + lane * 16384, 16384, bar + 8 * (buf * 4 + lane));
            if (s == NSEG - 1 && lane == 0) GTT(layer * 4 + 2, 5);
          }
          __syncwarp();
        }
      } else if (w == 1 && layer == 0) {
#pragma unroll 1
        for (int q = 4 * (4 - PF_C); q < 18; q++) {
          wait_flag(flags + FL_A + (PF_S0 + q) * 48 + kg * 8, 16);
          const int m = q >> 2;
          const uint8_t* W = m == 0 ? (const uint8_t*)Wo : m == 1 ? (const uint8_t*)Wv : m == 2 ? (const uint8_t*)Wk : m == 3 ? (const uint8_t*)Wq : (q & 1) ? g_w2 : g_w1;
          const int n = m < 4 ? 512 : (q & 1) ? 214 : 640, l0 = m < 4 ? blockIdx.x * 2048 + (q & 3) * 512 : blockIdx.x * n, lim = m < 4 ? 61440 : (q & 1) ? 6400 : 19200;
#pragma unroll 1
          for (int k = lane; k < n; k += 32) {
            if (l0 + k < lim) asm volatile("prefetch.global.L2 [%0];" :: "l"(W + (size_t)(l0 + k) * 128));
            __nanosleep(100);
          }
        }
      }
    }
  } else {
    constexpr int LD = 644;
    float* xs = (float*)smem;
    uint32_t par = 0;
    for (int task = blockIdx.x - 30; task < 2 * NSEG; task += 6, par ^= 1) {
      const int s = task >> 1, jj = task & 1;
      if (tid == 0) {
        mbar_expect(bar, 20480);
        bulk_g2s(sb + 49152, g_x + task * 16 * DM, 20480, bar);
      }
      if (wid == 1) { wait_flag(flags + FL_B + s * 8, 30); if (s == NSEG - 1 && lane == 0) GTT(layer * 4 + 2, 7); }
      __syncthreads();
      if (wid < 10) {
        float4 v[8];
#pragma unroll
        for (int k = 0; k < 8; k++) v[k] = EVF ? ldg4fh(acc + s * (32 * DM) + (wid * 8 + k) * 256 + jj * 128 + lane * 4, pol) : __ldcg((const float4*)(acc + s * (32 * DM) + (wid * 8 + k) * 256 + jj * 128 + lane * 4));
        float* xp = xs + (lane & 3) * 2 * LD + wid * 64 + (lane >> 2);
#pragma unroll
        for (int k = 0; k < 8; k++) { xp[k * 8] = v[k].x; xp[LD + k * 8] = v[k].y; xp[8 * LD + k * 8] = v[k].z; xp[9 * LD + k * 8] = v[k].w; }
      }
      mbar_wait(bar, par);
      __syncthreads();
#pragma unroll 1
      for (int row = wid; row < 16; row += 12) {
        const int tk = task * 16 + row;
        float v[20], sum = 0.f;
        const int pj = (lane & 24) + 2 * (lane & 3) + ((lane >> 2) & 1);
        bf16* dst = out ? out + tk * DM + lane * 2 : g_x + tk * DM + pj * 2;
#pragma unroll
        for (int k = 0; k < 10; k++) {
          const float2 u = *(const float2*)(xs + row * LD + k * 64 + lane * 2);
          const uint32_t r = *(const uint32_t*)(smem + 49152 + row * 1280 + k * 128 + pj * 4);
          v[2 * k] = u.x + bflo(r); v[2 * k + 1] = u.y + bfhi(r); sum += v[2 * k] + v[2 * k + 1];
          *(uint32_t*)(dst + k * 64) = pack2(v[2 * k], v[2 * k + 1]);
        }
        if (!out) {
#pragma unroll
          for (int o = 16; o; o >>= 1) sum += __shfl_xor_sync(~0u, sum, o);
          const float m = sum * (1.f / DM);
          float q = 0.f;
#pragma unroll
          for (int k = 0; k < 20; k++) { v[k] -= m; q += v[k] * v[k]; }
#pragma unroll
          for (int o = 16; o; o >>= 1) q += __shfl_xor_sync(~0u, q, o);
          const float rs = rsqrtf(q * (1.f / DM) + 1e-5f);
          uint8_t* xp = g_xt + (tk >> 7) * 163840 + (tk & 127) * 128 + (((lane >> 2) ^ (tk & 7)) << 4) + (lane & 3) * 4;
#pragma unroll
          for (int k = 0; k < 10; k++) *(uint32_t*)(xp + k * 16384) = pack2(v[2 * k] * rs, v[2 * k + 1] * rs);
        }
      }
      fence_async();
      __syncthreads();
      if (tid == 0 && !out) { red_release(flags + FL_LAYER + FL_T + (task >> 3) * 8, 1); }
    }
  }
  GT(layer * 4 + 2, 1);
  __syncwarp();
  asm volatile("griddepcontrol.wait;" ::: "memory");
  GT(layer * 4 + 2, 2);
}

constexpr int L_STAGE = 47104;
constexpr int L_KV = 0, L_B2 = 43008;
constexpr int L_W2 = 122880, L_BAR = L_W2 + 102400;
constexpr int LA_SMEM = L_BAR + 256;
__device__ __forceinline__ float phi(float t) { return (fmaxf(t, 0.f) + 1e-6f) + ex2(fminf(t * 1.4426950408889634f, 0.f)); }
__device__ __forceinline__ uint32_t phi2(float a, float b) { return pack2(phi(a), phi(b)); }
#define LA_LATE 6
#define PF_N0 2
#define PF_N1 0
#define PF_SLEEP 300

__global__ void __launch_bounds__(384, 1)
la_kernel(const bf16* __restrict__ xin, const bf16* __restrict__ Wq, const bf16* __restrict__ Wk, const bf16* __restrict__ Wv,
          const bf16* __restrict__ Wo, uint8_t* __restrict__ ar, int layer) {
  extern __shared__ __align__(1024) uint8_t smem[];
  const uint32_t sb = smem_u32(smem);
  check_smem_base(sb);
  const int tid = threadIdx.x, wid = __shfl_sync(~0u, tid >> 5, 0), wg = wid >> 2, w = wid & 3, lane = tid & 31, g = lane >> 2, i4 = lane & 3;
  const int cr = blockIdx.x & 1, hg = (blockIdx.x >> 1) & 7, tb = (blockIdx.x >> 4) * 2 + cr;
  const uint32_t bar = sb + L_BAR;
  uint32_t* flags = g_zero + Z_FLAGS + layer * FL_LAYER;
  asm volatile("griddepcontrol.launch_dependents;");
  GT(layer * 4, 0);
  if (wid == 0) {
    if (lane < 20) mbar_init(bar + 8 * lane, (lane >= 4 && lane < 8) ? (blockIdx.x < 128 ? 16 : 8) : lane >= 17 ? 8 : 1);
    asm volatile("fence.mbarrier_init.release.cluster;" ::: "memory");
    fence_async();
  }
  if (blockIdx.x >= 128) {
    __syncthreads();
    const int q = blockIdx.x - 128;
    const uint8_t* src = (const uint8_t*)Wo + q * 1966080;
    if (wid == 11) {
#pragma unroll 1
      for (int it = 0; it < 48; it++) {
        const int st = it & 3;
        if (it >= 4) mbar_wait(bar + 8 * (4 + st), ((it >> 2) & 1) ^ 1);
        if (lane == 0) mbar_expect(bar + 8 * st, 40960);
        __syncwarp();
        if (lane < 4) bulk_g2s(sb + st * 40960 + lane * 10240, src + it * 40960 + lane * 10240, 10240, bar + 8 * st);
      }
    } else if (wid < 8) {
      float c[20];
#pragma unroll
      for (int k = 0; k < 20; k++) c[k] = 0.f;
#pragma unroll 1
      for (int it = 0; it < 48; it++) {
        const int st = it & 3;
        mbar_wait(bar + 8 * st, (it >> 2) & 1);
#pragma unroll
        for (int k = 0; k < 20; k++) {
          const float2 u = lds2f(sb + st * 40960 + wid * 5120 + k * 256 + lane * 8);
          const uint32_t x = __float_as_uint(u.x), y = __float_as_uint(u.y);
          float* d = c + (k % 5) * 4;
          d[0] = fmaf(bflo(x), bflo(x), d[0]); d[1] = fmaf(bfhi(x), bfhi(x), d[1]); d[2] = fmaf(bflo(y), bflo(y), d[2]); d[3] = fmaf(bfhi(y), bfhi(y), d[3]);
        }
        __syncwarp();
        if (lane == 0) mbar_arrive(bar + 8 * (4 + st));
      }
      float* red = (float*)(smem + 163840);
#pragma unroll
      for (int k = 0; k < 5; k++) *(float4*)(red + wid * DM + k * 128 + lane * 4) = make_float4(c[4 * k], c[4 * k + 1], c[4 * k + 2], c[4 * k + 3]);
      bar_sync<1, 256>();
      for (int k = tid; k < DM; k += 256) {
        float t = 0.f;
#pragma unroll
        for (int j = 0; j < 8; j++) t += red[j * DM + k];
        g_nrm[q * DM + k] = t;
      }
      asm volatile("griddepcontrol.wait;" ::: "memory");
      bar_sync<1, 256>();
      if (tid == 0) red_release(flags + FL_N, 1);
      GT(0, 2);
    }
    return;
  }
  __syncthreads();
  asm volatile("barrier.cluster.arrive.relaxed.aligned;" ::: "memory");
  if (layer == 0) asm volatile("griddepcontrol.wait;" ::: "memory");
  asm volatile("barrier.cluster.wait.aligned;" ::: "memory");
  if (wg == 2) {
    asm volatile("setmaxnreg.dec.sync.aligned.u32 40;");
    if (w == 0) {
      if (lane < 4) {
        mbar_expect(bar + 8 * lane, L_STAGE);
        bulk_g2s_mc(sb + lane * L_STAGE + 16384 + cr * 15360, g_w1 + (hg * 10 + lane) * 30720 + cr * 15360, 15360, bar + 8 * lane);
      }
      if (layer == 1) { if (LA_LATE) wait_flag(flags + FL_T + 15 * 8, LA_LATE); wait_flag(flags + FL_T + tb * 8, 8); fence_async_global(); }
      if (lane < 4) bulk_g2s(sb + lane * L_STAGE, g_xt + (tb * 10 + lane) * 16384, 16384, bar + 8 * lane);
#pragma unroll 1
      for (int kc = 4; kc < 10; kc++) {
        const int st = kc & 3;
        mbar_wait(bar + 8 * (4 + st), ((kc >> 2) & 1) ^ 1);
        if (lane == 0) {
          mbar_expect(bar + 8 * st, L_STAGE);
          bulk_g2s_mc(sb + st * L_STAGE + 16384 + cr * 15360, g_w1 + (hg * 10 + kc) * 30720 + cr * 15360, 15360, bar + 8 * st);
          bulk_g2s(sb + st * L_STAGE, g_xt + (tb * 10 + kc) * 16384, 16384, bar + 8 * st);
        }
        __syncwarp();
      }
      mbar_wait(bar + 8 * 6, 1);
      mbar_wait(bar + 8 * 7, 1);
      if (lane == 0) mbar_expect(bar + 64, 102400);
      if (lane < 8) mbar_expect(bar + 8 * (9 + lane), 20480);
      __syncwarp();
      if (lane < 2) bulk_g2s_mc(sb + L_W2 + (cr * 2 + lane) * 25600, g_w2 + hg * 102400 + (cr * 2 + lane) * 25600, 25600, bar + 64);
      bar_sync<2, 288>();
      if (lane == 0) { red_release(flags + FL_O + tb * 8, 1); }
      wait_flag(flags + FL_O + tb * 8, 8);
      fence_async_global();
      if (lane < 6) bulk_g2s(sb + lane * 20480, g_oa + (tb * 8 + lane) * 20480, 20480, bar + 8 * (9 + lane));
#pragma unroll 1
      for (int p = 6; p < 8; p++) {
        mbar_wait(bar + 8 * (17 + p - 6), 0);
        if (lane == 0) bulk_g2s(sb + (p - 6) * 20480, g_oa + (tb * 8 + p) * 20480, 20480, bar + 8 * (9 + p));
      }
    } else {
      const int t = tid - 288;
#pragma unroll 1
      for (int k = t; k < 768; k += 96) *(uint4*)(ar + blockIdx.x * 12288 + k * 16) = make_uint4(0, 0, 0, 0);
      if (layer == 0) {
        float sv = 0.f;
        const uint4* pv = (const uint4*)((const uint8_t*)Wv + blockIdx.x * 61440) + t;
#pragma unroll 1
        for (int k = 0; k < 40; k += 5) {
          uint4 v[5];
#pragma unroll
          for (int j = 0; j < 5; j++) v[j] = __ldg(pv + (k + j) * 96);
#pragma unroll
          for (int j = 0; j < 5; j++) {
            sv = fmaf(bflo(v[j].x), bflo(v[j].x), fmaf(bfhi(v[j].x), bfhi(v[j].x), fmaf(bflo(v[j].y), bflo(v[j].y), fmaf(bfhi(v[j].y), bfhi(v[j].y), sv))));
            sv = fmaf(bflo(v[j].z), bflo(v[j].z), fmaf(bfhi(v[j].z), bfhi(v[j].z), fmaf(bflo(v[j].w), bflo(v[j].w), fmaf(bfhi(v[j].w), bfhi(v[j].w), sv))));
          }
        }
#pragma unroll
        for (int o = 16; o; o >>= 1) sv += __shfl_xor_sync(~0u, sv, o);
        if (lane == 0) atomicAdd((float*)(g_zero + Z_NORM), sv);
      }
#pragma unroll 1
      for (int k = 0; k < 5 * (layer ? PF_N1 : PF_N0); k++) {
        const int m = k / 5;
        const bf16* W = m == 0 ? Wq : m == 1 ? Wk : m == 2 ? Wv : Wo;
        asm volatile("prefetch.global.L2 [%0];" :: "l"((const uint8_t*)W + blockIdx.x * 61440 + (k - m * 5) * 12288 + t * 128));
        __nanosleep(PF_SLEEP);
      }
      if (t == 0) GTT(layer * 4, 14);
      bar_arrive<3, 352>();
    }
  } else {
    asm volatile("setmaxnreg.inc.sync.aligned.u32 232;");
    GT(layer * 4, 4);
    uint32_t pq[5][4];
    const int row0 = tb * 128 + wg * 64 + 16 * w + g;
    float* kv = (float*)(g_zero + Z_KV) + layer * KV_LAYER + hg * 1920;
    if (layer == 1) wait_flag(flags + FL_T + tb * 8, 8);
    uint32_t r[20];
    if (xin) {
      const bf16* xp = xin + row0 * DM + hg * 80 + 2 * i4;
#pragma unroll
      for (int j = 0; j < 10; j++) { r[2 * j] = __ldg((const uint32_t*)(xp + 8 * j)); r[2 * j + 1] = __ldg((const uint32_t*)(xp + 8 * DM + 8 * j)); }
    } else {
      const bf16* xp = g_x + row0 * DM + hg * 80 + 4 * i4;
#pragma unroll
      for (int j = 0; j < 5; j++) {
        const uint2 u = __ldcg((const uint2*)(xp + 16 * j)), v = __ldcg((const uint2*)(xp + 8 * DM + 16 * j));
        r[4 * j] = u.x; r[4 * j + 2] = u.y; r[4 * j + 1] = v.x; r[4 * j + 3] = v.y;
      }
    }
    {
      float d[120];
#pragma unroll 1
      for (int kc = 0; kc < 10; kc++) {
        const int st = kc & 3;
        const uint64_t da = mkdesc(SB0 + st * L_STAGE + wg * 8192, 16, 1024, 1), db = mkdesc(SB0 + st * L_STAGE + 16384, 3840, 128, 0);
        mbar_wait(bar + 8 * st, (kc >> 2) & 1);
        wg_fence();
#pragma unroll
        for (int k = 0; k < 4; k++) wg_ss_n240_ta0_tb1(d, da + 2 * k, db + k * 480, kc | k);
        wg_commit();
        if (kc > 0) { wg_wait<1>(); if (lane < 2) mbar_arrive_cl(mapa(bar + 8 * (4 + ((kc - 1) & 3)), lane)); }
      }
      wg_wait<0>();
      pin<120>(d);
      GT(layer * 4, 5);
      bar_sync<1, 256>();
      const uint32_t kb = sb + L_KV + (wg * 8 + 2 * w + ((lane >> 3) & 1)) * 2688 + (lane >> 4) * 128 + (lane & 7) * 16;
#pragma unroll
      for (int j = 0; j < 5; j++) stsm4(kb + 1280 + j * 256, pack2(d[80 + 8 * j], d[81 + 8 * j]), pack2(d[82 + 8 * j], d[83 + 8 * j]), pack2(d[84 + 8 * j], d[85 + 8 * j]), pack2(d[86 + 8 * j], d[87 + 8 * j]));
      stsm2(kb + 2560, 0x3F803F80u, 0x3F803F80u);
#pragma unroll
      for (int j = 0; j < 5; j++) stsm4(kb + j * 256, phi2(d[40 + 8 * j], d[41 + 8 * j]), phi2(d[42 + 8 * j], d[43 + 8 * j]), phi2(d[44 + 8 * j], d[45 + 8 * j]), phi2(d[46 + 8 * j], d[47 + 8 * j]));
      fence_async();
      bar_sync<1, 256>();
      float e[44];
      {
        const uint64_t da = mkdesc(SB0 + L_KV + wg * 1024, 2688, 128, 0), db = mkdesc(SB0 + L_KV + 1280, 2688, 128, 0);
        wg_fence();
#pragma unroll
        for (int k = 0; k < 8; k++) wg_ss_n88_ta1_tb1(e, da + k * 336, db + k * 336, k);
        wg_commit();
        wg_wait<0>();
        pin<44>(e);
      }
#pragma unroll
      for (int h = 0; h < 2; h++) {
        const int row = wg * 64 + 16 * w + 8 * h + g;
        const int c = row < 80 ? 2 * i4 - (row / 20) * 20 : 100;
        float* dst = kv + row * 24 + c;
#pragma unroll
        for (int j = 0; j < 10; j++)
          asm volatile("{\n.reg .pred p;\nsetp.lt.u32 p, %3, 20;\n@p red.relaxed.gpu.global.add.v2.f32 [%0], {%1,%2};\n}" :: "l"(dst + 8 * j), "f"(e[4 * j + 2 * h]), "f"(e[4 * j + 2 * h + 1]), "r"(c + 8 * j) : "memory");
        asm volatile("{\n.reg .pred p;\nsetp.ne.u32 p, %2, 0;\n@p red.relaxed.gpu.global.add.f32 [%0], %1;\n}" :: "l"(kv + row * 24 + 20), "f"(e[40 + 2 * h]), "r"((int)(row < 80 && i4 == 0)) : "memory");
      }
      bar_sync<1, 256>();
      GT(layer * 4, 6);
      if (tid == 0) { red_release(flags + FL_KV + hg * 8, 1); }
      __syncwarp();
      pin<40>(d);
#pragma unroll
      for (int k = 0; k < 5; k++) {
        pq[k][0] = phi2(d[8 * k], d[8 * k + 1]); pq[k][1] = phi2(d[8 * k + 2], d[8 * k + 3]);
        pq[k][2] = phi2(d[8 * k + 4], d[8 * k + 5]); pq[k][3] = phi2(d[8 * k + 6], d[8 * k + 7]);
      }
    }
#pragma unroll 1
    for (int k = tid; k < 1600; k += 256) sts4(sb + L_B2 + k * 16, 0, 0, 0, 0);
    GT(layer * 4, 7);
    if (wid == 0) wait_flag(flags + FL_KV + hg * 8, 16);
    GT(layer * 4, 8);
    bar_sync<1, 256>();
    if (tid < 240) {
      const int dd = tid / 3, part = tid - dd * 3, n = (dd / 20) * 20 + 8 * part;
      const float4 v0 = __ldcg((const float4*)(kv + dd * 24 + 8 * part)), v1 = __ldcg((const float4*)(kv + dd * 24 + 8 * part + 4));
      const float z = __ldcg(kv + dd * 24 + 20);
      const uint32_t a = sb + L_B2 + (dd >> 3) * 2560 + (dd & 7) * 16, zz = pack2(z, z);
      const uint32_t a0 = a + (n >> 3) * 128 + (n & 7) * 2, a1 = a + ((n + 4) >> 3) * 128 + ((n + 4) & 7) * 2;
      sts2(a0, pack2(v0.x, v0.y), pack2(v0.z, v0.w)); sts2(a0 + 1280, zz, zz);
      if (part < 2) { sts2(a1, pack2(v1.x, v1.y), pack2(v1.z, v1.w)); sts2(a1 + 1280, zz, zz); }
    }
    fence_async();
    bar_sync<1, 256>();
    {
      float o[80];
      const uint64_t db = mkdesc(SB0 + L_B2, 2560, 128, 0);
      wg_fence();
#pragma unroll
      for (int k = 0; k < 5; k++) wg_rs_n160_tb1(o, pq[k], db + k * 320, k);
      wg_commit();
      wg_wait<0>();
      pin<80>(o);
      uint8_t* op = g_oa + (tb * 8 + hg) * 20480 + (wg * 8 + 2 * w) * 128 + lane * 4;
#pragma unroll
      for (int j = 0; j < 20; j++) {
        const float inv = rcp(o[40 + 2 * j] + 1e-6f);
        *(uint32_t*)(op + (j >> 1) * 2048 + (j & 1) * 128) = pack2(o[2 * j] * inv, o[2 * j + 1] * inv);
      }
      GT(layer * 4, 9);
      bar_arrive<2, 288>();
    }
    float d[40];
    mbar_wait(bar + 64, 0);
#pragma unroll 1
    for (int p = 0; p < 8; p++) {
      const uint64_t da = mkdesc(SB0 + (p < 6 ? p : p - 6) * 20480 + wg * 1024, 2048, 128, 0), db = mkdesc(SB0 + L_W2 + p * 12800, 1280, 128, 0);
      mbar_wait(bar + 8 * (9 + p), 0);
      if (p == 0) GT(layer * 4, 11);
      wg_fence();
#pragma unroll
      for (int k = 0; k < 5; k++) wg_ss_n80_ta0_tb1(d, da + k * 256, db + k * 160, p | k);
      wg_commit();
      wg_wait<1>();
      if (lane == 0 && (p == 1 || p == 2)) mbar_arrive(bar + 8 * (17 + p - 1));
    }
    wg_wait<0>();
    pin<40>(d);
    GT(layer * 4, 12);
    float mean[2], m2[2];
#pragma unroll
    for (int h = 0; h < 2; h++) {
      float sum = 0.f;
#pragma unroll
      for (int j = 0; j < 10; j++) { d[4 * j + 2 * h] += bflo(r[2 * j + h]); d[4 * j + 2 * h + 1] += bfhi(r[2 * j + h]); sum += d[4 * j + 2 * h] + d[4 * j + 2 * h + 1]; }
      sum += __shfl_xor_sync(~0u, sum, 1); sum += __shfl_xor_sync(~0u, sum, 2);
      mean[h] = sum * (1.f / 80.f);
      float q = 0.f;
#pragma unroll
      for (int j = 0; j < 10; j++) { const float a = d[4 * j + 2 * h] - mean[h], b = d[4 * j + 2 * h + 1] - mean[h]; q = fmaf(a, a, fmaf(b, b, q)); }
      q += __shfl_xor_sync(~0u, q, 1); q += __shfl_xor_sync(~0u, q, 2);
      m2[h] = q;
    }
    float2* st = g_stats + (layer * S_TOK + row0) * 8;
    if (i4 < 2) {
      const float a = i4 ? mean[1] : mean[0], b = i4 ? m2[1] : m2[0];
      asm volatile("{\n.reg .b64 t;\nmov.b64 t, {%1,%2};\nst.relaxed.gpu.global.b64 [%0], t;\n}" :: "l"(st + i4 * 64 + hg), "r"(__float_as_uint(a)), "r"(__float_as_uint(b) & 0x7FFFFFFFu) : "memory");
    }
    uint4 y0, y1;
    int it = 0;
    while (true) {
      y0 = ld_poll(st + 2 * i4); y1 = ld_poll(st + 64 + 2 * i4);
      if (!__any_sync(~0u, (int)(y0.y | y0.w | y1.y | y1.w) < 0)) break;
      if (++it > 2000000) __trap();
    }
    GT(layer * 4, 13);
#pragma unroll
    for (int h = 0; h < 2; h++) {
      const uint4 y = h ? y1 : y0;
      const float ma = __uint_as_float(y.x), mb = __uint_as_float(y.z);
      float sm = ma + mb;
      sm += __shfl_xor_sync(~0u, sm, 1); sm += __shfl_xor_sync(~0u, sm, 2);
      const float mu = sm * 0.125f;
      float q = __uint_as_float(y.y) + __uint_as_float(y.w) + 80.f * ((ma - mu) * (ma - mu) + (mb - mu) * (mb - mu));
      q += __shfl_xor_sync(~0u, q, 1); q += __shfl_xor_sync(~0u, q, 2);
      const float rs = rsqrtf(q * (1.f / DM) + 1e-5f), sh = -mu * rs;
      const int tk = row0 + 8 * h;
      uint8_t* xp = g_xn + (tk >> 5) * 40960 + (tk & 31) * 128 + (i4 & 1) * 8;
#pragma unroll
      for (int jj = 0; jj < 5; jj++) {
        const int b16 = hg * 5 + jj;
        const float* a = d + 8 * jj + 2 * h;
        *(uint2*)(xp + (b16 >> 2) * 4096 + (((2 * (b16 & 3) + (i4 >> 1)) ^ g) << 4)) =
            make_uint2(pack2(fmaf(a[0], rs, sh), fmaf(a[1], rs, sh)), pack2(fmaf(a[4], rs, sh), fmaf(a[5], rs, sh)));
      }
    }
    {
      bf16* xp = g_x + row0 * DM + hg * 80 + 4 * i4;
#pragma unroll
      for (int j = 0; j < 5; j++) {
        *(uint2*)(xp + 16 * j) = make_uint2(pack2(d[8 * j], d[8 * j + 1]), pack2(d[8 * j + 4], d[8 * j + 5]));
        *(uint2*)(xp + 8 * DM + 16 * j) = make_uint2(pack2(d[8 * j + 2], d[8 * j + 3]), pack2(d[8 * j + 6], d[8 * j + 7]));
      }
    }
    bar_sync<3, 352>();
    if (tid == 0) { red_release(flags + FL_X, 1); }
    GT(layer * 4, 2);
    if (wid == 7) asm volatile("griddepcontrol.wait;" ::: "memory");
  }
}

__global__ void __launch_bounds__(256) prep_kernel(const bf16* __restrict__ x, const bf16* __restrict__ wqkv, const bf16* __restrict__ wo) {
  asm volatile("griddepcontrol.launch_dependents;");
  const int b = blockIdx.x, tid = threadIdx.x, lane = tid & 31;
  if (b < 160) GT(3, 0);
  if (b < 256) {
    const int row = b * 8 + (tid >> 5);
    float v[20], s = 0.f;
#pragma unroll
    for (int k = 0; k < 10; k++) { const uint32_t u = __ldg((const uint32_t*)(x + row * DM + k * 64 + lane * 2)); v[2 * k] = bflo(u); v[2 * k + 1] = bfhi(u); s += v[2 * k] + v[2 * k + 1]; }
#pragma unroll
    for (int o = 16; o; o >>= 1) s += __shfl_xor_sync(~0u, s, o);
    const float m = s * (1.f / DM);
    float q = 0.f;
#pragma unroll
    for (int k = 0; k < 20; k++) { v[k] -= m; q += v[k] * v[k]; }
#pragma unroll
    for (int o = 16; o; o >>= 1) q += __shfl_xor_sync(~0u, q, o);
    const float r = rsqrtf(q * (1.f / DM) + 1e-5f);
#pragma unroll
    for (int k = 0; k < 10; k++)
      *(uint32_t*)(g_xt + ((row >> 7) * 10 + k) * 16384 + (row & 127) * 128 + (((lane >> 2) ^ (row & 7)) << 4) + (lane & 3) * 4) = pack2(v[2 * k] * r, v[2 * k + 1] * r);
  } else if (b < 256 + 200) {
#pragma unroll
    for (int it = 0; it < 4; it++) {
      const int u = (b - 256) * 1024 + it * 256 + tid;
      if (u < 153600) {
        const int k8 = u & 7, nb = (u >> 3) % 30, kg = (u / 240) % 80, hg = u / 19200;
        *(uint4*)(g_w1 + u * 16) = __ldg((const uint4*)(wqkv + (kg * 8 + k8) * 1920 + (nb / 10) * 640 + hg * 80 + (nb % 10) * 8));
      } else {
        const int v = u - 153600, k8 = v & 7, nb = (v >> 3) % 10, kg = (v / 80) % 80, hg = v / 6400;
        *(uint4*)(g_w2 + v * 16) = __ldg((const uint4*)(wo + (kg * 8 + k8) * DM + hg * 80 + nb * 8));
      }
    }
  } else {
    const int t = (b - 456) * 256 + tid;
    for (int k = t; k < Z_END / 4; k += 16 * 256) ((uint4*)g_zero)[k] = make_uint4(0, 0, 0, 0);
    for (int k = t; k < 2 * S_TOK * 4; k += 16 * 256) ((uint4*)g_stats)[k] = make_uint4(~0u, ~0u, ~0u, ~0u);
    for (int k = t; k < 16 * DM; k += 16 * 256) { ((uint4*)g_acc)[k] = make_uint4(0, 0, 0, 0); ((uint4*)(g_acc + S_TOK * DM))[k] = make_uint4(0, 0, 0, 0); }
  }
  if (b < 160) GT(3, 2);
}

typedef CUresult (*EncodeFn)(CUtensorMap*, CUtensorMapDataType, cuuint32_t, void*, const cuuint64_t*, const cuuint64_t*, const cuuint32_t*,
                             const cuuint32_t*, CUtensorMapInterleave, CUtensorMapSwizzle, CUtensorMapL2promotion, CUtensorMapFloatOOBfill);
static void make_map(EncodeFn fn, CUtensorMap* m, const void* p, uint64_t cols, uint64_t rows, uint32_t bc, uint32_t br) {
  cuuint64_t dims[2] = {cols, rows}; cuuint64_t strides[1] = {cols * 2}; cuuint32_t box[2] = {bc, br}; cuuint32_t es[2] = {1, 1};
  fn(m, CU_TENSOR_MAP_DATA_TYPE_BFLOAT16, 2, (void*)p, dims, strides, box, es, CU_TENSOR_MAP_INTERLEAVE_NONE, CU_TENSOR_MAP_SWIZZLE_128B,
     CU_TENSOR_MAP_L2_PROMOTION_L2_128B, CU_TENSOR_MAP_FLOAT_OOB_FILL_NONE);
}

static void make_map_perm(EncodeFn fn, CUtensorMap* m, const void* p) {
  cuuint64_t dims[5] = {HE, 2, 2, 4, 40}; const cuuint64_t r = HE * 2; cuuint64_t strides[4] = {r, 8 * r, 2 * r, 16 * r};
  cuuint32_t box[5] = {64, 2, 2, 4, 4}; cuuint32_t es[5] = {1, 1, 1, 1, 1};
  fn(m, CU_TENSOR_MAP_DATA_TYPE_BFLOAT16, 5, (void*)p, dims, strides, box, es, CU_TENSOR_MAP_INTERLEAVE_NONE, CU_TENSOR_MAP_SWIZZLE_128B,
     CU_TENSOR_MAP_L2_PROMOTION_L2_128B, CU_TENSOR_MAP_FLOAT_OOB_FILL_NONE);
}

#define OPC_PDL 1
#define LA_PDL 1
#define REC_PDL 1
extern "C" void kernel_launch(void* const* d_in, const int* in_sizes, int n_in, void* d_out, int out_size) {
  const bf16* x = (const bf16*)d_in[0];
  const bf16* wqkv = (const bf16*)d_in[1];
  const bf16* wo_a = (const bf16*)d_in[2];
  const bf16* mem0 = (const bf16*)d_in[4];
  const bf16* Wq = (const bf16*)d_in[5];
  const bf16* Wk = (const bf16*)d_in[6];
  const bf16* Wv = (const bf16*)d_in[7];
  const bf16* Wo = (const bf16*)d_in[8];
  cudaStream_t st = cudaStreamPerThread;

  static EncodeFn enc = nullptr;
  static uint8_t* p_ar; static uint32_t* p_zero;
  if (!enc) {
    cudaDriverEntryPointQueryResult qr;
    void* fn = nullptr;
    cudaGetDriverEntryPoint("cuTensorMapEncodeTiled", &fn, cudaEnableDefault, &qr);
    enc = (EncodeFn)fn;
    cudaFuncSetAttribute(rec_kernel, cudaFuncAttributeMaxDynamicSharedMemorySize, REC_SMEM);
    cudaFuncSetAttribute(opc_kernel, cudaFuncAttributeMaxDynamicSharedMemorySize, OPC_SMEM);
    cudaFuncSetAttribute(la_kernel, cudaFuncAttributeMaxDynamicSharedMemorySize, LA_SMEM);
    cudaGetSymbolAddress((void**)&p_ar, g_ar); p_ar = (uint8_t*)(((uintptr_t)p_ar + 32767) & ~(uintptr_t)32767);
    cudaGetSymbolAddress((void**)&p_zero, g_zero);
  }
  CUtensorMap tmq, tmk, tmv, tmo;
  make_map_perm(enc, &tmq, Wq);
  make_map_perm(enc, &tmk, Wk);
  make_map_perm(enc, &tmv, Wv);
  make_map(enc, &tmo, Wo, DM, HE, 64, 64);

  cudaLaunchAttribute at[2];
  at[0].id = cudaLaunchAttributeProgrammaticStreamSerialization; at[0].val.programmaticStreamSerializationAllowed = 1;
  at[1].id = cudaLaunchAttributeClusterDimension; at[1].val.clusterDim.x = 3; at[1].val.clusterDim.y = 1; at[1].val.clusterDim.z = 1;
  cudaLaunchAttribute at2[2] = {at[1], at[0]};
  at2[0].val.clusterDim.x = 2;
  prep_kernel<<<472, 256, 0, st>>>(x, wqkv, wo_a);
  for (int l = 0; l < 2; l++) {
    cudaLaunchConfig_t cfg = {};
    cfg.blockDim = dim3(384); cfg.stream = st;
    cfg.gridDim = dim3(l == 0 ? 132 : 128); cfg.dynamicSmemBytes = LA_SMEM; cfg.attrs = at2; cfg.numAttrs = 1 + LA_PDL;
    cudaLaunchKernelEx(&cfg, la_kernel, l == 0 ? x : (const bf16*)nullptr, Wq, Wk, Wv, Wo, p_ar + l * AR_LAYER, l);
    cfg.gridDim = dim3(96); cfg.dynamicSmemBytes = REC_SMEM; cfg.attrs = at + 1 - REC_PDL; cfg.numAttrs = 1 + REC_PDL;
    cudaLaunchKernelEx(&cfg, rec_kernel, tmq, tmk, tmv, tmo, mem0, p_ar + l * AR_LAYER, p_zero + Z_FLAGS + l * FL_LAYER, l);
    cfg.gridDim = dim3(36); cfg.dynamicSmemBytes = OPC_SMEM; cfg.attrs = at; cfg.numAttrs = OPC_PDL;
    cudaLaunchKernelEx(&cfg, opc_kernel, tmo, l == 1 ? (bf16*)d_out : (bf16*)nullptr, l, Wq, Wk, Wv, Wo);
  }
}
```

```cpp
#include <cuda_runtime.h>
#include <cuda_bf16.h>
#include <cuda.h>
#include <stdint.h>

typedef __nv_bfloat16 bf16;
typedef unsigned long long u64;

constexpr int S_TOK = 2048, DM = 640, DH = 192, HE = 6144, NSEG = 64;

constexpr int AR_GROUP = 98304;
constexpr int AR_LAYER = 16 * AR_GROUP;
__device__ __align__(1024) uint8_t g_ar[2 * AR_LAYER + 32768];
__device__ __align__(1024) uint8_t g_xn[NSEG * 40960];
__device__ __align__(1024) uint8_t g_xt[S_TOK * DM * 2];
__device__ __align__(1024) uint8_t g_ot[NSEG * HE * 64];
__device__ __align__(1024) uint8_t g_oa[S_TOK * DM * 2];
__device__ __align__(1024) uint8_t g_w1[DM * 1920 * 2];
__device__ __align__(1024) uint8_t g_w2[DM * DM * 2];
__device__ __align__(1024) float g_acc[2 * S_TOK * DM];
__device__ __align__(1024) bf16 g_x[S_TOK * DM];
constexpr int FL_A = 0, FL_B = 64 * 6 * 8, FL_KV = FL_B + 64 * 8, FL_O = FL_KV + 8 * 8, FL_T = FL_O + 16 * 8, FL_X = FL_T + 16 * 8, FL_N = FL_X + 8, FL_LAYER = FL_N + 8;
constexpr int Z_FLAGS = 0, Z_NORM = 2 * FL_LAYER, Z_KV = Z_NORM + 8, KV_LAYER = 8 * 80 * 24, Z_END = Z_KV + 2 * KV_LAYER;
__device__ __align__(128) uint32_t g_zero[Z_END];
__device__ __align__(128) float g_nrm[4 * DM];
__device__ __align__(128) float2 g_stats[2 * S_TOK * 8];
#define GT(slot, k) do {} while (0)
#define GTT(slot, k) do {} while (0)

__device__ __forceinline__ uint32_t smem_u32(const void* p) { return (uint32_t)__cvta_generic_to_shared(p); }
__device__ __forceinline__ uint32_t mapa(uint32_t a, uint32_t r) { uint32_t o; asm("mapa.shared::cluster.u32 %0, %1, %2;" : "=r"(o) : "r"(a), "r"(r)); return o; }
__device__ __forceinline__ void mbar_init(uint32_t bar, uint32_t cnt) { asm volatile("mbarrier.init.shared::cta.b64 [%0], %1;" :: "r"(bar), "r"(cnt) : "memory"); }
__device__ __forceinline__ void mbar_expect(uint32_t bar, uint32_t tx) { asm volatile("mbarrier.arrive.expect_tx.shared::cta.b64 _, [%0], %1;" :: "r"(bar), "r"(tx) : "memory"); }
__device__ __forceinline__ void mbar_arrive(uint32_t bar) { asm volatile("mbarrier.arrive.shared::cta.b64 _, [%0];" :: "r"(bar) : "memory"); }
__device__ __forceinline__ void mbar_wait(uint32_t bar, uint32_t par) {
  asm volatile("{\n.reg .pred p;\n.reg .u32 c;\nmov.u32 c, 0;\n"
               "LW:\nmbarrier.try_wait.parity.shared::cta.b64 p, [%0], %1;\n@p bra LD;\n"
               "add.u32 c, c, 1;\nsetp.lt.u32 p, c, 4000000;\n@p bra LW;\ntrap;\nLD:\n}" :: "r"(bar), "r"(par) : "memory");
}
template <int ID, int N> __device__ __forceinline__ void bar_sync() { asm volatile("barrier.sync %0, %1;" :: "n"(ID), "n"(N) : "memory"); }
template <int ID, int N> __device__ __forceinline__ void bar_arrive() { asm volatile("barrier.arrive %0, %1;" :: "n"(ID), "n"(N) : "memory"); }
__device__ __forceinline__ void fence_async() { asm volatile("fence.proxy.async.shared::cta;" ::: "memory"); }
__device__ __forceinline__ void cluster_sync() { asm volatile("barrier.cluster.arrive.aligned;\nbarrier.cluster.wait.aligned;" ::: "memory"); }
__device__ __forceinline__ void wg_fence() { asm volatile("wgmma.fence.sync.aligned;" ::: "memory"); }
__device__ __forceinline__ void wg_commit() { asm volatile("wgmma.commit_group.sync.aligned;" ::: "memory"); }
template <int N> __device__ __forceinline__ void wg_wait() { asm volatile("wgmma.wait_group.sync.aligned %0;" :: "n"(N) : "memory"); }
template <int N> __device__ __forceinline__ void pin(float* d) {
#pragma unroll
  for (int i = 0; i < N; i++) asm volatile("" : "+f"(d[i]) :: "memory");
}
__device__ __forceinline__ constexpr uint64_t mkdesc(uint32_t addr, uint32_t lbo, uint32_t sbo, int sw) {
  return (uint64_t)((addr & 0x3FFFF) >> 4) | ((uint64_t)(lbo >> 4) << 16) | ((uint64_t)(sbo >> 4) << 32) | ((uint64_t)sw << 62);
}
constexpr uint32_t SB0 = 1024;
__device__ __forceinline__ void check_smem_base(uint32_t sb) { if ((sb & 0x3FFFF) != SB0) __trap(); }
__device__ __forceinline__ uint32_t cta_rank() { uint32_t r; asm volatile("mov.u32 %0, %%cluster_ctarank;" : "=r"(r)); return r; }
__device__ __forceinline__ uint32_t opaque(uint32_t v) { uint32_t o; asm volatile("mov.u32 %0, %1;" : "=r"(o) : "r"(v)); return o; }
__device__ __forceinline__ uint32_t pack2(float lo, float hi) { uint32_t r; asm("cvt.rn.bf16x2.f32 %0, %1, %2;" : "=r"(r) : "f"(hi), "f"(lo)); return r; }
__device__ __forceinline__ void ldsm4(uint32_t* r, uint32_t a) { asm volatile("ldmatrix.sync.aligned.m8n8.x4.shared.b16 {%0,%1,%2,%3}, [%4];" : "=r"(r[0]), "=r"(r[1]), "=r"(r[2]), "=r"(r[3]) : "r"(a) : "memory"); }
__device__ __forceinline__ void ldsm4t(uint32_t* r, uint32_t a) { asm volatile("ldmatrix.sync.aligned.m8n8.x4.trans.shared.b16 {%0,%1,%2,%3}, [%4];" : "=r"(r[0]), "=r"(r[1]), "=r"(r[2]), "=r"(r[3]) : "r"(a) : "memory"); }
__device__ __forceinline__ void ldsm1(uint32_t& r, uint32_t a) { asm volatile("ldmatrix.sync.aligned.m8n8.x1.shared.b16 {%0}, [%1];" : "=r"(r) : "r"(a) : "memory"); }
__device__ __forceinline__ void stsm4(uint32_t a, uint32_t r0, uint32_t r1, uint32_t r2, uint32_t r3) { asm volatile("stmatrix.sync.aligned.m8n8.x4.shared.b16 [%0], {%1,%2,%3,%4};" :: "r"(a), "r"(r0), "r"(r1), "r"(r2), "r"(r3) : "memory"); }
__device__ __forceinline__ void stsm1(uint32_t a, uint32_t r0) { asm volatile("stmatrix.sync.aligned.m8n8.x1.shared.b16 [%0], {%1};" :: "r"(a), "r"(r0) : "memory"); }
__device__ __forceinline__ void stsm4t(uint32_t a, uint32_t r0, uint32_t r1, uint32_t r2, uint32_t r3) { asm volatile("stmatrix.sync.aligned.m8n8.x4.trans.shared.b16 [%0], {%1,%2,%3,%4};" :: "r"(a), "r"(r0), "r"(r1), "r"(r2), "r"(r3) : "memory"); }
__device__ __forceinline__ void stsm2t(uint32_t a, uint32_t r0, uint32_t r1) { asm volatile("stmatrix.sync.aligned.m8n8.x2.trans.shared.b16 [%0], {%1,%2};" :: "r"(a), "r"(r0), "r"(r1) : "memory"); }
__device__ __forceinline__ void mma16816(float* c, const uint32_t* a, uint32_t b0, uint32_t b1) {
  asm volatile("mma.sync.aligned.m16n8k16.row.col.f32.bf16.bf16.f32 {%0,%1,%2,%3}, {%4,%5,%6,%7}, {%8,%9}, {%0,%1,%2,%3};"
               : "+f"(c[0]), "+f"(c[1]), "+f"(c[2]), "+f"(c[3]) : "r"(a[0]), "r"(a[1]), "r"(a[2]), "r"(a[3]), "r"(b0), "r"(b1));
}
__device__ __forceinline__ void mma1688(float* c, uint32_t a0, uint32_t a1, uint32_t b0) {
  asm volatile("mma.sync.aligned.m16n8k8.row.col.f32.bf16.bf16.f32 {%0,%1,%2,%3}, {%4,%5}, {%6}, {%0,%1,%2,%3};"
               : "+f"(c[0]), "+f"(c[1]), "+f"(c[2]), "+f"(c[3]) : "r"(a0), "r"(a1), "r"(b0));
}
__device__ __forceinline__ void sta1(uint32_t a, uint32_t v, uint32_t bar) { asm volatile("st.async.weak.shared::cluster.mbarrier::complete_tx::bytes.b32 [%0], %1, [%2];" :: "r"(a), "r"(v), "r"(bar) : "memory"); }
__device__ __forceinline__ void sta1p(uint32_t a, uint32_t v, uint32_t bar, bool p) { asm volatile("{\n.reg .pred p;\nsetp.ne.b32 p, %3, 0;\n@p st.async.weak.shared::cluster.mbarrier::complete_tx::bytes.b32 [%0], %1, [%2];\n}" :: "r"(a), "r"(v), "r"(bar), "r"((int)p) : "memory"); }
__device__ __forceinline__ void sta2(uint32_t a, uint32_t v0, uint32_t v1, uint32_t bar) { asm volatile("st.async.weak.shared::cluster.mbarrier::complete_tx::bytes.v2.b32 [%0], {%1,%2}, [%3];" :: "r"(a), "r"(v0), "r"(v1), "r"(bar) : "memory"); }
__device__ __forceinline__ void sta4(uint32_t a, uint32_t v0, uint32_t v1, uint32_t v2, uint32_t v3, uint32_t bar) { asm volatile("st.async.weak.shared::cluster.mbarrier::complete_tx::bytes.v4.b32 [%0], {%1,%2,%3,%4}, [%5];" :: "r"(a), "r"(v0), "r"(v1), "r"(v2), "r"(v3), "r"(bar) : "memory"); }
__device__ __forceinline__ float bflo(uint32_t v) { return __uint_as_float(v << 16); }
__device__ __forceinline__ float bfhi(uint32_t v) { return __uint_as_float(v & 0xFFFF0000u); }
__device__ __forceinline__ void sta2f(uint32_t a, float v0, float v1, uint32_t bar) { asm volatile("st.async.weak.shared::cluster.mbarrier::complete_tx::bytes.v2.f32 [%0], {%1,%2}, [%3];" :: "r"(a), "f"(v0), "f"(v1), "r"(bar) : "memory"); }
__device__ __forceinline__ void sta4f(uint32_t a, float v0, float v1, float v2, float v3, uint32_t bar) { asm volatile("st.async.weak.shared::cluster.mbarrier::complete_tx::bytes.v4.f32 [%0], {%1,%2,%3,%4}, [%5];" :: "r"(a), "f"(v0), "f"(v1), "f"(v2), "f"(v3), "r"(bar) : "memory"); }
__device__ __forceinline__ float4 lds4f(uint32_t a) { float4 v; asm volatile("ld.shared.v4.f32 {%0,%1,%2,%3}, [%4];" : "=f"(v.x), "=f"(v.y), "=f"(v.z), "=f"(v.w) : "r"(a) : "memory"); return v; }
__device__ __forceinline__ float2 lds2f(uint32_t a) { float2 v; asm volatile("ld.shared.v2.f32 {%0,%1}, [%2];" : "=f"(v.x), "=f"(v.y) : "r"(a) : "memory"); return v; }
__device__ __forceinline__ uint4 lds4(uint32_t a) { uint4 v; asm volatile("ld.shared.v4.u32 {%0,%1,%2,%3}, [%4];" : "=r"(v.x), "=r"(v.y), "=r"(v.z), "=r"(v.w) : "r"(a) : "memory"); return v; }
__device__ __forceinline__ uint32_t lds1(uint32_t a) { uint32_t v; asm volatile("ld.shared.u32 %0, [%1];" : "=r"(v) : "r"(a) : "memory"); return v; }
__device__ __forceinline__ void stsm2(uint32_t a, uint32_t r0, uint32_t r1) { asm volatile("stmatrix.sync.aligned.m8n8.x2.shared.b16 [%0], {%1,%2};" :: "r"(a), "r"(r0), "r"(r1) : "memory"); }
__device__ __forceinline__ float rcp(float x) { float y; asm("rcp.approx.ftz.f32 %0, %1;" : "=f"(y) : "f"(x)); return y; }
__device__ __forceinline__ void sts4(uint32_t a, uint32_t v0, uint32_t v1, uint32_t v2, uint32_t v3) { asm volatile("st.shared.v4.u32 [%0], {%1,%2,%3,%4};" :: "r"(a), "r"(v0), "r"(v1), "r"(v2), "r"(v3) : "memory"); }
__device__ __forceinline__ void bulk_s2c(uint32_t dst, uint32_t src, uint32_t bytes, uint32_t bar) {
  asm volatile("cp.async.bulk.shared::cluster.shared::cta.mbarrier::complete_tx::bytes [%0], [%1], %2, [%3];" :: "r"(dst), "r"(src), "r"(bytes), "r"(bar) : "memory");
}
__device__ __forceinline__ void stg4(void* p, uint4 v) { asm volatile("st.global.v4.u32 [%0], {%1,%2,%3,%4};" :: "l"(p), "r"(v.x), "r"(v.y), "r"(v.z), "r"(v.w) : "memory"); }
__device__ __forceinline__ void red_add(uint32_t* p, uint32_t v) { asm volatile("red.relaxed.gpu.global.add.u32 [%0], %1;" :: "l"(p), "r"(v) : "memory"); }
__device__ __forceinline__ void red_release(uint32_t* p, uint32_t v) { asm volatile("red.release.gpu.global.add.u32 [%0], %1;" :: "l"(p), "r"(v) : "memory"); }
__device__ __forceinline__ void fence_async_global() { asm volatile("fence.proxy.async.global;" ::: "memory"); }
__device__ __forceinline__ uint64_t policy_evict_first() { uint64_t p; asm("createpolicy.fractional.L2::evict_first.b64 %0, 1.0;" : "=l"(p)); return p; }
__device__ __forceinline__ void stg4h(void* p, uint4 v, uint64_t pol) { asm volatile("st.global.L2::cache_hint.v4.u32 [%0], {%1,%2,%3,%4}, %5;" :: "l"(p), "r"(v.x), "r"(v.y), "r"(v.z), "r"(v.w), "l"(pol) : "memory"); }
__device__ __forceinline__ void red4fh(float* p, float a, float b, float c, float d, uint64_t pol) { asm volatile("red.relaxed.gpu.global.add.L2::cache_hint.v4.f32 [%0], {%1,%2,%3,%4}, %5;" :: "l"(p), "f"(a), "f"(b), "f"(c), "f"(d), "l"(pol) : "memory"); }
__device__ __forceinline__ float4 ldg4fh(const float* p, uint64_t pol) { float4 v; asm volatile("ld.global.cg.L2::cache_hint.v4.f32 {%0,%1,%2,%3}, [%4], %5;" : "=f"(v.x), "=f"(v.y), "=f"(v.z), "=f"(v.w) : "l"(p), "l"(pol) : "memory"); return v; }
__device__ __forceinline__ void bulk_g2sh(uint32_t dst, const void* src, uint32_t bytes, uint32_t bar, uint64_t pol) {
  asm volatile("cp.async.bulk.shared::cluster.global.mbarrier::complete_tx::bytes.L2::cache_hint [%0], [%1], %2, [%3], %4;" :: "r"(dst), "l"(src), "r"(bytes), "r"(bar), "l"(pol) : "memory");
}
#define EVF 1
__device__ __forceinline__ void red4f(float* p, float a, float b, float c, float d) { asm volatile("red.relaxed.gpu.global.add.v4.f32 [%0], {%1,%2,%3,%4};" :: "l"(p), "f"(a), "f"(b), "f"(c), "f"(d) : "memory"); }
__device__ __forceinline__ void wait_flag(const uint32_t* p, uint32_t target) {
  uint32_t v; int it = 0;
  while (true) {
    asm volatile("ld.acquire.gpu.global.u32 %0, [%1];" : "=r"(v) : "l"(p) : "memory");
    if (__all_sync(~0u, v >= target)) break;
    if (++it > 4000000) __trap();
    __nanosleep(20);
  }
}
__device__ __forceinline__ void sts2(uint32_t a, uint32_t v0, uint32_t v1) { asm volatile("st.shared.v2.u32 [%0], {%1,%2};" :: "r"(a), "r"(v0), "r"(v1) : "memory"); }
__device__ __forceinline__ float sqrt_approx(float x) { float y; asm("sqrt.approx.f32 %0, %1;" : "=f"(y) : "f"(x)); return y; }
__device__ __forceinline__ void bulk_s2c_elect(uint32_t d1, uint32_t b1, uint32_t d2, uint32_t b2, uint32_t src) {
  asm volatile("{\n.reg .pred p;\nelect.sync _|p, 0xffffffff;\n"
               "@p cp.async.bulk.shared::cluster.shared::cta.mbarrier::complete_tx::bytes [%0], [%4], 1024, [%1];\n"
               "@p cp.async.bulk.shared::cluster.shared::cta.mbarrier::complete_tx::bytes [%2], [%4], 1024, [%3];\n}"
               :: "r"(d1), "r"(b1), "r"(d2), "r"(b2), "r"(src) : "memory");
}
__device__ __forceinline__ void mbar_arrive_elect(uint32_t bar) { asm volatile("{\n.reg .pred p;\nelect.sync _|p, 0xffffffff;\n@p mbarrier.arrive.shared::cta.b64 _, [%0];\n}" :: "r"(bar) : "memory"); }
__device__ __forceinline__ void cp16(uint32_t dst, const void* src) { asm volatile("cp.async.cg.shared.global [%0], [%1], 16;" :: "r"(dst), "l"(src) : "memory"); }
__device__ __forceinline__ void sts1(uint32_t a, uint32_t v) { asm volatile("st.shared.u32 [%0], %1;" :: "r"(a), "r"(v) : "memory"); }
__device__ __forceinline__ void bulk_g2s(uint32_t dst, const void* src, uint32_t bytes, uint32_t bar) {
  asm volatile("cp.async.bulk.shared::cluster.global.mbarrier::complete_tx::bytes [%0], [%1], %2, [%3];" :: "r"(dst), "l"(src), "r"(bytes), "r"(bar) : "memory");
}
__device__ __forceinline__ void bulk_g2s_mc(uint32_t dst, const void* src, uint32_t bytes, uint32_t bar) {
  asm volatile("cp.async.bulk.shared::cluster.global.mbarrier::complete_tx::bytes.multicast::cluster [%0], [%1], %2, [%3], %4;" :: "r"(dst), "l"(src), "r"(bytes), "r"(bar), "h"((uint16_t)3) : "memory");
}
__device__ __forceinline__ void mbar_arrive_cl(uint32_t bar) { asm volatile("mbarrier.arrive.shared::cluster.b64 _, [%0];" :: "r"(bar) : "memory"); }
__device__ __forceinline__ void tma2d(uint32_t dst, const CUtensorMap* m, int c0, int c1, uint32_t bar) {
  asm volatile("cp.async.bulk.tensor.2d.shared::cluster.global.mbarrier::complete_tx::bytes [%0], [%1, {%3, %4}], [%2];" :: "r"(dst), "l"((uint64_t)m), "r"(bar), "r"(c0), "r"(c1) : "memory");
}
__device__ __forceinline__ void tma5d(uint32_t dst, const CUtensorMap* m, int c0, int c4, uint32_t bar) {
  asm volatile("cp.async.bulk.tensor.5d.shared::cluster.global.mbarrier::complete_tx::bytes [%0], [%1, {%3, %5, %5, %5, %4}], [%2];" :: "r"(dst), "l"((uint64_t)m), "r"(bar), "r"(c0), "r"(c4), "r"(0) : "memory");
}
__device__ __forceinline__ void red64(void* p, uint32_t lo, uint32_t hi) { asm volatile("{\n.reg .b64 t;\nmov.b64 t, {%1,%2};\nred.relaxed.gpu.global.add.u64 [%0], t;\n}" :: "l"(p), "r"(lo), "r"(hi) : "memory"); }
__device__ __forceinline__ uint4 ld_poll(const void* p) {
  uint4 v;
  asm volatile("{\n.reg .b64 a, b;\nld.relaxed.gpu.global.v2.b64 {a, b}, [%4];\nmov.b64 {%0,%1}, a;\nmov.b64 {%2,%3}, b;\n}" : "=r"(v.x), "=r"(v.y), "=r"(v.z), "=r"(v.w) : "l"(p) : "memory");
  return v;
}
__device__ __forceinline__ uint32_t clk() { uint32_t c; asm volatile("mov.u32 %0, %%clock;" : "=r"(c) :: "memory"); return c; }
#define SCHED_FENCE() asm volatile("pmevent 0;" ::: "memory")
__device__ __forceinline__ float ex2(float x) { float y; asm("ex2.approx.ftz.f32 %0, %1;" : "=f"(y) : "f"(x)); return y; }

__device__ __forceinline__ void wg_ss_n240_ta0_tb1(float* d, uint64_t a, uint64_t b, int sc) {
  asm volatile("{\n.reg .pred p;\nsetp.ne.b32 p, %122, 0;\nwgmma.mma_async.sync.aligned.m64n240k16.f32.bf16.bf16 {%0, %1, %2, %3, %4, %5, %6, %7, %8, %9, %10, %11, %12, %13, %14, %15, %16, %17, %18, %19, %20, %21, %22, %23, %24, %25, %26, %27, %28, %29, %30, %31, %32, %33, %34, %35, %36, %37, %38, %39, %40, %41, %42, %43, %44, %45, %46, %47, %48, %49, %50, %51, %52, %53, %54, %55, %56, %57, %58, %59, %60, %61, %62, %63, %64, %65, %66, %67, %68, %69, %70, %71, %72, %73, %74, %75, %76, %77, %78, %79, %80, %81, %82, %83, %84, %85, %86, %87, %88, %89, %90, %91, %92, %93, %94, %95, %96, %97, %98, %99, %100, %101, %102, %103, %104, %105, %106, %107, %108, %109, %110, %111, %112, %113, %114, %115, %116, %117, %118, %119}, %120, %121, p, 1, 1, 0, 1;\n}\n"
    : "+f"(d[0]), "+f"(d[1]), "+f"(d[2]), "+f"(d[3]), "+f"(d[4]), "+f"(d[5]), "+f"(d[6]), "+f"(d[7]), "+f"(d[8]), "+f"(d[9]), "+f"(d[10]), "+f"(d[11]), "+f"(d[12]), "+f"(d[13]), "+f"(d[14]), "+f"(d[15]), "+f"(d[16]), "+f"(d[17]), "+f"(d[18]), "+f"(d[19]), "+f"(d[20]), "+f"(d[21]), "+f"(d[22]), "+f"(d[23]), "+f"(d[24]), "+f"(d[25]), "+f"(d[26]), "+f"(d[27]), "+f"(d[28]), "+f"(d[29]), "+f"(d[30]), "+f"(d[31]), "+f"(d[32]), "+f"(d[33]), "+f"(d[34]), "+f"(d[35]), "+f"(d[36]), "+f"(d[37]), "+f"(d[38]), "+f"(d[39]), "+f"(d[40]), "+f"(d[41]), "+f"(d[42]), "+f"(d[43]), "+f"(d[44]), "+f"(d[45]), "+f"(d[46]), "+f"(d[47]), "+f"(d[48]), "+f"(d[49]), "+f"(d[50]), "+f"(d[51]), "+f"(d[52]), "+f"(d[53]), "+f"(d[54]), "+f"(d[55]), "+f"(d[56]), "+f"(d[57]), "+f"(d[58]), "+f"(d[59]), "+f"(d[60]), "+f"(d[61]), "+f"(d[62]), "+f"(d[63]), "+f"(d[64]), "+f"(d[65]), "+f"(d[66]), "+f"(d[67]), "+f"(d[68]), "+f"(d[69]), "+f"(d[70]), "+f"(d[71]), "+f"(d[72]), "+f"(d[73]), "+f"(d[74]), "+f"(d[75]), "+f"(d[76]), "+f"(d[77]), "+f"(d[78]), "+f"(d[79]), "+f"(d[80]), "+f"(d[81]), "+f"(d[82]), "+f"(d[83]), "+f"(d[84]), "+f"(d[85]), "+f"(d[86]), "+f"(d[87]), "+f"(d[88]), "+f"(d[89]), "+f"(d[90]), "+f"(d[91]), "+f"(d[92]), "+f"(d[93]), "+f"(d[94]), "+f"(d[95]), "+f"(d[96]), "+f"(d[97]), "+f"(d[98]), "+f"(d[99]), "+f"(d[100]), "+f"(d[101]), "+f"(d[102]), "+f"(d[103]), "+f"(d[104]), "+f"(d[105]), "+f"(d[106]), "+f"(d[107]), "+f"(d[108]), "+f"(d[109]), "+f"(d[110]), "+f"(d[111]), "+f"(d[112]), "+f"(d[113]), "+f"(d[114]), "+f"(d[115]), "+f"(d[116]), "+f"(d[117]), "+f"(d[118]), "+f"(d[119])
    : "l"(a), "l"(b), "r"(sc));
}
__device__ __forceinline__ void wg_ss_n88_ta1_tb1(float* d, uint64_t a, uint64_t b, int sc) {
  asm volatile("{\n.reg .pred p;\nsetp.ne.b32 p, %46, 0;\nwgmma.mma_async.sync.aligned.m64n88k16.f32.bf16.bf16 {%0, %1, %2, %3, %4, %5, %6, %7, %8, %9, %10, %11, %12, %13, %14, %15, %16, %17, %18, %19, %20, %21, %22, %23, %24, %25, %26, %27, %28, %29, %30, %31, %32, %33, %34, %35, %36, %37, %38, %39, %40, %41, %42, %43}, %44, %45, p, 1, 1, 1, 1;\n}\n"
    : "+f"(d[0]), "+f"(d[1]), "+f"(d[2]), "+f"(d[3]), "+f"(d[4]), "+f"(d[5]), "+f"(d[6]), "+f"(d[7]), "+f"(d[8]), "+f"(d[9]), "+f"(d[10]), "+f"(d[11]), "+f"(d[12]), "+f"(d[13]), "+f"(d[14]), "+f"(d[15]), "+f"(d[16]), "+f"(d[17]), "+f"(d[18]), "+f"(d[19]), "+f"(d[20]), "+f"(d[21]), "+f"(d[22]), "+f"(d[23]), "+f"(d[24]), "+f"(d[25]), "+f"(d[26]), "+f"(d[27]), "+f"(d[28]), "+f"(d[29]), "+f"(d[30]), "+f"(d[31]), "+f"(d[32]), "+f"(d[33]), "+f"(d[34]), "+f"(d[35]), "+f"(d[36]), "+f"(d[37]), "+f"(d[38]), "+f"(d[39]), "+f"(d[40]), "+f"(d[41]), "+f"(d[42]), "+f"(d[43])
    : "l"(a), "l"(b), "r"(sc));
}
__device__ __forceinline__ void wg_rs_n160_tb1(float* d, const uint32_t* a, uint64_t b, int sc) {
  asm volatile("{\n.reg .pred p;\nsetp.ne.b32 p, %85, 0;\nwgmma.mma_async.sync.aligned.m64n160k16.f32.bf16.bf16 {%0, %1, %2, %3, %4, %5, %6, %7, %8, %9, %10, %11, %12, %13, %14, %15, %16, %17, %18, %19, %20, %21, %22, %23, %24, %25, %26, %27, %28, %29, %30, %31, %32, %33, %34, %35, %36, %37, %38, %39, %40, %41, %42, %43, %44, %45, %46, %47, %48, %49, %50, %51, %52, %53, %54, %55, %56, %57, %58, %59, %60, %61, %62, %63, %64, %65, %66, %67, %68, %69, %70, %71, %72, %73, %74, %75, %76, %77, %78, %79}, {%80, %81, %82, %83}, %84, p, 1, 1, 1;\n}\n"
    : "+f"(d[0]), "+f"(d[1]), "+f"(d[2]), "+f"(d[3]), "+f"(d[4]), "+f"(d[5]), "+f"(d[6]), "+f"(d[7]), "+f"(d[8]), "+f"(d[9]), "+f"(d[10]), "+f"(d[11]), "+f"(d[12]), "+f"(d[13]), "+f"(d[14]), "+f"(d[15]), "+f"(d[16]), "+f"(d[17]), "+f"(d[18]), "+f"(d[19]), "+f"(d[20]), "+f"(d[21]), "+f"(d[22]), "+f"(d[23]), "+f"(d[24]), "+f"(d[25]), "+f"(d[26]), "+f"(d[27]), "+f"(d[28]), "+f"(d[29]), "+f"(d[30]), "+f"(d[31]), "+f"(d[32]), "+f"(d[33]), "+f"(d[34]), "+f"(d[35]), "+f"(d[36]), "+f"(d[37]), "+f"(d[38]), "+f"(d[39]), "+f"(d[40]), "+f"(d[41]), "+f"(d[42]), "+f"(d[43]), "+f"(d[44]), "+f"(d[45]), "+f"(d[46]), "+f"(d[47]), "+f"(d[48]), "+f"(d[49]), "+f"(d[50]), "+f"(d[51]), "+f"(d[52]), "+f"(d[53]), "+f"(d[54]), "+f"(d[55]), "+f"(d[56]), "+f"(d[57]), "+f"(d[58]), "+f"(d[59]), "+f"(d[60]), "+f"(d[61]), "+f"(d[62]), "+f"(d[63]), "+f"(d[64]), "+f"(d[65]), "+f"(d[66]), "+f"(d[67]), "+f"(d[68]), "+f"(d[69]), "+f"(d[70]), "+f"(d[71]), "+f"(d[72]), "+f"(d[73]), "+f"(d[74]), "+f"(d[75]), "+f"(d[76]), "+f"(d[77]), "+f"(d[78]), "+f"(d[79])
    : "r"(a[0]), "r"(a[1]), "r"(a[2]), "r"(a[3]), "l"(b), "r"(sc));
}
__device__ __forceinline__ void wg_ss_n80_ta0_tb1(float* d, uint64_t a, uint64_t b, int sc) {
  asm volatile("{\n.reg .pred p;\nsetp.ne.b32 p, %42, 0;\nwgmma.mma_async.sync.aligned.m64n80k16.f32.bf16.bf16 {%0, %1, %2, %3, %4, %5, %6, %7, %8, %9, %10, %11, %12, %13, %14, %15, %16, %17, %18, %19, %20, %21, %22, %23, %24, %25, %26, %27, %28, %29, %30, %31, %32, %33, %34, %35, %36, %37, %38, %39}, %40, %41, p, 1, 1, 0, 1;\n}\n"
    : "+f"(d[0]), "+f"(d[1]), "+f"(d[2]), "+f"(d[3]), "+f"(d[4]), "+f"(d[5]), "+f"(d[6]), "+f"(d[7]), "+f"(d[8]), "+f"(d[9]), "+f"(d[10]), "+f"(d[11]), "+f"(d[12]), "+f"(d[13]), "+f"(d[14]), "+f"(d[15]), "+f"(d[16]), "+f"(d[17]), "+f"(d[18]), "+f"(d[19]), "+f"(d[20]), "+f"(d[21]), "+f"(d[22]), "+f"(d[23]), "+f"(d[24]), "+f"(d[25]), "+f"(d[26]), "+f"(d[27]), "+f"(d[28]), "+f"(d[29]), "+f"(d[30]), "+f"(d[31]), "+f"(d[32]), "+f"(d[33]), "+f"(d[34]), "+f"(d[35]), "+f"(d[36]), "+f"(d[37]), "+f"(d[38]), "+f"(d[39])
    : "l"(a), "l"(b), "r"(sc));
}
__device__ __forceinline__ void wg_rs_n32_tb1(float* d, const uint32_t* a, uint64_t b, int sc) {
  asm volatile("{\n.reg .pred p;\nsetp.ne.b32 p, %21, 0;\nwgmma.mma_async.sync.aligned.m64n32k16.f32.bf16.bf16 {%0, %1, %2, %3, %4, %5, %6, %7, %8, %9, %10, %11, %12, %13, %14, %15}, {%16, %17, %18, %19}, %20, p, 1, 1, 1;\n}\n"
    : "+f"(d[0]), "+f"(d[1]), "+f"(d[2]), "+f"(d[3]), "+f"(d[4]), "+f"(d[5]), "+f"(d[6]), "+f"(d[7]), "+f"(d[8]), "+f"(d[9]), "+f"(d[10]), "+f"(d[11]), "+f"(d[12]), "+f"(d[13]), "+f"(d[14]), "+f"(d[15])
    : "r"(a[0]), "r"(a[1]), "r"(a[2]), "r"(a[3]), "l"(b), "r"(sc));
}
__device__ __forceinline__ void wg_ss_n32_ta1_tb1(float* d, uint64_t a, uint64_t b, int sc) {
  asm volatile("{\n.reg .pred p;\nsetp.ne.b32 p, %18, 0;\nwgmma.mma_async.sync.aligned.m64n32k16.f32.bf16.bf16 {%0, %1, %2, %3, %4, %5, %6, %7, %8, %9, %10, %11, %12, %13, %14, %15}, %16, %17, p, 1, 1, 1, 1;\n}\n"
    : "+f"(d[0]), "+f"(d[1]), "+f"(d[2]), "+f"(d[3]), "+f"(d[4]), "+f"(d[5]), "+f"(d[6]), "+f"(d[7]), "+f"(d[8]), "+f"(d[9]), "+f"(d[10]), "+f"(d[11]), "+f"(d[12]), "+f"(d[13]), "+f"(d[14]), "+f"(d[15])
    : "l"(a), "l"(b), "r"(sc));
}
__device__ __forceinline__ void wg_rs_n32_tb0(float* d, const uint32_t* a, uint64_t b, int sc) {
  asm volatile("{\n.reg .pred p;\nsetp.ne.b32 p, %21, 0;\nwgmma.mma_async.sync.aligned.m64n32k16.f32.bf16.bf16 {%0, %1, %2, %3, %4, %5, %6, %7, %8, %9, %10, %11, %12, %13, %14, %15}, {%16, %17, %18, %19}, %20, p, 1, 1, 0;\n}\n"
    : "+f"(d[0]), "+f"(d[1]), "+f"(d[2]), "+f"(d[3]), "+f"(d[4]), "+f"(d[5]), "+f"(d[6]), "+f"(d[7]), "+f"(d[8]), "+f"(d[9]), "+f"(d[10]), "+f"(d[11]), "+f"(d[12]), "+f"(d[13]), "+f"(d[14]), "+f"(d[15])
    : "r"(a[0]), "r"(a[1]), "r"(a[2]), "r"(a[3]), "l"(b), "r"(sc));
}
__device__ __forceinline__ void wg_rs_n40_tb0(float* d, const uint32_t* a, uint64_t b, int sc) {
  asm volatile("{\n.reg .pred p;\nsetp.ne.b32 p, %25, 0;\nwgmma.mma_async.sync.aligned.m64n40k16.f32.bf16.bf16 {%0, %1, %2, %3, %4, %5, %6, %7, %8, %9, %10, %11, %12, %13, %14, %15, %16, %17, %18, %19}, {%20, %21, %22, %23}, %24, p, 1, 1, 0;\n}\n"
    : "+f"(d[0]), "+f"(d[1]), "+f"(d[2]), "+f"(d[3]), "+f"(d[4]), "+f"(d[5]), "+f"(d[6]), "+f"(d[7]), "+f"(d[8]), "+f"(d[9]), "+f"(d[10]), "+f"(d[11]), "+f"(d[12]), "+f"(d[13]), "+f"(d[14]), "+f"(d[15]), "+f"(d[16]), "+f"(d[17]), "+f"(d[18]), "+f"(d[19])
    : "r"(a[0]), "r"(a[1]), "r"(a[2]), "r"(a[3]), "l"(b), "r"(sc));
}
__device__ __forceinline__ void wg_rs_n8_tb1(float* d, const uint32_t* a, uint64_t b, int sc) {
  asm volatile("{\n.reg .pred p;\nsetp.ne.b32 p, %9, 0;\nwgmma.mma_async.sync.aligned.m64n8k16.f32.bf16.bf16 {%0, %1, %2, %3}, {%4, %5, %6, %7}, %8, p, 1, 1, 1;\n}\n"
    : "+f"(d[0]), "+f"(d[1]), "+f"(d[2]), "+f"(d[3])
    : "r"(a[0]), "r"(a[1]), "r"(a[2]), "r"(a[3]), "l"(b), "r"(sc));
}
__device__ __forceinline__ void wg_ss_n40_ta0_tb0(float* d, uint64_t a, uint64_t b, int sc) {
  asm volatile("{\n.reg .pred p;\nsetp.ne.b32 p, %22, 0;\nwgmma.mma_async.sync.aligned.m64n40k16.f32.bf16.bf16 {%0, %1, %2, %3, %4, %5, %6, %7, %8, %9, %10, %11, %12, %13, %14, %15, %16, %17, %18, %19}, %20, %21, p, 1, 1, 0, 0;\n}\n"
    : "+f"(d[0]), "+f"(d[1]), "+f"(d[2]), "+f"(d[3]), "+f"(d[4]), "+f"(d[5]), "+f"(d[6]), "+f"(d[7]), "+f"(d[8]), "+f"(d[9]), "+f"(d[10]), "+f"(d[11]), "+f"(d[12]), "+f"(d[13]), "+f"(d[14]), "+f"(d[15]), "+f"(d[16]), "+f"(d[17]), "+f"(d[18]), "+f"(d[19])
    : "l"(a), "l"(b), "r"(sc));
}
__device__ __forceinline__ void wg_ss_n40_ta1_tb0(float* d, uint64_t a, uint64_t b, int sc) {
  asm volatile("{\n.reg .pred p;\nsetp.ne.b32 p, %22, 0;\nwgmma.mma_async.sync.aligned.m64n40k16.f32.bf16.bf16 {%0, %1, %2, %3, %4, %5, %6, %7, %8, %9, %10, %11, %12, %13, %14, %15, %16, %17, %18, %19}, %20, %21, p, 1, 1, 1, 0;\n}\n"
    : "+f"(d[0]), "+f"(d[1]), "+f"(d[2]), "+f"(d[3]), "+f"(d[4]), "+f"(d[5]), "+f"(d[6]), "+f"(d[7]), "+f"(d[8]), "+f"(d[9]), "+f"(d[10]), "+f"(d[11]), "+f"(d[12]), "+f"(d[13]), "+f"(d[14]), "+f"(d[15]), "+f"(d[16]), "+f"(d[17]), "+f"(d[18]), "+f"(d[19])
    : "l"(a), "l"(b), "r"(sc));
}
__device__ __forceinline__ void wg_ss_n8_ta1_tb1(float* d, uint64_t a, uint64_t b, int sc) {
  asm volatile("{\n.reg .pred p;\nsetp.ne.b32 p, %6, 0;\nwgmma.mma_async.sync.aligned.m64n8k16.f32.bf16.bf16 {%0, %1, %2, %3}, %4, %5, p, 1, 1, 1, 1;\n}\n"
    : "+f"(d[0]), "+f"(d[1]), "+f"(d[2]), "+f"(d[3])
    : "l"(a), "l"(b), "r"(sc));
}

constexpr int O_WV = 0, O_WO = 81920, O_H = 163840, O_QK = 215040, O_SM = 228352, O_MISC = 229632;
constexpr int O_QM = O_QK + 1024, O_K = O_QK + 3072, O_OG = O_QK + 8192;
constexpr int SM_SLOT = 640;
constexpr int O_MAXS = O_MISC;
constexpr int O_BAR = O_MISC + 64;
constexpr int MB_XF = 0, MB_ML = 2, MB_MR = 4, MB_SM = 7, MB_SX = 8, MB_OG = 9, MB_W = 10;
constexpr int O_PROF = O_BAR + 8 * 24;
constexpr int REC_SMEM = O_PROF + 128;
constexpr int B_VOWN = 0, B_QK = 1, B_VGO = 2, B_SISS = 3, B_PM = 4, B_PX = 5, B_XGO = 6, B_PFREE = 7, B_WG2 = 8, B_VHALF = 9, B_VDONE = 10,
              B_PFREE1 = 11, B_SSENT = 12, B_SLD = 13, B_VEND = 14, B_XGO1 = 15;
#define POLL_DELAY 600
#define POLL_D0 300
#define POLL_STEP 100
#define TS0(idx) do {} while (0)
#define TS(idx) do {} while (0)
#define SLD_POS 0
#define WO_PROG 1
#define TRIG_LATE 1
#define XP_END 40
#define F_ORD 0
#define VEND_POS 2
#define SPEC_DEC 0
#define O_B1 5
#define O_C1 16
#define O_MODE 0
#define AR_MAP 1
#define EXP 0
#define FILL_B 4096
#define MP_D 3
#define MP_CH 4
#define MP_F 0
#define ML_N0 3
#define MR_N0 3
#define O_RSM 0x2AA0
#define O_RS __builtin_popcount(O_RSM)
#define O_IDX(j) __builtin_popcount(O_RSM & ((1 << (j)) - 1))
#define O_RS_POS 0
#define V_N1 2
#define V_N2 0
#define V_N3 4
#define V_OWN 6
#define V_S1 9
#define V_K1 (V_OWN + V_RS + V_S1)
#define V_K2 ((V_K1 > 20 ? V_K1 : 20) + V_S2)
#define V_S2 3
constexpr int V_RS = V_N1 + V_N2 + V_N3;
constexpr float SCL = 0.07216878364870322f;
constexpr float L2E = 1.4426950408889634f;
__device__ __forceinline__ constexpr int vord(int i) { return i < 4 ? 36 + i : i - 4; }
__device__ __forceinline__ constexpr uint32_t hoff(int k) { return ((k >> 2) * 5120 + (k & 3) * 32) >> 4; }

__device__ __forceinline__ constexpr int ar_chunk(int T) { return AR_MAP == 0 ? (T >> 2) * 8 + (T & 3) : T == 9 ? 19 : (T % 3) * 8 + T / 3; }
__device__ __forceinline__ void fix_red(uint8_t* p, const float* a, float sc) {
  int v0 = __float2int_rn(a[0] * sc), v1 = __float2int_rn(a[1] * sc), v2 = __float2int_rn(a[2] * sc), v3 = __float2int_rn(a[3] * sc);
  red64(p, ((uint32_t)v0 << 7) | 1u, ((uint32_t)v2 << 3) + (uint32_t)(v0 >> 25));
  red64(p + 1024, ((uint32_t)v1 << 7) | 1u, ((uint32_t)v3 << 3) + (uint32_t)(v1 >> 25));
}
__device__ __forceinline__ float max10(const float* t) {
  float m = fmaxf(fmaxf(fmaxf(t[0], t[1]), fmaxf(t[2], t[3])), fmaxf(fmaxf(t[4], t[5]), fmaxf(t[6], t[7])));
  m = fmaxf(m, fmaxf(t[8], t[9]));
  m = fmaxf(m, __shfl_xor_sync(~0u, m, 1));
  return fmaxf(m, __shfl_xor_sync(~0u, m, 2));
}
#define ACC2(k, p, u, v) { t[k] = bflo(p) + bflo(u) + bflo(v); t[k + 1] = bfhi(p) + bfhi(u) + bfhi(v); }

__global__ void __launch_bounds__(384, 1)
rec_kernel(const __grid_constant__ CUtensorMap tmq, const __grid_constant__ CUtensorMap tmk,
           const __grid_constant__ CUtensorMap tmv, const __grid_constant__ CUtensorMap tmo,
           const bf16* __restrict__ mem0, uint8_t* __restrict__ ar, uint32_t* __restrict__ flags, int layer) {
  extern __shared__ __align__(1024) uint8_t smem[];
  const uint32_t sb = smem_u32(smem);
  check_smem_base(sb);
  const int tid = threadIdx.x, wid = __shfl_sync(~0u, tid >> 5, 0), wg = wid >> 2, w = wid & 3;
  const int lane = __shfl_sync(~0u, tid & 31, tid & 31);
  const int head = blockIdx.x / 3, rank = blockIdx.x - head * 3;
  const int e0 = blockIdx.x * 64;
  const uint32_t bar = sb + O_BAR;
  const uint32_t sb1 = mapa(sb, rank == 2 ? 0 : rank + 1), sb2 = mapa(sb, rank == 0 ? 2 : rank - 1);
  auto chunk_of = [&](int p) { const int c = 3 * rank + p; return p == 9 ? 9 : c >= 9 ? c - 9 : c; };

  GT(layer * 4 + 1, 0);
  if (wid == 8) {
    if (lane < 24) mbar_init(bar + 8 * lane, lane == MB_ML ? ML_N0 : lane == MB_ML + 1 && ML_N0 < 4 ? 4 - ML_N0 : 1);
    asm volatile("fence.mbarrier_init.release.cluster;" ::: "memory");
    fence_async();
    __syncwarp();
    if (lane < 10) mbar_expect(bar + 8 * (MB_W + lane), 16384);
    __syncwarp();
    if (lane < 20) {
      const int m = (lane >> 1) & 1, p = (lane >> 2) * 2 + (lane & 1);
      tma5d(sb + m * 81920 + p * 8192, m ? &tmk : &tmq, e0, chunk_of(p) * 4, bar + 8 * (MB_W + m * 5 + (p >> 1)));
    }
  }
  __syncthreads();
  asm volatile("barrier.cluster.arrive.relaxed.aligned;" ::: "memory");

  if (wg < 2) {
    asm volatile("setmaxnreg.inc.sync.aligned.u32 208;");
    uint32_t a[40][4];
    const uint32_t swz = (lane & 7) * 128 + (((2 * w + ((lane >> 3) & 1)) ^ (lane & 7)) << 4);
    const uint32_t st_x = __shfl_sync(~0u, sb + O_QK + wg * 5120 + (lane >> 4) * 2048 + swz, lane);
    {
      const uint32_t la = sb + wg * 81920 + (lane >> 4) * 1024 + swz;
#pragma unroll
      for (int p = 0; p < 5; p++) {
        mbar_wait(bar + 8 * (MB_W + wg * 5 + p), 0);
#pragma unroll
        for (int k = 0; k < 8; k++) ldsm4t(a[p * 8 + k], la + (p * 8 + k) * 2048);
        if (p > 0) bar_sync<B_VGO, 288>();
        bar_arrive<B_PFREE, 288>();
      }
      bar_sync<B_VGO, 288>();
    }
    GT(layer * 4 + 1, 5);
    asm volatile("barrier.cluster.wait.aligned;" ::: "memory");
    const uint32_t ld_m = __shfl_sync(~0u, sb + O_H + (lane & 7) * 128 + (((lane >> 3) ^ (lane & 7)) << 4), lane);

    for (int s = 0; s < NSEG; s++) {
      const uint32_t par = s & 1;
      if (wid == 4) TS0(0);
      if (wid == 0) TS(30);
      {
        float ax[16];
        constexpr uint64_t db = mkdesc(SB0 + O_H + 1024, 16, 1024, 1);
        mbar_wait(bar + 8 * MB_XF, par);
        wg_fence();
#pragma unroll
        for (int k = 0; k < 20; k++) wg_rs_n32_tb0(ax, a[vord(k)], db + hoff(vord(k)), k);
        mbar_wait(bar + 8 * (MB_XF + 1), par);
        wg_fence();
#pragma unroll
        for (int k = 20; k < XP_END; k++) wg_rs_n32_tb0(ax, a[vord(k)], db + hoff(vord(k)), 1);
        wg_commit();
        if (s > 0) { if (wg == 0) bar_sync<B_PFREE, 256>(); else bar_sync<B_PFREE1, 256>(); }
        if (wid == 6 && lane == 0) { mbar_expect(bar + 8 * MB_SM, 2 * SM_SLOT + 48 + 48); mbar_expect(bar + 8 * MB_SX, 2 * 2176); }
        wg_wait<0>();
        pin<16>(ax);
        if (w == 0) TS(1 + 22 * wg);
        stsm4t(st_x, pack2(ax[0], ax[1]), pack2(ax[2], ax[3]), pack2(ax[4], ax[5]), pack2(ax[6], ax[7]));
        stsm4t(st_x + 4096, pack2(ax[8], ax[9]), pack2(ax[10], ax[11]), pack2(ax[12], ax[13]), pack2(ax[14], ax[15]));
        if (V_OWN > 0) bar_arrive<B_VOWN, 384>();
      }
      {
        float c[MP_CH][4];
#pragma unroll
        for (int k = 0; k < MP_CH; k++) c[k][0] = c[k][1] = c[k][2] = c[k][3] = 0.f;
        uint32_t b[MP_D][2][4];
        const uint32_t ld_m2 = opaque(ld_m ^ 64);
        SCHED_FENCE();
#define MORD(j) ((j) == 0 ? 9 : (j) < 4 ? (j) - 1 : 3 + ((j) - 4) / 2 + 3 * ((j) & 1))
#pragma unroll
        for (int j = 0; j < 10 + MP_D - 1; j++) {
          if (j < 10) {
            if (j == 0) { mbar_wait(bar + 8 * MB_ML, par); if (wid == 0) TS(2); }
            if (ML_N0 < 4 && j == ML_N0) { mbar_wait(bar + 8 * (MB_ML + 1), par); if (wid == 0) TS(3); }
            if (j == 4) { mbar_wait(bar + 8 * MB_MR, par); if (wid == 0) TS(4); }
            if (j == 4 + 2 * MR_N0) { mbar_wait(bar + 8 * (MB_MR + 1), par); if (wid == 0) TS(5); }
            ldsm4(b[j % MP_D][0], ld_m + MORD(j) * 5120);
            ldsm4(b[j % MP_D][1], ld_m2 + MORD(j) * 5120);
            if ((MP_F >> j) & 1) SCHED_FENCE();
          }
          const int u = j - (MP_D - 1);
          if (u >= 0) {
#pragma unroll
            for (int k = 0; k < 4; k++) mma16816(c[(4 * u + k) % MP_CH], a[4 * MORD(u) + k], b[u % MP_D][k >> 1][(k & 1) * 2], b[u % MP_D][k >> 1][(k & 1) * 2 + 1]);
          }
        }
        SCHED_FENCE();
        bar_arrive<B_VGO, 384>();
        SCHED_FENCE();
#pragma unroll
        for (int k = 0; k < 4; k++) c[0][k] = MP_CH == 4 ? (c[0][k] + c[1][k]) + (c[2][k] + c[MP_CH - 1][k]) : (c[1][k] + c[2][k]) + c[0][k];
        stsm2t(st_x + 1024 - wg * 3072, pack2(c[0][0], c[0][1]), pack2(c[0][2], c[0][3]));
        fence_async();
      }
      if (wg == 0) {
        bar_sync<B_QK, 256>();
        float sv[20];
        {
          constexpr uint64_t da = mkdesc(SB0 + O_QK, 16, 1024, 1), db = mkdesc(SB0 + O_K, 16, 2048, 1);
          wg_fence();
#pragma unroll
          for (int k = 0; k < 4; k++) wg_ss_n40_ta0_tb0(sv, da + 2 * k, db + 2 * k, k);
          wg_commit();
          bar_arrive<B_SISS, 256>();
        }
        if (w == 0) TS(6);
        SCHED_FENCE();
        const uint32_t ln = opaque(lane);
        uint32_t m0, m1, m2, m3, m4;
        {
          const uint32_t a1 = opaque(sb1 + O_SM + SM_SLOT + ln * 16), a2 = opaque(sb2 + O_SM + ln * 16);
          const uint32_t a3 = opaque(sb1 + O_SM + SM_SLOT + 512 + ln * 4), a4 = opaque(sb2 + O_SM + 512 + ln * 4);
          const uint32_t b1 = opaque(sb1 + O_BAR + 8 * MB_SM), b2 = opaque(sb2 + O_BAR + 8 * MB_SM);
          const uint32_t bt = opaque(mapa(sb, min(ln, 2u)) + O_BAR + 8 * MB_SM), at = opaque(bt + (O_MAXS + 48 - O_BAR - 8 * MB_SM));
          SCHED_FENCE();
          wg_wait<0>();
          pin<20>(sv);
          m0 = pack2(sv[2], sv[3]); m1 = pack2(sv[6], sv[7]); m2 = pack2(sv[10], sv[11]); m3 = pack2(sv[14], sv[15]); m4 = pack2(sv[18], sv[19]);
          if (w == 0) {
            sta4(a1, m0, m1, m2, m3, b1);
            sta4(a2, m0, m1, m2, m3, b2);
            sta1(a3, m4, b1);
            sta1(a4, m4, b2);
          }
          sta1p(at, 0u, bt, ln < 3);
          bar_arrive<B_SSENT, 256>();
          SCHED_FENCE();
        }
        const uint32_t p0 = pack2(sv[0], sv[1]), p1 = pack2(sv[4], sv[5]), p2 = pack2(sv[8], sv[9]), p3 = pack2(sv[12], sv[13]), p4 = pack2(sv[16], sv[17]);
        const uint32_t ox = O_K + w * 2048 + ln * 16, ox2 = O_K + 8192 + ln * 4;
        {
          const uint32_t a1 = opaque(sb1 + ox + 512), a2 = opaque(sb2 + ox), b1 = opaque(sb1 + O_BAR + 8 * MB_SX), b2 = opaque(sb2 + O_BAR + 8 * MB_SX);
          if (w == 0) {
            TS(7);
            const uint32_t om = opaque(sb + O_SM + ln * 16), om2 = opaque(sb + O_SM + 512 + ln * 4);
            const uint32_t pa0 = ld_m + (O_QM - O_H), pa1 = (ld_m ^ 64) + (O_QM - O_H);
            float t[10] = {bflo(m0), bfhi(m0), bflo(m1), bfhi(m1), bflo(m2), bfhi(m2), bflo(m3), bfhi(m3), bflo(m4), bfhi(m4)};
            pin<10>(t);
            SCHED_FENCE();
            mbar_wait(bar + 8 * MB_SM, par);
            const uint4 u = lds4(om), v = lds4(om + SM_SLOT);
            const uint32_t u4 = lds1(om2), v4 = lds1(om2 + SM_SLOT);
            sta4(a1, p0, p1, p2, p3, b1);
            sta4(a2, p0, p1, p2, p3, b2);
            if (SLD_POS == 0) bar_arrive<B_SLD, 256>();
            SCHED_FENCE();
#define ACC3(k, u, v) { t[k] += bflo(u) + bflo(v); t[k + 1] += bfhi(u) + bfhi(v); }
            ACC3(0, u.x, v.x) ACC3(2, u.y, v.y) ACC3(4, u.z, v.z) ACC3(6, u.w, v.w) ACC3(8, u4, v4)
            TS(8);
            const float mm = max10(t) * (SCL * L2E);
            if (SLD_POS == 1) { SCHED_FENCE(); bar_arrive<B_SLD, 256>(); SCHED_FENCE(); }
#pragma unroll
            for (int k = 0; k < 10; k++) t[k] = ex2(fmaf(t[k], SCL * L2E, -mm));
            stsm4(pa0, pack2(t[0], t[1]), pack2(t[2], t[3]), pack2(t[4], t[5]), pack2(t[6], t[7]));
            stsm1(pa1, pack2(t[8], t[9]));
            bar_arrive<B_PM, 160>();
            TS(9);
          } else {
            const uint32_t a3 = opaque(sb1 + ox2 + 128), a4 = opaque(sb2 + ox2);
            SCHED_FENCE();
            mbar_wait(bar + 8 * MB_SM, par);
            sta4(a1, p0, p1, p2, p3, b1);
            sta4(a2, p0, p1, p2, p3, b2);
            if (w == 3) { sta1(a3, p4, b1); sta1(a4, p4, b2); }
            bar_arrive<B_SLD, 256>();
          }
        }
        mbar_wait(bar + 8 * MB_SX, par);
        bar_sync<B_VEND, 256>();
        {
          float t[10];
          const uint4 u = lds4(sb + ox), v = lds4(sb + ox + 512);
          const uint32_t u4 = lds1(sb + ox2), v4 = lds1(sb + ox2 + 128);
          SCHED_FENCE();
          ACC2(0, p0, u.x, v.x) ACC2(2, p1, u.y, v.y) ACC2(4, p2, u.z, v.z) ACC2(6, p3, u.w, v.w) ACC2(8, p4, u4, v4)
          const int dq = 8 * w + (ln >> 2) - 2 * (ln & 3);
#pragma unroll
          for (int k = 1; k < 5; k++) {
            if (8 * (k - 1) > dq) t[2 * k] = -1e9f / SCL;
            if (8 * (k - 1) + 1 > dq) t[2 * k + 1] = -1e9f / SCL;
          }
          const float mm = max10(t) * (SCL * L2E);
#pragma unroll
          for (int k = 0; k < 10; k++) t[k] = ex2(fmaf(t[k], SCL * L2E, -mm));
          float sum = ((t[0] + t[1]) + (t[2] + t[3])) + ((t[4] + t[5]) + (t[6] + t[7])) + (t[8] + t[9]);
          sum += __shfl_xor_sync(~0u, sum, 1);
          sum += __shfl_xor_sync(~0u, sum, 2);
          const float inv = rcp(sum);
          const int rr = 2 * w + (ln & 1);
          const uint32_t pa = sb + O_QK + ((ln >> 1) & 3) * 2048 + rr * 128;
          stsm4(pa + (((ln >> 3) ^ rr) << 4), pack2(t[0] * inv, t[1] * inv), pack2(t[2] * inv, t[3] * inv), pack2(t[4] * inv, t[5] * inv), pack2(t[6] * inv, t[7] * inv));
          stsm2(pa + (((4 + ((ln >> 3) & 1)) ^ rr) << 4), pack2(t[8] * inv, t[9] * inv), 0u);
          fence_async();
        }
        bar_arrive<B_PX, 256>();
        if (w == 0) TS(10);
        bar_sync<B_XGO, 256>();
      } else {
        bar_arrive<B_QK, 256>();
        const int ln = opaque(lane);
        if (w == 2) {
          bar_sync<B_VHALF, 192>();
          if (ln == 0 && s > 0) { red_release(flags + FL_A + (e0 >> 10) * 8 + (s - 1) * 48, 1); }
          __syncwarp();
        }
        if (w == 3) {
          const int l = blockIdx.x * 2 + ln, s2 = s + 2;
          if (ln < 2 && l < 160 && s2 < NSEG - 1) {
            const int tile = l >> 4;
            const uint8_t* p = ar + (s2 >> 2) * AR_GROUP + (s2 & 1) * 128 + ((s2 >> 1) & 1) * 512 + ar_chunk(tile) * 4096 +
                               ((l >> 3) & 1) * 16384 + (l & 1) * 256 + ((l >> 1) & 3) * 1024;
            asm volatile("prefetch.global.L2 [%0];" :: "l"(p));
          }
        }
        if (w == 0) {
          const bool more = s + 1 < NSEG;
          if (ln < 2 && more) mbar_expect(bar + 8 * (MB_XF + ln), FILL_B * 5);
          const uint8_t* src = g_xn + (s + 1) * 40960 + chunk_of(ln) * 4096;
          bar_sync<B_VHALF, 192>();
          if ((ln < 4 || ln == 9) && more) bulk_g2s(sb + O_H + ln * 5120 + 1024, src, FILL_B, bar + 8 * MB_XF);
          bar_sync<B_VDONE, 160>();
          if (ln >= 4 && ln < 9 && more) bulk_g2s(sb + O_H + ln * 5120 + 1024, src, FILL_B, bar + 8 * (MB_XF + 1));
        }
        bar_sync<B_XGO1, 256>();
      }
    }
  } else {
    asm volatile("setmaxnreg.dec.sync.aligned.u32 88;");
    if (w == 1) {
      if (lane == 0) { mbar_expect(bar + 8 * (MB_W + 10), 81920); mbar_expect(bar + 8 * (MB_W + 11), 81920); }
#pragma unroll 1
      for (int p = 0; p < 5; p++) {
        bar_sync<B_PFREE, 288>();
        fence_async();
        if (lane < 2) tma5d(sb + O_WV + (2 * p + lane) * 8192, &tmv, e0, chunk_of(2 * p + lane) * 4, bar + 8 * (MB_W + 10));
        if (WO_PROG ? (lane >> 1) == p : (p == 4 && lane < 10)) {
          const int k = lane / 3, j = rank + lane - 3 * k;
          tma2d(sb + O_WO + lane * 8192, &tmo, lane == 9 ? 576 : (rank * 3 + k) * 64, head * DH + (j >= 3 ? j - 3 : j) * 64, bar + 8 * (MB_W + 11));
        }
        bar_arrive<B_VGO, 288>();
      }
    }
    if (w == 0) {
      if (lane < 2) mbar_expect(bar + 8 * (MB_XF + lane), 20480);
      wait_flag(flags + FL_X, 128);
      fence_async_global();
      if (lane < 10) bulk_g2s(sb + O_H + lane * 5120 + 1024, g_xn + chunk_of(lane) * 4096, 4096, bar + 8 * (MB_XF + (lane >= 4 && lane < 9)));
      if (!TRIG_LATE) asm volatile("griddepcontrol.launch_dependents;");
      if (lane == 0) GTT(layer * 4 + 1, 4);
    }
    bar_sync<B_WG2, 128>();
    asm volatile("barrier.cluster.wait.aligned;" ::: "memory");

    const int g = lane >> 2, i4 = lane & 3;
    const int myT = w == 0 ? 9 : rank * 3 + w - 1, myP = w == 0 ? 9 : w - 1;
    const int tok = 2 * ((lane >> 1) & 3) + ((lane >> 3) & 1);
    const uint32_t fw_off = sb + O_H + myP * 5120 + tok * 128 + (((2 * (lane >> 4) + (lane & 1)) ^ tok) << 4);
    const uint32_t prod_off = (w >> 1) * 16384 + (w & 1) * 2048 + ((g >> 1) & 1) * 256 + (i4 * 2 + (g >> 2)) * 16 + (g & 1) * 8;
    const uint32_t cons_off = ar_chunk(myT) * 4096 + (lane >> 3) * 1024 + (lane & 7) * 16;
    auto tile_off = [&](int k) { return AR_MAP == 0 ? ar_chunk(rank * 3 + k) * 4096 : (k * 8 + rank) * 4096; };
    constexpr uint32_t T9_OFF = ar_chunk(9) * 4096;

    uint32_t mx;
    auto forward = [&](const uint32_t* p) {
      const uint32_t c = O_H + myP * 5120, bo = O_BAR + 8 * (MB_MR + (w > MR_N0));
      sts4(fw_off, p[0], p[1], p[2], p[3]);
      sts4(fw_off ^ 64, p[4], p[5], p[6], p[7]);
      fence_async();
      __syncwarp();
      mbar_arrive_elect(bar + 8 * (MB_ML + (w >= ML_N0)));
      if (w > 0) bulk_s2c_elect(sb1 + c + 6 * 5120, sb1 + bo, sb2 + c + 3 * 5120, sb2 + bo, sb + c);
      SCHED_FENCE();
      mx = 0;
#pragma unroll
      for (int k = 0; k < 8; k++) mx = __vmaxu2(mx, p[k] & 0x7FFF7FFFu);
    };
    auto send_max = [&]() {
      mx = max(mx & 0xFFFFu, mx >> 16);
      mx = __reduce_max_sync(~0u, mx);
      { const uint32_t b = mapa(sb, min(lane, 2)); sta1p(b + O_MAXS + (rank * 4 + w) * 4, mx << 16, b + O_BAR + 8 * MB_SM, lane < 3); }
    };
    auto arm = [&]() { if (lane == 0 && w < (MR_N0 < 3 ? 3 : 2)) mbar_expect(bar + 8 * (w == 0 ? MB_OG : MB_MR - 1 + w), w == 0 ? 2048 : w == 1 ? 2048 * MR_N0 : 2048 * (3 - MR_N0)); };
    {
      arm();
      const uint32_t* mp = (const uint32_t*)(mem0 + tok * DM + myT * 64 + 16 * (lane >> 4) + 4 * (lane & 1));
      const uint32_t p[8] = {mp[0], mp[4], mp[1], mp[5], mp[16], mp[20], mp[17], mp[21]};
      forward(p);
    }
    float cbound;
    {
      wait_flag(g_zero + Z_FLAGS + FL_N, 4);
      const float sq = __ldcg((const float*)(g_zero + Z_NORM));
      float mx = 0.f;
#pragma unroll
      for (int k = 0; k < 5; k++) {
        const float4* p = (const float4*)g_nrm + k * 32 + lane;
        const float4 x = __ldcg(p), y = __ldcg(p + 160), z = __ldcg(p + 320), u = __ldcg(p + 480);
        mx = fmaxf(fmaxf(mx, fmaxf((x.x + y.x) + (z.x + u.x), (x.y + y.y) + (z.y + u.y))), fmaxf((x.z + y.z) + (z.z + u.z), (x.w + y.w) + (z.w + u.w)));
      }
#pragma unroll
      for (int o = 16; o; o >>= 1) mx = fmaxf(mx, __shfl_xor_sync(~0u, mx, o));
      cbound = sqrt_approx(sq) * sqrt_approx(mx) * (25.2982213f * 1.1f);
    }
    mbar_wait(bar + 8 * (MB_W + 10), 0);
    if (tid == 256) GTT(layer * 4 + 1, 7);

    const uint32_t la_w = sb + O_WV + ((lane >> 4) * 8 + (lane & 7)) * 128 + (((2 * w + ((lane >> 3) & 1)) ^ (lane & 7)) << 4);
    uint32_t af[V_RS][4];
#pragma unroll
    for (int k = 0; k < V_RS; k++) ldsm4t(af[k], la_w + vord(V_OWN + k) * 2048);
    uint32_t vf[10];
    uint4 oq0, oq1;
    uint8_t* op;
    auto pv_x = [&](int s) {
      float ox[16];
      const uint32_t vz[4] = {vf[8], vf[9], 0u, 0u};
      constexpr uint64_t dp = mkdesc(SB0 + O_QK, 16, 2048, 1);
      bar_sync<B_PX, 256>();
      wg_fence();
      wg_rs_n32_tb0(ox, vf, dp, 0);
      wg_rs_n32_tb0(ox, vf + 4, dp + 2, 1);
      wg_rs_n32_tb0(ox, vz, dp + 4, 1);
      wg_commit();
      const uint32_t ln = opaque(lane);
      op = g_ot + (size_t)s * (HE * 64) + (e0 + 16 * w) * 64 + (ln & 3) * 128 + (ln >> 2) * 16;
      wg_wait<0>();
      pin<16>(ox);
      oq0 = make_uint4(pack2(ox[0], ox[1]), pack2(ox[4], ox[5]), pack2(ox[8], ox[9]), pack2(ox[12], ox[13]));
      oq1 = make_uint4(pack2(ox[2], ox[3]), pack2(ox[6], ox[7]), pack2(ox[10], ox[11]), pack2(ox[14], ox[15]));
    };
    for (int s = 0;; s++) {
      const uint32_t par = s & 1;
      float sc, isc;
      uint32_t ao[O_RS > 0 ? O_RS : 1][4];
      {
        float av[20];
        constexpr uint64_t da = mkdesc(SB0 + O_WV, 1024, 1024, 1), db = mkdesc(SB0 + O_H, 16, 1024, 1);
#define V_RUN_RS(k0, k1) wg_fence(); _Pragma("unroll") for (int k = k0; k < k1; k++) wg_rs_n40_tb0(av, af[k], db + hoff(vord(V_OWN + k)), V_OWN + k);
#define V_RUN_SS(k0, k1) wg_fence(); _Pragma("unroll") for (int k = k0; k < k1; k++) wg_ss_n40_ta1_tb0(av, da + vord(k) * 128, db + hoff(vord(k)), k);
        if (V_OWN > 0) {
          bar_sync<B_VOWN, 384>();
          V_RUN_SS(0, V_OWN)
          if (w == 0) TS(29);
          SCHED_FENCE();
        }
        send_max();
        bar_sync<B_VGO, 384>();
        V_RUN_RS(0, V_N1)
        if (w == 0) TS(11);
        bar_sync<B_SISS, 256>();
        V_RUN_RS(V_N1, V_N1 + V_N2)
        bar_sync<B_SSENT, 256>();
        V_RUN_SS(V_OWN + V_RS, V_K1)
        V_RUN_RS(V_N1 + V_N2, V_RS)
        const uint32_t ln = opaque(lane);
        const uint32_t amx = opaque(sb + O_MAXS + 4 * min(ln, 11u));
        SCHED_FENCE();
        mbar_wait(bar + 8 * MB_SM, par);
        const uint32_t mxl = lds1(amx);
        if (s == 0) { mbar_wait(bar + 8 * (MB_W + 11), 0); if (TRIG_LATE) asm volatile("griddepcontrol.launch_dependents;"); if (tid == 256) GTT(layer * 4 + 1, 8); }
        bar_sync<B_SLD, 256>();
        V_RUN_SS(V_K1, 20)
        wg_commit();
        V_RUN_SS((V_K1 > 20 ? V_K1 : 20), V_K2)
        wg_commit();
        wg_wait<1>();
        bar_arrive<B_VHALF, 192>();
        V_RUN_SS(V_K2, 40)
        wg_commit();
        SCHED_FENCE();
        if (w == 0) TS(12);
        {
          const float bnd = cbound * fmaxf(1.f, __uint_as_float(__reduce_max_sync(~0u, mxl)));
          const uint32_t eb = min(max(__float_as_uint(bnd) >> 23, 31u), 254u);
          sc = __uint_as_float(opaque((280u - eb) << 23));
          isc = __uint_as_float(opaque((eb - 29u) << 23));
        }
        const uint32_t pa = sb + O_QM + (ln & 7) * 128;
        const uint32_t pa0 = opaque(pa + (((ln >> 3) ^ (ln & 7)) << 4)), pa1 = opaque(pa0 ^ 64);
        const uint32_t o = O_OG + w * 256 + ln * 4;
        const uint32_t a0 = opaque(sb + o), a1 = opaque(sb1 + o + 4096), a2 = opaque(sb1 + o + 4096 + 128), a3 = opaque(sb2 + o + 2048), a4 = opaque(sb2 + o + 2048 + 128);
        const uint32_t b1 = opaque(sb1 + O_BAR + 8 * MB_OG), b2 = opaque(sb2 + O_BAR + 8 * MB_OG);
        const uint32_t c1 = opaque(0x3F803F80u);
        const uint32_t one[4] = {c1, c1, c1, c1};
        uint32_t pm[5];
        float s0[4] = {0.f, 0.f, 0.f, 0.f}, s1[4] = {0.f, 0.f, 0.f, 0.f}, s2[4] = {0.f, 0.f, 0.f, 0.f};
#define LD_AO _Pragma("unroll") for (int j = 0; j < 16; j++) if ((O_RSM >> j) & 1) ldsm4t(ao[O_IDX(j)], la_w + O_WO + (1 + (j >> 3)) * 24576 + (4 + (j & 7)) * 2048);
        if (VEND_POS == 2) bar_arrive<B_VEND, 256>();
        SCHED_FENCE();
        if (F_ORD == 0) {
          bar_sync<B_PM, 160>();
          ldsm4(pm, pa0);
          ldsm1(pm[4], pa1);
          if (VEND_POS == 0) bar_arrive<B_VEND, 256>();
          SCHED_FENCE();
        }
        wg_wait<0>();
        pin<20>(av);
        if (VEND_POS == 3) { bar_arrive<B_VEND, 256>(); SCHED_FENCE(); }
        if (w == 0) TS(13);
        if (O_RS_POS == 0) { LD_AO }
#pragma unroll
        for (int k = 0; k < 10; k++) vf[k] = pack2(av[2 * k], av[2 * k + 1]);
        if (F_ORD == 1) {
          SCHED_FENCE();
          bar_sync<B_PM, 160>();
          ldsm4(pm, pa0);
          ldsm1(pm[4], pa1);
          if (VEND_POS == 0) bar_arrive<B_VEND, 256>();
          if (O_RS_POS == 3) { LD_AO }
        }
        if (s == NSEG - 1) break;
        {
          float o0[4] = {0.f, 0.f, 0.f, 0.f}, o1[4] = {0.f, 0.f, 0.f, 0.f}, o2[4] = {0.f, 0.f, 0.f, 0.f};
          mma16816(s0, one, pm[0], pm[1]);
          mma16816(s1, one, pm[2], pm[3]);
          mma1688(s2, c1, c1, pm[4]);
          mma16816(o0, vf, pm[0], pm[1]);
          mma16816(o1, vf + 4, pm[2], pm[3]);
          mma1688(o2, vf[8], vf[9], pm[4]);
          const float i0 = rcp(s0[0] + s1[0] + s2[0]), i1 = rcp(s0[1] + s1[1] + s2[1]);
          const uint32_t p0 = pack2((o0[0] + o1[0] + o2[0]) * i0, (o0[1] + o1[1] + o2[1]) * i1), p1 = pack2((o0[2] + o1[2] + o2[2]) * i0, (o0[3] + o1[3] + o2[3]) * i1);
          sta1(a1, p0, b1); sta1(a2, p1, b1);
          sta1(a3, p0, b2); sta1(a4, p1, b2);
          sts1(a0, p0); sts1(a0 + 128, p1);
          if (O_RS_POS == 2) {
#pragma unroll
            for (int j = 0; j < 16; j++) if ((O_RSM >> j) & 1) ldsm4t(ao[O_IDX(j)], la_w + O_WO + (1 + (j >> 3)) * 24576 + (4 + (j & 7)) * 2048);
          }
          if (VEND_POS == 1) bar_arrive<B_VEND, 256>();
          fence_async();
        }
      }
      uint8_t* arp;
      uint32_t t1;
      {
        bar_sync<B_WG2, 128>();
        float c9[4], ca[4], cb[4], cc[4];
        constexpr uint64_t da = mkdesc(SB0 + O_WO, 1024, 1024, 1), db = mkdesc(SB0 + O_OG, 128, 128, 0);
#define O_RUN(acc, tile, k0, k1) _Pragma("unroll") for (int k = k0; k < k1; k++) wg_ss_n8_ta1_tb1(acc, da + (tile) * 1536 + k * 128, db + (k >> 2) * 128 + (k & 3) * 16, k);
        wg_fence();
        O_RUN(c9, 3, 0, 4)
        wg_commit();
        if (w == 0) TS(14);
        O_RUN(ca, 0, 0, 4) O_RUN(cb, 1, 0, 4) O_RUN(cc, 2, 0, 4)
        wg_commit();
        SCHED_FENCE();
        arp = ar + (s >> 2) * AR_GROUP + (s & 1) * 128 + ((s >> 1) & 1) * 512;
        uint8_t* pp = arp + opaque(prod_off);
        wg_wait<1>();
        pin<4>(c9);
        fix_red(pp + T9_OFF, c9, sc);
        SCHED_FENCE();
        if (O_RS_POS == 1) {
#pragma unroll
          for (int j = 0; j < 16; j++) if ((O_RSM >> j) & 1) ldsm4t(ao[O_IDX(j)], la_w + O_WO + (1 + (j >> 3)) * 24576 + (4 + (j & 7)) * 2048);
        }
        mbar_wait(bar + 8 * MB_OG, par);
        wg_fence();
        O_RUN(ca, 0, 4, 12)
        wg_commit();
        bar_arrive<B_VDONE, 160>();
        if (w == 0) TS(15);
#define O_MIX(acc, j0, j1) _Pragma("unroll") for (int j = j0; j < j1; j++) { const int k = 4 + (j & 7); \
          if ((O_RSM >> j) & 1) wg_rs_n8_tb1(acc, ao[O_IDX(j) < O_RS ? O_IDX(j) : 0], db + (k >> 2) * 128 + (k & 3) * 16, 1); \
          else wg_ss_n8_ta1_tb1(acc, da + (1 + (j >> 3)) * 1536 + k * 128, db + (k >> 2) * 128 + (k & 3) * 16, 1); }
        O_MIX(cb, 0, O_B1)
        wg_commit();
        if (O_MODE != 1) {
          wg_wait<1>();
          pin<4>(ca);
          if (!(EXP & 1)) fix_red(pp + tile_off(0), ca, sc);
          SCHED_FENCE();
          if (w == 0) TS(16);
          if (O_MODE == 2) {
            wg_wait<0>();
            pin<4>(cb);
            if (!(EXP & 1)) fix_red(pp + tile_off(1), cb, sc);
          }
          wg_fence();
        }
        if (O_B1 < 8) { O_MIX(cb, O_B1, 8) wg_commit(); }
        if (O_C1 < 16) {
          O_MIX(cc, 8, O_C1)
          wg_commit();
          wg_wait<1>();
          pin<4>(cb);
          if (!(EXP & 1)) fix_red(pp + tile_off(1), cb, sc);
          SCHED_FENCE();
          wg_fence();
        }
        O_MIX(cc, (O_C1 < 16 ? O_C1 : 8), 16)
        wg_commit();
        bar_arrive<B_XGO1, 256>();
        bar_arrive<B_XGO, 256>();
        if (O_MODE != 2 && O_C1 == 16) {
          wg_wait<1>();
          if (O_MODE == 1) { pin<4>(ca); if (!(EXP & 1)) fix_red(pp + tile_off(0), ca, sc); }
          pin<4>(cb);
          if (!(EXP & 1)) fix_red(pp + tile_off(1), cb, sc);
          SCHED_FENCE();
        }
        wg_wait<0>();
        pin<4>(cc);
        fix_red(pp + tile_off(2), cc, sc);
        t1 = clk();
        if (w == 3) TS(17);
      }
      pv_x(s);
      bar_arrive<B_PFREE, 256>();
      bar_arrive<B_PFREE1, 256>();
      if (w == 0) TS(28);
#pragma unroll
      for (int k = 0; k < V_RS; k++) ldsm4t(af[k], la_w + vord(V_OWN + k) * 2048);
      {
        arm();
        const int dly = w == 0 ? POLL_D0 : POLL_DELAY - (3 - w) * POLL_STEP;
        const uint32_t need = w == 0 ? 96 : ((EXP & 1) && w < 3) ? 0 : 32;
        const uint8_t* cp = arp + opaque(cons_off);
        uint4 y[4];
        int it = 0;
        while ((int)(clk() - t1) < dly) {}
        if (w == 3) TS(18);
        y[0] = ld_poll(cp); y[1] = ld_poll(cp + 256); y[2] = ld_poll(cp + 16384); y[3] = ld_poll(cp + 16384 + 256);
        if (EXP & 2) {} else if (EVF) { const uint64_t pol = policy_evict_first(); stg4h(op, oq0, pol); stg4h(op + 512, oq1, pol); } else { stg4(op, oq0); stg4(op + 512, oq1); }
        uint32_t p[8];
        const float isl = isc * 0.5f, bias = -(float)(need >> 3) * isl;
        while (true) {
          const uint32_t bad = ((y[0].x ^ need) | (y[0].z ^ need) | (y[1].x ^ need) | (y[1].z ^ need)) | ((y[2].x ^ need) | (y[2].z ^ need) | (y[3].x ^ need) | (y[3].z ^ need));
          const bool again = __any_sync(~0u, (bad & 127u) != 0);
          if (SPEC_DEC || !again) {
#pragma unroll
            for (int k = 0; k < 4; k++) {
              p[2 * k] = pack2(fmaf((float)(int)__funnelshift_r(y[k].x, y[k].y, 3), isl, bias), fmaf((float)(int)__funnelshift_r(y[k].z, y[k].w, 3), isl, bias));
              p[2 * k + 1] = pack2((float)(int)y[k].y * isc, (float)(int)y[k].w * isc);
            }
            if (SPEC_DEC) {
#pragma unroll
              for (int k = 0; k < 8; k++) asm volatile("" : "+r"(p[k]));
            }
          }
          if (!again) break;
          if (++it > 2000000) __trap();
          y[0] = ld_poll(cp); y[1] = ld_poll(cp + 256); y[2] = ld_poll(cp + 16384); y[3] = ld_poll(cp + 16384 + 256);
        }
        TS(19 + w);
        forward(p);
      }
    }
    if (VEND_POS == 1) bar_arrive<B_VEND, 256>();
    bar_arrive<B_VDONE, 160>();
    bar_arrive<B_XGO1, 256>();
    bar_arrive<B_XGO, 256>();
    pv_x(NSEG - 1);
    if (EVF) { const uint64_t pol = policy_evict_first(); stg4h(op, oq0, pol); stg4h(op + 512, oq1, pol); } else { stg4(op, oq0); stg4(op + 512, oq1); }
    bar_sync<B_WG2, 128>();
    if (tid == 256) { red_release(flags + FL_A + (e0 >> 10) * 8 + (NSEG - 1) * 48, 1); }
    __syncwarp();
  }
  asm volatile("barrier.cluster.arrive.relaxed.aligned;\nbarrier.cluster.wait.aligned;" ::: "memory");
  GT(layer * 4 + 1, 2);
  if (wid == 0) asm volatile("griddepcontrol.wait;" ::: "memory");
}

constexpr int P_B = 0, P_A = 131072, P_BAR = 196608, OPC_SMEM = P_BAR + 256;
#define PF_C 2
#define PF_S0 43
constexpr int OP_KR = 48;

__global__ void __launch_bounds__(384, 1)
opc_kernel(const __grid_constant__ CUtensorMap tmo, bf16* __restrict__ out, int layer,
           const bf16* __restrict__ Wq, const bf16* __restrict__ Wk, const bf16* __restrict__ Wv, const bf16* __restrict__ Wo) {
  extern __shared__ __align__(1024) uint8_t smem[];
  asm volatile("griddepcontrol.launch_dependents;");
  GT(layer * 4 + 2, 0);
  const uint32_t sb = smem_u32(smem);
  check_smem_base(sb);
  const int tid = threadIdx.x, wid = __shfl_sync(~0u, tid >> 5, 0), wg = wid >> 2, w = wid & 3, lane = tid & 31;
  const uint32_t bar = sb + P_BAR;
  uint32_t* flags = g_zero + Z_FLAGS + layer * FL_LAYER;
  float* acc = g_acc + layer * (S_TOK * DM);
  const uint64_t pol = policy_evict_first();
  if (wid == 0) {
    if (lane < 16) mbar_init(bar + 8 * lane, (lane == 8 || lane == 9) ? 8 : 1);
    fence_async();
  }
  __syncthreads();
  if (blockIdx.x < 30) {
    const int cg = blockIdx.x % 5, kg = blockIdx.x / 5;
    if (wg < 2) {
      asm volatile("setmaxnreg.inc.sync.aligned.u32 240;");
      uint32_t a[OP_KR][4];
      const uint32_t la = sb + P_B + ((lane >> 4) * 8 + (lane & 7)) * 128 + (((2 * w + ((lane >> 3) & 1)) ^ (lane & 7)) << 4);
      mbar_wait(bar + 80, 0);
#pragma unroll
      for (int k = 0; k < 32; k++) ldsm4t(a[k], la + wg * 65536 + k * 2048);
      bar_arrive<2, 288>();
      mbar_wait(bar + 88, 0);
#pragma unroll
      for (int k = 0; k < 16; k++) ldsm4t(a[32 + k], la + wg * 32768 + k * 2048);
      bar_arrive<3, 288>();
      mbar_wait(bar + 96, 0);
      float* ap = acc + (cg * 8 + wg * 4 + w) * 512 + lane * 4;
      for (int s = 0; s < NSEG; s++) {
        const int buf = s & 1;
        const uint32_t par = (s >> 1) & 1;
        float d[16];
        const uint64_t db = mkdesc(SB0 + P_B + buf * 65536, 512, 128, 0), da = mkdesc(SB0 + P_A + wg * 32768, 1024, 1024, 1);
        float* p = ap + s * (32 * DM);
        if (kg < 4 && s + 2 < NSEG) { if (EVF) stg4h(p + 2 * 32 * DM + kg * 128, make_uint4(0, 0, 0, 0), pol); else stg4(p + 2 * 32 * DM + kg * 128, make_uint4(0, 0, 0, 0)); }
#pragma unroll
        for (int q = 0; q < 4; q++) {
          mbar_wait(bar + 8 * (buf * 4 + q), par);
          wg_fence();
#pragma unroll
          for (int k = 16 * q; k < 16 * q + 16; k++) {
            if (k < OP_KR) wg_rs_n32_tb1(d, a[k < OP_KR ? k : 0], db + k * 64, k);
            else wg_ss_n32_ta1_tb1(d, da + (k - OP_KR) * 128, db + k * 64, 1);
          }
        }
        wg_commit();
        wg_wait<0>();
        pin<16>(d);
        if (lane == 0) mbar_arrive(bar + 8 * (8 + buf));
        if (s == NSEG - 1) GT(layer * 4 + 2, 6);
        if (EVF) {
          red4fh(p, d[0], d[1], d[4], d[5], pol);
          red4fh(p + 128, d[8], d[9], d[12], d[13], pol);
          red4fh(p + 256, d[2], d[3], d[6], d[7], pol);
          red4fh(p + 384, d[10], d[11], d[14], d[15], pol);
        } else {
          red4f(p, d[0], d[1], d[4], d[5]);
          red4f(p + 128, d[8], d[9], d[12], d[13]);
          red4f(p + 256, d[2], d[3], d[6], d[7]);
          red4f(p + 384, d[10], d[11], d[14], d[15]);
        }
        bar_sync<1, 256>();
        if (tid == 0) { red_release(flags + FL_B + s * 8, 1); }
        __syncwarp();
      }
    } else {
      asm volatile("setmaxnreg.dec.sync.aligned.u32 24;");
      if (w == 0) {
        if (lane == 0) { mbar_expect(bar + 80, 131072); mbar_expect(bar + 96, 65536); mbar_expect(bar + 88, 65536); }
        __syncwarp();
        if (lane < 16) tma2d(sb + P_B + lane * 8192, &tmo, cg * 128 + (lane >> 3) * 64, kg * 1024 + (lane & 7) * 64, bar + 80);
        else if (lane < 24) tma2d(sb + P_B + lane * 8192, &tmo, cg * 128 + ((lane >> 2) & 1) * 64, kg * 1024 + 768 + (lane & 3) * 64, bar + 96);
        bar_sync<2, 288>();
        fence_async();
        if (lane < 8) tma2d(sb + P_B + lane * 8192, &tmo, cg * 128 + (lane >> 2) * 64, kg * 1024 + 512 + (lane & 3) * 64, bar + 88);
        bar_sync<3, 288>();
        for (int s = 0; s < NSEG; s++) {
          const int buf = s & 1;
          if (s >= 2) mbar_wait(bar + 8 * (8 + buf), ((s >> 1) & 1) ^ 1);
          if (s >= 2) wait_flag(flags + FL_B + (s - 2) * 8, 30);
          wait_flag(flags + FL_A + s * 48 + kg * 8, 16);
          fence_async_global();
          if (lane < 4) {
            mbar_expect(bar + 8 * (buf * 4 + lane), 16384);
            if (EVF) bulk_g2sh(sb + P_B + buf * 65536 + lane * 16384, g_ot + (size_t)s * (HE * 64) + kg * 65536 + lane * 16384, 16384, bar + 8 * (buf * 4 + lane), pol);
            else bulk_g2s(sb + P_B + buf * 65536 + lane * 16384, g_ot + (size_t)s * (HE * 64) + kg * 65536 + lane * 16384, 16384, bar + 8 * (buf * 4 + lane));
            if (s == NSEG - 1 && lane == 0) GTT(layer * 4 + 2, 5);
          }
          __syncwarp();
        }
      } else if (w == 1 && layer == 0) {
#pragma unroll 1
        for (int q = 4 * (4 - PF_C); q < 18; q++) {
          wait_flag(flags + FL_A + (PF_S0 + q) * 48 + kg * 8, 16);
          const int m = q >> 2;
          const uint8_t* W = m == 0 ? (const uint8_t*)Wo : m == 1 ? (const uint8_t*)Wv : m == 2 ? (const uint8_t*)Wk : m == 3 ? (const uint8_t*)Wq : (q & 1) ? g_w2 : g_w1;
          const int n = m < 4 ? 512 : (q & 1) ? 214 : 640, l0 = m < 4 ? blockIdx.x * 2048 + (q & 3) * 512 : blockIdx.x * n, lim = m < 4 ? 61440 : (q & 1) ? 6400 : 19200;
#pragma unroll 1
          for (int k = lane; k < n; k += 32) {
            if (l0 + k < lim) asm volatile("prefetch.global.L2 [%0];" :: "l"(W + (size_t)(l0 + k) * 128));
            __nanosleep(100);
          }
        }
      }
    }
  } else {
    constexpr int LD = 644;
    float* xs = (float*)smem;
    uint32_t par = 0;
    for (int task = blockIdx.x - 30; task < 2 * NSEG; task += 6, par ^= 1) {
      const int s = task >> 1, jj = task & 1;
      if (tid == 0) {
        mbar_expect(bar, 20480);
        bulk_g2s(sb + 49152, g_x + task * 16 * DM, 20480, bar);
      }
      if (wid == 1) { wait_flag(flags + FL_B + s * 8, 30); if (s == NSEG - 1 && lane == 0) GTT(layer * 4 + 2, 7); }
      __syncthreads();
      if (wid < 10) {
        float4 v[8];
#pragma unroll
        for (int k = 0; k < 8; k++) v[k] = EVF ? ldg4fh(acc + s * (32 * DM) + (wid * 8 + k) * 256 + jj * 128 + lane * 4, pol) : __ldcg((const float4*)(acc + s * (32 * DM) + (wid * 8 + k) * 256 + jj * 128 + lane * 4));
        float* xp = xs + (lane & 3) * 2 * LD + wid * 64 + (lane >> 2);
#pragma unroll
        for (int k = 0; k < 8; k++) { xp[k * 8] = v[k].x; xp[LD + k * 8] = v[k].y; xp[8 * LD + k * 8] = v[k].z; xp[9 * LD + k * 8] = v[k].w; }
      }
      mbar_wait(bar, par);
      __syncthreads();
#pragma unroll 1
      for (int row = wid; row < 16; row += 12) {
        const int tk = task * 16 + row;
        float v[20], sum = 0.f;
        const int pj = (lane & 24) + 2 * (lane & 3) + ((lane >> 2) & 1);
        bf16* dst = out ? out + tk * DM + lane * 2 : g_x + tk * DM + pj * 2;
#pragma unroll
        for (int k = 0; k < 10; k++) {
          const float2 u = *(const float2*)(xs + row * LD + k * 64 + lane * 2);
          const uint32_t r = *(const uint32_t*)(smem + 49152 + row * 1280 + k * 128 + pj * 4);
          v[2 * k] = u.x + bflo(r); v[2 * k + 1] = u.y + bfhi(r); sum += v[2 * k] + v[2 * k + 1];
          *(uint32_t*)(dst + k * 64) = pack2(v[2 * k], v[2 * k + 1]);
        }
        if (!out) {
#pragma unroll
          for (int o = 16; o; o >>= 1) sum += __shfl_xor_sync(~0u, sum, o);
          const float m = sum * (1.f / DM);
          float q = 0.f;
#pragma unroll
          for (int k = 0; k < 20; k++) { v[k] -= m; q += v[k] * v[k]; }
#pragma unroll
          for (int o = 16; o; o >>= 1) q += __shfl_xor_sync(~0u, q, o);
          const float rs = rsqrtf(q * (1.f / DM) + 1e-5f);
          uint8_t* xp = g_xt + (tk >> 7) * 163840 + (tk & 127) * 128 + (((lane >> 2) ^ (tk & 7)) << 4) + (lane & 3) * 4;
#pragma unroll
          for (int k = 0; k < 10; k++) *(uint32_t*)(xp + k * 16384) = pack2(v[2 * k] * rs, v[2 * k + 1] * rs);
        }
      }
      fence_async();
      __syncthreads();
      if (tid == 0 && !out) { red_release(flags + FL_LAYER + FL_T + (task >> 3) * 8, 1); }
    }
  }
  GT(layer * 4 + 2, 1);
  __syncwarp();
  asm volatile("griddepcontrol.wait;" ::: "memory");
  GT(layer * 4 + 2, 2);
}

constexpr int L_STAGE = 47104;
constexpr int L_KV = 0, L_B2 = 43008;
constexpr int L_W2 = 122880, L_BAR = L_W2 + 102400;
constexpr int LA_SMEM = L_BAR + 256;
__device__ __forceinline__ float phi(float t) { return (fmaxf(t, 0.f) + 1e-6f) + ex2(fminf(t * 1.4426950408889634f, 0.f)); }
__device__ __forceinline__ uint32_t phi2(float a, float b) { return pack2(phi(a), phi(b)); }
#define LA_LATE 6
#define PF_N0 2
#define PF_N1 0
#define PF_SLEEP 300

__global__ void __launch_bounds__(384, 1)
la_kernel(const bf16* __restrict__ xin, const bf16* __restrict__ Wq, const bf16* __restrict__ Wk, const bf16* __restrict__ Wv,
          const bf16* __restrict__ Wo, uint8_t* __restrict__ ar, int layer) {
  extern __shared__ __align__(1024) uint8_t smem[];
  const uint32_t sb = smem_u32(smem);
  check_smem_base(sb);
  const int tid = threadIdx.x, wid = __shfl_sync(~0u, tid >> 5, 0), wg = wid >> 2, w = wid & 3, lane = tid & 31, g = lane >> 2, i4 = lane & 3;
  const int cr = blockIdx.x & 1, hg = (blockIdx.x >> 1) & 7, tb = (blockIdx.x >> 4) * 2 + cr;
  const uint32_t bar = sb + L_BAR;
  uint32_t* flags = g_zero + Z_FLAGS + layer * FL_LAYER;
  asm volatile("griddepcontrol.launch_dependents;");
  GT(layer * 4, 0);
  if (wid == 0) {
    if (lane < 20) mbar_init(bar + 8 * lane, (lane >= 4 && lane < 8) ? (blockIdx.x < 128 ? 16 : 8) : lane >= 17 ? 8 : 1);
    asm volatile("fence.mbarrier_init.release.cluster;" ::: "memory");
    fence_async();
  }
  if (blockIdx.x >= 128) {
    __syncthreads();
    const int q = blockIdx.x - 128;
    const uint8_t* src = (const uint8_t*)Wo + q * 1966080;
    if (wid == 11) {
#pragma unroll 1
      for (int it = 0; it < 48; it++) {
        const int st = it & 3;
        if (it >= 4) mbar_wait(bar + 8 * (4 + st), ((it >> 2) & 1) ^ 1);
        if (lane == 0) mbar_expect(bar + 8 * st, 40960);
        __syncwarp();
        if (lane < 4) bulk_g2s(sb + st * 40960 + lane * 10240, src + it * 40960 + lane * 10240, 10240, bar + 8 * st);
      }
    } else if (wid < 8) {
      float c[20];
#pragma unroll
      for (int k = 0; k < 20; k++) c[k] = 0.f;
#pragma unroll 1
      for (int it = 0; it < 48; it++) {
        const int st = it & 3;
        mbar_wait(bar + 8 * st, (it >> 2) & 1);
#pragma unroll
        for (int k = 0; k < 20; k++) {
          const float2 u = lds2f(sb + st * 40960 + wid * 5120 + k * 256 + lane * 8);
          const uint32_t x = __float_as_uint(u.x), y = __float_as_uint(u.y);
          float* d = c + (k % 5) * 4;
          d[0] = fmaf(bflo(x), bflo(x), d[0]); d[1] = fmaf(bfhi(x), bfhi(x), d[1]); d[2] = fmaf(bflo(y), bflo(y), d[2]); d[3] = fmaf(bfhi(y), bfhi(y), d[3]);
        }
        __syncwarp();
        if (lane == 0) mbar_arrive(bar + 8 * (4 + st));
      }
      float* red = (float*)(smem + 163840);
#pragma unroll
      for (int k = 0; k < 5; k++) *(float4*)(red + wid * DM + k * 128 + lane * 4) = make_float4(c[4 * k], c[4 * k + 1], c[4 * k + 2], c[4 * k + 3]);
      bar_sync<1, 256>();
      for (int k = tid; k < DM; k += 256) {
        float t = 0.f;
#pragma unroll
        for (int j = 0; j < 8; j++) t += red[j * DM + k];
        g_nrm[q * DM + k] = t;
      }
      asm volatile("griddepcontrol.wait;" ::: "memory");
      bar_sync<1, 256>();
      if (tid == 0) red_release(flags + FL_N, 1);
      GT(0, 2);
    }
    return;
  }
  __syncthreads();
  asm volatile("barrier.cluster.arrive.relaxed.aligned;" ::: "memory");
  if (layer == 0) asm volatile("griddepcontrol.wait;" ::: "memory");
  asm volatile("barrier.cluster.wait.aligned;" ::: "memory");
  if (wg == 2) {
    asm volatile("setmaxnreg.dec.sync.aligned.u32 40;");
    if (w == 0) {
      if (lane < 4) {
        mbar_expect(bar + 8 * lane, L_STAGE);
        bulk_g2s_mc(sb + lane * L_STAGE + 16384 + cr * 15360, g_w1 + (hg * 10 + lane) * 30720 + cr * 15360, 15360, bar + 8 * lane);
      }
      if (layer == 1) { if (LA_LATE) wait_flag(flags + FL_T + 15 * 8, LA_LATE); wait_flag(flags + FL_T + tb * 8, 8); fence_async_global(); }
      if (lane < 4) bulk_g2s(sb + lane * L_STAGE, g_xt + (tb * 10 + lane) * 16384, 16384, bar + 8 * lane);
#pragma unroll 1
      for (int kc = 4; kc < 10; kc++) {
        const int st = kc & 3;
        mbar_wait(bar + 8 * (4 + st), ((kc >> 2) & 1) ^ 1);
        if (lane == 0) {
          mbar_expect(bar + 8 * st, L_STAGE);
          bulk_g2s_mc(sb + st * L_STAGE + 16384 + cr * 15360, g_w1 + (hg * 10 + kc) * 30720 + cr * 15360, 15360, bar + 8 * st);
          bulk_g2s(sb + st * L_STAGE, g_xt + (tb * 10 + kc) * 16384, 16384, bar + 8 * st);
        }
        __syncwarp();
      }
      mbar_wait(bar + 8 * 6, 1);
      mbar_wait(bar + 8 * 7, 1);
      if (lane == 0) mbar_expect(bar + 64, 102400);
      if (lane < 8) mbar_expect(bar + 8 * (9 + lane), 20480);
      __syncwarp();
      if (lane < 2) bulk_g2s_mc(sb + L_W2 + (cr * 2 + lane) * 25600, g_w2 + hg * 102400 + (cr * 2 + lane) * 25600, 25600, bar + 64);
      bar_sync<2, 288>();
      if (lane == 0) { red_release(flags + FL_O + tb * 8, 1); }
      wait_flag(flags + FL_O + tb * 8, 8);
      fence_async_global();
      if (lane < 6) bulk_g2s(sb + lane * 20480, g_oa + (tb * 8 + lane) * 20480, 20480, bar + 8 * (9 + lane));
#pragma unroll 1
      for (int p = 6; p < 8; p++) {
        mbar_wait(bar + 8 * (17 + p - 6), 0);
        if (lane == 0) bulk_g2s(sb + (p - 6) * 20480, g_oa + (tb * 8 + p) * 20480, 20480, bar + 8 * (9 + p));
      }
    } else {
      const int t = tid - 288;
#pragma unroll 1
      for (int k = t; k < 768; k += 96) *(uint4*)(ar + blockIdx.x * 12288 + k * 16) = make_uint4(0, 0, 0, 0);
      if (layer == 0) {
        float sv = 0.f;
        const uint4* pv = (const uint4*)((const uint8_t*)Wv + blockIdx.x * 61440) + t;
#pragma unroll 1
        for (int k = 0; k < 40; k += 5) {
          uint4 v[5];
#pragma unroll
          for (int j = 0; j < 5; j++) v[j] = __ldg(pv + (k + j) * 96);
#pragma unroll
          for (int j = 0; j < 5; j++) {
            sv = fmaf(bflo(v[j].x), bflo(v[j].x), fmaf(bfhi(v[j].x), bfhi(v[j].x), fmaf(bflo(v[j].y), bflo(v[j].y), fmaf(bfhi(v[j].y), bfhi(v[j].y), sv))));
            sv = fmaf(bflo(v[j].z), bflo(v[j].z), fmaf(bfhi(v[j].z), bfhi(v[j].z), fmaf(bflo(v[j].w), bflo(v[j].w), fmaf(bfhi(v[j].w), bfhi(v[j].w), sv))));
          }
        }
#pragma unroll
        for (int o = 16; o; o >>= 1) sv += __shfl_xor_sync(~0u, sv, o);
        if (lane == 0) atomicAdd((float*)(g_zero + Z_NORM), sv);
      }
#pragma unroll 1
      for (int k = 0; k < 5 * (layer ? PF_N1 : PF_N0); k++) {
        const int m = k / 5;
        const bf16* W = m == 0 ? Wq : m == 1 ? Wk : m == 2 ? Wv : Wo;
        asm volatile("prefetch.global.L2 [%0];" :: "l"((const uint8_t*)W + blockIdx.x * 61440 + (k - m * 5) * 12288 + t * 128));
        __nanosleep(PF_SLEEP);
      }
      if (t == 0) GTT(layer * 4, 14);
      bar_arrive<3, 352>();
    }
  } else {
    asm volatile("setmaxnreg.inc.sync.aligned.u32 232;");
    GT(layer * 4, 4);
    uint32_t pq[5][4];
    const int row0 = tb * 128 + wg * 64 + 16 * w + g;
    float* kv = (float*)(g_zero + Z_KV) + layer * KV_LAYER + hg * 1920;
    if (layer == 1) wait_flag(flags + FL_T + tb * 8, 8);
    uint32_t r[20];
    if (xin) {
      const bf16* xp = xin + row0 * DM + hg * 80 + 2 * i4;
#pragma unroll
      for (int j = 0; j < 10; j++) { r[2 * j] = __ldg((const uint32_t*)(xp + 8 * j)); r[2 * j + 1] = __ldg((const uint32_t*)(xp + 8 * DM + 8 * j)); }
    } else {
      const bf16* xp = g_x + row0 * DM + hg * 80 + 4 * i4;
#pragma unroll
      for (int j = 0; j < 5; j++) {
        const uint2 u = __ldcg((const uint2*)(xp + 16 * j)), v = __ldcg((const uint2*)(xp + 8 * DM + 16 * j));
        r[4 * j] = u.x; r[4 * j + 2] = u.y; r[4 * j + 1] = v.x; r[4 * j + 3] = v.y;
      }
    }
    {
      float d[120];
#pragma unroll 1
      for (int kc = 0; kc < 10; kc++) {
        const int st = kc & 3;
        const uint64_t da = mkdesc(SB0 + st * L_STAGE + wg * 8192, 16, 1024, 1), db = mkdesc(SB0 + st * L_STAGE + 16384, 3840, 128, 0);
        mbar_wait(bar + 8 * st, (kc >> 2) & 1);
        wg_fence();
#pragma unroll
        for (int k = 0; k < 4; k++) wg_ss_n240_ta0_tb1(d, da + 2 * k, db + k * 480, kc | k);
        wg_commit();
        if (kc > 0) { wg_wait<1>(); if (lane < 2) mbar_arrive_cl(mapa(bar + 8 * (4 + ((kc - 1) & 3)), lane)); }
      }
      wg_wait<0>();
      pin<120>(d);
      GT(layer * 4, 5);
      bar_sync<1, 256>();
      const uint32_t kb = sb + L_KV + (wg * 8 + 2 * w + ((lane >> 3) & 1)) * 2688 + (lane >> 4) * 128 + (lane & 7) * 16;
#pragma unroll
      for (int j = 0; j < 5; j++) stsm4(kb + 1280 + j * 256, pack2(d[80 + 8 * j], d[81 + 8 * j]), pack2(d[82 + 8 * j], d[83 + 8 * j]), pack2(d[84 + 8 * j], d[85 + 8 * j]), pack2(d[86 + 8 * j], d[87 + 8 * j]));
      stsm2(kb + 2560, 0x3F803F80u, 0x3F803F80u);
#pragma unroll
      for (int j = 0; j < 5; j++) stsm4(kb + j * 256, phi2(d[40 + 8 * j], d[41 + 8 * j]), phi2(d[42 + 8 * j], d[43 + 8 * j]), phi2(d[44 + 8 * j], d[45 + 8 * j]), phi2(d[46 + 8 * j], d[47 + 8 * j]));
      fence_async();
      bar_sync<1, 256>();
      float e[44];
      {
        const uint64_t da = mkdesc(SB0 + L_KV + wg * 1024, 2688, 128, 0), db = mkdesc(SB0 + L_KV + 1280, 2688, 128, 0);
        wg_fence();
#pragma unroll
        for (int k = 0; k < 8; k++) wg_ss_n88_ta1_tb1(e, da + k * 336, db + k * 336, k);
        wg_commit();
        wg_wait<0>();
        pin<44>(e);
      }
#pragma unroll
      for (int h = 0; h < 2; h++) {
        const int row = wg * 64 + 16 * w + 8 * h + g;
        const int c = row < 80 ? 2 * i4 - (row / 20) * 20 : 100;
        float* dst = kv + row * 24 + c;
#pragma unroll
        for (int j = 0; j < 10; j++)
          asm volatile("{\n.reg .pred p;\nsetp.lt.u32 p, %3, 20;\n@p red.relaxed.gpu.global.add.v2.f32 [%0], {%1,%2};\n}" :: "l"(dst + 8 * j), "f"(e[4 * j + 2 * h]), "f"(e[4 * j + 2 * h + 1]), "r"(c + 8 * j) : "memory");
        asm volatile("{\n.reg .pred p;\nsetp.ne.u32 p, %2, 0;\n@p red.relaxed.gpu.global.add.f32 [%0], %1;\n}" :: "l"(kv + row * 24 + 20), "f"(e[40 + 2 * h]), "r"((int)(row < 80 && i4 == 0)) : "memory");
      }
      bar_sync<1, 256>();
      GT(layer * 4, 6);
      if (tid == 0) { red_release(flags + FL_KV + hg * 8, 1); }
      __syncwarp();
      pin<40>(d);
#pragma unroll
      for (int k = 0; k < 5; k++) {
        pq[k][0] = phi2(d[8 * k], d[8 * k + 1]); pq[k][1] = phi2(d[8 * k + 2], d[8 * k + 3]);
        pq[k][2] = phi2(d[8 * k + 4], d[8 * k + 5]); pq[k][3] = phi2(d[8 * k + 6], d[8 * k + 7]);
      }
    }
#pragma unroll 1
    for (int k = tid; k < 1600; k += 256) sts4(sb + L_B2 + k * 16, 0, 0, 0, 0);
    GT(layer * 4, 7);
    if (wid == 0) wait_flag(flags + FL_KV + hg * 8, 16);
    GT(layer * 4, 8);
    bar_sync<1, 256>();
    if (tid < 240) {
      const int dd = tid / 3, part = tid - dd * 3, n = (dd / 20) * 20 + 8 * part;
      const float4 v0 = __ldcg((const float4*)(kv + dd * 24 + 8 * part)), v1 = __ldcg((const float4*)(kv + dd * 24 + 8 * part + 4));
      const float z = __ldcg(kv + dd * 24 + 20);
      const uint32_t a = sb + L_B2 + (dd >> 3) * 2560 + (dd & 7) * 16, zz = pack2(z, z);
      const uint32_t a0 = a + (n >> 3) * 128 + (n & 7) * 2, a1 = a + ((n + 4) >> 3) * 128 + ((n + 4) & 7) * 2;
      sts2(a0, pack2(v0.x, v0.y), pack2(v0.z, v0.w)); sts2(a0 + 1280, zz, zz);
      if (part < 2) { sts2(a1, pack2(v1.x, v1.y), pack2(v1.z, v1.w)); sts2(a1 + 1280, zz, zz); }
    }
    fence_async();
    bar_sync<1, 256>();
    {
      float o[80];
      const uint64_t db = mkdesc(SB0 + L_B2, 2560, 128, 0);
      wg_fence();
#pragma unroll
      for (int k = 0; k < 5; k++) wg_rs_n160_tb1(o, pq[k], db + k * 320, k);
      wg_commit();
      wg_wait<0>();
      pin<80>(o);
      uint8_t* op = g_oa + (tb * 8 + hg) * 20480 + (wg * 8 + 2 * w) * 128 + lane * 4;
#pragma unroll
      for (int j = 0; j < 20; j++) {
        const float inv = rcp(o[40 + 2 * j] + 1e-6f);
        *(uint32_t*)(op + (j >> 1) * 2048 + (j & 1) * 128) = pack2(o[2 * j] * inv, o[2 * j + 1] * inv);
      }
      GT(layer * 4, 9);
      bar_arrive<2, 288>();
    }
    float d[40];
    mbar_wait(bar + 64, 0);
#pragma unroll 1
    for (int p = 0; p < 8; p++) {
      const uint64_t da = mkdesc(SB0 + (p < 6 ? p : p - 6) * 20480 + wg * 1024, 2048, 128, 0), db = mkdesc(SB0 + L_W2 + p * 12800, 1280, 128, 0);
      mbar_wait(bar + 8 * (9 + p), 0);
      if (p == 0) GT(layer * 4, 11);
      wg_fence();
#pragma unroll
      for (int k = 0; k < 5; k++) wg_ss_n80_ta0_tb1(d, da + k * 256, db + k * 160, p | k);
      wg_commit();
      wg_wait<1>();
      if (lane == 0 && (p == 1 || p == 2)) mbar_arrive(bar + 8 * (17 + p - 1));
    }
    wg_wait<0>();
    pin<40>(d);
    GT(layer * 4, 12);
    float mean[2], m2[2];
#pragma unroll
    for (int h = 0; h < 2; h++) {
      float sum = 0.f;
#pragma unroll
      for (int j = 0; j < 10; j++) { d[4 * j + 2 * h] += bflo(r[2 * j + h]); d[4 * j + 2 * h + 1] += bfhi(r[2 * j + h]); sum += d[4 * j + 2 * h] + d[4 * j + 2 * h + 1]; }
      sum += __shfl_xor_sync(~0u, sum, 1); sum += __shfl_xor_sync(~0u, sum, 2);
      mean[h] = sum * (1.f / 80.f);
      float q = 0.f;
#pragma unroll
      for (int j = 0; j < 10; j++) { const float a = d[4 * j + 2 * h] - mean[h], b = d[4 * j + 2 * h + 1] - mean[h]; q = fmaf(a, a, fmaf(b, b, q)); }
      q += __shfl_xor_sync(~0u, q, 1); q += __shfl_xor_sync(~0u, q, 2);
      m2[h] = q;
    }
    float2* st = g_stats + (layer * S_TOK + row0) * 8;
    if (i4 < 2) {
      const float a = i4 ? mean[1] : mean[0], b = i4 ? m2[1] : m2[0];
      asm volatile("{\n.reg .b64 t;\nmov.b64 t, {%1,%2};\nst.relaxed.gpu.global.b64 [%0], t;\n}" :: "l"(st + i4 * 64 + hg), "r"(__float_as_uint(a)), "r"(__float_as_uint(b) & 0x7FFFFFFFu) : "memory");
    }
    uint4 y0, y1;
    int it = 0;
    while (true) {
      y0 = ld_poll(st + 2 * i4); y1 = ld_poll(st + 64 + 2 * i4);
      if (!__any_sync(~0u, (int)(y0.y | y0.w | y1.y | y1.w) < 0)) break;
      if (++it > 2000000) __trap();
    }
    GT(layer * 4, 13);
#pragma unroll
    for (int h = 0; h < 2; h++) {
      const uint4 y = h ? y1 : y0;
      const float ma = __uint_as_float(y.x), mb = __uint_as_float(y.z);
      float sm = ma + mb;
      sm += __shfl_xor_sync(~0u, sm, 1); sm += __shfl_xor_sync(~0u, sm, 2);
      const float mu = sm * 0.125f;
      float q = __uint_as_float(y.y) + __uint_as_float(y.w) + 80.f * ((ma - mu) * (ma - mu) + (mb - mu) * (mb - mu));
      q += __shfl_xor_sync(~0u, q, 1); q += __shfl_xor_sync(~0u, q, 2);
      const float rs = rsqrtf(q * (1.f / DM) + 1e-5f), sh = -mu * rs;
      const int tk = row0 + 8 * h;
      uint8_t* xp = g_xn + (tk >> 5) * 40960 + (tk & 31) * 128 + (i4 & 1) * 8;
#pragma unroll
      for (int jj = 0; jj < 5; jj++) {
        const int b16 = hg * 5 + jj;
        const float* a = d + 8 * jj + 2 * h;
        *(uint2*)(xp + (b16 >> 2) * 4096 + (((2 * (b16 & 3) + (i4 >> 1)) ^ g) << 4)) =
            make_uint2(pack2(fmaf(a[0], rs, sh), fmaf(a[1], rs, sh)), pack2(fmaf(a[4], rs, sh), fmaf(a[5], rs, sh)));
      }
    }
    {
      bf16* xp = g_x + row0 * DM + hg * 80 + 4 * i4;
#pragma unroll
      for (int j = 0; j < 5; j++) {
        *(uint2*)(xp + 16 * j) = make_uint2(pack2(d[8 * j], d[8 * j + 1]), pack2(d[8 * j + 4], d[8 * j + 5]));
        *(uint2*)(xp + 8 * DM + 16 * j) = make_uint2(pack2(d[8 * j + 2], d[8 * j + 3]), pack2(d[8 * j + 6], d[8 * j + 7]));
      }
    }
    bar_sync<3, 352>();
    if (tid == 0) { red_release(flags + FL_X, 1); }
    GT(layer * 4, 2);
    if (wid == 7) asm volatile("griddepcontrol.wait;" ::: "memory");
  }
}

__global__ void __launch_bounds__(256) prep_kernel(const bf16* __restrict__ x, const bf16* __restrict__ wqkv, const bf16* __restrict__ wo) {
  asm volatile("griddepcontrol.launch_dependents;");
  const int b = blockIdx.x, tid = threadIdx.x, lane = tid & 31;
  if (b < 160) GT(3, 0);
  if (b < 256) {
    const int row = b * 8 + (tid >> 5);
    float v[20], s = 0.f;
#pragma unroll
    for (int k = 0; k < 10; k++) { const uint32_t u = __ldg((const uint32_t*)(x + row * DM + k * 64 + lane * 2)); v[2 * k] = bflo(u); v[2 * k + 1] = bfhi(u); s += v[2 * k] + v[2 * k + 1]; }
#pragma unroll
    for (int o = 16; o; o >>= 1) s += __shfl_xor_sync(~0u, s, o);
    const float m = s * (1.f / DM);
    float q = 0.f;
#pragma unroll
    for (int k = 0; k < 20; k++) { v[k] -= m; q += v[k] * v[k]; }
#pragma unroll
    for (int o = 16; o; o >>= 1) q += __shfl_xor_sync(~0u, q, o);
    const float r = rsqrtf(q * (1.f / DM) + 1e-5f);
#pragma unroll
    for (int k = 0; k < 10; k++)
      *(uint32_t*)(g_xt + ((row >> 7) * 10 + k) * 16384 + (row & 127) * 128 + (((lane >> 2) ^ (row & 7)) << 4) + (lane & 3) * 4) = pack2(v[2 * k] * r, v[2 * k + 1] * r);
  } else if (b < 256 + 200) {
#pragma unroll
    for (int it = 0; it < 4; it++) {
      const int u = (b - 256) * 1024 + it * 256 + tid;
      if (u < 153600) {
        const int k8 = u & 7, nb = (u >> 3) % 30, kg = (u / 240) % 80, hg = u / 19200;
        *(uint4*)(g_w1 + u * 16) = __ldg((const uint4*)(wqkv + (kg * 8 + k8) * 1920 + (nb / 10) * 640 + hg * 80 + (nb % 10) * 8));
      } else {
        const int v = u - 153600, k8 = v & 7, nb = (v >> 3) % 10, kg = (v / 80) % 80, hg = v / 6400;
        *(uint4*)(g_w2 + v * 16) = __ldg((const uint4*)(wo + (kg * 8 + k8) * DM + hg * 80 + nb * 8));
      }
    }
  } else {
    const int t = (b - 456) * 256 + tid;
    for (int k = t; k < Z_END / 4; k += 16 * 256) ((uint4*)g_zero)[k] = make_uint4(0, 0, 0, 0);
    for (int k = t; k < 2 * S_TOK * 4; k += 16 * 256) ((uint4*)g_stats)[k] = make_uint4(~0u, ~0u, ~0u, ~0u);
    for (int k = t; k < 16 * DM; k += 16 * 256) { ((uint4*)g_acc)[k] = make_uint4(0, 0, 0, 0); ((uint4*)(g_acc + S_TOK * DM))[k] = make_uint4(0, 0, 0, 0); }
  }
  if (b < 160) GT(3, 2);
}

typedef CUresult (*EncodeFn)(CUtensorMap*, CUtensorMapDataType, cuuint32_t, void*, const cuuint64_t*, const cuuint64_t*, const cuuint32_t*,
                             const cuuint32_t*, CUtensorMapInterleave, CUtensorMapSwizzle, CUtensorMapL2promotion, CUtensorMapFloatOOBfill);
static void make_map(EncodeFn fn, CUtensorMap* m, const void* p, uint64_t cols, uint64_t rows, uint32_t bc, uint32_t br) {
  cuuint64_t dims[2] = {cols, rows}; cuuint64_t strides[1] = {cols * 2}; cuuint32_t box[2] = {bc, br}; cuuint32_t es[2] = {1, 1};
  fn(m, CU_TENSOR_MAP_DATA_TYPE_BFLOAT16, 2, (void*)p, dims, strides, box, es, CU_TENSOR_MAP_INTERLEAVE_NONE, CU_TENSOR_MAP_SWIZZLE_128B,
     CU_TENSOR_MAP_L2_PROMOTION_L2_128B, CU_TENSOR_MAP_FLOAT_OOB_FILL_NONE);
}

static void make_map_perm(EncodeFn fn, CUtensorMap* m, const void* p) {
  cuuint64_t dims[5] = {HE, 2, 2, 4, 40}; const cuuint64_t r = HE * 2; cuuint64_t strides[4] = {r, 8 * r, 2 * r, 16 * r};
  cuuint32_t box[5] = {64, 2, 2, 4, 4}; cuuint32_t es[5] = {1, 1, 1, 1, 1};
  fn(m, CU_TENSOR_MAP_DATA_TYPE_BFLOAT16, 5, (void*)p, dims, strides, box, es, CU_TENSOR_MAP_INTERLEAVE_NONE, CU_TENSOR_MAP_SWIZZLE_128B,
     CU_TENSOR_MAP_L2_PROMOTION_L2_128B, CU_TENSOR_MAP_FLOAT_OOB_FILL_NONE);
}

#define OPC_PDL 1
#define LA_PDL 1
#define REC_PDL 1
extern "C" void kernel_launch(void* const* d_in, const int* in_sizes, int n_in, void* d_out, int out_size) {
  const bf16* x = (const bf16*)d_in[0];
  const bf16* wqkv = (const bf16*)d_in[1];
  const bf16* wo_a = (const bf16*)d_in[2];
  const bf16* mem0 = (const bf16*)d_in[4];
  const bf16* Wq = (const bf16*)d_in[5];
  const bf16* Wk = (const bf16*)d_in[6];
  const bf16* Wv = (const bf16*)d_in[7];
  const bf16* Wo = (const bf16*)d_in[8];
  cudaStream_t st = cudaStreamPerThread;

  static EncodeFn enc = nullptr;
  static uint8_t* p_ar; static uint32_t* p_zero;
  if (!enc) {
    cudaDriverEntryPointQueryResult qr;
    void* fn = nullptr;
    cudaGetDriverEntryPoint("cuTensorMapEncodeTiled", &fn, cudaEnableDefault, &qr);
    enc = (EncodeFn)fn;
    cudaFuncSetAttribute(rec_kernel, cudaFuncAttributeMaxDynamicSharedMemorySize, REC_SMEM);
    cudaFuncSetAttribute(opc_kernel, cudaFuncAttributeMaxDynamicSharedMemorySize, OPC_SMEM);
    cudaFuncSetAttribute(la_kernel, cudaFuncAttributeMaxDynamicSharedMemorySize, LA_SMEM);
    cudaGetSymbolAddress((void**)&p_ar, g_ar); p_ar = (uint8_t*)(((uintptr_t)p_ar + 32767) & ~(uintptr_t)32767);
    cudaGetSymbolAddress((void**)&p_zero, g_zero);
  }
  CUtensorMap tmq, tmk, tmv, tmo;
  make_map_perm(enc, &tmq, Wq);
  make_map_perm(enc, &tmk, Wk);
  make_map_perm(enc, &tmv, Wv);
  make_map(enc, &tmo, Wo, DM, HE, 64, 64);

  cudaLaunchAttribute at[2];
  at[0].id = cudaLaunchAttributeProgrammaticStreamSerialization; at[0].val.programmaticStreamSerializationAllowed = 1;
  at[1].id = cudaLaunchAttributeClusterDimension; at[1].val.clusterDim.x = 3; at[1].val.clusterDim.y = 1; at[1].val.clusterDim.z = 1;
  cudaLaunchAttribute at2[2] = {at[1], at[0]};
  at2[0].val.clusterDim.x = 2;
  prep_kernel<<<472, 256, 0, st>>>(x, wqkv, wo_a);
  for (int l = 0; l < 2; l++) {
    cudaLaunchConfig_t cfg = {};
    cfg.blockDim = dim3(384); cfg.stream = st;
    cfg.gridDim = dim3(l == 0 ? 132 : 128); cfg.dynamicSmemBytes = LA_SMEM; cfg.attrs = at2; cfg.numAttrs = 1 + LA_PDL;
    cudaLaunchKernelEx(&cfg, la_kernel, l == 0 ? x : (const bf16*)nullptr, Wq, Wk, Wv, Wo, p_ar + l * AR_LAYER, l);
    cfg.gridDim = dim3(96); cfg.dynamicSmemBytes = REC_SMEM; cfg.attrs = at + 1 - REC_PDL; cfg.numAttrs = 1 + REC_PDL;
    cudaLaunchKernelEx(&cfg, rec_kernel, tmq, tmk, tmv, tmo, mem0, p_ar + l * AR_LAYER, p_zero + Z_FLAGS + l * FL_LAYER, l);
    cfg.gridDim = dim3(36); cfg.dynamicSmemBytes = OPC_SMEM; cfg.attrs = at; cfg.numAttrs = OPC_PDL;
    cudaLaunchKernelEx(&cfg, opc_kernel, tmo, l == 1 ? (bf16*)d_out : (bf16*)nullptr, l, Wq, Wk, Wv, Wo);
  }
}
```

```cpp
#include <cuda_runtime.h>
#include <cuda_bf16.h>
#include <cuda.h>
#include <stdint.h>

typedef __nv_bfloat16 bf16;
typedef unsigned long long u64;

constexpr int S_TOK = 2048, DM = 640, DH = 192, HE = 6144, NSEG = 64;

constexpr int AR_GROUP = 98304;
constexpr int AR_LAYER = 16 * AR_GROUP;
__device__ __align__(1024) uint8_t g_ar[2 * AR_LAYER + 32768];
__device__ __align__(1024) uint8_t g_xn[NSEG * 40960];
__device__ __align__(1024) uint8_t g_xt[S_TOK * DM * 2];
__device__ __align__(1024) uint8_t g_ot[NSEG * HE * 64];
__device__ __align__(1024) uint8_t g_oa[S_TOK * DM * 2];
__device__ __align__(1024) uint8_t g_w1[DM * 1920 * 2];
__device__ __align__(1024) uint8_t g_w2[DM * 672 * 2];
__device__ __align__(1024) float g_acc[2 * S_TOK * DM];
__device__ __align__(1024) bf16 g_x[S_TOK * DM];
constexpr int FL_A = 0, FL_B = 64 * 6 * 8, FL_KV = FL_B + 64 * 8, FL_O = FL_KV + 8 * 8, FL_T = FL_O + 16 * 8, FL_X = FL_T + 16 * 8, FL_N = FL_X + 8, FL_XN = FL_N + 8, FL_LAYER = FL_XN + 32 * 8;
constexpr int Z_FLAGS = 0, Z_NORM = 2 * FL_LAYER, Z_KV = Z_NORM + 8, KV_LAYER = 8 * 80 * 24, Z_END = Z_KV + 2 * KV_LAYER;
__device__ __align__(128) uint32_t g_zero[Z_END];
__device__ __align__(128) float g_nrm[4 * DM];
#define GT(slot, k) do {} while (0)
#define GTT(slot, k) do {} while (0)

__device__ __forceinline__ uint32_t smem_u32(const void* p) { return (uint32_t)__cvta_generic_to_shared(p); }
__device__ __forceinline__ uint32_t mapa(uint32_t a, uint32_t r) { uint32_t o; asm("mapa.shared::cluster.u32 %0, %1, %2;" : "=r"(o) : "r"(a), "r"(r)); return o; }
__device__ __forceinline__ void mbar_init(uint32_t bar, uint32_t cnt) { asm volatile("mbarrier.init.shared::cta.b64 [%0], %1;" :: "r"(bar), "r"(cnt) : "memory"); }
__device__ __forceinline__ void mbar_expect(uint32_t bar, uint32_t tx) { asm volatile("mbarrier.arrive.expect_tx.shared::cta.b64 _, [%0], %1;" :: "r"(bar), "r"(tx) : "memory"); }
__device__ __forceinline__ void mbar_arrive(uint32_t bar) { asm volatile("mbarrier.arrive.shared::cta.b64 _, [%0];" :: "r"(bar) : "memory"); }
__device__ __forceinline__ void mbar_wait(uint32_t bar, uint32_t par) {
  asm volatile("{\n.reg .pred p;\n.reg .u32 c;\nmov.u32 c, 0;\n"
               "LW:\nmbarrier.try_wait.parity.shared::cta.b64 p, [%0], %1;\n@p bra LD;\n"
               "add.u32 c, c, 1;\nsetp.lt.u32 p, c, 4000000;\n@p bra LW;\ntrap;\nLD:\n}" :: "r"(bar), "r"(par) : "memory");
}
template <int ID, int N> __device__ __forceinline__ void bar_sync() { asm volatile("barrier.sync %0, %1;" :: "n"(ID), "n"(N) : "memory"); }
template <int ID, int N> __device__ __forceinline__ void bar_arrive() { asm volatile("barrier.arrive %0, %1;" :: "n"(ID), "n"(N) : "memory"); }
__device__ __forceinline__ void fence_async() { asm volatile("fence.proxy.async.shared::cta;" ::: "memory"); }
__device__ __forceinline__ void cluster_sync() { asm volatile("barrier.cluster.arrive.aligned;\nbarrier.cluster.wait.aligned;" ::: "memory"); }
__device__ __forceinline__ void wg_fence() { asm volatile("wgmma.fence.sync.aligned;" ::: "memory"); }
__device__ __forceinline__ void wg_commit() { asm volatile("wgmma.commit_group.sync.aligned;" ::: "memory"); }
template <int N> __device__ __forceinline__ void wg_wait() { asm volatile("wgmma.wait_group.sync.aligned %0;" :: "n"(N) : "memory"); }
template <int N> __device__ __forceinline__ void pin(float* d) {
#pragma unroll
  for (int i = 0; i < N; i++) asm volatile("" : "+f"(d[i]) :: "memory");
}
__device__ __forceinline__ constexpr uint64_t mkdesc(uint32_t addr, uint32_t lbo, uint32_t sbo, int sw) {
  return (uint64_t)((addr & 0x3FFFF) >> 4) | ((uint64_t)(lbo >> 4) << 16) | ((uint64_t)(sbo >> 4) << 32) | ((uint64_t)sw << 62);
}
constexpr uint32_t SB0 = 1024;
__device__ __forceinline__ void check_smem_base(uint32_t sb) { if ((sb & 0x3FFFF) != SB0) __trap(); }
__device__ __forceinline__ uint32_t cta_rank() { uint32_t r; asm volatile("mov.u32 %0, %%cluster_ctarank;" : "=r"(r)); return r; }
__device__ __forceinline__ uint32_t opaque(uint32_t v) { uint32_t o; asm volatile("mov.u32 %0, %1;" : "=r"(o) : "r"(v)); return o; }
__device__ __forceinline__ uint32_t pack2(float lo, float hi) { uint32_t r; asm("cvt.rn.bf16x2.f32 %0, %1, %2;" : "=r"(r) : "f"(hi), "f"(lo)); return r; }
__device__ __forceinline__ void ldsm4(uint32_t* r, uint32_t a) { asm volatile("ldmatrix.sync.aligned.m8n8.x4.shared.b16 {%0,%1,%2,%3}, [%4];" : "=r"(r[0]), "=r"(r[1]), "=r"(r[2]), "=r"(r[3]) : "r"(a) : "memory"); }
__device__ __forceinline__ void ldsm4t(uint32_t* r, uint32_t a) { asm volatile("ldmatrix.sync.aligned.m8n8.x4.trans.shared.b16 {%0,%1,%2,%3}, [%4];" : "=r"(r[0]), "=r"(r[1]), "=r"(r[2]), "=r"(r[3]) : "r"(a) : "memory"); }
__device__ __forceinline__ void ldsm1(uint32_t& r, uint32_t a) { asm volatile("ldmatrix.sync.aligned.m8n8.x1.shared.b16 {%0}, [%1];" : "=r"(r) : "r"(a) : "memory"); }
__device__ __forceinline__ void stsm4(uint32_t a, uint32_t r0, uint32_t r1, uint32_t r2, uint32_t r3) { asm volatile("stmatrix.sync.aligned.m8n8.x4.shared.b16 [%0], {%1,%2,%3,%4};" :: "r"(a), "r"(r0), "r"(r1), "r"(r2), "r"(r3) : "memory"); }
__device__ __forceinline__ void stsm1(uint32_t a, uint32_t r0) { asm volatile("stmatrix.sync.aligned.m8n8.x1.shared.b16 [%0], {%1};" :: "r"(a), "r"(r0) : "memory"); }
__device__ __forceinline__ void stsm4t(uint32_t a, uint32_t r0, uint32_t r1, uint32_t r2, uint32_t r3) { asm volatile("stmatrix.sync.aligned.m8n8.x4.trans.shared.b16 [%0], {%1,%2,%3,%4};" :: "r"(a), "r"(r0), "r"(r1), "r"(r2), "r"(r3) : "memory"); }
__device__ __forceinline__ void stsm2t(uint32_t a, uint32_t r0, uint32_t r1) { asm volatile("stmatrix.sync.aligned.m8n8.x2.trans.shared.b16 [%0], {%1,%2};" :: "r"(a), "r"(r0), "r"(r1) : "memory"); }
__device__ __forceinline__ void mma16816(float* c, const uint32_t* a, uint32_t b0, uint32_t b1) {
  asm volatile("mma.sync.aligned.m16n8k16.row.col.f32.bf16.bf16.f32 {%0,%1,%2,%3}, {%4,%5,%6,%7}, {%8,%9}, {%0,%1,%2,%3};"
               : "+f"(c[0]), "+f"(c[1]), "+f"(c[2]), "+f"(c[3]) : "r"(a[0]), "r"(a[1]), "r"(a[2]), "r"(a[3]), "r"(b0), "r"(b1));
}
__device__ __forceinline__ void mma1688(float* c, uint32_t a0, uint32_t a1, uint32_t b0) {
  asm volatile("mma.sync.aligned.m16n8k8.row.col.f32.bf16.bf16.f32 {%0,%1,%2,%3}, {%4,%5}, {%6}, {%0,%1,%2,%3};"
               : "+f"(c[0]), "+f"(c[1]), "+f"(c[2]), "+f"(c[3]) : "r"(a0), "r"(a1), "r"(b0));
}
__device__ __forceinline__ void sta1(uint32_t a, uint32_t v, uint32_t bar) { asm volatile("st.async.weak.shared::cluster.mbarrier::complete_tx::bytes.b32 [%0], %1, [%2];" :: "r"(a), "r"(v), "r"(bar) : "memory"); }
__device__ __forceinline__ void sta1p(uint32_t a, uint32_t v, uint32_t bar, bool p) { asm volatile("{\n.reg .pred p;\nsetp.ne.b32 p, %3, 0;\n@p st.async.weak.shared::cluster.mbarrier::complete_tx::bytes.b32 [%0], %1, [%2];\n}" :: "r"(a), "r"(v), "r"(bar), "r"((int)p) : "memory"); }
__device__ __forceinline__ void sta2(uint32_t a, uint32_t v0, uint32_t v1, uint32_t bar) { asm volatile("st.async.weak.shared::cluster.mbarrier::complete_tx::bytes.v2.b32 [%0], {%1,%2}, [%3];" :: "r"(a), "r"(v0), "r"(v1), "r"(bar) : "memory"); }
__device__ __forceinline__ void sta4(uint32_t a, uint32_t v0, uint32_t v1, uint32_t v2, uint32_t v3, uint32_t bar) { asm volatile("st.async.weak.shared::cluster.mbarrier::complete_tx::bytes.v4.b32 [%0], {%1,%2,%3,%4}, [%5];" :: "r"(a), "r"(v0), "r"(v1), "r"(v2), "r"(v3), "r"(bar) : "memory"); }
__device__ __forceinline__ float bflo(uint32_t v) { return __uint_as_float(v << 16); }
__device__ __forceinline__ float bfhi(uint32_t v) { return __uint_as_float(v & 0xFFFF0000u); }
__device__ __forceinline__ void sta2f(uint32_t a, float v0, float v1, uint32_t bar) { asm volatile("st.async.weak.shared::cluster.mbarrier::complete_tx::bytes.v2.f32 [%0], {%1,%2}, [%3];" :: "r"(a), "f"(v0), "f"(v1), "r"(bar) : "memory"); }
__device__ __forceinline__ void sta4f(uint32_t a, float v0, float v1, float v2, float v3, uint32_t bar) { asm volatile("st.async.weak.shared::cluster.mbarrier::complete_tx::bytes.v4.f32 [%0], {%1,%2,%3,%4}, [%5];" :: "r"(a), "f"(v0), "f"(v1), "f"(v2), "f"(v3), "r"(bar) : "memory"); }
__device__ __forceinline__ float4 lds4f(uint32_t a) { float4 v; asm volatile("ld.shared.v4.f32 {%0,%1,%2,%3}, [%4];" : "=f"(v.x), "=f"(v.y), "=f"(v.z), "=f"(v.w) : "r"(a) : "memory"); return v; }
__device__ __forceinline__ float2 lds2f(uint32_t a) { float2 v; asm volatile("ld.shared.v2.f32 {%0,%1}, [%2];" : "=f"(v.x), "=f"(v.y) : "r"(a) : "memory"); return v; }
__device__ __forceinline__ uint4 lds4(uint32_t a) { uint4 v; asm volatile("ld.shared.v4.u32 {%0,%1,%2,%3}, [%4];" : "=r"(v.x), "=r"(v.y), "=r"(v.z), "=r"(v.w) : "r"(a) : "memory"); return v; }
__device__ __forceinline__ uint32_t lds1(uint32_t a) { uint32_t v; asm volatile("ld.shared.u32 %0, [%1];" : "=r"(v) : "r"(a) : "memory"); return v; }
__device__ __forceinline__ void stsm2(uint32_t a, uint32_t r0, uint32_t r1) { asm volatile("stmatrix.sync.aligned.m8n8.x2.shared.b16 [%0], {%1,%2};" :: "r"(a), "r"(r0), "r"(r1) : "memory"); }
__device__ __forceinline__ float rcp(float x) { float y; asm("rcp.approx.ftz.f32 %0, %1;" : "=f"(y) : "f"(x)); return y; }
__device__ __forceinline__ void sts4(uint32_t a, uint32_t v0, uint32_t v1, uint32_t v2, uint32_t v3) { asm volatile("st.shared.v4.u32 [%0], {%1,%2,%3,%4};" :: "r"(a), "r"(v0), "r"(v1), "r"(v2), "r"(v3) : "memory"); }
__device__ __forceinline__ void bulk_s2c(uint32_t dst, uint32_t src, uint32_t bytes, uint32_t bar) {
  asm volatile("cp.async.bulk.shared::cluster.shared::cta.mbarrier::complete_tx::bytes [%0], [%1], %2, [%3];" :: "r"(dst), "r"(src), "r"(bytes), "r"(bar) : "memory");
}
__device__ __forceinline__ void stg4(void* p, uint4 v) { asm volatile("st.global.v4.u32 [%0], {%1,%2,%3,%4};" :: "l"(p), "r"(v.x), "r"(v.y), "r"(v.z), "r"(v.w) : "memory"); }
__device__ __forceinline__ void red_add(uint32_t* p, uint32_t v) { asm volatile("red.relaxed.gpu.global.add.u32 [%0], %1;" :: "l"(p), "r"(v) : "memory"); }
__device__ __forceinline__ void red_release(uint32_t* p, uint32_t v) { asm volatile("red.release.gpu.global.add.u32 [%0], %1;" :: "l"(p), "r"(v) : "memory"); }
__device__ __forceinline__ void fence_async_global() { asm volatile("fence.proxy.async.global;" ::: "memory"); }
__device__ __forceinline__ uint64_t policy_evict_first() { uint64_t p; asm("createpolicy.fractional.L2::evict_first.b64 %0, 1.0;" : "=l"(p)); return p; }
__device__ __forceinline__ void stg4h(void* p, uint4 v, uint64_t pol) { asm volatile("st.global.L2::cache_hint.v4.u32 [%0], {%1,%2,%3,%4}, %5;" :: "l"(p), "r"(v.x), "r"(v.y), "r"(v.z), "r"(v.w), "l"(pol) : "memory"); }
__device__ __forceinline__ void red4fh(float* p, float a, float b, float c, float d, uint64_t pol) { asm volatile("red.relaxed.gpu.global.add.L2::cache_hint.v4.f32 [%0], {%1,%2,%3,%4}, %5;" :: "l"(p), "f"(a), "f"(b), "f"(c), "f"(d), "l"(pol) : "memory"); }
__device__ __forceinline__ float4 ldg4fh(const float* p, uint64_t pol) { float4 v; asm volatile("ld.global.cg.L2::cache_hint.v4.f32 {%0,%1,%2,%3}, [%4], %5;" : "=f"(v.x), "=f"(v.y), "=f"(v.z), "=f"(v.w) : "l"(p), "l"(pol) : "memory"); return v; }
__device__ __forceinline__ void bulk_g2sh(uint32_t dst, const void* src, uint32_t bytes, uint32_t bar, uint64_t pol) {
  asm volatile("cp.async.bulk.shared::cluster.global.mbarrier::complete_tx::bytes.L2::cache_hint [%0], [%1], %2, [%3], %4;" :: "r"(dst), "l"(src), "r"(bytes), "r"(bar), "l"(pol) : "memory");
}
#define EVF 1
__device__ __forceinline__ void red4f(float* p, float a, float b, float c, float d) { asm volatile("red.relaxed.gpu.global.add.v4.f32 [%0], {%1,%2,%3,%4};" :: "l"(p), "f"(a), "f"(b), "f"(c), "f"(d) : "memory"); }
__device__ __forceinline__ void wait_flag(const uint32_t* p, uint32_t target) {
  uint32_t v; int it = 0;
  while (true) {
    asm volatile("ld.acquire.gpu.global.u32 %0, [%1];" : "=r"(v) : "l"(p) : "memory");
    if (__all_sync(~0u, v >= target)) break;
    if (++it > 4000000) __trap();
    __nanosleep(20);
  }
}
__device__ __forceinline__ void sts2(uint32_t a, uint32_t v0, uint32_t v1) { asm volatile("st.shared.v2.u32 [%0], {%1,%2};" :: "r"(a), "r"(v0), "r"(v1) : "memory"); }
__device__ __forceinline__ float sqrt_approx(float x) { float y; asm("sqrt.approx.f32 %0, %1;" : "=f"(y) : "f"(x)); return y; }
__device__ __forceinline__ void bulk_s2c_elect(uint32_t d1, uint32_t b1, uint32_t d2, uint32_t b2, uint32_t src) {
  asm volatile("{\n.reg .pred p;\nelect.sync _|p, 0xffffffff;\n"
               "@p cp.async.bulk.shared::cluster.shared::cta.mbarrier::complete_tx::bytes [%0], [%4], 1024, [%1];\n"
               "@p cp.async.bulk.shared::cluster.shared::cta.mbarrier::complete_tx::bytes [%2], [%4], 1024, [%3];\n}"
               :: "r"(d1), "r"(b1), "r"(d2), "r"(b2), "r"(src) : "memory");
}
__device__ __forceinline__ void mbar_arrive_elect(uint32_t bar) { asm volatile("{\n.reg .pred p;\nelect.sync _|p, 0xffffffff;\n@p mbarrier.arrive.shared::cta.b64 _, [%0];\n}" :: "r"(bar) : "memory"); }
__device__ __forceinline__ void cp16(uint32_t dst, const void* src) { asm volatile("cp.async.cg.shared.global [%0], [%1], 16;" :: "r"(dst), "l"(src) : "memory"); }
__device__ __forceinline__ void sts1(uint32_t a, uint32_t v) { asm volatile("st.shared.u32 [%0], %1;" :: "r"(a), "r"(v) : "memory"); }
__device__ __forceinline__ void bulk_g2s(uint32_t dst, const void* src, uint32_t bytes, uint32_t bar) {
  asm volatile("cp.async.bulk.shared::cluster.global.mbarrier::complete_tx::bytes [%0], [%1], %2, [%3];" :: "r"(dst), "l"(src), "r"(bytes), "r"(bar) : "memory");
}
__device__ __forceinline__ void bulk_g2s_mc(uint32_t dst, const void* src, uint32_t bytes, uint32_t bar) {
  asm volatile("cp.async.bulk.shared::cluster.global.mbarrier::complete_tx::bytes.multicast::cluster [%0], [%1], %2, [%3], %4;" :: "r"(dst), "l"(src), "r"(bytes), "r"(bar), "h"((uint16_t)3) : "memory");
}
__device__ __forceinline__ void mbar_arrive_cl(uint32_t bar) { asm volatile("mbarrier.arrive.shared::cluster.b64 _, [%0];" :: "r"(bar) : "memory"); }
__device__ __forceinline__ void tma2d(uint32_t dst, const CUtensorMap* m, int c0, int c1, uint32_t bar) {
  asm volatile("cp.async.bulk.tensor.2d.shared::cluster.global.mbarrier::complete_tx::bytes [%0], [%1, {%3, %4}], [%2];" :: "r"(dst), "l"((uint64_t)m), "r"(bar), "r"(c0), "r"(c1) : "memory");
}
__device__ __forceinline__ void tma5d(uint32_t dst, const CUtensorMap* m, int c0, int c4, uint32_t bar) {
  asm volatile("cp.async.bulk.tensor.5d.shared::cluster.global.mbarrier::complete_tx::bytes [%0], [%1, {%3, %5, %5, %5, %4}], [%2];" :: "r"(dst), "l"((uint64_t)m), "r"(bar), "r"(c0), "r"(c4), "r"(0) : "memory");
}
__device__ __forceinline__ void red64(void* p, uint32_t lo, uint32_t hi) { asm volatile("{\n.reg .b64 t;\nmov.b64 t, {%1,%2};\nred.relaxed.gpu.global.add.u64 [%0], t;\n}" :: "l"(p), "r"(lo), "r"(hi) : "memory"); }
__device__ __forceinline__ uint4 ld_poll(const void* p) {
  uint4 v;
  asm volatile("{\n.reg .b64 a, b;\nld.relaxed.gpu.global.v2.b64 {a, b}, [%4];\nmov.b64 {%0,%1}, a;\nmov.b64 {%2,%3}, b;\n}" : "=r"(v.x), "=r"(v.y), "=r"(v.z), "=r"(v.w) : "l"(p) : "memory");
  return v;
}
__device__ __forceinline__ uint32_t clk() { uint32_t c; asm volatile("mov.u32 %0, %%clock;" : "=r"(c) :: "memory"); return c; }
#define SCHED_FENCE() asm volatile("pmevent 0;" ::: "memory")
__device__ __forceinline__ float ex2(float x) { float y; asm("ex2.approx.ftz.f32 %0, %1;" : "=f"(y) : "f"(x)); return y; }

__device__ __forceinline__ void wg_ss_n240_ta0_tb1(float* d, uint64_t a, uint64_t b, int sc) {
  asm volatile("{\n.reg .pred p;\nsetp.ne.b32 p, %122, 0;\nwgmma.mma_async.sync.aligned.m64n240k16.f32.bf16.bf16 {%0, %1, %2, %3, %4, %5, %6, %7, %8, %9, %10, %11, %12, %13, %14, %15, %16, %17, %18, %19, %20, %21, %22, %23, %24, %25, %26, %27, %28, %29, %30, %31, %32, %33, %34, %35, %36, %37, %38, %39, %40, %41, %42, %43, %44, %45, %46, %47, %48, %49, %50, %51, %52, %53, %54, %55, %56, %57, %58, %59, %60, %61, %62, %63, %64, %65, %66, %67, %68, %69, %70, %71, %72, %73, %74, %75, %76, %77, %78, %79, %80, %81, %82, %83, %84, %85, %86, %87, %88, %89, %90, %91, %92, %93, %94, %95, %96, %97, %98, %99, %100, %101, %102, %103, %104, %105, %106, %107, %108, %109, %110, %111, %112, %113, %114, %115, %116, %117, %118, %119}, %120, %121, p, 1, 1, 0, 1;\n}\n"
    : "+f"(d[0]), "+f"(d[1]), "+f"(d[2]), "+f"(d[3]), "+f"(d[4]), "+f"(d[5]), "+f"(d[6]), "+f"(d[7]), "+f"(d[8]), "+f"(d[9]), "+f"(d[10]), "+f"(d[11]), "+f"(d[12]), "+f"(d[13]), "+f"(d[14]), "+f"(d[15]), "+f"(d[16]), "+f"(d[17]), "+f"(d[18]), "+f"(d[19]), "+f"(d[20]), "+f"(d[21]), "+f"(d[22]), "+f"(d[23]), "+f"(d[24]), "+f"(d[25]), "+f"(d[26]), "+f"(d[27]), "+f"(d[28]), "+f"(d[29]), "+f"(d[30]), "+f"(d[31]), "+f"(d[32]), "+f"(d[33]), "+f"(d[34]), "+f"(d[35]), "+f"(d[36]), "+f"(d[37]), "+f"(d[38]), "+f"(d[39]), "+f"(d[40]), "+f"(d[41]), "+f"(d[42]), "+f"(d[43]), "+f"(d[44]), "+f"(d[45]), "+f"(d[46]), "+f"(d[47]), "+f"(d[48]), "+f"(d[49]), "+f"(d[50]), "+f"(d[51]), "+f"(d[52]), "+f"(d[53]), "+f"(d[54]), "+f"(d[55]), "+f"(d[56]), "+f"(d[57]), "+f"(d[58]), "+f"(d[59]), "+f"(d[60]), "+f"(d[61]), "+f"(d[62]), "+f"(d[63]), "+f"(d[64]), "+f"(d[65]), "+f"(d[66]), "+f"(d[67]), "+f"(d[68]), "+f"(d[69]), "+f"(d[70]), "+f"(d[71]), "+f"(d[72]), "+f"(d[73]), "+f"(d[74]), "+f"(d[75]), "+f"(d[76]), "+f"(d[77]), "+f"(d[78]), "+f"(d[79]), "+f"(d[80]), "+f"(d[81]), "+f"(d[82]), "+f"(d[83]), "+f"(d[84]), "+f"(d[85]), "+f"(d[86]), "+f"(d[87]), "+f"(d[88]), "+f"(d[89]), "+f"(d[90]), "+f"(d[91]), "+f"(d[92]), "+f"(d[93]), "+f"(d[94]), "+f"(d[95]), "+f"(d[96]), "+f"(d[97]), "+f"(d[98]), "+f"(d[99]), "+f"(d[100]), "+f"(d[101]), "+f"(d[102]), "+f"(d[103]), "+f"(d[104]), "+f"(d[105]), "+f"(d[106]), "+f"(d[107]), "+f"(d[108]), "+f"(d[109]), "+f"(d[110]), "+f"(d[111]), "+f"(d[112]), "+f"(d[113]), "+f"(d[114]), "+f"(d[115]), "+f"(d[116]), "+f"(d[117]), "+f"(d[118]), "+f"(d[119])
    : "l"(a), "l"(b), "r"(sc));
}
__device__ __forceinline__ void wg_ss_n88_ta1_tb1(float* d, uint64_t a, uint64_t b, int sc) {
  asm volatile("{\n.reg .pred p;\nsetp.ne.b32 p, %46, 0;\nwgmma.mma_async.sync.aligned.m64n88k16.f32.bf16.bf16 {%0, %1, %2, %3, %4, %5, %6, %7, %8, %9, %10, %11, %12, %13, %14, %15, %16, %17, %18, %19, %20, %21, %22, %23, %24, %25, %26, %27, %28, %29, %30, %31, %32, %33, %34, %35, %36, %37, %38, %39, %40, %41, %42, %43}, %44, %45, p, 1, 1, 1, 1;\n}\n"
    : "+f"(d[0]), "+f"(d[1]), "+f"(d[2]), "+f"(d[3]), "+f"(d[4]), "+f"(d[5]), "+f"(d[6]), "+f"(d[7]), "+f"(d[8]), "+f"(d[9]), "+f"(d[10]), "+f"(d[11]), "+f"(d[12]), "+f"(d[13]), "+f"(d[14]), "+f"(d[15]), "+f"(d[16]), "+f"(d[17]), "+f"(d[18]), "+f"(d[19]), "+f"(d[20]), "+f"(d[21]), "+f"(d[22]), "+f"(d[23]), "+f"(d[24]), "+f"(d[25]), "+f"(d[26]), "+f"(d[27]), "+f"(d[28]), "+f"(d[29]), "+f"(d[30]), "+f"(d[31]), "+f"(d[32]), "+f"(d[33]), "+f"(d[34]), "+f"(d[35]), "+f"(d[36]), "+f"(d[37]), "+f"(d[38]), "+f"(d[39]), "+f"(d[40]), "+f"(d[41]), "+f"(d[42]), "+f"(d[43])
    : "l"(a), "l"(b), "r"(sc));
}
__device__ __forceinline__ void wg_rs_n160_tb1(float* d, const uint32_t* a, uint64_t b, int sc) {
  asm volatile("{\n.reg .pred p;\nsetp.ne.b32 p, %85, 0;\nwgmma.mma_async.sync.aligned.m64n160k16.f32.bf16.bf16 {%0, %1, %2, %3, %4, %5, %6, %7, %8, %9, %10, %11, %12, %13, %14, %15, %16, %17, %18, %19, %20, %21, %22, %23, %24, %25, %26, %27, %28, %29, %30, %31, %32, %33, %34, %35, %36, %37, %38, %39, %40, %41, %42, %43, %44, %45, %46, %47, %48, %49, %50, %51, %52, %53, %54, %55, %56, %57, %58, %59, %60, %61, %62, %63, %64, %65, %66, %67, %68, %69, %70, %71, %72, %73, %74, %75, %76, %77, %78, %79}, {%80, %81, %82, %83}, %84, p, 1, 1, 1;\n}\n"
    : "+f"(d[0]), "+f"(d[1]), "+f"(d[2]), "+f"(d[3]), "+f"(d[4]), "+f"(d[5]), "+f"(d[6]), "+f"(d[7]), "+f"(d[8]), "+f"(d[9]), "+f"(d[10]), "+f"(d[11]), "+f"(d[12]), "+f"(d[13]), "+f"(d[14]), "+f"(d[15]), "+f"(d[16]), "+f"(d[17]), "+f"(d[18]), "+f"(d[19]), "+f"(d[20]), "+f"(d[21]), "+f"(d[22]), "+f"(d[23]), "+f"(d[24]), "+f"(d[25]), "+f"(d[26]), "+f"(d[27]), "+f"(d[28]), "+f"(d[29]), "+f"(d[30]), "+f"(d[31]), "+f"(d[32]), "+f"(d[33]), "+f"(d[34]), "+f"(d[35]), "+f"(d[36]), "+f"(d[37]), "+f"(d[38]), "+f"(d[39]), "+f"(d[40]), "+f"(d[41]), "+f"(d[42]), "+f"(d[43]), "+f"(d[44]), "+f"(d[45]), "+f"(d[46]), "+f"(d[47]), "+f"(d[48]), "+f"(d[49]), "+f"(d[50]), "+f"(d[51]), "+f"(d[52]), "+f"(d[53]), "+f"(d[54]), "+f"(d[55]), "+f"(d[56]), "+f"(d[57]), "+f"(d[58]), "+f"(d[59]), "+f"(d[60]), "+f"(d[61]), "+f"(d[62]), "+f"(d[63]), "+f"(d[64]), "+f"(d[65]), "+f"(d[66]), "+f"(d[67]), "+f"(d[68]), "+f"(d[69]), "+f"(d[70]), "+f"(d[71]), "+f"(d[72]), "+f"(d[73]), "+f"(d[74]), "+f"(d[75]), "+f"(d[76]), "+f"(d[77]), "+f"(d[78]), "+f"(d[79])
    : "r"(a[0]), "r"(a[1]), "r"(a[2]), "r"(a[3]), "l"(b), "r"(sc));
}
__device__ __forceinline__ void wg_ss_n112_ta0_tb1(float* d, uint64_t a, uint64_t b, int sc) {
  asm volatile("{\n.reg .pred p;\nsetp.ne.b32 p, %58, 0;\nwgmma.mma_async.sync.aligned.m64n112k16.f32.bf16.bf16 {%0, %1, %2, %3, %4, %5, %6, %7, %8, %9, %10, %11, %12, %13, %14, %15, %16, %17, %18, %19, %20, %21, %22, %23, %24, %25, %26, %27, %28, %29, %30, %31, %32, %33, %34, %35, %36, %37, %38, %39, %40, %41, %42, %43, %44, %45, %46, %47, %48, %49, %50, %51, %52, %53, %54, %55}, %56, %57, p, 1, 1, 0, 1;\n}\n"
    : "+f"(d[0]), "+f"(d[1]), "+f"(d[2]), "+f"(d[3]), "+f"(d[4]), "+f"(d[5]), "+f"(d[6]), "+f"(d[7]), "+f"(d[8]), "+f"(d[9]), "+f"(d[10]), "+f"(d[11]), "+f"(d[12]), "+f"(d[13]), "+f"(d[14]), "+f"(d[15]), "+f"(d[16]), "+f"(d[17]), "+f"(d[18]), "+f"(d[19]), "+f"(d[20]), "+f"(d[21]), "+f"(d[22]), "+f"(d[23]), "+f"(d[24]), "+f"(d[25]), "+f"(d[26]), "+f"(d[27]), "+f"(d[28]), "+f"(d[29]), "+f"(d[30]), "+f"(d[31]), "+f"(d[32]), "+f"(d[33]), "+f"(d[34]), "+f"(d[35]), "+f"(d[36]), "+f"(d[37]), "+f"(d[38]), "+f"(d[39]), "+f"(d[40]), "+f"(d[41]), "+f"(d[42]), "+f"(d[43]), "+f"(d[44]), "+f"(d[45]), "+f"(d[46]), "+f"(d[47]), "+f"(d[48]), "+f"(d[49]), "+f"(d[50]), "+f"(d[51]), "+f"(d[52]), "+f"(d[53]), "+f"(d[54]), "+f"(d[55])
    : "l"(a), "l"(b), "r"(sc));
}
__device__ __forceinline__ void wg_rs_n32_tb1(float* d, const uint32_t* a, uint64_t b, int sc) {
  asm volatile("{\n.reg .pred p;\nsetp.ne.b32 p, %21, 0;\nwgmma.mma_async.sync.aligned.m64n32k16.f32.bf16.bf16 {%0, %1, %2, %3, %4, %5, %6, %7, %8, %9, %10, %11, %12, %13, %14, %15}, {%16, %17, %18, %19}, %20, p, 1, 1, 1;\n}\n"
    : "+f"(d[0]), "+f"(d[1]), "+f"(d[2]), "+f"(d[3]), "+f"(d[4]), "+f"(d[5]), "+f"(d[6]), "+f"(d[7]), "+f"(d[8]), "+f"(d[9]), "+f"(d[10]), "+f"(d[11]), "+f"(d[12]), "+f"(d[13]), "+f"(d[14]), "+f"(d[15])
    : "r"(a[0]), "r"(a[1]), "r"(a[2]), "r"(a[3]), "l"(b), "r"(sc));
}
__device__ __forceinline__ void wg_ss_n32_ta1_tb1(float* d, uint64_t a, uint64_t b, int sc) {
  asm volatile("{\n.reg .pred p;\nsetp.ne.b32 p, %18, 0;\nwgmma.mma_async.sync.aligned.m64n32k16.f32.bf16.bf16 {%0, %1, %2, %3, %4, %5, %6, %7, %8, %9, %10, %11, %12, %13, %14, %15}, %16, %17, p, 1, 1, 1, 1;\n}\n"
    : "+f"(d[0]), "+f"(d[1]), "+f"(d[2]), "+f"(d[3]), "+f"(d[4]), "+f"(d[5]), "+f"(d[6]), "+f"(d[7]), "+f"(d[8]), "+f"(d[9]), "+f"(d[10]), "+f"(d[11]), "+f"(d[12]), "+f"(d[13]), "+f"(d[14]), "+f"(d[15])
    : "l"(a), "l"(b), "r"(sc));
}
__device__ __forceinline__ void wg_rs_n32_tb0(float* d, const uint32_t* a, uint64_t b, int sc) {
  asm volatile("{\n.reg .pred p;\nsetp.ne.b32 p, %21, 0;\nwgmma.mma_async.sync.aligned.m64n32k16.f32.bf16.bf16 {%0, %1, %2, %3, %4, %5, %6, %7, %8, %9, %10, %11, %12, %13, %14, %15}, {%16, %17, %18, %19}, %20, p, 1, 1, 0;\n}\n"
    : "+f"(d[0]), "+f"(d[1]), "+f"(d[2]), "+f"(d[3]), "+f"(d[4]), "+f"(d[5]), "+f"(d[6]), "+f"(d[7]), "+f"(d[8]), "+f"(d[9]), "+f"(d[10]), "+f"(d[11]), "+f"(d[12]), "+f"(d[13]), "+f"(d[14]), "+f"(d[15])
    : "r"(a[0]), "r"(a[1]), "r"(a[2]), "r"(a[3]), "l"(b), "r"(sc));
}
__device__ __forceinline__ void wg_rs_n40_tb0(float* d, const uint32_t* a, uint64_t b, int sc) {
  asm volatile("{\n.reg .pred p;\nsetp.ne.b32 p, %25, 0;\nwgmma.mma_async.sync.aligned.m64n40k16.f32.bf16.bf16 {%0, %1, %2, %3, %4, %5, %6, %7, %8, %9, %10, %11, %12, %13, %14, %15, %16, %17, %18, %19}, {%20, %21, %22, %23}, %24, p, 1, 1, 0;\n}\n"
    : "+f"(d[0]), "+f"(d[1]), "+f"(d[2]), "+f"(d[3]), "+f"(d[4]), "+f"(d[5]), "+f"(d[6]), "+f"(d[7]), "+f"(d[8]), "+f"(d[9]), "+f"(d[10]), "+f"(d[11]), "+f"(d[12]), "+f"(d[13]), "+f"(d[14]), "+f"(d[15]), "+f"(d[16]), "+f"(d[17]), "+f"(d[18]), "+f"(d[19])
    : "r"(a[0]), "r"(a[1]), "r"(a[2]), "r"(a[3]), "l"(b), "r"(sc));
}
__device__ __forceinline__ void wg_rs_n8_tb1(float* d, const uint32_t* a, uint64_t b, int sc) {
  asm volatile("{\n.reg .pred p;\nsetp.ne.b32 p, %9, 0;\nwgmma.mma_async.sync.aligned.m64n8k16.f32.bf16.bf16 {%0, %1, %2, %3}, {%4, %5, %6, %7}, %8, p, 1, 1, 1;\n}\n"
    : "+f"(d[0]), "+f"(d[1]), "+f"(d[2]), "+f"(d[3])
    : "r"(a[0]), "r"(a[1]), "r"(a[2]), "r"(a[3]), "l"(b), "r"(sc));
}
__device__ __forceinline__ void wg_ss_n40_ta0_tb0(float* d, uint64_t a, uint64_t b, int sc) {
  asm volatile("{\n.reg .pred p;\nsetp.ne.b32 p, %22, 0;\nwgmma.mma_async.sync.aligned.m64n40k16.f32.bf16.bf16 {%0, %1, %2, %3, %4, %5, %6, %7, %8, %9, %10, %11, %12, %13, %14, %15, %16, %17, %18, %19}, %20, %21, p, 1, 1, 0, 0;\n}\n"
    : "+f"(d[0]), "+f"(d[1]), "+f"(d[2]), "+f"(d[3]), "+f"(d[4]), "+f"(d[5]), "+f"(d[6]), "+f"(d[7]), "+f"(d[8]), "+f"(d[9]), "+f"(d[10]), "+f"(d[11]), "+f"(d[12]), "+f"(d[13]), "+f"(d[14]), "+f"(d[15]), "+f"(d[16]), "+f"(d[17]), "+f"(d[18]), "+f"(d[19])
    : "l"(a), "l"(b), "r"(sc));
}
__device__ __forceinline__ void wg_ss_n40_ta1_tb0(float* d, uint64_t a, uint64_t b, int sc) {
  asm volatile("{\n.reg .pred p;\nsetp.ne.b32 p, %22, 0;\nwgmma.mma_async.sync.aligned.m64n40k16.f32.bf16.bf16 {%0, %1, %2, %3, %4, %5, %6, %7, %8, %9, %10, %11, %12, %13, %14, %15, %16, %17, %18, %19}, %20, %21, p, 1, 1, 1, 0;\n}\n"
    : "+f"(d[0]), "+f"(d[1]), "+f"(d[2]), "+f"(d[3]), "+f"(d[4]), "+f"(d[5]), "+f"(d[6]), "+f"(d[7]), "+f"(d[8]), "+f"(d[9]), "+f"(d[10]), "+f"(d[11]), "+f"(d[12]), "+f"(d[13]), "+f"(d[14]), "+f"(d[15]), "+f"(d[16]), "+f"(d[17]), "+f"(d[18]), "+f"(d[19])
    : "l"(a), "l"(b), "r"(sc));
}
__device__ __forceinline__ void wg_ss_n8_ta1_tb1(float* d, uint64_t a, uint64_t b, int sc) {
  asm volatile("{\n.reg .pred p;\nsetp.ne.b32 p, %6, 0;\nwgmma.mma_async.sync.aligned.m64n8k16.f32.bf16.bf16 {%0, %1, %2, %3}, %4, %5, p, 1, 1, 1, 1;\n}\n"
    : "+f"(d[0]), "+f"(d[1]), "+f"(d[2]), "+f"(d[3])
    : "l"(a), "l"(b), "r"(sc));
}

constexpr int O_WV = 0, O_WO = 81920, O_H = 163840, O_QK = 215040, O_SM = 228352, O_MISC = 229632;
constexpr int O_QM = O_QK + 1024, O_K = O_QK + 3072, O_OG = O_QK + 8192;
constexpr int SM_SLOT = 640;
constexpr int O_MAXS = O_MISC;
constexpr int O_BAR = O_MISC + 64;
constexpr int MB_XF = 0, MB_ML = 2, MB_MR = 4, MB_SM = 7, MB_SX = 8, MB_OG = 9, MB_W = 10, MB_WC = 30;
constexpr int O_PROF = O_BAR + 8 * 40;
constexpr int REC_SMEM = O_PROF + 128;
constexpr int B_VOWN = 0, B_QK = 1, B_VGO = 2, B_SISS = 3, B_PM = 4, B_PX = 5, B_XGO = 6, B_PFREE = 7, B_WG2 = 8, B_VHALF = 9, B_VDONE = 10,
              B_PFREE1 = 11, B_SSENT = 12, B_SLD = 13, B_VEND = 14, B_XGO1 = 15;
#define POLL_DELAY 600
#define POLL_D0 300
#define POLL_STEP 100
#define TS0(idx) do {} while (0)
#define TS(idx) do {} while (0)
#define SLD_POS 0
#define W_OPEN 16
#define W_WIN 3
#define TRIG_LATE 1
#define XP_END 40
#define F_ORD 0
#define VEND_POS 2
#define SPEC_DEC 0
#define O_B1 5
#define O_C1 16
#define O_MODE 0
#define AR_MAP 1
#define EXP 0
#define FILL_B 4096
#define MP_D 3
#define MP_CH 4
#define MP_F 0
#define ML_N0 3
#define MR_N0 3
#define O_RSM 0x2AA0
#define O_RS __builtin_popcount(O_RSM)
#define O_IDX(j) __builtin_popcount(O_RSM & ((1 << (j)) - 1))
#define O_RS_POS 0
#define V_N1 2
#define V_N2 0
#define V_N3 4
#define V_OWN 6
#define V_S1 9
#define V_K1 (V_OWN + V_RS + V_S1)
#define V_K2 ((V_K1 > 20 ? V_K1 : 20) + V_S2)
#define V_S2 3
constexpr int V_RS = V_N1 + V_N2 + V_N3;
constexpr float SCL = 0.07216878364870322f;
constexpr float L2E = 1.4426950408889634f;
__device__ __forceinline__ constexpr int vord(int i) { return i < 4 ? 36 + i : i - 4; }
__device__ __forceinline__ constexpr uint32_t hoff(int k) { return ((k >> 2) * 5120 + (k & 3) * 32) >> 4; }

__device__ __forceinline__ constexpr int ar_chunk(int T) { return AR_MAP == 0 ? (T >> 2) * 8 + (T & 3) : T == 9 ? 19 : (T % 3) * 8 + T / 3; }
__device__ __forceinline__ void fix_red(uint8_t* p, const float* a, float sc) {
  int v0 = __float2int_rn(a[0] * sc), v1 = __float2int_rn(a[1] * sc), v2 = __float2int_rn(a[2] * sc), v3 = __float2int_rn(a[3] * sc);
  red64(p, ((uint32_t)v0 << 7) | 1u, ((uint32_t)v2 << 3) + (uint32_t)(v0 >> 25));
  red64(p + 1024, ((uint32_t)v1 << 7) | 1u, ((uint32_t)v3 << 3) + (uint32_t)(v1 >> 25));
}
__device__ __forceinline__ float max10(const float* t) {
  float m = fmaxf(fmaxf(fmaxf(t[0], t[1]), fmaxf(t[2], t[3])), fmaxf(fmaxf(t[4], t[5]), fmaxf(t[6], t[7])));
  m = fmaxf(m, fmaxf(t[8], t[9]));
  m = fmaxf(m, __shfl_xor_sync(~0u, m, 1));
  return fmaxf(m, __shfl_xor_sync(~0u, m, 2));
}
#define ACC2(k, p, u, v) { t[k] = bflo(p) + bflo(u) + bflo(v); t[k + 1] = bfhi(p) + bfhi(u) + bfhi(v); }

#define NLB 5
constexpr int LB_STAGE = 36864, LB_ST = 6 * LB_STAGE;
__device__ __forceinline__ void lb_role(const uint32_t sb, const bf16* __restrict__ xin, uint32_t* __restrict__ flags, int layer) {
  const int tid = threadIdx.x, wid = __shfl_sync(~0u, tid >> 5, 0), wg = wid >> 2, w = wid & 3, lane = tid & 31, g = lane >> 2, i4 = lane & 3;
  const int cl = blockIdx.x / 3, rank = blockIdx.x - cl * 3;
  const uint32_t bar = sb + O_BAR;
  asm volatile("griddepcontrol.launch_dependents;");
  if (wid == 8) {
    if (lane < 14) mbar_init(bar + 8 * lane, lane >= 6 && lane < 12 ? 8 : 1);
    asm volatile("fence.mbarrier_init.release.cluster;" ::: "memory");
    fence_async();
  }
  __syncthreads();
  asm volatile("barrier.cluster.arrive.relaxed.aligned;" ::: "memory");
  if (wid == 8) {
    int st = 0; uint32_t ph = 1;
    const uint8_t* wsrc = g_w2 + rank * 286720;
    if (lane < 6) { mbar_expect(bar + 8 * lane, LB_STAGE); bulk_g2s(sb + lane * LB_STAGE + 8192, wsrc + lane * 28672, 28672, bar + 8 * lane); }
#pragma unroll 1
    for (int tile = cl; tile < 32; tile += NLB) {
      wait_flag(flags + FL_O + (tile >> 1) * 8, 8);
      fence_async_global();
#pragma unroll 1
      for (int kc = 0; kc < 10; kc++) {
        const bool pre = tile == cl && kc < 6;
        mbar_wait(bar + 8 * (6 + st), ph);
        if (lane == 0) {
          if (!pre) { mbar_expect(bar + 8 * st, LB_STAGE); bulk_g2s(sb + st * LB_STAGE + 8192, wsrc + kc * 28672, 28672, bar + 8 * st); }
          bulk_g2s(sb + st * LB_STAGE, g_oa + tile * 81920 + kc * 8192, 8192, bar + 8 * st);
        }
        __syncwarp();
        if (++st == 6) { st = 0; ph ^= 1; }
      }
    }
    asm volatile("barrier.cluster.wait.aligned;" ::: "memory");
  } else if (wg < 2) {
    asm volatile("barrier.cluster.wait.aligned;" ::: "memory");
    const int u = 2 * rank + wg, nb = u == 5 ? 5 : 7;
    int st = 0; uint32_t ph = 0, it = 0;
#pragma unroll 1
    for (int tile = cl; tile < 32; tile += NLB, it++) {
      const int row0 = tile * 64 + 16 * w + g;
      float d[56];
      if (layer == 1) wait_flag(flags + FL_T + (tile >> 1) * 8, 8);
      uint32_t rr[28];
      if (xin) {
        const uint32_t* xp = (const uint32_t*)(xin + row0 * DM + u * 112 + 2 * i4);
#pragma unroll
        for (int j = 0; j < 7; j++) {
          const uint32_t* q = xp + (j < nb ? 8 * j : 0);
          rr[4 * j] = __ldg(q); rr[4 * j + 2] = __ldg(q + 4); rr[4 * j + 1] = __ldg(q + 4 * DM); rr[4 * j + 3] = __ldg(q + 4 * DM + 4);
        }
      } else {
        const uint2* xp = (const uint2*)(g_x + row0 * DM + u * 112 + 4 * i4);
#pragma unroll
        for (int j = 0; j < 7; j++) {
          const uint2* q = xp + (j < nb ? 4 * j : 0);
          const uint2 x = __ldcg(q), y = __ldcg(q + 2 * DM);
          rr[4 * j] = x.x; rr[4 * j + 2] = x.y; rr[4 * j + 1] = y.x; rr[4 * j + 3] = y.y;
        }
      }
      if (tid == 0) mbar_expect(bar + 8 * (12 + (it & 1)), 3072);
#pragma unroll 1
      for (int kc = 0; kc < 10; kc++) {
        const uint64_t da = mkdesc(SB0 + st * LB_STAGE, 1024, 128, 0), db = mkdesc(SB0 + st * LB_STAGE + 8192 + wg * 1792, 3584, 128, 0);
        mbar_wait(bar + 8 * st, ph);
        wg_fence();
#pragma unroll
        for (int k = 0; k < 4; k++) wg_ss_n112_ta0_tb1(d, da + k * 128, db + k * 448, kc | k);
        wg_commit();
        wg_wait<1>();
        if (kc > 0 && lane == 0) mbar_arrive(bar + 8 * (6 + (st == 0 ? 5 : st - 1)));
        if (++st == 6) { st = 0; ph ^= 1; }
      }
      wg_wait<0>();
      pin<56>(d);
      if (lane == 0) mbar_arrive(bar + 8 * (6 + (st == 0 ? 5 : st - 1)));
      if (nb == 5) {
#pragma unroll
        for (int j = 20; j < 28; j++) rr[j] = 0;
      }
#pragma unroll
      for (int j = 0; j < 28; j++) { d[2 * j] += bflo(rr[j]); d[2 * j + 1] += bfhi(rr[j]); }
      const float cnt = nb * 16.f;
      const uint32_t so = LB_ST + (it & 1) * 3072 + (16 * w + g) * 48;
#pragma unroll
      for (int h = 0; h < 2; h++) {
        float sum = 0.f;
#pragma unroll
        for (int j = 0; j < 14; j++) sum += d[4 * j + 2 * h] + d[4 * j + 2 * h + 1];
        sum += __shfl_xor_sync(~0u, sum, 1); sum += __shfl_xor_sync(~0u, sum, 2);
        const float mean = sum * rcp(cnt);
        float q = 0.f, q2 = 0.f;
#pragma unroll
        for (int j = 0; j < 14; j++) {
          const float a = d[4 * j + 2 * h] - mean, b = d[4 * j + 2 * h + 1] - mean;
          if (j < 10) q = fmaf(a, a, fmaf(b, b, q)); else q2 = fmaf(a, a, fmaf(b, b, q2));
        }
        if (nb == 7) q += q2;
        q += __shfl_xor_sync(~0u, q, 1); q += __shfl_xor_sync(~0u, q, 2);
        if (i4 < 3) { const uint32_t b = mapa(sb, i4); sta2f(b + so + h * 384 + u * 8, sum, q, b + O_BAR + 8 * (12 + (it & 1))); }
      }
      mbar_wait(bar + 8 * (12 + (it & 1)), (it >> 1) & 1);
#pragma unroll
      for (int h = 0; h < 2; h++) {
        const float4 x = lds4f(sb + so + h * 384), y = lds4f(sb + so + h * 384 + 16), z = lds4f(sb + so + h * 384 + 32);
        const float mu = (((x.x + x.z) + (y.x + y.z)) + (z.x + z.z)) * (1.f / DM);
        const float e0 = x.x * (1.f / 112.f) - mu, e1 = x.z * (1.f / 112.f) - mu, e2 = y.x * (1.f / 112.f) - mu, e3 = y.z * (1.f / 112.f) - mu;
        const float e4 = z.x * (1.f / 112.f) - mu, e5 = z.z * (1.f / 80.f) - mu;
        const float q = (((x.y + x.w) + (y.y + y.w)) + (z.y + z.w)) + 112.f * ((e0 * e0 + e1 * e1) + (e2 * e2 + e3 * e3) + e4 * e4) + 80.f * e5 * e5;
        const float rs = rsqrtf(q * (1.f / DM) + 1e-5f), sh = -mu * rs;
        const int tk = row0 + 8 * h;
        uint8_t* xp = g_xn + (tk >> 5) * 40960 + (tk & 31) * 128 + (i4 & 1) * 8;
        bf16* rp = g_x + tk * DM + u * 112 + 4 * i4;
#pragma unroll
        for (int j = 0; j < 7; j++) {
          if (j < nb) {
            const int b16 = u * 7 + j;
            const float* a = d + 8 * j + 2 * h;
            *(uint2*)(xp + (b16 >> 2) * 4096 + (((2 * (b16 & 3) + (i4 >> 1)) ^ g) << 4)) =
                make_uint2(pack2(fmaf(a[0], rs, sh), fmaf(a[1], rs, sh)), pack2(fmaf(a[4], rs, sh), fmaf(a[5], rs, sh)));
            *(uint2*)(rp + 16 * j) = make_uint2(pack2(a[0], a[1]), pack2(a[4], a[5]));
          }
        }
      }
      bar_sync<1, 256>();
      if (tid == 0) { red_release(flags + FL_XN + tile * 8, 1); if (it == 0) GTT(layer * 4 + 1, 9); }
      __syncwarp();
    }
  } else {
    asm volatile("barrier.cluster.wait.aligned;" ::: "memory");
  }
  asm volatile("barrier.cluster.arrive.relaxed.aligned;\nbarrier.cluster.wait.aligned;" ::: "memory");
  GT(layer * 4 + 1, 10);
}

__global__ void __launch_bounds__(384, 1)
rec_kernel(const __grid_constant__ CUtensorMap tmq, const __grid_constant__ CUtensorMap tmk,
           const __grid_constant__ CUtensorMap tmv, const __grid_constant__ CUtensorMap tmo,
           const bf16* __restrict__ xin, const bf16* __restrict__ mem0, uint8_t* __restrict__ ar, uint32_t* __restrict__ flags, int layer) {
  extern __shared__ __align__(1024) uint8_t smem[];
  const uint32_t sb = smem_u32(smem);
  check_smem_base(sb);
  GT(layer * 4 + 1, 0);
  if (blockIdx.x < 3 * NLB) { lb_role(sb, xin, flags, layer); return; }
  const int bid = blockIdx.x - 3 * NLB;
  const int tid = threadIdx.x, wid = __shfl_sync(~0u, tid >> 5, 0), wg = wid >> 2, w = wid & 3;
  const int lane = __shfl_sync(~0u, tid & 31, tid & 31);
  const int head = bid / 3, rank = bid - head * 3;
  const int e0 = bid * 64;
  const uint32_t bar = sb + O_BAR;
  const uint32_t sb1 = mapa(sb, rank == 2 ? 0 : rank + 1), sb2 = mapa(sb, rank == 0 ? 2 : rank - 1);
  auto chunk_of = [&](int p) { const int c = 3 * rank + p; return p == 9 ? 9 : c >= 9 ? c - 9 : c; };

  auto load_piece = [&](int i) {
    if (lane == 0) mbar_expect(bar + 8 * (MB_W + i), 16384);
    __syncwarp();
    if (lane < 2) {
      if (i < 15) {
        const int m = i < 10 ? i & 1 : 0, p = (i < 10 ? i >> 1 : i - 10) * 2 + lane;
        tma5d(sb + m * 81920 + p * 8192, i >= 10 ? &tmv : m ? &tmk : &tmq, e0, chunk_of(p) * 4, bar + 8 * (MB_W + i));
      } else {
        const int p = (i - 15) * 2 + lane, k = p / 3, j = rank + p - 3 * k;
        tma2d(sb + O_WO + p * 8192, &tmo, p == 9 ? 576 : (rank * 3 + k) * 64, head * DH + (j >= 3 ? j - 3 : j) * 64, bar + 8 * (MB_W + i));
      }
    }
  };
  if (wid == 9) {
    mbar_init(bar + 8 * lane, lane == MB_ML ? ML_N0 : lane == MB_ML + 1 && ML_N0 < 4 ? 4 - ML_N0 : lane >= MB_WC ? 4 : 1);
    if (lane < 8) mbar_init(bar + 8 * (32 + lane), 4);
    asm volatile("fence.mbarrier_init.release.cluster;" ::: "memory");
    fence_async();
    __syncwarp();
#pragma unroll 1
    for (int i = 0; i < W_WIN; i++) load_piece(i);
  }
  __syncthreads();
  asm volatile("barrier.cluster.arrive.relaxed.aligned;" ::: "memory");

  if (wg < 2) {
    asm volatile("setmaxnreg.inc.sync.aligned.u32 208;");
    uint32_t a[40][4];
    const uint32_t swz = (lane & 7) * 128 + (((2 * w + ((lane >> 3) & 1)) ^ (lane & 7)) << 4);
    const uint32_t st_x = __shfl_sync(~0u, sb + O_QK + wg * 5120 + (lane >> 4) * 2048 + swz, lane);
    {
      const uint32_t la = sb + wg * 81920 + (lane >> 4) * 1024 + swz;
#pragma unroll
      for (int p = 0; p < 5; p++) {
        mbar_wait(bar + 8 * (MB_W + 2 * p + wg), 0);
#pragma unroll
        for (int k = 0; k < 8; k++) ldsm4t(a[p * 8 + k], la + (p * 8 + k) * 2048);
        fence_async();
        __syncwarp();
        mbar_arrive_elect(bar + 8 * (MB_WC + wg * 5 + p));
      }
    }
    GT(layer * 4 + 1, 5);
    asm volatile("barrier.cluster.wait.aligned;" ::: "memory");
    const uint32_t ld_m = __shfl_sync(~0u, sb + O_H + (lane & 7) * 128 + (((lane >> 3) ^ (lane & 7)) << 4), lane);

    for (int s = 0; s < NSEG; s++) {
      const uint32_t par = s & 1;
      if (wid == 4) TS0(0);
      if (wid == 0) TS(30);
      {
        float ax[16];
        constexpr uint64_t db = mkdesc(SB0 + O_H + 1024, 16, 1024, 1);
        mbar_wait(bar + 8 * MB_XF, par);
        wg_fence();
#pragma unroll
        for (int k = 0; k < 20; k++) wg_rs_n32_tb0(ax, a[vord(k)], db + hoff(vord(k)), k);
        mbar_wait(bar + 8 * (MB_XF + 1), par);
        wg_fence();
#pragma unroll
        for (int k = 20; k < XP_END; k++) wg_rs_n32_tb0(ax, a[vord(k)], db + hoff(vord(k)), 1);
        wg_commit();
        if (s > 0) { if (wg == 0) bar_sync<B_PFREE, 256>(); else bar_sync<B_PFREE1, 256>(); }
        if (wid == 6 && lane == 0) { mbar_expect(bar + 8 * MB_SM, 2 * SM_SLOT + 48 + 48); mbar_expect(bar + 8 * MB_SX, 2 * 2176); }
        wg_wait<0>();
        pin<16>(ax);
        if (w == 0) TS(1 + 22 * wg);
        stsm4t(st_x, pack2(ax[0], ax[1]), pack2(ax[2], ax[3]), pack2(ax[4], ax[5]), pack2(ax[6], ax[7]));
        stsm4t(st_x + 4096, pack2(ax[8], ax[9]), pack2(ax[10], ax[11]), pack2(ax[12], ax[13]), pack2(ax[14], ax[15]));
        if (V_OWN > 0) bar_arrive<B_VOWN, 384>();
      }
      {
        float c[MP_CH][4];
#pragma unroll
        for (int k = 0; k < MP_CH; k++) c[k][0] = c[k][1] = c[k][2] = c[k][3] = 0.f;
        uint32_t b[MP_D][2][4];
        const uint32_t ld_m2 = opaque(ld_m ^ 64);
        SCHED_FENCE();
#define MORD(j) ((j) == 0 ? 9 : (j) < 4 ? (j) - 1 : 3 + ((j) - 4) / 2 + 3 * ((j) & 1))
#pragma unroll
        for (int j = 0; j < 10 + MP_D - 1; j++) {
          if (j < 10) {
            if (j == 0) { mbar_wait(bar + 8 * MB_ML, par); if (wid == 0) TS(2); }
            if (ML_N0 < 4 && j == ML_N0) { mbar_wait(bar + 8 * (MB_ML + 1), par); if (wid == 0) TS(3); }
            if (j == 4) { mbar_wait(bar + 8 * MB_MR, par); if (wid == 0) TS(4); }
            if (j == 4 + 2 * MR_N0) { mbar_wait(bar + 8 * (MB_MR + 1), par); if (wid == 0) TS(5); }
            ldsm4(b[j % MP_D][0], ld_m + MORD(j) * 5120);
            ldsm4(b[j % MP_D][1], ld_m2 + MORD(j) * 5120);
            if ((MP_F >> j) & 1) SCHED_FENCE();
          }
          const int u = j - (MP_D - 1);
          if (u >= 0) {
#pragma unroll
            for (int k = 0; k < 4; k++) mma16816(c[(4 * u + k) % MP_CH], a[4 * MORD(u) + k], b[u % MP_D][k >> 1][(k & 1) * 2], b[u % MP_D][k >> 1][(k & 1) * 2 + 1]);
          }
        }
        SCHED_FENCE();
        bar_arrive<B_VGO, 384>();
        SCHED_FENCE();
#pragma unroll
        for (int k = 0; k < 4; k++) c[0][k] = MP_CH == 4 ? (c[0][k] + c[1][k]) + (c[2][k] + c[MP_CH - 1][k]) : (c[1][k] + c[2][k]) + c[0][k];
        stsm2t(st_x + 1024 - wg * 3072, pack2(c[0][0], c[0][1]), pack2(c[0][2], c[0][3]));
        fence_async();
      }
      if (wg == 0) {
        bar_sync<B_QK, 256>();
        float sv[20];
        {
          constexpr uint64_t da = mkdesc(SB0 + O_QK, 16, 1024, 1), db = mkdesc(SB0 + O_K, 16, 2048, 1);
          wg_fence();
#pragma unroll
          for (int k = 0; k < 4; k++) wg_ss_n40_ta0_tb0(sv, da + 2 * k, db + 2 * k, k);
          wg_commit();
          bar_arrive<B_SISS, 256>();
        }
        if (w == 0) TS(6);
        SCHED_FENCE();
        const uint32_t ln = opaque(lane);
        uint32_t m0, m1, m2, m3, m4;
        {
          const uint32_t a1 = opaque(sb1 + O_SM + SM_SLOT + ln * 16), a2 = opaque(sb2 + O_SM + ln * 16);
          const uint32_t a3 = opaque(sb1 + O_SM + SM_SLOT + 512 + ln * 4), a4 = opaque(sb2 + O_SM + 512 + ln * 4);
          const uint32_t b1 = opaque(sb1 + O_BAR + 8 * MB_SM), b2 = opaque(sb2 + O_BAR + 8 * MB_SM);
          const uint32_t bt = opaque(mapa(sb, min(ln, 2u)) + O_BAR + 8 * MB_SM), at = opaque(bt + (O_MAXS + 48 - O_BAR - 8 * MB_SM));
          SCHED_FENCE();
          wg_wait<0>();
          pin<20>(sv);
          m0 = pack2(sv[2], sv[3]); m1 = pack2(sv[6], sv[7]); m2 = pack2(sv[10], sv[11]); m3 = pack2(sv[14], sv[15]); m4 = pack2(sv[18], sv[19]);
          if (w == 0) {
            sta4(a1, m0, m1, m2, m3, b1);
            sta4(a2, m0, m1, m2, m3, b2);
            sta1(a3, m4, b1);
            sta1(a4, m4, b2);
          }
          sta1p(at, 0u, bt, ln < 3);
          bar_arrive<B_SSENT, 256>();
          SCHED_FENCE();
        }
        const uint32_t p0 = pack2(sv[0], sv[1]), p1 = pack2(sv[4], sv[5]), p2 = pack2(sv[8], sv[9]), p3 = pack2(sv[12], sv[13]), p4 = pack2(sv[16], sv[17]);
        const uint32_t ox = O_K + w * 2048 + ln * 16, ox2 = O_K + 8192 + ln * 4;
        {
          const uint32_t a1 = opaque(sb1 + ox + 512), a2 = opaque(sb2 + ox), b1 = opaque(sb1 + O_BAR + 8 * MB_SX), b2 = opaque(sb2 + O_BAR + 8 * MB_SX);
          if (w == 0) {
            TS(7);
            const uint32_t om = opaque(sb + O_SM + ln * 16), om2 = opaque(sb + O_SM + 512 + ln * 4);
            const uint32_t pa0 = ld_m + (O_QM - O_H), pa1 = (ld_m ^ 64) + (O_QM - O_H);
            float t[10] = {bflo(m0), bfhi(m0), bflo(m1), bfhi(m1), bflo(m2), bfhi(m2), bflo(m3), bfhi(m3), bflo(m4), bfhi(m4)};
            pin<10>(t);
            SCHED_FENCE();
            mbar_wait(bar + 8 * MB_SM, par);
            const uint4 u = lds4(om), v = lds4(om + SM_SLOT);
            const uint32_t u4 = lds1(om2), v4 = lds1(om2 + SM_SLOT);
            sta4(a1, p0, p1, p2, p3, b1);
            sta4(a2, p0, p1, p2, p3, b2);
            if (SLD_POS == 0) bar_arrive<B_SLD, 256>();
            SCHED_FENCE();
#define ACC3(k, u, v) { t[k] += bflo(u) + bflo(v); t[k + 1] += bfhi(u) + bfhi(v); }
            ACC3(0, u.x, v.x) ACC3(2, u.y, v.y) ACC3(4, u.z, v.z) ACC3(6, u.w, v.w) ACC3(8, u4, v4)
            TS(8);
            const float mm = max10(t) * (SCL * L2E);
            if (SLD_POS == 1) { SCHED_FENCE(); bar_arrive<B_SLD, 256>(); SCHED_FENCE(); }
#pragma unroll
            for (int k = 0; k < 10; k++) t[k] = ex2(fmaf(t[k], SCL * L2E, -mm));
            stsm4(pa0, pack2(t[0], t[1]), pack2(t[2], t[3]), pack2(t[4], t[5]), pack2(t[6], t[7]));
            stsm1(pa1, pack2(t[8], t[9]));
            bar_arrive<B_PM, 160>();
            TS(9);
          } else {
            const uint32_t a3 = opaque(sb1 + ox2 + 128), a4 = opaque(sb2 + ox2);
            SCHED_FENCE();
            mbar_wait(bar + 8 * MB_SM, par);
            sta4(a1, p0, p1, p2, p3, b1);
            sta4(a2, p0, p1, p2, p3, b2);
            if (w == 3) { sta1(a3, p4, b1); sta1(a4, p4, b2); }
            bar_arrive<B_SLD, 256>();
          }
        }
        mbar_wait(bar + 8 * MB_SX, par);
        bar_sync<B_VEND, 256>();
        {
          float t[10];
          const uint4 u = lds4(sb + ox), v = lds4(sb + ox + 512);
          const uint32_t u4 = lds1(sb + ox2), v4 = lds1(sb + ox2 + 128);
          SCHED_FENCE();
          ACC2(0, p0, u.x, v.x) ACC2(2, p1, u.y, v.y) ACC2(4, p2, u.z, v.z) ACC2(6, p3, u.w, v.w) ACC2(8, p4, u4, v4)
          const int dq = 8 * w + (ln >> 2) - 2 * (ln & 3);
#pragma unroll
          for (int k = 1; k < 5; k++) {
            if (8 * (k - 1) > dq) t[2 * k] = -1e9f / SCL;
            if (8 * (k - 1) + 1 > dq) t[2 * k + 1] = -1e9f / SCL;
          }
          const float mm = max10(t) * (SCL * L2E);
#pragma unroll
          for (int k = 0; k < 10; k++) t[k] = ex2(fmaf(t[k], SCL * L2E, -mm));
          float sum = ((t[0] + t[1]) + (t[2] + t[3])) + ((t[4] + t[5]) + (t[6] + t[7])) + (t[8] + t[9]);
          sum += __shfl_xor_sync(~0u, sum, 1);
          sum += __shfl_xor_sync(~0u, sum, 2);
          const float inv = rcp(sum);
          const int rr = 2 * w + (ln & 1);
          const uint32_t pa = sb + O_QK + ((ln >> 1) & 3) * 2048 + rr * 128;
          stsm4(pa + (((ln >> 3) ^ rr) << 4), pack2(t[0] * inv, t[1] * inv), pack2(t[2] * inv, t[3] * inv), pack2(t[4] * inv, t[5] * inv), pack2(t[6] * inv, t[7] * inv));
          stsm2(pa + (((4 + ((ln >> 3) & 1)) ^ rr) << 4), pack2(t[8] * inv, t[9] * inv), 0u);
          fence_async();
        }
        bar_arrive<B_PX, 256>();
        if (w == 0) TS(10);
        bar_sync<B_XGO, 256>();
      } else {
        bar_arrive<B_QK, 256>();
        const int ln = opaque(lane);
        if (w == 2) {
          bar_sync<B_VHALF, 192>();
          if (ln == 0 && s > 0) { red_release(flags + FL_A + (e0 >> 10) * 8 + (s - 1) * 48, 1); }
          __syncwarp();
        }
        if (w == 3) {
          const int l = bid * 2 + ln, s2 = s + 2;
          if (ln < 2 && l < 160 && s2 < NSEG - 1) {
            const int tile = l >> 4;
            const uint8_t* p = ar + (s2 >> 2) * AR_GROUP + (s2 & 1) * 128 + ((s2 >> 1) & 1) * 512 + ar_chunk(tile) * 4096 +
                               ((l >> 3) & 1) * 16384 + (l & 1) * 256 + ((l >> 1) & 3) * 1024;
            asm volatile("prefetch.global.L2 [%0];" :: "l"(p));
          }
        }
        if (w == 0) {
          const bool more = s + 1 < NSEG;
          if (ln < 2 && more) mbar_expect(bar + 8 * (MB_XF + ln), FILL_B * 5);
          const uint8_t* src = g_xn + (s + 1) * 40960 + chunk_of(ln) * 4096;
          if ((s & 1) && more) { wait_flag(flags + FL_XN + ((s + 1) >> 1) * 8, 3); fence_async_global(); }
          bar_sync<B_VHALF, 192>();
          if ((ln < 4 || ln == 9) && more) bulk_g2s(sb + O_H + ln * 5120 + 1024, src, FILL_B, bar + 8 * MB_XF);
          bar_sync<B_VDONE, 160>();
          if (ln >= 4 && ln < 9 && more) bulk_g2s(sb + O_H + ln * 5120 + 1024, src, FILL_B, bar + 8 * (MB_XF + 1));
        }
        bar_sync<B_XGO1, 256>();
      }
    }
  } else {
    asm volatile("setmaxnreg.dec.sync.aligned.u32 88;");
    asm volatile("barrier.cluster.wait.aligned;" ::: "memory");

    const int g = lane >> 2, i4 = lane & 3;
    const int myT = w == 0 ? 9 : rank * 3 + w - 1, myP = w == 0 ? 9 : w - 1;
    const int tok = 2 * ((lane >> 1) & 3) + ((lane >> 3) & 1);
    const uint32_t fw_off = sb + O_H + myP * 5120 + tok * 128 + (((2 * (lane >> 4) + (lane & 1)) ^ tok) << 4);
    const uint32_t prod_off = (w >> 1) * 16384 + (w & 1) * 2048 + ((g >> 1) & 1) * 256 + (i4 * 2 + (g >> 2)) * 16 + (g & 1) * 8;
    const uint32_t cons_off = ar_chunk(myT) * 4096 + (lane >> 3) * 1024 + (lane & 7) * 16;
    auto tile_off = [&](int k) { return AR_MAP == 0 ? ar_chunk(rank * 3 + k) * 4096 : (k * 8 + rank) * 4096; };
    constexpr uint32_t T9_OFF = ar_chunk(9) * 4096;

    uint32_t mx;
    auto forward = [&](const uint32_t* p) {
      const uint32_t c = O_H + myP * 5120, bo = O_BAR + 8 * (MB_MR + (w > MR_N0));
      sts4(fw_off, p[0], p[1], p[2], p[3]);
      sts4(fw_off ^ 64, p[4], p[5], p[6], p[7]);
      fence_async();
      __syncwarp();
      mbar_arrive_elect(bar + 8 * (MB_ML + (w >= ML_N0)));
      if (w > 0) bulk_s2c_elect(sb1 + c + 6 * 5120, sb1 + bo, sb2 + c + 3 * 5120, sb2 + bo, sb + c);
      SCHED_FENCE();
      mx = 0;
#pragma unroll
      for (int k = 0; k < 8; k++) mx = __vmaxu2(mx, p[k] & 0x7FFF7FFFu);
    };
    auto send_max = [&]() {
      mx = max(mx & 0xFFFFu, mx >> 16);
      mx = __reduce_max_sync(~0u, mx);
      { const uint32_t b = mapa(sb, min(lane, 2)); sta1p(b + O_MAXS + (rank * 4 + w) * 4, mx << 16, b + O_BAR + 8 * MB_SM, lane < 3); }
    };
    auto arm = [&]() { if (lane == 0 && w < (MR_N0 < 3 ? 3 : 2)) mbar_expect(bar + 8 * (w == 0 ? MB_OG : MB_MR - 1 + w), w == 0 ? 2048 : w == 1 ? 2048 * MR_N0 : 2048 * (3 - MR_N0)); };
    {
      arm();
      const uint32_t* mp = (const uint32_t*)(mem0 + tok * DM + myT * 64 + 16 * (lane >> 4) + 4 * (lane & 1));
      const uint32_t p[8] = {mp[0], mp[4], mp[1], mp[5], mp[16], mp[20], mp[17], mp[21]};
      forward(p);
    }
    if (w == 1) {
#pragma unroll 1
      for (int i = W_WIN; i < 20; i++) {
        if (i <= W_OPEN) mbar_wait(bar + 8 * (MB_W + i - W_WIN), 0);
        if (i >= 10) mbar_wait(bar + 8 * (MB_WC + i - 10), 0);
        load_piece(i);
      }
    }
    if (w == 0) {
      if (lane < 2) mbar_expect(bar + 8 * (MB_XF + lane), 20480);
      wait_flag(flags + FL_XN, 3);
      fence_async_global();
      if (lane < 10) bulk_g2s(sb + O_H + lane * 5120 + 1024, g_xn + chunk_of(lane) * 4096, 4096, bar + 8 * (MB_XF + (lane >= 4 && lane < 9)));
      if (!TRIG_LATE) asm volatile("griddepcontrol.launch_dependents;");
      if (lane == 0) GTT(layer * 4 + 1, 4);
    }
    if (w == 2) {
      wait_flag(flags + FL_X, 128);
      wait_flag(g_zero + Z_FLAGS + FL_N, 4);
      const float sq = __ldcg((const float*)(g_zero + Z_NORM));
      float mx = 0.f;
#pragma unroll
      for (int k = 0; k < 5; k++) {
        const float4* p = (const float4*)g_nrm + k * 32 + lane;
        const float4 x = __ldcg(p), y = __ldcg(p + 160), z = __ldcg(p + 320), u = __ldcg(p + 480);
        mx = fmaxf(fmaxf(mx, fmaxf((x.x + y.x) + (z.x + u.x), (x.y + y.y) + (z.y + u.y))), fmaxf((x.z + y.z) + (z.z + u.z), (x.w + y.w) + (z.w + u.w)));
      }
#pragma unroll
      for (int o = 16; o; o >>= 1) mx = fmaxf(mx, __shfl_xor_sync(~0u, mx, o));
      sts1(sb + O_MAXS + 52, __float_as_uint(sqrt_approx(sq) * sqrt_approx(mx) * (25.2982213f * 1.1f)));
    }
    bar_sync<B_WG2, 128>();
    const float cbound = __uint_as_float(lds1(sb + O_MAXS + 52));
#pragma unroll 1
    for (int i = 10; i < 15; i++) mbar_wait(bar + 8 * (MB_W + i), 0);
    if (tid == 256) GTT(layer * 4 + 1, 7);

    const uint32_t la_w = sb + O_WV + ((lane >> 4) * 8 + (lane & 7)) * 128 + (((2 * w + ((lane >> 3) & 1)) ^ (lane & 7)) << 4);
    uint32_t af[V_RS][4];
#pragma unroll
    for (int k = 0; k < V_RS; k++) ldsm4t(af[k], la_w + vord(V_OWN + k) * 2048);
    uint32_t vf[10];
    uint4 oq0, oq1;
    uint8_t* op;
    auto pv_x = [&](int s) {
      float ox[16];
      const uint32_t vz[4] = {vf[8], vf[9], 0u, 0u};
      constexpr uint64_t dp = mkdesc(SB0 + O_QK, 16, 2048, 1);
      bar_sync<B_PX, 256>();
      wg_fence();
      wg_rs_n32_tb0(ox, vf, dp, 0);
      wg_rs_n32_tb0(ox, vf + 4, dp + 2, 1);
      wg_rs_n32_tb0(ox, vz, dp + 4, 1);
      wg_commit();
      const uint32_t ln = opaque(lane);
      op = g_ot + (size_t)s * (HE * 64) + (e0 + 16 * w) * 64 + (ln & 3) * 128 + (ln >> 2) * 16;
      wg_wait<0>();
      pin<16>(ox);
      oq0 = make_uint4(pack2(ox[0], ox[1]), pack2(ox[4], ox[5]), pack2(ox[8], ox[9]), pack2(ox[12], ox[13]));
      oq1 = make_uint4(pack2(ox[2], ox[3]), pack2(ox[6], ox[7]), pack2(ox[10], ox[11]), pack2(ox[14], ox[15]));
    };
    for (int s = 0;; s++) {
      const uint32_t par = s & 1;
      float sc, isc;
      uint32_t ao[O_RS > 0 ? O_RS : 1][4];
      {
        float av[20];
        constexpr uint64_t da = mkdesc(SB0 + O_WV, 1024, 1024, 1), db = mkdesc(SB0 + O_H, 16, 1024, 1);
#define V_RUN_RS(k0, k1) wg_fence(); _Pragma("unroll") for (int k = k0; k < k1; k++) wg_rs_n40_tb0(av, af[k], db + hoff(vord(V_OWN + k)), V_OWN + k);
#define V_RUN_SS(k0, k1) wg_fence(); _Pragma("unroll") for (int k = k0; k < k1; k++) wg_ss_n40_ta1_tb0(av, da + vord(k) * 128, db + hoff(vord(k)), k);
        if (V_OWN > 0) {
          bar_sync<B_VOWN, 384>();
          V_RUN_SS(0, V_OWN)
          if (w == 0) TS(29);
          SCHED_FENCE();
        }
        send_max();
        bar_sync<B_VGO, 384>();
        V_RUN_RS(0, V_N1)
        if (w == 0) TS(11);
        bar_sync<B_SISS, 256>();
        V_RUN_RS(V_N1, V_N1 + V_N2)
        bar_sync<B_SSENT, 256>();
        V_RUN_SS(V_OWN + V_RS, V_K1)
        V_RUN_RS(V_N1 + V_N2, V_RS)
        const uint32_t ln = opaque(lane);
        const uint32_t amx = opaque(sb + O_MAXS + 4 * min(ln, 11u));
        SCHED_FENCE();
        mbar_wait(bar + 8 * MB_SM, par);
        const uint32_t mxl = lds1(amx);
        if (s == 0) {
#pragma unroll 1
          for (int i = 15; i < 20; i++) mbar_wait(bar + 8 * (MB_W + i), 0);
          if (TRIG_LATE) asm volatile("griddepcontrol.launch_dependents;"); if (tid == 256) GTT(layer * 4 + 1, 8); }
        bar_sync<B_SLD, 256>();
        V_RUN_SS(V_K1, 20)
        wg_commit();
        V_RUN_SS((V_K1 > 20 ? V_K1 : 20), V_K2)
        wg_commit();
        wg_wait<1>();
        bar_arrive<B_VHALF, 192>();
        V_RUN_SS(V_K2, 40)
        wg_commit();
        SCHED_FENCE();
        if (w == 0) TS(12);
        {
          const float bnd = cbound * fmaxf(1.f, __uint_as_float(__reduce_max_sync(~0u, mxl)));
          const uint32_t eb = min(max(__float_as_uint(bnd) >> 23, 31u), 254u);
          sc = __uint_as_float(opaque((280u - eb) << 23));
          isc = __uint_as_float(opaque((eb - 29u) << 23));
        }
        const uint32_t pa = sb + O_QM + (ln & 7) * 128;
        const uint32_t pa0 = opaque(pa + (((ln >> 3) ^ (ln & 7)) << 4)), pa1 = opaque(pa0 ^ 64);
        const uint32_t o = O_OG + w * 256 + ln * 4;
        const uint32_t a0 = opaque(sb + o), a1 = opaque(sb1 + o + 4096), a2 = opaque(sb1 + o + 4096 + 128), a3 = opaque(sb2 + o + 2048), a4 = opaque(sb2 + o + 2048 + 128);
        const uint32_t b1 = opaque(sb1 + O_BAR + 8 * MB_OG), b2 = opaque(sb2 + O_BAR + 8 * MB_OG);
        const uint32_t c1 = opaque(0x3F803F80u);
        const uint32_t one[4] = {c1, c1, c1, c1};
        uint32_t pm[5];
        float s0[4] = {0.f, 0.f, 0.f, 0.f}, s1[4] = {0.f, 0.f, 0.f, 0.f}, s2[4] = {0.f, 0.f, 0.f, 0.f};
#define LD_AO _Pragma("unroll") for (int j = 0; j < 16; j++) if ((O_RSM >> j) & 1) ldsm4t(ao[O_IDX(j)], la_w + O_WO + (1 + (j >> 3)) * 24576 + (4 + (j & 7)) * 2048);
        if (VEND_POS == 2) bar_arrive<B_VEND, 256>();
        SCHED_FENCE();
        if (F_ORD == 0) {
          bar_sync<B_PM, 160>();
          ldsm4(pm, pa0);
          ldsm1(pm[4], pa1);
          if (VEND_POS == 0) bar_arrive<B_VEND, 256>();
          SCHED_FENCE();
        }
        wg_wait<0>();
        pin<20>(av);
        if (VEND_POS == 3) { bar_arrive<B_VEND, 256>(); SCHED_FENCE(); }
        if (w == 0) TS(13);
        if (O_RS_POS == 0) { LD_AO }
#pragma unroll
        for (int k = 0; k < 10; k++) vf[k] = pack2(av[2 * k], av[2 * k + 1]);
        if (F_ORD == 1) {
          SCHED_FENCE();
          bar_sync<B_PM, 160>();
          ldsm4(pm, pa0);
          ldsm1(pm[4], pa1);
          if (VEND_POS == 0) bar_arrive<B_VEND, 256>();
          if (O_RS_POS == 3) { LD_AO }
        }
        if (s == NSEG - 1) break;
        {
          float o0[4] = {0.f, 0.f, 0.f, 0.f}, o1[4] = {0.f, 0.f, 0.f, 0.f}, o2[4] = {0.f, 0.f, 0.f, 0.f};
          mma16816(s0, one, pm[0], pm[1]);
          mma16816(s1, one, pm[2], pm[3]);
          mma1688(s2, c1, c1, pm[4]);
          mma16816(o0, vf, pm[0], pm[1]);
          mma16816(o1, vf + 4, pm[2], pm[3]);
          mma1688(o2, vf[8], vf[9], pm[4]);
          const float i0 = rcp(s0[0] + s1[0] + s2[0]), i1 = rcp(s0[1] + s1[1] + s2[1]);
          const uint32_t p0 = pack2((o0[0] + o1[0] + o2[0]) * i0, (o0[1] + o1[1] + o2[1]) * i1), p1 = pack2((o0[2] + o1[2] + o2[2]) * i0, (o0[3] + o1[3] + o2[3]) * i1);
          sta1(a1, p0, b1); sta1(a2, p1, b1);
          sta1(a3, p0, b2); sta1(a4, p1, b2);
          sts1(a0, p0); sts1(a0 + 128, p1);
          if (O_RS_POS == 2) {
#pragma unroll
            for (int j = 0; j < 16; j++) if ((O_RSM >> j) & 1) ldsm4t(ao[O_IDX(j)], la_w + O_WO + (1 + (j >> 3)) * 24576 + (4 + (j & 7)) * 2048);
          }
          if (VEND_POS == 1) bar_arrive<B_VEND, 256>();
          fence_async();
        }
      }
      uint8_t* arp;
      uint32_t t1;
      {
        bar_sync<B_WG2, 128>();
        float c9[4], ca[4], cb[4], cc[4];
        constexpr uint64_t da = mkdesc(SB0 + O_WO, 1024, 1024, 1), db = mkdesc(SB0 + O_OG, 128, 128, 0);
#define O_RUN(acc, tile, k0, k1) _Pragma("unroll") for (int k = k0; k < k1; k++) wg_ss_n8_ta1_tb1(acc, da + (tile) * 1536 + k * 128, db + (k >> 2) * 128 + (k & 3) * 16, k);
        wg_fence();
        O_RUN(c9, 3, 0, 4)
        wg_commit();
        if (w == 0) TS(14);
        O_RUN(ca, 0, 0, 4) O_RUN(cb, 1, 0, 4) O_RUN(cc, 2, 0, 4)
        wg_commit();
        SCHED_FENCE();
        arp = ar + (s >> 2) * AR_GROUP + (s & 1) * 128 + ((s >> 1) & 1) * 512;
        uint8_t* pp = arp + opaque(prod_off);
        wg_wait<1>();
        pin<4>(c9);
        fix_red(pp + T9_OFF, c9, sc);
        SCHED_FENCE();
        if (O_RS_POS == 1) {
#pragma unroll
          for (int j = 0; j < 16; j++) if ((O_RSM >> j) & 1) ldsm4t(ao[O_IDX(j)], la_w + O_WO + (1 + (j >> 3)) * 24576 + (4 + (j & 7)) * 2048);
        }
        mbar_wait(bar + 8 * MB_OG, par);
        wg_fence();
        O_RUN(ca, 0, 4, 12)
        wg_commit();
        bar_arrive<B_VDONE, 160>();
        if (w == 0) TS(15);
#define O_MIX(acc, j0, j1) _Pragma("unroll") for (int j = j0; j < j1; j++) { const int k = 4 + (j & 7); \
          if ((O_RSM >> j) & 1) wg_rs_n8_tb1(acc, ao[O_IDX(j) < O_RS ? O_IDX(j) : 0], db + (k >> 2) * 128 + (k & 3) * 16, 1); \
          else wg_ss_n8_ta1_tb1(acc, da + (1 + (j >> 3)) * 1536 + k * 128, db + (k >> 2) * 128 + (k & 3) * 16, 1); }
        O_MIX(cb, 0, O_B1)
        wg_commit();
        if (O_MODE != 1) {
          wg_wait<1>();
          pin<4>(ca);
          if (!(EXP & 1)) fix_red(pp + tile_off(0), ca, sc);
          SCHED_FENCE();
          if (w == 0) TS(16);
          if (O_MODE == 2) {
            wg_wait<0>();
            pin<4>(cb);
            if (!(EXP & 1)) fix_red(pp + tile_off(1), cb, sc);
          }
          wg_fence();
        }
        if (O_B1 < 8) { O_MIX(cb, O_B1, 8) wg_commit(); }
        if (O_C1 < 16) {
          O_MIX(cc, 8, O_C1)
          wg_commit();
          wg_wait<1>();
          pin<4>(cb);
          if (!(EXP & 1)) fix_red(pp + tile_off(1), cb, sc);
          SCHED_FENCE();
          wg_fence();
        }
        O_MIX(cc, (O_C1 < 16 ? O_C1 : 8), 16)
        wg_commit();
        bar_arrive<B_XGO1, 256>();
        bar_arrive<B_XGO, 256>();
        if (O_MODE != 2 && O_C1 == 16) {
          wg_wait<1>();
          if (O_MODE == 1) { pin<4>(ca); if (!(EXP & 1)) fix_red(pp + tile_off(0), ca, sc); }
          pin<4>(cb);
          if (!(EXP & 1)) fix_red(pp + tile_off(1), cb, sc);
          SCHED_FENCE();
        }
        wg_wait<0>();
        pin<4>(cc);
        fix_red(pp + tile_off(2), cc, sc);
        t1 = clk();
        if (w == 3) TS(17);
      }
      pv_x(s);
      bar_arrive<B_PFREE, 256>();
      bar_arrive<B_PFREE1, 256>();
      if (w == 0) TS(28);
#pragma unroll
      for (int k = 0; k < V_RS; k++) ldsm4t(af[k], la_w + vord(V_OWN + k) * 2048);
      {
        arm();
        const int dly = w == 0 ? POLL_D0 : POLL_DELAY - (3 - w) * POLL_STEP;
        const uint32_t need = w == 0 ? 96 : ((EXP & 1) && w < 3) ? 0 : 32;
        const uint8_t* cp = arp + opaque(cons_off);
        uint4 y[4];
        int it = 0;
        while ((int)(clk() - t1) < dly) {}
        if (w == 3) TS(18);
        y[0] = ld_poll(cp); y[1] = ld_poll(cp + 256); y[2] = ld_poll(cp + 16384); y[3] = ld_poll(cp + 16384 + 256);
        if (EXP & 2) {} else if (EVF) { const uint64_t pol = policy_evict_first(); stg4h(op, oq0, pol); stg4h(op + 512, oq1, pol); } else { stg4(op, oq0); stg4(op + 512, oq1); }
        uint32_t p[8];
        const float isl = isc * 0.5f, bias = -(float)(need >> 3) * isl;
        while (true) {
          const uint32_t bad = ((y[0].x ^ need) | (y[0].z ^ need) | (y[1].x ^ need) | (y[1].z ^ need)) | ((y[2].x ^ need) | (y[2].z ^ need) | (y[3].x ^ need) | (y[3].z ^ need));
          const bool again = __any_sync(~0u, (bad & 127u) != 0);
          if (SPEC_DEC || !again) {
#pragma unroll
            for (int k = 0; k < 4; k++) {
              p[2 * k] = pack2(fmaf((float)(int)__funnelshift_r(y[k].x, y[k].y, 3), isl, bias), fmaf((float)(int)__funnelshift_r(y[k].z, y[k].w, 3), isl, bias));
              p[2 * k + 1] = pack2((float)(int)y[k].y * isc, (float)(int)y[k].w * isc);
            }
            if (SPEC_DEC) {
#pragma unroll
              for (int k = 0; k < 8; k++) asm volatile("" : "+r"(p[k]));
            }
          }
          if (!again) break;
          if (++it > 2000000) __trap();
          y[0] = ld_poll(cp); y[1] = ld_poll(cp + 256); y[2] = ld_poll(cp + 16384); y[3] = ld_poll(cp + 16384 + 256);
        }
        TS(19 + w);
        forward(p);
      }
    }
    if (VEND_POS == 1) bar_arrive<B_VEND, 256>();
    bar_arrive<B_VDONE, 160>();
    bar_arrive<B_XGO1, 256>();
    bar_arrive<B_XGO, 256>();
    pv_x(NSEG - 1);
    if (EVF) { const uint64_t pol = policy_evict_first(); stg4h(op, oq0, pol); stg4h(op + 512, oq1, pol); } else { stg4(op, oq0); stg4(op + 512, oq1); }
    bar_sync<B_WG2, 128>();
    if (tid == 256) { red_release(flags + FL_A + (e0 >> 10) * 8 + (NSEG - 1) * 48, 1); }
    __syncwarp();
  }
  asm volatile("barrier.cluster.arrive.relaxed.aligned;\nbarrier.cluster.wait.aligned;" ::: "memory");
  GT(layer * 4 + 1, 2);
  if (wid == 0) asm volatile("griddepcontrol.wait;" ::: "memory");
}

constexpr int P_B = 0, P_A = 131072, P_BAR = 196608, OPC_SMEM = P_BAR + 256;
#define PF_C 2
#define PF_S0 43
constexpr int OP_KR = 48;

__global__ void __launch_bounds__(384, 1)
opc_kernel(const __grid_constant__ CUtensorMap tmo, bf16* __restrict__ out, int layer,
           const bf16* __restrict__ Wq, const bf16* __restrict__ Wk, const bf16* __restrict__ Wv, const bf16* __restrict__ Wo) {
  extern __shared__ __align__(1024) uint8_t smem[];
  asm volatile("griddepcontrol.launch_dependents;");
  GT(layer * 4 + 2, 0);
  const uint32_t sb = smem_u32(smem);
  check_smem_base(sb);
  const int tid = threadIdx.x, wid = __shfl_sync(~0u, tid >> 5, 0), wg = wid >> 2, w = wid & 3, lane = tid & 31;
  const uint32_t bar = sb + P_BAR;
  uint32_t* flags = g_zero + Z_FLAGS + layer * FL_LAYER;
  float* acc = g_acc + layer * (S_TOK * DM);
  const uint64_t pol = policy_evict_first();
  if (wid == 0) {
    if (lane < 16) mbar_init(bar + 8 * lane, (lane == 8 || lane == 9) ? 8 : 1);
    fence_async();
  }
  __syncthreads();
  if (blockIdx.x < 30) {
    const int cg = blockIdx.x % 5, kg = blockIdx.x / 5;
    if (wg < 2) {
      asm volatile("setmaxnreg.inc.sync.aligned.u32 240;");
      uint32_t a[OP_KR][4];
      const uint32_t la = sb + P_B + ((lane >> 4) * 8 + (lane & 7)) * 128 + (((2 * w + ((lane >> 3) & 1)) ^ (lane & 7)) << 4);
      mbar_wait(bar + 80, 0);
#pragma unroll
      for (int k = 0; k < 32; k++) ldsm4t(a[k], la + wg * 65536 + k * 2048);
      bar_arrive<2, 288>();
      mbar_wait(bar + 88, 0);
#pragma unroll
      for (int k = 0; k < 16; k++) ldsm4t(a[32 + k], la + wg * 32768 + k * 2048);
      bar_arrive<3, 288>();
      mbar_wait(bar + 96, 0);
      float* ap = acc + (cg * 8 + wg * 4 + w) * 512 + lane * 4;
      for (int s = 0; s < NSEG; s++) {
        const int buf = s & 1;
        const uint32_t par = (s >> 1) & 1;
        float d[16];
        const uint64_t db = mkdesc(SB0 + P_B + buf * 65536, 512, 128, 0), da = mkdesc(SB0 + P_A + wg * 32768, 1024, 1024, 1);
        float* p = ap + s * (32 * DM);
        if (kg < 4 && s + 2 < NSEG) { if (EVF) stg4h(p + 2 * 32 * DM + kg * 128, make_uint4(0, 0, 0, 0), pol); else stg4(p + 2 * 32 * DM + kg * 128, make_uint4(0, 0, 0, 0)); }
#pragma unroll
        for (int q = 0; q < 4; q++) {
          mbar_wait(bar + 8 * (buf * 4 + q), par);
          wg_fence();
#pragma unroll
          for (int k = 16 * q; k < 16 * q + 16; k++) {
            if (k < OP_KR) wg_rs_n32_tb1(d, a[k < OP_KR ? k : 0], db + k * 64, k);
            else wg_ss_n32_ta1_tb1(d, da + (k - OP_KR) * 128, db + k * 64, 1);
          }
        }
        wg_commit();
        wg_wait<0>();
        pin<16>(d);
        if (lane == 0) mbar_arrive(bar + 8 * (8 + buf));
        if (s == NSEG - 1) GT(layer * 4 + 2, 6);
        if (EVF) {
          red4fh(p, d[0], d[1], d[4], d[5], pol);
          red4fh(p + 128, d[8], d[9], d[12], d[13], pol);
          red4fh(p + 256, d[2], d[3], d[6], d[7], pol);
          red4fh(p + 384, d[10], d[11], d[14], d[15], pol);
        } else {
          red4f(p, d[0], d[1], d[4], d[5]);
          red4f(p + 128, d[8], d[9], d[12], d[13]);
          red4f(p + 256, d[2], d[3], d[6], d[7]);
          red4f(p + 384, d[10], d[11], d[14], d[15]);
        }
        bar_sync<1, 256>();
        if (tid == 0) { red_release(flags + FL_B + s * 8, 1); }
        __syncwarp();
      }
    } else {
      asm volatile("setmaxnreg.dec.sync.aligned.u32 24;");
      if (w == 0) {
        if (lane == 0) { mbar_expect(bar + 80, 131072); mbar_expect(bar + 96, 65536); mbar_expect(bar + 88, 65536); }
        __syncwarp();
        if (lane < 16) tma2d(sb + P_B + lane * 8192, &tmo, cg * 128 + (lane >> 3) * 64, kg * 1024 + (lane & 7) * 64, bar + 80);
        else if (lane < 24) tma2d(sb + P_B + lane * 8192, &tmo, cg * 128 + ((lane >> 2) & 1) * 64, kg * 1024 + 768 + (lane & 3) * 64, bar + 96);
        bar_sync<2, 288>();
        fence_async();
        if (lane < 8) tma2d(sb + P_B + lane * 8192, &tmo, cg * 128 + (lane >> 2) * 64, kg * 1024 + 512 + (lane & 3) * 64, bar + 88);
        bar_sync<3, 288>();
        for (int s = 0; s < NSEG; s++) {
          const int buf = s & 1;
          if (s >= 2) mbar_wait(bar + 8 * (8 + buf), ((s >> 1) & 1) ^ 1);
          if (s >= 2) wait_flag(flags + FL_B + (s - 2) * 8, 30);
          wait_flag(flags + FL_A + s * 48 + kg * 8, 16);
          fence_async_global();
          if (lane < 4) {
            mbar_expect(bar + 8 * (buf * 4 + lane), 16384);
            if (EVF) bulk_g2sh(sb + P_B + buf * 65536 + lane * 16384, g_ot + (size_t)s * (HE * 64) + kg * 65536 + lane * 16384, 16384, bar + 8 * (buf * 4 + lane), pol);
            else bulk_g2s(sb + P_B + buf * 65536 + lane * 16384, g_ot + (size_t)s * (HE * 64) + kg * 65536 + lane * 16384, 16384, bar + 8 * (buf * 4 + lane));
            if (s == NSEG - 1 && lane == 0) GTT(layer * 4 + 2, 5);
          }
          __syncwarp();
        }
      } else if (w == 1 && layer == 0) {
#pragma unroll 1
        for (int q = 4 * (4 - PF_C); q < 18; q++) {
          wait_flag(flags + FL_A + (PF_S0 + q) * 48 + kg * 8, 16);
          const int m = q >> 2;
          const uint8_t* W = m == 0 ? (const uint8_t*)Wo : m == 1 ? (const uint8_t*)Wv : m == 2 ? (const uint8_t*)Wk : m == 3 ? (const uint8_t*)Wq : (q & 1) ? g_w2 : g_w1;
          const int n = m < 4 ? 512 : (q & 1) ? 224 : 640, l0 = m < 4 ? blockIdx.x * 2048 + (q & 3) * 512 : blockIdx.x * n, lim = m < 4 ? 61440 : (q & 1) ? 6720 : 19200;
#pragma unroll 1
          for (int k = lane; k < n; k += 32) {
            if (l0 + k < lim) asm volatile("prefetch.global.L2 [%0];" :: "l"(W + (size_t)(l0 + k) * 128));
            __nanosleep(100);
          }
        }
      }
    }
  } else {
    constexpr int LD = 644;
    float* xs = (float*)smem;
    uint32_t par = 0;
    for (int task = blockIdx.x - 30; task < 2 * NSEG; task += 6, par ^= 1) {
      const int s = task >> 1, jj = task & 1;
      if (wid == 0) {
        wait_flag(flags + FL_XN + (task >> 2) * 8, 3);
        fence_async_global();
        if (lane == 0) { mbar_expect(bar, 20480); bulk_g2s(sb + 49152, g_x + task * 16 * DM, 20480, bar); }
      }
      if (wid == 1) { wait_flag(flags + FL_B + s * 8, 30); if (s == NSEG - 1 && lane == 0) GTT(layer * 4 + 2, 7); }
      __syncthreads();
      if (wid < 10) {
        float4 v[8];
#pragma unroll
        for (int k = 0; k < 8; k++) v[k] = EVF ? ldg4fh(acc + s * (32 * DM) + (wid * 8 + k) * 256 + jj * 128 + lane * 4, pol) : __ldcg((const float4*)(acc + s * (32 * DM) + (wid * 8 + k) * 256 + jj * 128 + lane * 4));
        float* xp = xs + (lane & 3) * 2 * LD + wid * 64 + (lane >> 2);
#pragma unroll
        for (int k = 0; k < 8; k++) { xp[k * 8] = v[k].x; xp[LD + k * 8] = v[k].y; xp[8 * LD + k * 8] = v[k].z; xp[9 * LD + k * 8] = v[k].w; }
      }
      mbar_wait(bar, par);
      __syncthreads();
#pragma unroll 1
      for (int row = wid; row < 16; row += 12) {
        const int tk = task * 16 + row;
        float v[20], sum = 0.f;
        const int pj = (lane & 24) + 2 * (lane & 3) + ((lane >> 2) & 1);
        bf16* dst = out ? out + tk * DM + lane * 2 : g_x + tk * DM + pj * 2;
#pragma unroll
        for (int k = 0; k < 10; k++) {
          const float2 u = *(const float2*)(xs + row * LD + k * 64 + lane * 2);
          const uint32_t r = *(const uint32_t*)(smem + 49152 + row * 1280 + k * 128 + pj * 4);
          v[2 * k] = u.x + bflo(r); v[2 * k + 1] = u.y + bfhi(r); sum += v[2 * k] + v[2 * k + 1];
          *(uint32_t*)(dst + k * 64) = pack2(v[2 * k], v[2 * k + 1]);
        }
        if (!out) {
#pragma unroll
          for (int o = 16; o; o >>= 1) sum += __shfl_xor_sync(~0u, sum, o);
          const float m = sum * (1.f / DM);
          float q = 0.f;
#pragma unroll
          for (int k = 0; k < 20; k++) { v[k] -= m; q += v[k] * v[k]; }
#pragma unroll
          for (int o = 16; o; o >>= 1) q += __shfl_xor_sync(~0u, q, o);
          const float rs = rsqrtf(q * (1.f / DM) + 1e-5f);
          uint8_t* xp = g_xt + (tk >> 7) * 163840 + (tk & 127) * 128 + (((lane >> 2) ^ (tk & 7)) << 4) + (lane & 3) * 4;
#pragma unroll
          for (int k = 0; k < 10; k++) *(uint32_t*)(xp + k * 16384) = pack2(v[2 * k] * rs, v[2 * k + 1] * rs);
        }
      }
      fence_async();
      __syncthreads();
      if (tid == 0 && !out) { red_release(flags + FL_LAYER + FL_T + (task >> 3) * 8, 1); }
    }
  }
  GT(layer * 4 + 2, 1);
  __syncwarp();
  asm volatile("griddepcontrol.wait;" ::: "memory");
  GT(layer * 4 + 2, 2);
}

constexpr int L_STAGE = 47104;
constexpr int L_KV = 0, L_B2 = 43008;
constexpr int L_BAR = 4 * L_STAGE;
constexpr int LA_SMEM = L_BAR + 256;
__device__ __forceinline__ float phi(float t) { return (fmaxf(t, 0.f) + 1e-6f) + ex2(fminf(t * 1.4426950408889634f, 0.f)); }
__device__ __forceinline__ uint32_t phi2(float a, float b) { return pack2(phi(a), phi(b)); }
#define LA_LATE 6
#define PF_N0 2
#define PF_N1 0
#define PF_SLEEP 300

__global__ void __launch_bounds__(384, 1)
la_kernel(const bf16* __restrict__ Wq, const bf16* __restrict__ Wk, const bf16* __restrict__ Wv,
          const bf16* __restrict__ Wo, uint8_t* __restrict__ ar, int layer) {
  extern __shared__ __align__(1024) uint8_t smem[];
  const uint32_t sb = smem_u32(smem);
  check_smem_base(sb);
  const int tid = threadIdx.x, wid = __shfl_sync(~0u, tid >> 5, 0), wg = wid >> 2, w = wid & 3, lane = tid & 31, g = lane >> 2, i4 = lane & 3;
  const int cr = blockIdx.x & 1, hg = (blockIdx.x >> 1) & 7, tb = (blockIdx.x >> 4) * 2 + cr;
  const uint32_t bar = sb + L_BAR;
  uint32_t* flags = g_zero + Z_FLAGS + layer * FL_LAYER;
  asm volatile("griddepcontrol.launch_dependents;");
  GT(layer * 4, 0);
  if (wid == 0) {
    if (lane < 8) mbar_init(bar + 8 * lane, lane >= 4 ? (blockIdx.x < 128 ? 16 : 8) : 1);
    asm volatile("fence.mbarrier_init.release.cluster;" ::: "memory");
    fence_async();
  }
  if (blockIdx.x >= 128) {
    __syncthreads();
    const int q = blockIdx.x - 128;
    const uint8_t* src = (const uint8_t*)Wo + q * 1966080;
    if (wid == 11) {
#pragma unroll 1
      for (int it = 0; it < 48; it++) {
        const int st = it & 3;
        if (it >= 4) mbar_wait(bar + 8 * (4 + st), ((it >> 2) & 1) ^ 1);
        if (lane == 0) mbar_expect(bar + 8 * st, 40960);
        __syncwarp();
        if (lane < 4) bulk_g2s(sb + st * 40960 + lane * 10240, src + it * 40960 + lane * 10240, 10240, bar + 8 * st);
      }
    } else if (wid < 8) {
      float c[20];
#pragma unroll
      for (int k = 0; k < 20; k++) c[k] = 0.f;
#pragma unroll 1
      for (int it = 0; it < 48; it++) {
        const int st = it & 3;
        mbar_wait(bar + 8 * st, (it >> 2) & 1);
#pragma unroll
        for (int k = 0; k < 20; k++) {
          const float2 u = lds2f(sb + st * 40960 + wid * 5120 + k * 256 + lane * 8);
          const uint32_t x = __float_as_uint(u.x), y = __float_as_uint(u.y);
          float* d = c + (k % 5) * 4;
          d[0] = fmaf(bflo(x), bflo(x), d[0]); d[1] = fmaf(bfhi(x), bfhi(x), d[1]); d[2] = fmaf(bflo(y), bflo(y), d[2]); d[3] = fmaf(bfhi(y), bfhi(y), d[3]);
        }
        __syncwarp();
        if (lane == 0) mbar_arrive(bar + 8 * (4 + st));
      }
      float* red = (float*)(smem + 163840);
#pragma unroll
      for (int k = 0; k < 5; k++) *(float4*)(red + wid * DM + k * 128 + lane * 4) = make_float4(c[4 * k], c[4 * k + 1], c[4 * k + 2], c[4 * k + 3]);
      bar_sync<1, 256>();
      for (int k = tid; k < DM; k += 256) {
        float t = 0.f;
#pragma unroll
        for (int j = 0; j < 8; j++) t += red[j * DM + k];
        g_nrm[q * DM + k] = t;
      }
      asm volatile("griddepcontrol.wait;" ::: "memory");
      bar_sync<1, 256>();
      if (tid == 0) red_release(flags + FL_N, 1);
      GT(0, 2);
    }
    return;
  }
  __syncthreads();
  asm volatile("barrier.cluster.arrive.relaxed.aligned;" ::: "memory");
  if (layer == 0) asm volatile("griddepcontrol.wait;" ::: "memory");
  asm volatile("barrier.cluster.wait.aligned;" ::: "memory");
  if (wg == 2) {
    asm volatile("setmaxnreg.dec.sync.aligned.u32 40;");
    if (w == 0) {
      if (lane < 4) {
        mbar_expect(bar + 8 * lane, L_STAGE);
        bulk_g2s_mc(sb + lane * L_STAGE + 16384 + cr * 15360, g_w1 + (hg * 10 + lane) * 30720 + cr * 15360, 15360, bar + 8 * lane);
      }
      if (layer == 1) { if (LA_LATE) wait_flag(flags + FL_T + 15 * 8, LA_LATE); wait_flag(flags + FL_T + tb * 8, 8); fence_async_global(); }
      if (lane < 4) bulk_g2s(sb + lane * L_STAGE, g_xt + (tb * 10 + lane) * 16384, 16384, bar + 8 * lane);
#pragma unroll 1
      for (int kc = 4; kc < 10; kc++) {
        const int st = kc & 3;
        mbar_wait(bar + 8 * (4 + st), ((kc >> 2) & 1) ^ 1);
        if (lane == 0) {
          mbar_expect(bar + 8 * st, L_STAGE);
          bulk_g2s_mc(sb + st * L_STAGE + 16384 + cr * 15360, g_w1 + (hg * 10 + kc) * 30720 + cr * 15360, 15360, bar + 8 * st);
          bulk_g2s(sb + st * L_STAGE, g_xt + (tb * 10 + kc) * 16384, 16384, bar + 8 * st);
        }
        __syncwarp();
      }
    } else {
      const int t = tid - 288;
#pragma unroll 1
      for (int k = t; k < 768; k += 96) *(uint4*)(ar + blockIdx.x * 12288 + k * 16) = make_uint4(0, 0, 0, 0);
      if (layer == 0) {
        float sv = 0.f;
        const uint4* pv = (const uint4*)((const uint8_t*)Wv + blockIdx.x * 61440) + t;
#pragma unroll 1
        for (int k = 0; k < 40; k += 5) {
          uint4 v[5];
#pragma unroll
          for (int j = 0; j < 5; j++) v[j] = __ldg(pv + (k + j) * 96);
#pragma unroll
          for (int j = 0; j < 5; j++) {
            sv = fmaf(bflo(v[j].x), bflo(v[j].x), fmaf(bfhi(v[j].x), bfhi(v[j].x), fmaf(bflo(v[j].y), bflo(v[j].y), fmaf(bfhi(v[j].y), bfhi(v[j].y), sv))));
            sv = fmaf(bflo(v[j].z), bflo(v[j].z), fmaf(bfhi(v[j].z), bfhi(v[j].z), fmaf(bflo(v[j].w), bflo(v[j].w), fmaf(bfhi(v[j].w), bfhi(v[j].w), sv))));
          }
        }
#pragma unroll
        for (int o = 16; o; o >>= 1) sv += __shfl_xor_sync(~0u, sv, o);
        if (lane == 0) atomicAdd((float*)(g_zero + Z_NORM), sv);
      }
#pragma unroll 1
      for (int k = 0; k < 5 * (layer ? PF_N1 : PF_N0); k++) {
        const int m = k / 5;
        const bf16* W = m == 0 ? Wq : m == 1 ? Wk : m == 2 ? Wv : Wo;
        asm volatile("prefetch.global.L2 [%0];" :: "l"((const uint8_t*)W + blockIdx.x * 61440 + (k - m * 5) * 12288 + t * 128));
        __nanosleep(PF_SLEEP);
      }
      if (t == 0) GTT(layer * 4, 14);
      bar_arrive<3, 352>();
    }
  } else {
    asm volatile("setmaxnreg.inc.sync.aligned.u32 232;");
    GT(layer * 4, 4);
    uint32_t pq[5][4];
    float* kv = (float*)(g_zero + Z_KV) + layer * KV_LAYER + hg * 1920;
    {
      float d[120];
#pragma unroll 1
      for (int kc = 0; kc < 10; kc++) {
        const int st = kc & 3;
        const uint64_t da = mkdesc(SB0 + st * L_STAGE + wg * 8192, 16, 1024, 1), db = mkdesc(SB0 + st * L_STAGE + 16384, 3840, 128, 0);
        mbar_wait(bar + 8 * st, (kc >> 2) & 1);
        wg_fence();
#pragma unroll
        for (int k = 0; k < 4; k++) wg_ss_n240_ta0_tb1(d, da + 2 * k, db + k * 480, kc | k);
        wg_commit();
        if (kc > 0) { wg_wait<1>(); if (lane < 2) mbar_arrive_cl(mapa(bar + 8 * (4 + ((kc - 1) & 3)), lane)); }
      }
      wg_wait<0>();
      pin<120>(d);
      GT(layer * 4, 5);
      bar_sync<1, 256>();
      const uint32_t kb = sb + L_KV + (wg * 8 + 2 * w + ((lane >> 3) & 1)) * 2688 + (lane >> 4) * 128 + (lane & 7) * 16;
#pragma unroll
      for (int j = 0; j < 5; j++) stsm4(kb + 1280 + j * 256, pack2(d[80 + 8 * j], d[81 + 8 * j]), pack2(d[82 + 8 * j], d[83 + 8 * j]), pack2(d[84 + 8 * j], d[85 + 8 * j]), pack2(d[86 + 8 * j], d[87 + 8 * j]));
      stsm2(kb + 2560, 0x3F803F80u, 0x3F803F80u);
#pragma unroll
      for (int j = 0; j < 5; j++) stsm4(kb + j * 256, phi2(d[40 + 8 * j], d[41 + 8 * j]), phi2(d[42 + 8 * j], d[43 + 8 * j]), phi2(d[44 + 8 * j], d[45 + 8 * j]), phi2(d[46 + 8 * j], d[47 + 8 * j]));
      fence_async();
      bar_sync<1, 256>();
      float e[44];
      {
        const uint64_t da = mkdesc(SB0 + L_KV + wg * 1024, 2688, 128, 0), db = mkdesc(SB0 + L_KV + 1280, 2688, 128, 0);
        wg_fence();
#pragma unroll
        for (int k = 0; k < 8; k++) wg_ss_n88_ta1_tb1(e, da + k * 336, db + k * 336, k);
        wg_commit();
        wg_wait<0>();
        pin<44>(e);
      }
#pragma unroll
      for (int h = 0; h < 2; h++) {
        const int row = wg * 64 + 16 * w + 8 * h + g;
        const int c = row < 80 ? 2 * i4 - (row / 20) * 20 : 100;
        float* dst = kv + row * 24 + c;
#pragma unroll
        for (int j = 0; j < 10; j++)
          asm volatile("{\n.reg .pred p;\nsetp.lt.u32 p, %3, 20;\n@p red.relaxed.gpu.global.add.v2.f32 [%0], {%1,%2};\n}" :: "l"(dst + 8 * j), "f"(e[4 * j + 2 * h]), "f"(e[4 * j + 2 * h + 1]), "r"(c + 8 * j) : "memory");
        asm volatile("{\n.reg .pred p;\nsetp.ne.u32 p, %2, 0;\n@p red.relaxed.gpu.global.add.f32 [%0], %1;\n}" :: "l"(kv + row * 24 + 20), "f"(e[40 + 2 * h]), "r"((int)(row < 80 && i4 == 0)) : "memory");
      }
      bar_sync<1, 256>();
      GT(layer * 4, 6);
      if (tid == 0) { red_release(flags + FL_KV + hg * 8, 1); }
      __syncwarp();
      pin<40>(d);
#pragma unroll
      for (int k = 0; k < 5; k++) {
        pq[k][0] = phi2(d[8 * k], d[8 * k + 1]); pq[k][1] = phi2(d[8 * k + 2], d[8 * k + 3]);
        pq[k][2] = phi2(d[8 * k + 4], d[8 * k + 5]); pq[k][3] = phi2(d[8 * k + 6], d[8 * k + 7]);
      }
    }
#pragma unroll 1
    for (int k = tid; k < 1600; k += 256) sts4(sb + L_B2 + k * 16, 0, 0, 0, 0);
    GT(layer * 4, 7);
    if (wid == 0) wait_flag(flags + FL_KV + hg * 8, 16);
    GT(layer * 4, 8);
    bar_sync<1, 256>();
    if (tid < 240) {
      const int dd = tid / 3, part = tid - dd * 3, n = (dd / 20) * 20 + 8 * part;
      const float4 v0 = __ldcg((const float4*)(kv + dd * 24 + 8 * part)), v1 = __ldcg((const float4*)(kv + dd * 24 + 8 * part + 4));
      const float z = __ldcg(kv + dd * 24 + 20);
      const uint32_t a = sb + L_B2 + (dd >> 3) * 2560 + (dd & 7) * 16, zz = pack2(z, z);
      const uint32_t a0 = a + (n >> 3) * 128 + (n & 7) * 2, a1 = a + ((n + 4) >> 3) * 128 + ((n + 4) & 7) * 2;
      sts2(a0, pack2(v0.x, v0.y), pack2(v0.z, v0.w)); sts2(a0 + 1280, zz, zz);
      if (part < 2) { sts2(a1, pack2(v1.x, v1.y), pack2(v1.z, v1.w)); sts2(a1 + 1280, zz, zz); }
    }
    fence_async();
    bar_sync<1, 256>();
    {
      float o[80];
      const uint64_t db = mkdesc(SB0 + L_B2, 2560, 128, 0);
      wg_fence();
#pragma unroll
      for (int k = 0; k < 5; k++) wg_rs_n160_tb1(o, pq[k], db + k * 320, k);
      wg_commit();
      wg_wait<0>();
      pin<80>(o);
      uint8_t* op = g_oa + (tb * 2 + wg) * 81920 + hg * 10240 + w * 256 + lane * 4;
#pragma unroll
      for (int j = 0; j < 20; j++) {
        const float inv = rcp(o[40 + 2 * j] + 1e-6f);
        *(uint32_t*)(op + (j >> 1) * 1024 + (j & 1) * 128) = pack2(o[2 * j] * inv, o[2 * j + 1] * inv);
      }
      GT(layer * 4, 9);
    }
    bar_sync<3, 352>();
    if (tid == 0) { red_release(flags + FL_O + tb * 8, 1); red_add(flags + FL_X, 1); }
    GT(layer * 4, 2);
    if (wid == 7) asm volatile("griddepcontrol.wait;" ::: "memory");
  }
}

__global__ void __launch_bounds__(256) prep_kernel(const bf16* __restrict__ x, const bf16* __restrict__ wqkv, const bf16* __restrict__ wo) {
  asm volatile("griddepcontrol.launch_dependents;");
  const int b = blockIdx.x, tid = threadIdx.x, lane = tid & 31;
  if (b < 160) GT(3, 0);
  if (b < 256) {
    const int row = b * 8 + (tid >> 5);
    float v[20], s = 0.f;
#pragma unroll
    for (int k = 0; k < 10; k++) { const uint32_t u = __ldg((const uint32_t*)(x + row * DM + k * 64 + lane * 2)); v[2 * k] = bflo(u); v[2 * k + 1] = bfhi(u); s += v[2 * k] + v[2 * k + 1]; }
#pragma unroll
    for (int o = 16; o; o >>= 1) s += __shfl_xor_sync(~0u, s, o);
    const float m = s * (1.f / DM);
    float q = 0.f;
#pragma unroll
    for (int k = 0; k < 20; k++) { v[k] -= m; q += v[k] * v[k]; }
#pragma unroll
    for (int o = 16; o; o >>= 1) q += __shfl_xor_sync(~0u, q, o);
    const float r = rsqrtf(q * (1.f / DM) + 1e-5f);
#pragma unroll
    for (int k = 0; k < 10; k++)
      *(uint32_t*)(g_xt + ((row >> 7) * 10 + k) * 16384 + (row & 127) * 128 + (((lane >> 2) ^ (row & 7)) << 4) + (lane & 3) * 4) = pack2(v[2 * k] * r, v[2 * k + 1] * r);
  } else if (b < 256 + 203) {
#pragma unroll
    for (int it = 0; it < 4; it++) {
      const int u = (b - 256) * 1024 + it * 256 + tid;
      if (u < 153600) {
        const int k8 = u & 7, nb = (u >> 3) % 30, kg = (u / 240) % 80, hg = u / 19200;
        *(uint4*)(g_w1 + u * 16) = __ldg((const uint4*)(wqkv + (kg * 8 + k8) * 1920 + (nb / 10) * 640 + hg * 80 + (nb % 10) * 8));
      } else {
        const int v = u - 153600, k8 = v & 7, nb = (v >> 3) % 28, kg = (v / 224) % 80, c = (v / 17920) * 224 + nb * 8;
        if (v < 53760) *(uint4*)(g_w2 + v * 16) = c < DM ? __ldg((const uint4*)(wo + (kg * 8 + k8) * DM + c)) : make_uint4(0, 0, 0, 0);
      }
    }
  } else {
    const int t = (b - 459) * 256 + tid;
    for (int k = t; k < Z_END / 4; k += 16 * 256) ((uint4*)g_zero)[k] = make_uint4(0, 0, 0, 0);
    for (int k = t; k < 16 * DM; k += 16 * 256) { ((uint4*)g_acc)[k] = make_uint4(0, 0, 0, 0); ((uint4*)(g_acc + S_TOK * DM))[k] = make_uint4(0, 0, 0, 0); }
  }
  if (b < 160) GT(3, 2);
}

typedef CUresult (*EncodeFn)(CUtensorMap*, CUtensorMapDataType, cuuint32_t, void*, const cuuint64_t*, const cuuint64_t*, const cuuint32_t*,
                             const cuuint32_t*, CUtensorMapInterleave, CUtensorMapSwizzle, CUtensorMapL2promotion, CUtensorMapFloatOOBfill);
static void make_map(EncodeFn fn, CUtensorMap* m, const void* p, uint64_t cols, uint64_t rows, uint32_t bc, uint32_t br) {
  cuuint64_t dims[2] = {cols, rows}; cuuint64_t strides[1] = {cols * 2}; cuuint32_t box[2] = {bc, br}; cuuint32_t es[2] = {1, 1};
  fn(m, CU_TENSOR_MAP_DATA_TYPE_BFLOAT16, 2, (void*)p, dims, strides, box, es, CU_TENSOR_MAP_INTERLEAVE_NONE, CU_TENSOR_MAP_SWIZZLE_128B,
     CU_TENSOR_MAP_L2_PROMOTION_L2_128B, CU_TENSOR_MAP_FLOAT_OOB_FILL_NONE);
}

static void make_map_perm(EncodeFn fn, CUtensorMap* m, const void* p) {
  cuuint64_t dims[5] = {HE, 2, 2, 4, 40}; const cuuint64_t r = HE * 2; cuuint64_t strides[4] = {r, 8 * r, 2 * r, 16 * r};
  cuuint32_t box[5] = {64, 2, 2, 4, 4}; cuuint32_t es[5] = {1, 1, 1, 1, 1};
  fn(m, CU_TENSOR_MAP_DATA_TYPE_BFLOAT16, 5, (void*)p, dims, strides, box, es, CU_TENSOR_MAP_INTERLEAVE_NONE, CU_TENSOR_MAP_SWIZZLE_128B,
     CU_TENSOR_MAP_L2_PROMOTION_L2_128B, CU_TENSOR_MAP_FLOAT_OOB_FILL_NONE);
}

#define OPC_PDL 1
#define LA_PDL 1
#define REC_PDL 1
extern "C" void kernel_launch(void* const* d_in, const int* in_sizes, int n_in, void* d_out, int out_size) {
  const bf16* x = (const bf16*)d_in[0];
  const bf16* wqkv = (const bf16*)d_in[1];
  const bf16* wo_a = (const bf16*)d_in[2];
  const bf16* mem0 = (const bf16*)d_in[4];
  const bf16* Wq = (const bf16*)d_in[5];
  const bf16* Wk = (const bf16*)d_in[6];
  const bf16* Wv = (const bf16*)d_in[7];
  const bf16* Wo = (const bf16*)d_in[8];
  cudaStream_t st = cudaStreamPerThread;

  static EncodeFn enc = nullptr;
  static uint8_t* p_ar; static uint32_t* p_zero;
  if (!enc) {
    cudaDriverEntryPointQueryResult qr;
    void* fn = nullptr;
    cudaGetDriverEntryPoint("cuTensorMapEncodeTiled", &fn, cudaEnableDefault, &qr);
    enc = (EncodeFn)fn;
    cudaFuncSetAttribute(rec_kernel, cudaFuncAttributeMaxDynamicSharedMemorySize, REC_SMEM);
    cudaFuncSetAttribute(opc_kernel, cudaFuncAttributeMaxDynamicSharedMemorySize, OPC_SMEM);
    cudaFuncSetAttribute(la_kernel, cudaFuncAttributeMaxDynamicSharedMemorySize, LA_SMEM);
    cudaGetSymbolAddress((void**)&p_ar, g_ar); p_ar = (uint8_t*)(((uintptr_t)p_ar + 32767) & ~(uintptr_t)32767);
    cudaGetSymbolAddress((void**)&p_zero, g_zero);
  }
  CUtensorMap tmq, tmk, tmv, tmo;
  make_map_perm(enc, &tmq, Wq);
  make_map_perm(enc, &tmk, Wk);
  make_map_perm(enc, &tmv, Wv);
  make_map(enc, &tmo, Wo, DM, HE, 64, 64);

  cudaLaunchAttribute at[2];
  at[0].id = cudaLaunchAttributeProgrammaticStreamSerialization; at[0].val.programmaticStreamSerializationAllowed = 1;
  at[1].id = cudaLaunchAttributeClusterDimension; at[1].val.clusterDim.x = 3; at[1].val.clusterDim.y = 1; at[1].val.clusterDim.z = 1;
  cudaLaunchAttribute at2[2] = {at[1], at[0]};
  at2[0].val.clusterDim.x = 2;
  prep_kernel<<<475, 256, 0, st>>>(x, wqkv, wo_a);
  for (int l = 0; l < 2; l++) {
    cudaLaunchConfig_t cfg = {};
    cfg.blockDim = dim3(384); cfg.stream = st;
    cfg.gridDim = dim3(l == 0 ? 132 : 128); cfg.dynamicSmemBytes = LA_SMEM; cfg.attrs = at2; cfg.numAttrs = 1 + LA_PDL;
    cudaLaunchKernelEx(&cfg, la_kernel, Wq, Wk, Wv, Wo, p_ar + l * AR_LAYER, l);
    cfg.gridDim = dim3(96 + 3 * NLB); cfg.dynamicSmemBytes = REC_SMEM; cfg.attrs = at + 1 - REC_PDL; cfg.numAttrs = 1 + REC_PDL;
    cudaLaunchKernelEx(&cfg, rec_kernel, tmq, tmk, tmv, tmo, l == 0 ? x : (const bf16*)nullptr, mem0, p_ar + l * AR_LAYER, p_zero + Z_FLAGS + l * FL_LAYER, l);
    cfg.gridDim = dim3(36); cfg.dynamicSmemBytes = OPC_SMEM; cfg.attrs = at; cfg.numAttrs = OPC_PDL;
    cudaLaunchKernelEx(&cfg, opc_kernel, tmo, l == 1 ? (bf16*)d_out : (bf16*)nullptr, l, Wq, Wk, Wv, Wo);
  }
}
```

```cpp
#include <cuda_runtime.h>
#include <cuda_bf16.h>
#include <cuda.h>
#include <stdint.h>

typedef __nv_bfloat16 bf16;
typedef unsigned long long u64;

constexpr int S_TOK = 2048, DM = 640, DH = 192, HE = 6144, NSEG = 64;

constexpr int AR_GROUP = 98304;
constexpr int AR_LAYER = 16 * AR_GROUP;
__device__ __align__(1024) uint8_t g_ar[2 * AR_LAYER + 32768];
__device__ __align__(1024) uint8_t g_xn[NSEG * 40960];
__device__ __align__(1024) uint8_t g_xt[S_TOK * DM * 2];
__device__ __align__(1024) uint8_t g_ot[NSEG * HE * 64];
__device__ __align__(1024) uint8_t g_oa[S_TOK * DM * 2];
__device__ __align__(1024) uint8_t g_w1[DM * 1920 * 2];
__device__ __align__(1024) uint8_t g_w2[DM * 672 * 2];
__device__ __align__(1024) float g_acc[2 * S_TOK * DM];
__device__ __align__(1024) bf16 g_x[S_TOK * DM];
constexpr int FL_A = 0, FL_B = 64 * 6 * 8, FL_KV = FL_B + 64 * 8, FL_O = FL_KV + 8 * 8, FL_T = FL_O + 16 * 8, FL_X = FL_T + 16 * 8, FL_N = FL_X + 8, FL_XN = FL_N + 8, FL_LAYER = FL_XN + 32 * 8;
constexpr int Z_FLAGS = 0, Z_NORM = 2 * FL_LAYER, Z_KV = Z_NORM + 8, KV_LAYER = 8 * 80 * 24, Z_END = Z_KV + 2 * KV_LAYER;
__device__ __align__(128) uint32_t g_zero[Z_END];
__device__ __align__(128) float g_nrm[4 * DM];
#define GT(slot, k) do {} while (0)
#define GTT(slot, k) do {} while (0)

__device__ __forceinline__ uint32_t smem_u32(const void* p) { return (uint32_t)__cvta_generic_to_shared(p); }
__device__ __forceinline__ uint32_t mapa(uint32_t a, uint32_t r) { uint32_t o; asm("mapa.shared::cluster.u32 %0, %1, %2;" : "=r"(o) : "r"(a), "r"(r)); return o; }
__device__ __forceinline__ void mbar_init(uint32_t bar, uint32_t cnt) { asm volatile("mbarrier.init.shared::cta.b64 [%0], %1;" :: "r"(bar), "r"(cnt) : "memory"); }
__device__ __forceinline__ void mbar_expect(uint32_t bar, uint32_t tx) { asm volatile("mbarrier.arrive.expect_tx.shared::cta.b64 _, [%0], %1;" :: "r"(bar), "r"(tx) : "memory"); }
__device__ __forceinline__ void mbar_arrive(uint32_t bar) { asm volatile("mbarrier.arrive.shared::cta.b64 _, [%0];" :: "r"(bar) : "memory"); }
__device__ __forceinline__ void mbar_wait(uint32_t bar, uint32_t par) {
  asm volatile("{\n.reg .pred p;\n.reg .u32 c;\nmov.u32 c, 0;\n"
               "LW:\nmbarrier.try_wait.parity.shared::cta.b64 p, [%0], %1;\n@p bra LD;\n"
               "add.u32 c, c, 1;\nsetp.lt.u32 p, c, 4000000;\n@p bra LW;\ntrap;\nLD:\n}" :: "r"(bar), "r"(par) : "memory");
}
template <int ID, int N> __device__ __forceinline__ void bar_sync() { asm volatile("barrier.sync %0, %1;" :: "n"(ID), "n"(N) : "memory"); }
template <int ID, int N> __device__ __forceinline__ void bar_arrive() { asm volatile("barrier.arrive %0, %1;" :: "n"(ID), "n"(N) : "memory"); }
__device__ __forceinline__ void fence_async() { asm volatile("fence.proxy.async.shared::cta;" ::: "memory"); }
__device__ __forceinline__ void cluster_sync() { asm volatile("barrier.cluster.arrive.aligned;\nbarrier.cluster.wait.aligned;" ::: "memory"); }
__device__ __forceinline__ void wg_fence() { asm volatile("wgmma.fence.sync.aligned;" ::: "memory"); }
__device__ __forceinline__ void wg_commit() { asm volatile("wgmma.commit_group.sync.aligned;" ::: "memory"); }
template <int N> __device__ __forceinline__ void wg_wait() { asm volatile("wgmma.wait_group.sync.aligned %0;" :: "n"(N) : "memory"); }
template <int N> __device__ __forceinline__ void pin(float* d) {
#pragma unroll
  for (int i = 0; i < N; i++) asm volatile("" : "+f"(d[i]) :: "memory");
}
__device__ __forceinline__ constexpr uint64_t mkdesc(uint32_t addr, uint32_t lbo, uint32_t sbo, int sw) {
  return (uint64_t)((addr & 0x3FFFF) >> 4) | ((uint64_t)(lbo >> 4) << 16) | ((uint64_t)(sbo >> 4) << 32) | ((uint64_t)sw << 62);
}
constexpr uint32_t SB0 = 1024;
__device__ __forceinline__ void check_smem_base(uint32_t sb) { if ((sb & 0x3FFFF) != SB0) __trap(); }
__device__ __forceinline__ uint32_t cta_rank() { uint32_t r; asm volatile("mov.u32 %0, %%cluster_ctarank;" : "=r"(r)); return r; }
__device__ __forceinline__ uint32_t opaque(uint32_t v) { uint32_t o; asm volatile("mov.u32 %0, %1;" : "=r"(o) : "r"(v)); return o; }
__device__ __forceinline__ uint32_t pack2(float lo, float hi) { uint32_t r; asm("cvt.rn.bf16x2.f32 %0, %1, %2;" : "=r"(r) : "f"(hi), "f"(lo)); return r; }
__device__ __forceinline__ void ldsm4(uint32_t* r, uint32_t a) { asm volatile("ldmatrix.sync.aligned.m8n8.x4.shared.b16 {%0,%1,%2,%3}, [%4];" : "=r"(r[0]), "=r"(r[1]), "=r"(r[2]), "=r"(r[3]) : "r"(a) : "memory"); }
__device__ __forceinline__ void ldsm4t(uint32_t* r, uint32_t a) { asm volatile("ldmatrix.sync.aligned.m8n8.x4.trans.shared.b16 {%0,%1,%2,%3}, [%4];" : "=r"(r[0]), "=r"(r[1]), "=r"(r[2]), "=r"(r[3]) : "r"(a) : "memory"); }
__device__ __forceinline__ void ldsm1(uint32_t& r, uint32_t a) { asm volatile("ldmatrix.sync.aligned.m8n8.x1.shared.b16 {%0}, [%1];" : "=r"(r) : "r"(a) : "memory"); }
__device__ __forceinline__ void stsm4(uint32_t a, uint32_t r0, uint32_t r1, uint32_t r2, uint32_t r3) { asm volatile("stmatrix.sync.aligned.m8n8.x4.shared.b16 [%0], {%1,%2,%3,%4};" :: "r"(a), "r"(r0), "r"(r1), "r"(r2), "r"(r3) : "memory"); }
__device__ __forceinline__ void stsm1(uint32_t a, uint32_t r0) { asm volatile("stmatrix.sync.aligned.m8n8.x1.shared.b16 [%0], {%1};" :: "r"(a), "r"(r0) : "memory"); }
__device__ __forceinline__ void stsm4t(uint32_t a, uint32_t r0, uint32_t r1, uint32_t r2, uint32_t r3) { asm volatile("stmatrix.sync.aligned.m8n8.x4.trans.shared.b16 [%0], {%1,%2,%3,%4};" :: "r"(a), "r"(r0), "r"(r1), "r"(r2), "r"(r3) : "memory"); }
__device__ __forceinline__ void stsm2t(uint32_t a, uint32_t r0, uint32_t r1) { asm volatile("stmatrix.sync.aligned.m8n8.x2.trans.shared.b16 [%0], {%1,%2};" :: "r"(a), "r"(r0), "r"(r1) : "memory"); }
__device__ __forceinline__ void mma16816(float* c, const uint32_t* a, uint32_t b0, uint32_t b1) {
  asm volatile("mma.sync.aligned.m16n8k16.row.col.f32.bf16.bf16.f32 {%0,%1,%2,%3}, {%4,%5,%6,%7}, {%8,%9}, {%0,%1,%2,%3};"
               : "+f"(c[0]), "+f"(c[1]), "+f"(c[2]), "+f"(c[3]) : "r"(a[0]), "r"(a[1]), "r"(a[2]), "r"(a[3]), "r"(b0), "r"(b1));
}
__device__ __forceinline__ void mma1688(float* c, uint32_t a0, uint32_t a1, uint32_t b0) {
  asm volatile("mma.sync.aligned.m16n8k8.row.col.f32.bf16.bf16.f32 {%0,%1,%2,%3}, {%4,%5}, {%6}, {%0,%1,%2,%3};"
               : "+f"(c[0]), "+f"(c[1]), "+f"(c[2]), "+f"(c[3]) : "r"(a0), "r"(a1), "r"(b0));
}
__device__ __forceinline__ void sta1(uint32_t a, uint32_t v, uint32_t bar) { asm volatile("st.async.weak.shared::cluster.mbarrier::complete_tx::bytes.b32 [%0], %1, [%2];" :: "r"(a), "r"(v), "r"(bar) : "memory"); }
__device__ __forceinline__ void sta1p(uint32_t a, uint32_t v, uint32_t bar, bool p) { asm volatile("{\n.reg .pred p;\nsetp.ne.b32 p, %3, 0;\n@p st.async.weak.shared::cluster.mbarrier::complete_tx::bytes.b32 [%0], %1, [%2];\n}" :: "r"(a), "r"(v), "r"(bar), "r"((int)p) : "memory"); }
__device__ __forceinline__ void sta2(uint32_t a, uint32_t v0, uint32_t v1, uint32_t bar) { asm volatile("st.async.weak.shared::cluster.mbarrier::complete_tx::bytes.v2.b32 [%0], {%1,%2}, [%3];" :: "r"(a), "r"(v0), "r"(v1), "r"(bar) : "memory"); }
__device__ __forceinline__ void sta4(uint32_t a, uint32_t v0, uint32_t v1, uint32_t v2, uint32_t v3, uint32_t bar) { asm volatile("st.async.weak.shared::cluster.mbarrier::complete_tx::bytes.v4.b32 [%0], {%1,%2,%3,%4}, [%5];" :: "r"(a), "r"(v0), "r"(v1), "r"(v2), "r"(v3), "r"(bar) : "memory"); }
__device__ __forceinline__ float bflo(uint32_t v) { return __uint_as_float(v << 16); }
__device__ __forceinline__ float bfhi(uint32_t v) { return __uint_as_float(v & 0xFFFF0000u); }
__device__ __forceinline__ void sta2f(uint32_t a, float v0, float v1, uint32_t bar) { asm volatile("st.async.weak.shared::cluster.mbarrier::complete_tx::bytes.v2.f32 [%0], {%1,%2}, [%3];" :: "r"(a), "f"(v0), "f"(v1), "r"(bar) : "memory"); }
__device__ __forceinline__ void sta4f(uint32_t a, float v0, float v1, float v2, float v3, uint32_t bar) { asm volatile("st.async.weak.shared::cluster.mbarrier::complete_tx::bytes.v4.f32 [%0], {%1,%2,%3,%4}, [%5];" :: "r"(a), "f"(v0), "f"(v1), "f"(v2), "f"(v3), "r"(bar) : "memory"); }
__device__ __forceinline__ float4 lds4f(uint32_t a) { float4 v; asm volatile("ld.shared.v4.f32 {%0,%1,%2,%3}, [%4];" : "=f"(v.x), "=f"(v.y), "=f"(v.z), "=f"(v.w) : "r"(a) : "memory"); return v; }
__device__ __forceinline__ float2 lds2f(uint32_t a) { float2 v; asm volatile("ld.shared.v2.f32 {%0,%1}, [%2];" : "=f"(v.x), "=f"(v.y) : "r"(a) : "memory"); return v; }
__device__ __forceinline__ uint4 lds4(uint32_t a) { uint4 v; asm volatile("ld.shared.v4.u32 {%0,%1,%2,%3}, [%4];" : "=r"(v.x), "=r"(v.y), "=r"(v.z), "=r"(v.w) : "r"(a) : "memory"); return v; }
__device__ __forceinline__ uint32_t lds1(uint32_t a) { uint32_t v; asm volatile("ld.shared.u32 %0, [%1];" : "=r"(v) : "r"(a) : "memory"); return v; }
__device__ __forceinline__ void stsm2(uint32_t a, uint32_t r0, uint32_t r1) { asm volatile("stmatrix.sync.aligned.m8n8.x2.shared.b16 [%0], {%1,%2};" :: "r"(a), "r"(r0), "r"(r1) : "memory"); }
__device__ __forceinline__ float rcp(float x) { float y; asm("rcp.approx.ftz.f32 %0, %1;" : "=f"(y) : "f"(x)); return y; }
__device__ __forceinline__ void sts4(uint32_t a, uint32_t v0, uint32_t v1, uint32_t v2, uint32_t v3) { asm volatile("st.shared.v4.u32 [%0], {%1,%2,%3,%4};" :: "r"(a), "r"(v0), "r"(v1), "r"(v2), "r"(v3) : "memory"); }
__device__ __forceinline__ void bulk_s2c(uint32_t dst, uint32_t src, uint32_t bytes, uint32_t bar) {
  asm volatile("cp.async.bulk.shared::cluster.shared::cta.mbarrier::complete_tx::bytes [%0], [%1], %2, [%3];" :: "r"(dst), "r"(src), "r"(bytes), "r"(bar) : "memory");
}
__device__ __forceinline__ void stg4(void* p, uint4 v) { asm volatile("st.global.v4.u32 [%0], {%1,%2,%3,%4};" :: "l"(p), "r"(v.x), "r"(v.y), "r"(v.z), "r"(v.w) : "memory"); }
__device__ __forceinline__ void red_add(uint32_t* p, uint32_t v) { asm volatile("red.relaxed.gpu.global.add.u32 [%0], %1;" :: "l"(p), "r"(v) : "memory"); }
__device__ __forceinline__ void red_release(uint32_t* p, uint32_t v) { asm volatile("red.release.gpu.global.add.u32 [%0], %1;" :: "l"(p), "r"(v) : "memory"); }
__device__ __forceinline__ void fence_async_global() { asm volatile("fence.proxy.async.global;" ::: "memory"); }
__device__ __forceinline__ uint64_t policy_evict_first() { uint64_t p; asm("createpolicy.fractional.L2::evict_first.b64 %0, 1.0;" : "=l"(p)); return p; }
__device__ __forceinline__ void stg4h(void* p, uint4 v, uint64_t pol) { asm volatile("st.global.L2::cache_hint.v4.u32 [%0], {%1,%2,%3,%4}, %5;" :: "l"(p), "r"(v.x), "r"(v.y), "r"(v.z), "r"(v.w), "l"(pol) : "memory"); }
__device__ __forceinline__ void red4fh(float* p, float a, float b, float c, float d, uint64_t pol) { asm volatile("red.relaxed.gpu.global.add.L2::cache_hint.v4.f32 [%0], {%1,%2,%3,%4}, %5;" :: "l"(p), "f"(a), "f"(b), "f"(c), "f"(d), "l"(pol) : "memory"); }
__device__ __forceinline__ float4 ldg4fh(const float* p, uint64_t pol) { float4 v; asm volatile("ld.global.cg.L2::cache_hint.v4.f32 {%0,%1,%2,%3}, [%4], %5;" : "=f"(v.x), "=f"(v.y), "=f"(v.z), "=f"(v.w) : "l"(p), "l"(pol) : "memory"); return v; }
__device__ __forceinline__ void bulk_g2sh(uint32_t dst, const void* src, uint32_t bytes, uint32_t bar, uint64_t pol) {
  asm volatile("cp.async.bulk.shared::cluster.global.mbarrier::complete_tx::bytes.L2::cache_hint [%0], [%1], %2, [%3], %4;" :: "r"(dst), "l"(src), "r"(bytes), "r"(bar), "l"(pol) : "memory");
}
#define OT_MASK 63
#define AC_MASK 63
#define EVF 1
__device__ __forceinline__ void red4f(float* p, float a, float b, float c, float d) { asm volatile("red.relaxed.gpu.global.add.v4.f32 [%0], {%1,%2,%3,%4};" :: "l"(p), "f"(a), "f"(b), "f"(c), "f"(d) : "memory"); }
__device__ __forceinline__ void wait_flag(const uint32_t* p, uint32_t target) {
  uint32_t v; int it = 0;
  while (true) {
    asm volatile("ld.acquire.gpu.global.u32 %0, [%1];" : "=r"(v) : "l"(p) : "memory");
    if (__all_sync(~0u, v >= target)) break;
    if (++it > 4000000) __trap();
    __nanosleep(20);
  }
}
__device__ __forceinline__ void sts2(uint32_t a, uint32_t v0, uint32_t v1) { asm volatile("st.shared.v2.u32 [%0], {%1,%2};" :: "r"(a), "r"(v0), "r"(v1) : "memory"); }
__device__ __forceinline__ float sqrt_approx(float x) { float y; asm("sqrt.approx.f32 %0, %1;" : "=f"(y) : "f"(x)); return y; }
__device__ __forceinline__ void bulk_s2c_elect(uint32_t d1, uint32_t b1, uint32_t d2, uint32_t b2, uint32_t src) {
  asm volatile("{\n.reg .pred p;\nelect.sync _|p, 0xffffffff;\n"
               "@p cp.async.bulk.shared::cluster.shared::cta.mbarrier::complete_tx::bytes [%0], [%4], 1024, [%1];\n"
               "@p cp.async.bulk.shared::cluster.shared::cta.mbarrier::complete_tx::bytes [%2], [%4], 1024, [%3];\n}"
               :: "r"(d1), "r"(b1), "r"(d2), "r"(b2), "r"(src) : "memory");
}
__device__ __forceinline__ void mbar_arrive_elect(uint32_t bar) { asm volatile("{\n.reg .pred p;\nelect.sync _|p, 0xffffffff;\n@p mbarrier.arrive.shared::cta.b64 _, [%0];\n}" :: "r"(bar) : "memory"); }
__device__ __forceinline__ void cp16(uint32_t dst, const void* src) { asm volatile("cp.async.cg.shared.global [%0], [%1], 16;" :: "r"(dst), "l"(src) : "memory"); }
__device__ __forceinline__ void sts1(uint32_t a, uint32_t v) { asm volatile("st.shared.u32 [%0], %1;" :: "r"(a), "r"(v) : "memory"); }
__device__ __forceinline__ void bulk_g2s(uint32_t dst, const void* src, uint32_t bytes, uint32_t bar) {
  asm volatile("cp.async.bulk.shared::cluster.global.mbarrier::complete_tx::bytes [%0], [%1], %2, [%3];" :: "r"(dst), "l"(src), "r"(bytes), "r"(bar) : "memory");
}
__device__ __forceinline__ void bulk_g2s_mc(uint32_t dst, const void* src, uint32_t bytes, uint32_t bar) {
  asm volatile("cp.async.bulk.shared::cluster.global.mbarrier::complete_tx::bytes.multicast::cluster [%0], [%1], %2, [%3], %4;" :: "r"(dst), "l"(src), "r"(bytes), "r"(bar), "h"((uint16_t)3) : "memory");
}
__device__ __forceinline__ void mbar_arrive_cl(uint32_t bar) { asm volatile("mbarrier.arrive.shared::cluster.b64 _, [%0];" :: "r"(bar) : "memory"); }
__device__ __forceinline__ void tma2d(uint32_t dst, const CUtensorMap* m, int c0, int c1, uint32_t bar) {
  asm volatile("cp.async.bulk.tensor.2d.shared::cluster.global.mbarrier::complete_tx::bytes [%0], [%1, {%3, %4}], [%2];" :: "r"(dst), "l"((uint64_t)m), "r"(bar), "r"(c0), "r"(c1) : "memory");
}
__device__ __forceinline__ void tma5d(uint32_t dst, const CUtensorMap* m, int c0, int c4, uint32_t bar) {
  asm volatile("cp.async.bulk.tensor.5d.shared::cluster.global.mbarrier::complete_tx::bytes [%0], [%1, {%3, %5, %5, %5, %4}], [%2];" :: "r"(dst), "l"((uint64_t)m), "r"(bar), "r"(c0), "r"(c4), "r"(0) : "memory");
}
__device__ __forceinline__ void red64(void* p, uint32_t lo, uint32_t hi) { asm volatile("{\n.reg .b64 t;\nmov.b64 t, {%1,%2};\nred.relaxed.gpu.global.add.u64 [%0], t;\n}" :: "l"(p), "r"(lo), "r"(hi) : "memory"); }
__device__ __forceinline__ uint4 ld_poll(const void* p) {
  uint4 v;
  asm volatile("{\n.reg .b64 a, b;\nld.relaxed.gpu.global.v2.b64 {a, b}, [%4];\nmov.b64 {%0,%1}, a;\nmov.b64 {%2,%3}, b;\n}" : "=r"(v.x), "=r"(v.y), "=r"(v.z), "=r"(v.w) : "l"(p) : "memory");
  return v;
}
__device__ __forceinline__ uint32_t clk() { uint32_t c; asm volatile("mov.u32 %0, %%clock;" : "=r"(c) :: "memory"); return c; }
#define SCHED_FENCE() asm volatile("pmevent 0;" ::: "memory")
__device__ __forceinline__ float ex2(float x) { float y; asm("ex2.approx.ftz.f32 %0, %1;" : "=f"(y) : "f"(x)); return y; }

__device__ __forceinline__ void wg_ss_n240_ta0_tb1(float* d, uint64_t a, uint64_t b, int sc) {
  asm volatile("{\n.reg .pred p;\nsetp.ne.b32 p, %122, 0;\nwgmma.mma_async.sync.aligned.m64n240k16.f32.bf16.bf16 {%0, %1, %2, %3, %4, %5, %6, %7, %8, %9, %10, %11, %12, %13, %14, %15, %16, %17, %18, %19, %20, %21, %22, %23, %24, %25, %26, %27, %28, %29, %30, %31, %32, %33, %34, %35, %36, %37, %38, %39, %40, %41, %42, %43, %44, %45, %46, %47, %48, %49, %50, %51, %52, %53, %54, %55, %56, %57, %58, %59, %60, %61, %62, %63, %64, %65, %66, %67, %68, %69, %70, %71, %72, %73, %74, %75, %76, %77, %78, %79, %80, %81, %82, %83, %84, %85, %86, %87, %88, %89, %90, %91, %92, %93, %94, %95, %96, %97, %98, %99, %100, %101, %102, %103, %104, %105, %106, %107, %108, %109, %110, %111, %112, %113, %114, %115, %116, %117, %118, %119}, %120, %121, p, 1, 1, 0, 1;\n}\n"
    : "+f"(d[0]), "+f"(d[1]), "+f"(d[2]), "+f"(d[3]), "+f"(d[4]), "+f"(d[5]), "+f"(d[6]), "+f"(d[7]), "+f"(d[8]), "+f"(d[9]), "+f"(d[10]), "+f"(d[11]), "+f"(d[12]), "+f"(d[13]), "+f"(d[14]), "+f"(d[15]), "+f"(d[16]), "+f"(d[17]), "+f"(d[18]), "+f"(d[19]), "+f"(d[20]), "+f"(d[21]), "+f"(d[22]), "+f"(d[23]), "+f"(d[24]), "+f"(d[25]), "+f"(d[26]), "+f"(d[27]), "+f"(d[28]), "+f"(d[29]), "+f"(d[30]), "+f"(d[31]), "+f"(d[32]), "+f"(d[33]), "+f"(d[34]), "+f"(d[35]), "+f"(d[36]), "+f"(d[37]), "+f"(d[38]), "+f"(d[39]), "+f"(d[40]), "+f"(d[41]), "+f"(d[42]), "+f"(d[43]), "+f"(d[44]), "+f"(d[45]), "+f"(d[46]), "+f"(d[47]), "+f"(d[48]), "+f"(d[49]), "+f"(d[50]), "+f"(d[51]), "+f"(d[52]), "+f"(d[53]), "+f"(d[54]), "+f"(d[55]), "+f"(d[56]), "+f"(d[57]), "+f"(d[58]), "+f"(d[59]), "+f"(d[60]), "+f"(d[61]), "+f"(d[62]), "+f"(d[63]), "+f"(d[64]), "+f"(d[65]), "+f"(d[66]), "+f"(d[67]), "+f"(d[68]), "+f"(d[69]), "+f"(d[70]), "+f"(d[71]), "+f"(d[72]), "+f"(d[73]), "+f"(d[74]), "+f"(d[75]), "+f"(d[76]), "+f"(d[77]), "+f"(d[78]), "+f"(d[79]), "+f"(d[80]), "+f"(d[81]), "+f"(d[82]), "+f"(d[83]), "+f"(d[84]), "+f"(d[85]), "+f"(d[86]), "+f"(d[87]), "+f"(d[88]), "+f"(d[89]), "+f"(d[90]), "+f"(d[91]), "+f"(d[92]), "+f"(d[93]), "+f"(d[94]), "+f"(d[95]), "+f"(d[96]), "+f"(d[97]), "+f"(d[98]), "+f"(d[99]), "+f"(d[100]), "+f"(d[101]), "+f"(d[102]), "+f"(d[103]), "+f"(d[104]), "+f"(d[105]), "+f"(d[106]), "+f"(d[107]), "+f"(d[108]), "+f"(d[109]), "+f"(d[110]), "+f"(d[111]), "+f"(d[112]), "+f"(d[113]), "+f"(d[114]), "+f"(d[115]), "+f"(d[116]), "+f"(d[117]), "+f"(d[118]), "+f"(d[119])
    : "l"(a), "l"(b), "r"(sc));
}
__device__ __forceinline__ void wg_ss_n88_ta1_tb1(float* d, uint64_t a, uint64_t b, int sc) {
  asm volatile("{\n.reg .pred p;\nsetp.ne.b32 p, %46, 0;\nwgmma.mma_async.sync.aligned.m64n88k16.f32.bf16.bf16 {%0, %1, %2, %3, %4, %5, %6, %7, %8, %9, %10, %11, %12, %13, %14, %15, %16, %17, %18, %19, %20, %21, %22, %23, %24, %25, %26, %27, %28, %29, %30, %31, %32, %33, %34, %35, %36, %37, %38, %39, %40, %41, %42, %43}, %44, %45, p, 1, 1, 1, 1;\n}\n"
    : "+f"(d[0]), "+f"(d[1]), "+f"(d[2]), "+f"(d[3]), "+f"(d[4]), "+f"(d[5]), "+f"(d[6]), "+f"(d[7]), "+f"(d[8]), "+f"(d[9]), "+f"(d[10]), "+f"(d[11]), "+f"(d[12]), "+f"(d[13]), "+f"(d[14]), "+f"(d[15]), "+f"(d[16]), "+f"(d[17]), "+f"(d[18]), "+f"(d[19]), "+f"(d[20]), "+f"(d[21]), "+f"(d[22]), "+f"(d[23]), "+f"(d[24]), "+f"(d[25]), "+f"(d[26]), "+f"(d[27]), "+f"(d[28]), "+f"(d[29]), "+f"(d[30]), "+f"(d[31]), "+f"(d[32]), "+f"(d[33]), "+f"(d[34]), "+f"(d[35]), "+f"(d[36]), "+f"(d[37]), "+f"(d[38]), "+f"(d[39]), "+f"(d[40]), "+f"(d[41]), "+f"(d[42]), "+f"(d[43])
    : "l"(a), "l"(b), "r"(sc));
}
__device__ __forceinline__ void wg_rs_n160_tb1(float* d, const uint32_t* a, uint64_t b, int sc) {
  asm volatile("{\n.reg .pred p;\nsetp.ne.b32 p, %85, 0;\nwgmma.mma_async.sync.aligned.m64n160k16.f32.bf16.bf16 {%0, %1, %2, %3, %4, %5, %6, %7, %8, %9, %10, %11, %12, %13, %14, %15, %16, %17, %18, %19, %20, %21, %22, %23, %24, %25, %26, %27, %28, %29, %30, %31, %32, %33, %34, %35, %36, %37, %38, %39, %40, %41, %42, %43, %44, %45, %46, %47, %48, %49, %50, %51, %52, %53, %54, %55, %56, %57, %58, %59, %60, %61, %62, %63, %64, %65, %66, %67, %68, %69, %70, %71, %72, %73, %74, %75, %76, %77, %78, %79}, {%80, %81, %82, %83}, %84, p, 1, 1, 1;\n}\n"
    : "+f"(d[0]), "+f"(d[1]), "+f"(d[2]), "+f"(d[3]), "+f"(d[4]), "+f"(d[5]), "+f"(d[6]), "+f"(d[7]), "+f"(d[8]), "+f"(d[9]), "+f"(d[10]), "+f"(d[11]), "+f"(d[12]), "+f"(d[13]), "+f"(d[14]), "+f"(d[15]), "+f"(d[16]), "+f"(d[17]), "+f"(d[18]), "+f"(d[19]), "+f"(d[20]), "+f"(d[21]), "+f"(d[22]), "+f"(d[23]), "+f"(d[24]), "+f"(d[25]), "+f"(d[26]), "+f"(d[27]), "+f"(d[28]), "+f"(d[29]), "+f"(d[30]), "+f"(d[31]), "+f"(d[32]), "+f"(d[33]), "+f"(d[34]), "+f"(d[35]), "+f"(d[36]), "+f"(d[37]), "+f"(d[38]), "+f"(d[39]), "+f"(d[40]), "+f"(d[41]), "+f"(d[42]), "+f"(d[43]), "+f"(d[44]), "+f"(d[45]), "+f"(d[46]), "+f"(d[47]), "+f"(d[48]), "+f"(d[49]), "+f"(d[50]), "+f"(d[51]), "+f"(d[52]), "+f"(d[53]), "+f"(d[54]), "+f"(d[55]), "+f"(d[56]), "+f"(d[57]), "+f"(d[58]), "+f"(d[59]), "+f"(d[60]), "+f"(d[61]), "+f"(d[62]), "+f"(d[63]), "+f"(d[64]), "+f"(d[65]), "+f"(d[66]), "+f"(d[67]), "+f"(d[68]), "+f"(d[69]), "+f"(d[70]), "+f"(d[71]), "+f"(d[72]), "+f"(d[73]), "+f"(d[74]), "+f"(d[75]), "+f"(d[76]), "+f"(d[77]), "+f"(d[78]), "+f"(d[79])
    : "r"(a[0]), "r"(a[1]), "r"(a[2]), "r"(a[3]), "l"(b), "r"(sc));
}
__device__ __forceinline__ void wg_ss_n112_ta0_tb1(float* d, uint64_t a, uint64_t b, int sc) {
  asm volatile("{\n.reg .pred p;\nsetp.ne.b32 p, %58, 0;\nwgmma.mma_async.sync.aligned.m64n112k16.f32.bf16.bf16 {%0, %1, %2, %3, %4, %5, %6, %7, %8, %9, %10, %11, %12, %13, %14, %15, %16, %17, %18, %19, %20, %21, %22, %23, %24, %25, %26, %27, %28, %29, %30, %31, %32, %33, %34, %35, %36, %37, %38, %39, %40, %41, %42, %43, %44, %45, %46, %47, %48, %49, %50, %51, %52, %53, %54, %55}, %56, %57, p, 1, 1, 0, 1;\n}\n"
    : "+f"(d[0]), "+f"(d[1]), "+f"(d[2]), "+f"(d[3]), "+f"(d[4]), "+f"(d[5]), "+f"(d[6]), "+f"(d[7]), "+f"(d[8]), "+f"(d[9]), "+f"(d[10]), "+f"(d[11]), "+f"(d[12]), "+f"(d[13]), "+f"(d[14]), "+f"(d[15]), "+f"(d[16]), "+f"(d[17]), "+f"(d[18]), "+f"(d[19]), "+f"(d[20]), "+f"(d[21]), "+f"(d[22]), "+f"(d[23]), "+f"(d[24]), "+f"(d[25]), "+f"(d[26]), "+f"(d[27]), "+f"(d[28]), "+f"(d[29]), "+f"(d[30]), "+f"(d[31]), "+f"(d[32]), "+f"(d[33]), "+f"(d[34]), "+f"(d[35]), "+f"(d[36]), "+f"(d[37]), "+f"(d[38]), "+f"(d[39]), "+f"(d[40]), "+f"(d[41]), "+f"(d[42]), "+f"(d[43]), "+f"(d[44]), "+f"(d[45]), "+f"(d[46]), "+f"(d[47]), "+f"(d[48]), "+f"(d[49]), "+f"(d[50]), "+f"(d[51]), "+f"(d[52]), "+f"(d[53]), "+f"(d[54]), "+f"(d[55])
    : "l"(a), "l"(b), "r"(sc));
}
__device__ __forceinline__ void wg_rs_n32_tb1(float* d, const uint32_t* a, uint64_t b, int sc) {
  asm volatile("{\n.reg .pred p;\nsetp.ne.b32 p, %21, 0;\nwgmma.mma_async.sync.aligned.m64n32k16.f32.bf16.bf16 {%0, %1, %2, %3, %4, %5, %6, %7, %8, %9, %10, %11, %12, %13, %14, %15}, {%16, %17, %18, %19}, %20, p, 1, 1, 1;\n}\n"
    : "+f"(d[0]), "+f"(d[1]), "+f"(d[2]), "+f"(d[3]), "+f"(d[4]), "+f"(d[5]), "+f"(d[6]), "+f"(d[7]), "+f"(d[8]), "+f"(d[9]), "+f"(d[10]), "+f"(d[11]), "+f"(d[12]), "+f"(d[13]), "+f"(d[14]), "+f"(d[15])
    : "r"(a[0]), "r"(a[1]), "r"(a[2]), "r"(a[3]), "l"(b), "r"(sc));
}
__device__ __forceinline__ void wg_ss_n32_ta1_tb1(float* d, uint64_t a, uint64_t b, int sc) {
  asm volatile("{\n.reg .pred p;\nsetp.ne.b32 p, %18, 0;\nwgmma.mma_async.sync.aligned.m64n32k16.f32.bf16.bf16 {%0, %1, %2, %3, %4, %5, %6, %7, %8, %9, %10, %11, %12, %13, %14, %15}, %16, %17, p, 1, 1, 1, 1;\n}\n"
    : "+f"(d[0]), "+f"(d[1]), "+f"(d[2]), "+f"(d[3]), "+f"(d[4]), "+f"(d[5]), "+f"(d[6]), "+f"(d[7]), "+f"(d[8]), "+f"(d[9]), "+f"(d[10]), "+f"(d[11]), "+f"(d[12]), "+f"(d[13]), "+f"(d[14]), "+f"(d[15])
    : "l"(a), "l"(b), "r"(sc));
}
__device__ __forceinline__ void wg_rs_n32_tb0(float* d, const uint32_t* a, uint64_t b, int sc) {
  asm volatile("{\n.reg .pred p;\nsetp.ne.b32 p, %21, 0;\nwgmma.mma_async.sync.aligned.m64n32k16.f32.bf16.bf16 {%0, %1, %2, %3, %4, %5, %6, %7, %8, %9, %10, %11, %12, %13, %14, %15}, {%16, %17, %18, %19}, %20, p, 1, 1, 0;\n}\n"
    : "+f"(d[0]), "+f"(d[1]), "+f"(d[2]), "+f"(d[3]), "+f"(d[4]), "+f"(d[5]), "+f"(d[6]), "+f"(d[7]), "+f"(d[8]), "+f"(d[9]), "+f"(d[10]), "+f"(d[11]), "+f"(d[12]), "+f"(d[13]), "+f"(d[14]), "+f"(d[15])
    : "r"(a[0]), "r"(a[1]), "r"(a[2]), "r"(a[3]), "l"(b), "r"(sc));
}
__device__ __forceinline__ void wg_rs_n40_tb0(float* d, const uint32_t* a, uint64_t b, int sc) {
  asm volatile("{\n.reg .pred p;\nsetp.ne.b32 p, %25, 0;\nwgmma.mma_async.sync.aligned.m64n40k16.f32.bf16.bf16 {%0, %1, %2, %3, %4, %5, %6, %7, %8, %9, %10, %11, %12, %13, %14, %15, %16, %17, %18, %19}, {%20, %21, %22, %23}, %24, p, 1, 1, 0;\n}\n"
    : "+f"(d[0]), "+f"(d[1]), "+f"(d[2]), "+f"(d[3]), "+f"(d[4]), "+f"(d[5]), "+f"(d[6]), "+f"(d[7]), "+f"(d[8]), "+f"(d[9]), "+f"(d[10]), "+f"(d[11]), "+f"(d[12]), "+f"(d[13]), "+f"(d[14]), "+f"(d[15]), "+f"(d[16]), "+f"(d[17]), "+f"(d[18]), "+f"(d[19])
    : "r"(a[0]), "r"(a[1]), "r"(a[2]), "r"(a[3]), "l"(b), "r"(sc));
}
__device__ __forceinline__ void wg_rs_n8_tb1(float* d, const uint32_t* a, uint64_t b, int sc) {
  asm volatile("{\n.reg .pred p;\nsetp.ne.b32 p, %9, 0;\nwgmma.mma_async.sync.aligned.m64n8k16.f32.bf16.bf16 {%0, %1, %2, %3}, {%4, %5, %6, %7}, %8, p, 1, 1, 1;\n}\n"
    : "+f"(d[0]), "+f"(d[1]), "+f"(d[2]), "+f"(d[3])
    : "r"(a[0]), "r"(a[1]), "r"(a[2]), "r"(a[3]), "l"(b), "r"(sc));
}
__device__ __forceinline__ void wg_ss_n40_ta0_tb0(float* d, uint64_t a, uint64_t b, int sc) {
  asm volatile("{\n.reg .pred p;\nsetp.ne.b32 p, %22, 0;\nwgmma.mma_async.sync.aligned.m64n40k16.f32.bf16.bf16 {%0, %1, %2, %3, %4, %5, %6, %7, %8, %9, %10, %11, %12, %13, %14, %15, %16, %17, %18, %19}, %20, %21, p, 1, 1, 0, 0;\n}\n"
    : "+f"(d[0]), "+f"(d[1]), "+f"(d[2]), "+f"(d[3]), "+f"(d[4]), "+f"(d[5]), "+f"(d[6]), "+f"(d[7]), "+f"(d[8]), "+f"(d[9]), "+f"(d[10]), "+f"(d[11]), "+f"(d[12]), "+f"(d[13]), "+f"(d[14]), "+f"(d[15]), "+f"(d[16]), "+f"(d[17]), "+f"(d[18]), "+f"(d[19])
    : "l"(a), "l"(b), "r"(sc));
}
__device__ __forceinline__ void wg_ss_n40_ta1_tb0(float* d, uint64_t a, uint64_t b, int sc) {
  asm volatile("{\n.reg .pred p;\nsetp.ne.b32 p, %22, 0;\nwgmma.mma_async.sync.aligned.m64n40k16.f32.bf16.bf16 {%0, %1, %2, %3, %4, %5, %6, %7, %8, %9, %10, %11, %12, %13, %14, %15, %16, %17, %18, %19}, %20, %21, p, 1, 1, 1, 0;\n}\n"
    : "+f"(d[0]), "+f"(d[1]), "+f"(d[2]), "+f"(d[3]), "+f"(d[4]), "+f"(d[5]), "+f"(d[6]), "+f"(d[7]), "+f"(d[8]), "+f"(d[9]), "+f"(d[10]), "+f"(d[11]), "+f"(d[12]), "+f"(d[13]), "+f"(d[14]), "+f"(d[15]), "+f"(d[16]), "+f"(d[17]), "+f"(d[18]), "+f"(d[19])
    : "l"(a), "l"(b), "r"(sc));
}
__device__ __forceinline__ void wg_ss_n8_ta1_tb1(float* d, uint64_t a, uint64_t b, int sc) {
  asm volatile("{\n.reg .pred p;\nsetp.ne.b32 p, %6, 0;\nwgmma.mma_async.sync.aligned.m64n8k16.f32.bf16.bf16 {%0, %1, %2, %3}, %4, %5, p, 1, 1, 1, 1;\n}\n"
    : "+f"(d[0]), "+f"(d[1]), "+f"(d[2]), "+f"(d[3])
    : "l"(a), "l"(b), "r"(sc));
}

constexpr int O_WV = 0, O_WO = 81920, O_H = 163840, O_QK = 215040, O_SM = 228352, O_MISC = 229632;
constexpr int O_QM = O_QK + 1024, O_K = O_QK + 3072, O_OG = O_QK + 8192;
constexpr int SM_SLOT = 640;
constexpr int O_MAXS = O_MISC;
constexpr int O_BAR = O_MISC + 64;
constexpr int MB_XF = 0, MB_ML = 2, MB_MR = 4, MB_SM = 7, MB_SX = 8, MB_OG = 9, MB_W = 10, MB_WC = 30;
constexpr int O_PROF = O_BAR + 8 * 40;
constexpr int REC_SMEM = O_PROF + 128;
constexpr int B_VOWN = 0, B_QK = 1, B_VGO = 2, B_SISS = 3, B_PM = 4, B_PX = 5, B_XGO = 6, B_PFREE = 7, B_WG2 = 8, B_VHALF = 9, B_VDONE = 10,
              B_PFREE1 = 11, B_SSENT = 12, B_SLD = 13, B_VEND = 14, B_XGO1 = 15;
#define POLL_DELAY 600
#define POLL_D0 300
#define POLL_STEP 100
#define TS0(idx) do {} while (0)
#define TS(idx) do {} while (0)
#define SLD_POS 0
#define W_OPEN 16
#define W_WIN 3
#define TRIG_LATE 1
#define XP_END 40
#define F_ORD 0
#define VEND_POS 2
#define SPEC_DEC 0
#define O_B1 5
#define O_C1 16
#define O_MODE 0
#define AR_MAP 1
#define EXP 0
#define FILL_B 4096
#define MP_D 3
#define MP_CH 4
#define MP_F 0
#define ML_N0 3
#define MR_N0 3
#define O_RSM 0x2AA0
#define O_RS __builtin_popcount(O_RSM)
#define O_IDX(j) __builtin_popcount(O_RSM & ((1 << (j)) - 1))
#define O_RS_POS 0
#define V_N1 2
#define V_N2 0
#define V_N3 4
#define V_OWN 6
#define V_S1 9
#define V_K1 (V_OWN + V_RS + V_S1)
#define V_K2 ((V_K1 > 20 ? V_K1 : 20) + V_S2)
#define V_S2 3
constexpr int V_RS = V_N1 + V_N2 + V_N3;
constexpr float SCL = 0.07216878364870322f;
constexpr float L2E = 1.4426950408889634f;
__device__ __forceinline__ constexpr int vord(int i) { return i < 4 ? 36 + i : i - 4; }
__device__ __forceinline__ constexpr uint32_t hoff(int k) { return ((k >> 2) * 5120 + (k & 3) * 32) >> 4; }

__device__ __forceinline__ constexpr int ar_chunk(int T) { return AR_MAP == 0 ? (T >> 2) * 8 + (T & 3) : T == 9 ? 19 : (T % 3) * 8 + T / 3; }
__device__ __forceinline__ void fix_red(uint8_t* p, const float* a, float sc) {
  int v0 = __float2int_rn(a[0] * sc), v1 = __float2int_rn(a[1] * sc), v2 = __float2int_rn(a[2] * sc), v3 = __float2int_rn(a[3] * sc);
  red64(p, ((uint32_t)v0 << 7) | 1u, ((uint32_t)v2 << 3) + (uint32_t)(v0 >> 25));
  red64(p + 1024, ((uint32_t)v1 << 7) | 1u, ((uint32_t)v3 << 3) + (uint32_t)(v1 >> 25));
}
__device__ __forceinline__ float max10(const float* t) {
  float m = fmaxf(fmaxf(fmaxf(t[0], t[1]), fmaxf(t[2], t[3])), fmaxf(fmaxf(t[4], t[5]), fmaxf(t[6], t[7])));
  m = fmaxf(m, fmaxf(t[8], t[9]));
  m = fmaxf(m, __shfl_xor_sync(~0u, m, 1));
  return fmaxf(m, __shfl_xor_sync(~0u, m, 2));
}
#define ACC2(k, p, u, v) { t[k] = bflo(p) + bflo(u) + bflo(v); t[k + 1] = bfhi(p) + bfhi(u) + bfhi(v); }

#define LBT 0
#define NLB 5
constexpr int LB_STAGE = 36864, LB_ST = 6 * LB_STAGE;
__device__ __forceinline__ void lb_role(const uint32_t sb, const CUtensorMap* tmx, uint32_t* __restrict__ flags, int layer) {
  const int tid = threadIdx.x, wid = __shfl_sync(~0u, tid >> 5, 0), wg = wid >> 2, w = wid & 3, lane = tid & 31, g = lane >> 2, i4 = lane & 3;
  const int cl = blockIdx.x / 3, rank = blockIdx.x - cl * 3;
  const uint32_t bar = sb + O_BAR;
  asm volatile("griddepcontrol.launch_dependents;");
  if (wid == 8) {
    if (lane < 14) mbar_init(bar + 8 * lane, lane >= 6 && lane < 12 ? 8 : 1);
    asm volatile("fence.mbarrier_init.release.cluster;" ::: "memory");
    fence_async();
  }
  __syncthreads();
  asm volatile("barrier.cluster.arrive.relaxed.aligned;" ::: "memory");
  if (wid == 8) {
    int st = 0; uint32_t ph = 1;
    const uint8_t* wsrc = g_w2 + rank * 286720;
    if (lane < 6) { mbar_expect(bar + 8 * lane, LB_STAGE); bulk_g2s(sb + lane * LB_STAGE + 8192, wsrc + lane * 28672, 28672, bar + 8 * lane); }
    if (layer == 1) wait_flag(flags + FL_T + (lane & 15) * 8, 8);
#pragma unroll 1
    for (int tile = cl; tile < 32; tile += NLB) {
      wait_flag(flags + FL_O + (tile >> 1) * 8, 8);
      if (tile == cl + LBT * NLB && lane == 0) GTT(layer * 4 + 1, 11);
      fence_async_global();
#pragma unroll 1
      for (int kc = 0; kc < 10; kc++) {
        const bool pre = tile == cl && kc < 6;
        mbar_wait(bar + 8 * (6 + st), ph);
        if (lane == 0) {
          if (!pre) { mbar_expect(bar + 8 * st, LB_STAGE); bulk_g2s(sb + st * LB_STAGE + 8192, wsrc + kc * 28672, 28672, bar + 8 * st); }
          bulk_g2s(sb + st * LB_STAGE, g_oa + tile * 81920 + kc * 8192, 8192, bar + 8 * st);
        }
        __syncwarp();
        if (++st == 6) { st = 0; ph ^= 1; }
      }
      mbar_wait(bar + 8 * (6 + st), ph);
      if (lane == 0) { mbar_expect(bar + 8 * st, 64 * 464); tma2d(sb + st * LB_STAGE, tmx, rank * 224, tile * 64, bar + 8 * st); }
      __syncwarp();
      if (++st == 6) { st = 0; ph ^= 1; }
    }
    asm volatile("barrier.cluster.wait.aligned;" ::: "memory");
  } else if (wg < 2) {
    asm volatile("barrier.cluster.wait.aligned;" ::: "memory");
    const int u = 2 * rank + wg, nb = u == 5 ? 5 : 7;
    int st = 0; uint32_t ph = 0, it = 0;
#pragma unroll 1
    for (int tile = cl; tile < 32; tile += NLB, it++) {
      const int row0 = tile * 64 + 16 * w + g;
      float d[56];
      if (tid == 0) mbar_expect(bar + 8 * (12 + (it & 1)), 3072);
#pragma unroll 1
      for (int kc = 0; kc < 10; kc++) {
        const uint64_t da = mkdesc(SB0 + st * LB_STAGE, 1024, 128, 0), db = mkdesc(SB0 + st * LB_STAGE + 8192 + wg * 1792, 3584, 128, 0);
        mbar_wait(bar + 8 * st, ph);
        if (it == LBT && kc == 0) GT(layer * 4 + 1, 12);
        wg_fence();
#pragma unroll
        for (int k = 0; k < 4; k++) wg_ss_n112_ta0_tb1(d, da + k * 128, db + k * 448, kc | k);
        wg_commit();
        wg_wait<1>();
        if (kc > 0 && lane == 0) mbar_arrive(bar + 8 * (6 + (st == 0 ? 5 : st - 1)));
        if (++st == 6) { st = 0; ph ^= 1; }
      }
      wg_wait<0>();
      pin<56>(d);
      if (it == LBT) GT(layer * 4 + 1, 13);
      if (lane == 0) mbar_arrive(bar + 8 * (6 + (st == 0 ? 5 : st - 1)));
      mbar_wait(bar + 8 * st, ph);
      {
        const uint32_t x0 = sb + st * LB_STAGE + (16 * w + g) * 464 + wg * 224 + (layer ? 8 : 4) * i4, x1 = x0 + (layer ? 4 : 16);
#pragma unroll
        for (int j = 0; j < 28; j++) {
          const uint32_t v = lds1(((j & 2) ? x1 : x0) + (j >> 2) * 32 + (j & 1) * 3712);
          d[2 * j] += bflo(v); d[2 * j + 1] += bfhi(v);
        }
      }
      fence_async();
      __syncwarp();
      if (lane == 0) mbar_arrive(bar + 8 * (6 + st));
      if (++st == 6) { st = 0; ph ^= 1; }
      const float cnt = nb * 16.f;
      const uint32_t so = LB_ST + (it & 1) * 3072 + (16 * w + g) * 48;
#pragma unroll
      for (int h = 0; h < 2; h++) {
        float sum = 0.f;
#pragma unroll
        for (int j = 0; j < 14; j++) sum += d[4 * j + 2 * h] + d[4 * j + 2 * h + 1];
        sum += __shfl_xor_sync(~0u, sum, 1); sum += __shfl_xor_sync(~0u, sum, 2);
        const float mean = sum * rcp(cnt);
        float q = 0.f, q2 = 0.f;
#pragma unroll
        for (int j = 0; j < 14; j++) {
          const float a = d[4 * j + 2 * h] - mean, b = d[4 * j + 2 * h + 1] - mean;
          if (j < 10) q = fmaf(a, a, fmaf(b, b, q)); else q2 = fmaf(a, a, fmaf(b, b, q2));
        }
        if (nb == 7) q += q2;
        q += __shfl_xor_sync(~0u, q, 1); q += __shfl_xor_sync(~0u, q, 2);
        if (i4 < 3) { const uint32_t b = mapa(sb, i4); sta2f(b + so + h * 384 + u * 8, sum, q, b + O_BAR + 8 * (12 + (it & 1))); }
      }
      mbar_wait(bar + 8 * (12 + (it & 1)), (it >> 1) & 1);
      if (it == LBT) GT(layer * 4 + 1, 14);
#pragma unroll
      for (int h = 0; h < 2; h++) {
        const float4 x = lds4f(sb + so + h * 384), y = lds4f(sb + so + h * 384 + 16), z = lds4f(sb + so + h * 384 + 32);
        const float mu = (((x.x + x.z) + (y.x + y.z)) + (z.x + z.z)) * (1.f / DM);
        const float e0 = x.x * (1.f / 112.f) - mu, e1 = x.z * (1.f / 112.f) - mu, e2 = y.x * (1.f / 112.f) - mu, e3 = y.z * (1.f / 112.f) - mu;
        const float e4 = z.x * (1.f / 112.f) - mu, e5 = z.z * (1.f / 80.f) - mu;
        const float q = (((x.y + x.w) + (y.y + y.w)) + (z.y + z.w)) + 112.f * ((e0 * e0 + e1 * e1) + (e2 * e2 + e3 * e3) + e4 * e4) + 80.f * e5 * e5;
        const float rs = rsqrtf(q * (1.f / DM) + 1e-5f), sh = -mu * rs;
        const int tk = row0 + 8 * h;
        uint8_t* xp = g_xn + (tk >> 5) * 40960 + (tk & 31) * 128 + (i4 & 1) * 8;
#pragma unroll
        for (int j = 0; j < 7; j++) {
          if (j < nb) {
            const int b16 = u * 7 + j;
            const float* a = d + 8 * j + 2 * h;
            *(uint2*)(xp + (b16 >> 2) * 4096 + (((2 * (b16 & 3) + (i4 >> 1)) ^ g) << 4)) =
                make_uint2(pack2(fmaf(a[0], rs, sh), fmaf(a[1], rs, sh)), pack2(fmaf(a[4], rs, sh), fmaf(a[5], rs, sh)));
          }
        }
      }
      if (it == LBT) GT(layer * 4 + 1, 15);
      bar_arrive<1, 288>();
      bar_sync<2, 288>();
#pragma unroll
      for (int j = 0; j < 14; j++) {
        const float* a = d + 8 * (j >> 1) + 2 * (j & 1);
        if ((j >> 1) < nb) *(uint2*)(g_x + (row0 + 8 * (j & 1)) * DM + u * 112 + 4 * i4 + 16 * (j >> 1)) = make_uint2(pack2(a[0], a[1]), pack2(a[4], a[5]));
      }
      bar_arrive<3, 288>();
    }
  } else {
    asm volatile("barrier.cluster.wait.aligned;" ::: "memory");
    if (wid == 9) {
#pragma unroll 1
      for (int tile = cl; tile < 32; tile += NLB) {
        bar_sync<1, 288>();
        if (tile != cl) bar_arrive<2, 288>();
        if (lane == 0) { red_release(flags + FL_XN + tile * 8, 1); if (tile == cl + LBT * NLB) GTT(layer * 4 + 1, 9); }
        __syncwarp();
        if (tile == cl) bar_arrive<2, 288>();
        bar_sync<3, 288>();
        if (lane == 0) red_release(flags + FL_XN + tile * 8 + 1, 1);
        __syncwarp();
      }
    }
  }
  asm volatile("barrier.cluster.arrive.relaxed.aligned;\nbarrier.cluster.wait.aligned;" ::: "memory");
  GT(layer * 4 + 1, 10);
}

__global__ void __launch_bounds__(384, 1)
rec_kernel(const __grid_constant__ CUtensorMap tmq, const __grid_constant__ CUtensorMap tmk,
           const __grid_constant__ CUtensorMap tmv, const __grid_constant__ CUtensorMap tmo,
           const __grid_constant__ CUtensorMap tmx, const bf16* __restrict__ mem0, uint8_t* __restrict__ ar, uint32_t* __restrict__ flags, int layer) {
  extern __shared__ __align__(1024) uint8_t smem[];
  const uint32_t sb = smem_u32(smem);
  check_smem_base(sb);
  GT(layer * 4 + 1, 0);
  if (blockIdx.x < 3 * NLB) { lb_role(sb, &tmx, flags, layer); return; }
  const int bid = blockIdx.x - 3 * NLB;
  const int tid = threadIdx.x, wid = __shfl_sync(~0u, tid >> 5, 0), wg = wid >> 2, w = wid & 3;
  const int lane = __shfl_sync(~0u, tid & 31, tid & 31);
  const int head = bid / 3, rank = bid - head * 3;
  const int e0 = bid * 64;
  const uint32_t bar = sb + O_BAR;
  const uint32_t sb1 = mapa(sb, rank == 2 ? 0 : rank + 1), sb2 = mapa(sb, rank == 0 ? 2 : rank - 1);
  auto chunk_of = [&](int p) { const int c = 3 * rank + p; return p == 9 ? 9 : c >= 9 ? c - 9 : c; };

  auto load_piece = [&](int i) {
    if (lane == 0) mbar_expect(bar + 8 * (MB_W + i), 16384);
    __syncwarp();
    if (lane < 2) {
      if (i < 15) {
        const int m = i < 10 ? i & 1 : 0, p = (i < 10 ? i >> 1 : i - 10) * 2 + lane;
        tma5d(sb + m * 81920 + p * 8192, i >= 10 ? &tmv : m ? &tmk : &tmq, e0, chunk_of(p) * 4, bar + 8 * (MB_W + i));
      } else {
        const int p = (i - 15) * 2 + lane, k = p / 3, j = rank + p - 3 * k;
        tma2d(sb + O_WO + p * 8192, &tmo, p == 9 ? 576 : (rank * 3 + k) * 64, head * DH + (j >= 3 ? j - 3 : j) * 64, bar + 8 * (MB_W + i));
      }
    }
  };
  if (wid == 9) {
    mbar_init(bar + 8 * lane, lane == MB_ML ? ML_N0 : lane == MB_ML + 1 && ML_N0 < 4 ? 4 - ML_N0 : lane >= MB_WC ? 4 : 1);
    if (lane < 8) mbar_init(bar + 8 * (32 + lane), 4);
    asm volatile("fence.mbarrier_init.release.cluster;" ::: "memory");
    fence_async();
    __syncwarp();
#pragma unroll 1
    for (int i = 0; i < W_WIN; i++) load_piece(i);
  }
  __syncthreads();
  asm volatile("barrier.cluster.arrive.relaxed.aligned;" ::: "memory");

  if (wg < 2) {
    asm volatile("setmaxnreg.inc.sync.aligned.u32 208;");
    uint32_t a[40][4];
    const uint32_t swz = (lane & 7) * 128 + (((2 * w + ((lane >> 3) & 1)) ^ (lane & 7)) << 4);
    const uint32_t st_x = __shfl_sync(~0u, sb + O_QK + wg * 5120 + (lane >> 4) * 2048 + swz, lane);
    {
      const uint32_t la = sb + wg * 81920 + (lane >> 4) * 1024 + swz;
#pragma unroll
      for (int p = 0; p < 5; p++) {
        mbar_wait(bar + 8 * (MB_W + 2 * p + wg), 0);
#pragma unroll
        for (int k = 0; k < 8; k++) ldsm4t(a[p * 8 + k], la + (p * 8 + k) * 2048);
        fence_async();
        __syncwarp();
        mbar_arrive_elect(bar + 8 * (MB_WC + wg * 5 + p));
      }
    }
    GT(layer * 4 + 1, 5);
    asm volatile("barrier.cluster.wait.aligned;" ::: "memory");
    const uint32_t ld_m = __shfl_sync(~0u, sb + O_H + (lane & 7) * 128 + (((lane >> 3) ^ (lane & 7)) << 4), lane);

    for (int s = 0; s < NSEG; s++) {
      const uint32_t par = s & 1;
      if (wid == 4) TS0(0);
      if (wid == 0) TS(30);
      {
        float ax[16];
        constexpr uint64_t db = mkdesc(SB0 + O_H + 1024, 16, 1024, 1);
        mbar_wait(bar + 8 * MB_XF, par);
        wg_fence();
#pragma unroll
        for (int k = 0; k < 20; k++) wg_rs_n32_tb0(ax, a[vord(k)], db + hoff(vord(k)), k);
        mbar_wait(bar + 8 * (MB_XF + 1), par);
        wg_fence();
#pragma unroll
        for (int k = 20; k < XP_END; k++) wg_rs_n32_tb0(ax, a[vord(k)], db + hoff(vord(k)), 1);
        wg_commit();
        if (s > 0) { if (wg == 0) bar_sync<B_PFREE, 256>(); else bar_sync<B_PFREE1, 256>(); }
        if (wid == 6 && lane == 0) { mbar_expect(bar + 8 * MB_SM, 2 * SM_SLOT + 48 + 48); mbar_expect(bar + 8 * MB_SX, 2 * 2176); }
        wg_wait<0>();
        pin<16>(ax);
        if (w == 0) TS(1 + 22 * wg);
        stsm4t(st_x, pack2(ax[0], ax[1]), pack2(ax[2], ax[3]), pack2(ax[4], ax[5]), pack2(ax[6], ax[7]));
        stsm4t(st_x + 4096, pack2(ax[8], ax[9]), pack2(ax[10], ax[11]), pack2(ax[12], ax[13]), pack2(ax[14], ax[15]));
        if (V_OWN > 0) bar_arrive<B_VOWN, 384>();
      }
      {
        float c[MP_CH][4];
#pragma unroll
        for (int k = 0; k < MP_CH; k++) c[k][0] = c[k][1] = c[k][2] = c[k][3] = 0.f;
        uint32_t b[MP_D][2][4];
        const uint32_t ld_m2 = opaque(ld_m ^ 64);
        SCHED_FENCE();
#define MORD(j) ((j) == 0 ? 9 : (j) < 4 ? (j) - 1 : 3 + ((j) - 4) / 2 + 3 * ((j) & 1))
#pragma unroll
        for (int j = 0; j < 10 + MP_D - 1; j++) {
          if (j < 10) {
            if (j == 0) { mbar_wait(bar + 8 * MB_ML, par); if (wid == 0) TS(2); }
            if (ML_N0 < 4 && j == ML_N0) { mbar_wait(bar + 8 * (MB_ML + 1), par); if (wid == 0) TS(3); }
            if (j == 4) { mbar_wait(bar + 8 * MB_MR, par); if (wid == 0) TS(4); }
            if (j == 4 + 2 * MR_N0) { mbar_wait(bar + 8 * (MB_MR + 1), par); if (wid == 0) TS(5); }
            ldsm4(b[j % MP_D][0], ld_m + MORD(j) * 5120);
            ldsm4(b[j % MP_D][1], ld_m2 + MORD(j) * 5120);
            if ((MP_F >> j) & 1) SCHED_FENCE();
          }
          const int u = j - (MP_D - 1);
          if (u >= 0) {
#pragma unroll
            for (int k = 0; k < 4; k++) mma16816(c[(4 * u + k) % MP_CH], a[4 * MORD(u) + k], b[u % MP_D][k >> 1][(k & 1) * 2], b[u % MP_D][k >> 1][(k & 1) * 2 + 1]);
          }
        }
        SCHED_FENCE();
        bar_arrive<B_VGO, 384>();
        SCHED_FENCE();
#pragma unroll
        for (int k = 0; k < 4; k++) c[0][k] = MP_CH == 4 ? (c[0][k] + c[1][k]) + (c[2][k] + c[MP_CH - 1][k]) : (c[1][k] + c[2][k]) + c[0][k];
        stsm2t(st_x + 1024 - wg * 3072, pack2(c[0][0], c[0][1]), pack2(c[0][2], c[0][3]));
        fence_async();
      }
      if (wg == 0) {
        bar_sync<B_QK, 256>();
        float sv[20];
        {
          constexpr uint64_t da = mkdesc(SB0 + O_QK, 16, 1024, 1), db = mkdesc(SB0 + O_K, 16, 2048, 1);
          wg_fence();
#pragma unroll
          for (int k = 0; k < 4; k++) wg_ss_n40_ta0_tb0(sv, da + 2 * k, db + 2 * k, k);
          wg_commit();
          bar_arrive<B_SISS, 256>();
        }
        if (w == 0) TS(6);
        SCHED_FENCE();
        const uint32_t ln = opaque(lane);
        uint32_t m0, m1, m2, m3, m4;
        {
          const uint32_t a1 = opaque(sb1 + O_SM + SM_SLOT + ln * 16), a2 = opaque(sb2 + O_SM + ln * 16);
          const uint32_t a3 = opaque(sb1 + O_SM + SM_SLOT + 512 + ln * 4), a4 = opaque(sb2 + O_SM + 512 + ln * 4);
          const uint32_t b1 = opaque(sb1 + O_BAR + 8 * MB_SM), b2 = opaque(sb2 + O_BAR + 8 * MB_SM);
          const uint32_t bt = opaque(mapa(sb, min(ln, 2u)) + O_BAR + 8 * MB_SM), at = opaque(bt + (O_MAXS + 48 - O_BAR - 8 * MB_SM));
          SCHED_FENCE();
          wg_wait<0>();
          pin<20>(sv);
          m0 = pack2(sv[2], sv[3]); m1 = pack2(sv[6], sv[7]); m2 = pack2(sv[10], sv[11]); m3 = pack2(sv[14], sv[15]); m4 = pack2(sv[18], sv[19]);
          if (w == 0) {
            sta4(a1, m0, m1, m2, m3, b1);
            sta4(a2, m0, m1, m2, m3, b2);
            sta1(a3, m4, b1);
            sta1(a4, m4, b2);
          }
          sta1p(at, 0u, bt, ln < 3);
          bar_arrive<B_SSENT, 256>();
          SCHED_FENCE();
        }
        const uint32_t p0 = pack2(sv[0], sv[1]), p1 = pack2(sv[4], sv[5]), p2 = pack2(sv[8], sv[9]), p3 = pack2(sv[12], sv[13]), p4 = pack2(sv[16], sv[17]);
        const uint32_t ox = O_K + w * 2048 + ln * 16, ox2 = O_K + 8192 + ln * 4;
        {
          const uint32_t a1 = opaque(sb1 + ox + 512), a2 = opaque(sb2 + ox), b1 = opaque(sb1 + O_BAR + 8 * MB_SX), b2 = opaque(sb2 + O_BAR + 8 * MB_SX);
          if (w == 0) {
            TS(7);
            const uint32_t om = opaque(sb + O_SM + ln * 16), om2 = opaque(sb + O_SM + 512 + ln * 4);
            const uint32_t pa0 = ld_m + (O_QM - O_H), pa1 = (ld_m ^ 64) + (O_QM - O_H);
            float t[10] = {bflo(m0), bfhi(m0), bflo(m1), bfhi(m1), bflo(m2), bfhi(m2), bflo(m3), bfhi(m3), bflo(m4), bfhi(m4)};
            pin<10>(t);
            SCHED_FENCE();
            mbar_wait(bar + 8 * MB_SM, par);
            const uint4 u = lds4(om), v = lds4(om + SM_SLOT);
            const uint32_t u4 = lds1(om2), v4 = lds1(om2 + SM_SLOT);
            sta4(a1, p0, p1, p2, p3, b1);
            sta4(a2, p0, p1, p2, p3, b2);
            if (SLD_POS == 0) bar_arrive<B_SLD, 256>();
            SCHED_FENCE();
#define ACC3(k, u, v) { t[k] += bflo(u) + bflo(v); t[k + 1] += bfhi(u) + bfhi(v); }
            ACC3(0, u.x, v.x) ACC3(2, u.y, v.y) ACC3(4, u.z, v.z) ACC3(6, u.w, v.w) ACC3(8, u4, v4)
            TS(8);
            const float mm = max10(t) * (SCL * L2E);
            if (SLD_POS == 1) { SCHED_FENCE(); bar_arrive<B_SLD, 256>(); SCHED_FENCE(); }
#pragma unroll
            for (int k = 0; k < 10; k++) t[k] = ex2(fmaf(t[k], SCL * L2E, -mm));
            stsm4(pa0, pack2(t[0], t[1]), pack2(t[2], t[3]), pack2(t[4], t[5]), pack2(t[6], t[7]));
            stsm1(pa1, pack2(t[8], t[9]));
            bar_arrive<B_PM, 160>();
            TS(9);
          } else {
            const uint32_t a3 = opaque(sb1 + ox2 + 128), a4 = opaque(sb2 + ox2);
            SCHED_FENCE();
            mbar_wait(bar + 8 * MB_SM, par);
            sta4(a1, p0, p1, p2, p3, b1);
            sta4(a2, p0, p1, p2, p3, b2);
            if (w == 3) { sta1(a3, p4, b1); sta1(a4, p4, b2); }
            bar_arrive<B_SLD, 256>();
          }
        }
        mbar_wait(bar + 8 * MB_SX, par);
        bar_sync<B_VEND, 256>();
        {
          float t[10];
          const uint4 u = lds4(sb + ox), v = lds4(sb + ox + 512);
          const uint32_t u4 = lds1(sb + ox2), v4 = lds1(sb + ox2 + 128);
          SCHED_FENCE();
          ACC2(0, p0, u.x, v.x) ACC2(2, p1, u.y, v.y) ACC2(4, p2, u.z, v.z) ACC2(6, p3, u.w, v.w) ACC2(8, p4, u4, v4)
          const int dq = 8 * w + (ln >> 2) - 2 * (ln & 3);
#pragma unroll
          for (int k = 1; k < 5; k++) {
            if (8 * (k - 1) > dq) t[2 * k] = -1e9f / SCL;
            if (8 * (k - 1) + 1 > dq) t[2 * k + 1] = -1e9f / SCL;
          }
          const float mm = max10(t) * (SCL * L2E);
#pragma unroll
          for (int k = 0; k < 10; k++) t[k] = ex2(fmaf(t[k], SCL * L2E, -mm));
          float sum = ((t[0] + t[1]) + (t[2] + t[3])) + ((t[4] + t[5]) + (t[6] + t[7])) + (t[8] + t[9]);
          sum += __shfl_xor_sync(~0u, sum, 1);
          sum += __shfl_xor_sync(~0u, sum, 2);
          const float inv = rcp(sum);
          const int rr = 2 * w + (ln & 1);
          const uint32_t pa = sb + O_QK + ((ln >> 1) & 3) * 2048 + rr * 128;
          stsm4(pa + (((ln >> 3) ^ rr) << 4), pack2(t[0] * inv, t[1] * inv), pack2(t[2] * inv, t[3] * inv), pack2(t[4] * inv, t[5] * inv), pack2(t[6] * inv, t[7] * inv));
          stsm2(pa + (((4 + ((ln >> 3) & 1)) ^ rr) << 4), pack2(t[8] * inv, t[9] * inv), 0u);
          fence_async();
        }
        bar_arrive<B_PX, 256>();
        if (w == 0) TS(10);
        bar_sync<B_XGO, 256>();
      } else {
        bar_arrive<B_QK, 256>();
        const int ln = opaque(lane);
        if (w == 2) {
          bar_sync<B_VHALF, 192>();
          if (ln == 0 && s > 0) { red_release(flags + FL_A + (e0 >> 10) * 8 + (s - 1) * 48, 1); }
          __syncwarp();
        }
        if (w == 3) {
          const int l = bid * 2 + ln, s2 = s + 2;
          if (ln < 2 && l < 160 && s2 < NSEG - 1) {
            const int tile = l >> 4;
            const uint8_t* p = ar + (s2 >> 2) * AR_GROUP + (s2 & 1) * 128 + ((s2 >> 1) & 1) * 512 + ar_chunk(tile) * 4096 +
                               ((l >> 3) & 1) * 16384 + (l & 1) * 256 + ((l >> 1) & 3) * 1024;
            asm volatile("prefetch.global.L2 [%0];" :: "l"(p));
          }
        }
        if (w == 0) {
          const bool more = s + 1 < NSEG;
          if (ln < 2 && more) mbar_expect(bar + 8 * (MB_XF + ln), FILL_B * 5);
          const uint8_t* src = g_xn + (s + 1) * 40960 + chunk_of(ln) * 4096;
          if ((s & 1) && more) { wait_flag(flags + FL_XN + ((s + 1) >> 1) * 8, 3); fence_async_global(); }
          bar_sync<B_VHALF, 192>();
          if ((ln < 4 || ln == 9) && more) bulk_g2s(sb + O_H + ln * 5120 + 1024, src, FILL_B, bar + 8 * MB_XF);
          bar_sync<B_VDONE, 160>();
          if (ln >= 4 && ln < 9 && more) bulk_g2s(sb + O_H + ln * 5120 + 1024, src, FILL_B, bar + 8 * (MB_XF + 1));
        }
        bar_sync<B_XGO1, 256>();
      }
    }
  } else {
    asm volatile("setmaxnreg.dec.sync.aligned.u32 88;");
    asm volatile("barrier.cluster.wait.aligned;" ::: "memory");

    const int g = lane >> 2, i4 = lane & 3;
    const int myT = w == 0 ? 9 : rank * 3 + w - 1, myP = w == 0 ? 9 : w - 1;
    const int tok = 2 * ((lane >> 1) & 3) + ((lane >> 3) & 1);
    const uint32_t fw_off = sb + O_H + myP * 5120 + tok * 128 + (((2 * (lane >> 4) + (lane & 1)) ^ tok) << 4);
    const uint32_t prod_off = (w >> 1) * 16384 + (w & 1) * 2048 + ((g >> 1) & 1) * 256 + (i4 * 2 + (g >> 2)) * 16 + (g & 1) * 8;
    const uint32_t cons_off = ar_chunk(myT) * 4096 + (lane >> 3) * 1024 + (lane & 7) * 16;
    auto tile_off = [&](int k) { return AR_MAP == 0 ? ar_chunk(rank * 3 + k) * 4096 : (k * 8 + rank) * 4096; };
    constexpr uint32_t T9_OFF = ar_chunk(9) * 4096;

    uint32_t mx;
    auto forward = [&](const uint32_t* p) {
      const uint32_t c = O_H + myP * 5120, bo = O_BAR + 8 * (MB_MR + (w > MR_N0));
      sts4(fw_off, p[0], p[1], p[2], p[3]);
      sts4(fw_off ^ 64, p[4], p[5], p[6], p[7]);
      fence_async();
      __syncwarp();
      mbar_arrive_elect(bar + 8 * (MB_ML + (w >= ML_N0)));
      if (w > 0) bulk_s2c_elect(sb1 + c + 6 * 5120, sb1 + bo, sb2 + c + 3 * 5120, sb2 + bo, sb + c);
      SCHED_FENCE();
      mx = 0;
#pragma unroll
      for (int k = 0; k < 8; k++) mx = __vmaxu2(mx, p[k] & 0x7FFF7FFFu);
    };
    auto send_max = [&]() {
      mx = max(mx & 0xFFFFu, mx >> 16);
      mx = __reduce_max_sync(~0u, mx);
      { const uint32_t b = mapa(sb, min(lane, 2)); sta1p(b + O_MAXS + (rank * 4 + w) * 4, mx << 16, b + O_BAR + 8 * MB_SM, lane < 3); }
    };
    auto arm = [&]() { if (lane == 0 && w < (MR_N0 < 3 ? 3 : 2)) mbar_expect(bar + 8 * (w == 0 ? MB_OG : MB_MR - 1 + w), w == 0 ? 2048 : w == 1 ? 2048 * MR_N0 : 2048 * (3 - MR_N0)); };
    {
      arm();
      const uint32_t* mp = (const uint32_t*)(mem0 + tok * DM + myT * 64 + 16 * (lane >> 4) + 4 * (lane & 1));
      const uint32_t p[8] = {mp[0], mp[4], mp[1], mp[5], mp[16], mp[20], mp[17], mp[21]};
      forward(p);
    }
    if (w == 1) {
#pragma unroll 1
      for (int i = W_WIN; i < 20; i++) {
        if (i <= W_OPEN) mbar_wait(bar + 8 * (MB_W + i - W_WIN), 0);
        if (i >= 10) mbar_wait(bar + 8 * (MB_WC + i - 10), 0);
        load_piece(i);
      }
    }
    if (w == 0) {
      if (lane < 2) mbar_expect(bar + 8 * (MB_XF + lane), 20480);
      wait_flag(flags + FL_XN, 3);
      fence_async_global();
      if (lane < 10) bulk_g2s(sb + O_H + lane * 5120 + 1024, g_xn + chunk_of(lane) * 4096, 4096, bar + 8 * (MB_XF + (lane >= 4 && lane < 9)));
      if (!TRIG_LATE) asm volatile("griddepcontrol.launch_dependents;");
      if (lane == 0) GTT(layer * 4 + 1, 4);
    }
    if (w == 2) {
      wait_flag(flags + FL_X, 128);
      wait_flag(g_zero + Z_FLAGS + FL_N, 4);
      const float sq = __ldcg((const float*)(g_zero + Z_NORM));
      float mx = 0.f;
#pragma unroll
      for (int k = 0; k < 5; k++) {
        const float4* p = (const float4*)g_nrm + k * 32 + lane;
        const float4 x = __ldcg(p), y = __ldcg(p + 160), z = __ldcg(p + 320), u = __ldcg(p + 480);
        mx = fmaxf(fmaxf(mx, fmaxf((x.x + y.x) + (z.x + u.x), (x.y + y.y) + (z.y + u.y))), fmaxf((x.z + y.z) + (z.z + u.z), (x.w + y.w) + (z.w + u.w)));
      }
#pragma unroll
      for (int o = 16; o; o >>= 1) mx = fmaxf(mx, __shfl_xor_sync(~0u, mx, o));
      sts1(sb + O_MAXS + 52, __float_as_uint(sqrt_approx(sq) * sqrt_approx(mx) * (25.2982213f * 1.1f)));
    }
    bar_sync<B_WG2, 128>();
    const float cbound = __uint_as_float(lds1(sb + O_MAXS + 52));
#pragma unroll 1
    for (int i = 10; i < 15; i++) mbar_wait(bar + 8 * (MB_W + i), 0);
    if (tid == 256) GTT(layer * 4 + 1, 7);

    const uint32_t la_w = sb + O_WV + ((lane >> 4) * 8 + (lane & 7)) * 128 + (((2 * w + ((lane >> 3) & 1)) ^ (lane & 7)) << 4);
    uint32_t af[V_RS][4];
#pragma unroll
    for (int k = 0; k < V_RS; k++) ldsm4t(af[k], la_w + vord(V_OWN + k) * 2048);
    uint32_t vf[10];
    uint4 oq0, oq1;
    uint8_t* op;
    auto pv_x = [&](int s) {
      float ox[16];
      const uint32_t vz[4] = {vf[8], vf[9], 0u, 0u};
      constexpr uint64_t dp = mkdesc(SB0 + O_QK, 16, 2048, 1);
      bar_sync<B_PX, 256>();
      wg_fence();
      wg_rs_n32_tb0(ox, vf, dp, 0);
      wg_rs_n32_tb0(ox, vf + 4, dp + 2, 1);
      wg_rs_n32_tb0(ox, vz, dp + 4, 1);
      wg_commit();
      const uint32_t ln = opaque(lane);
      op = g_ot + (size_t)(s & OT_MASK) * (HE * 64) + (e0 + 16 * w) * 64 + (ln & 3) * 128 + (ln >> 2) * 16;
      wg_wait<0>();
      pin<16>(ox);
      oq0 = make_uint4(pack2(ox[0], ox[1]), pack2(ox[4], ox[5]), pack2(ox[8], ox[9]), pack2(ox[12], ox[13]));
      oq1 = make_uint4(pack2(ox[2], ox[3]), pack2(ox[6], ox[7]), pack2(ox[10], ox[11]), pack2(ox[14], ox[15]));
    };
    for (int s = 0;; s++) {
      const uint32_t par = s & 1;
      float sc, isc;
      uint32_t ao[O_RS > 0 ? O_RS : 1][4];
      {
        float av[20];
        constexpr uint64_t da = mkdesc(SB0 + O_WV, 1024, 1024, 1), db = mkdesc(SB0 + O_H, 16, 1024, 1);
#define V_RUN_RS(k0, k1) wg_fence(); _Pragma("unroll") for (int k = k0; k < k1; k++) wg_rs_n40_tb0(av, af[k], db + hoff(vord(V_OWN + k)), V_OWN + k);
#define V_RUN_SS(k0, k1) wg_fence(); _Pragma("unroll") for (int k = k0; k < k1; k++) wg_ss_n40_ta1_tb0(av, da + vord(k) * 128, db + hoff(vord(k)), k);
        if (V_OWN > 0) {
          bar_sync<B_VOWN, 384>();
          V_RUN_SS(0, V_OWN)
          if (w == 0) TS(29);
          SCHED_FENCE();
        }
        send_max();
        bar_sync<B_VGO, 384>();
        V_RUN_RS(0, V_N1)
        if (w == 0) TS(11);
        bar_sync<B_SISS, 256>();
        V_RUN_RS(V_N1, V_N1 + V_N2)
        bar_sync<B_SSENT, 256>();
        V_RUN_SS(V_OWN + V_RS, V_K1)
        V_RUN_RS(V_N1 + V_N2, V_RS)
        const uint32_t ln = opaque(lane);
        const uint32_t amx = opaque(sb + O_MAXS + 4 * min(ln, 11u));
        SCHED_FENCE();
        mbar_wait(bar + 8 * MB_SM, par);
        const uint32_t mxl = lds1(amx);
        if (s == 0) {
#pragma unroll 1
          for (int i = 15; i < 20; i++) mbar_wait(bar + 8 * (MB_W + i), 0);
          if (TRIG_LATE) asm volatile("griddepcontrol.launch_dependents;"); if (tid == 256) GTT(layer * 4 + 1, 8); }
        bar_sync<B_SLD, 256>();
        V_RUN_SS(V_K1, 20)
        wg_commit();
        V_RUN_SS((V_K1 > 20 ? V_K1 : 20), V_K2)
        wg_commit();
        wg_wait<1>();
        bar_arrive<B_VHALF, 192>();
        V_RUN_SS(V_K2, 40)
        wg_commit();
        SCHED_FENCE();
        if (w == 0) TS(12);
        {
          const float bnd = cbound * fmaxf(1.f, __uint_as_float(__reduce_max_sync(~0u, mxl)));
          const uint32_t eb = min(max(__float_as_uint(bnd) >> 23, 31u), 254u);
          sc = __uint_as_float(opaque((280u - eb) << 23));
          isc = __uint_as_float(opaque((eb - 29u) << 23));
        }
        const uint32_t pa = sb + O_QM + (ln & 7) * 128;
        const uint32_t pa0 = opaque(pa + (((ln >> 3) ^ (ln & 7)) << 4)), pa1 = opaque(pa0 ^ 64);
        const uint32_t o = O_OG + w * 256 + ln * 4;
        const uint32_t a0 = opaque(sb + o), a1 = opaque(sb1 + o + 4096), a2 = opaque(sb1 + o + 4096 + 128), a3 = opaque(sb2 + o + 2048), a4 = opaque(sb2 + o + 2048 + 128);
        const uint32_t b1 = opaque(sb1 + O_BAR + 8 * MB_OG), b2 = opaque(sb2 + O_BAR + 8 * MB_OG);
        const uint32_t c1 = opaque(0x3F803F80u);
        const uint32_t one[4] = {c1, c1, c1, c1};
        uint32_t pm[5];
        float s0[4] = {0.f, 0.f, 0.f, 0.f}, s1[4] = {0.f, 0.f, 0.f, 0.f}, s2[4] = {0.f, 0.f, 0.f, 0.f};
#define LD_AO _Pragma("unroll") for (int j = 0; j < 16; j++) if ((O_RSM >> j) & 1) ldsm4t(ao[O_IDX(j)], la_w + O_WO + (1 + (j >> 3)) * 24576 + (4 + (j & 7)) * 2048);
        if (VEND_POS == 2) bar_arrive<B_VEND, 256>();
        SCHED_FENCE();
        if (F_ORD == 0) {
          bar_sync<B_PM, 160>();
          ldsm4(pm, pa0);
          ldsm1(pm[4], pa1);
          if (VEND_POS == 0) bar_arrive<B_VEND, 256>();
          SCHED_FENCE();
        }
        wg_wait<0>();
        pin<20>(av);
        if (VEND_POS == 3) { bar_arrive<B_VEND, 256>(); SCHED_FENCE(); }
        if (w == 0) TS(13);
        if (O_RS_POS == 0) { LD_AO }
#pragma unroll
        for (int k = 0; k < 10; k++) vf[k] = pack2(av[2 * k], av[2 * k + 1]);
        if (F_ORD == 1) {
          SCHED_FENCE();
          bar_sync<B_PM, 160>();
          ldsm4(pm, pa0);
          ldsm1(pm[4], pa1);
          if (VEND_POS == 0) bar_arrive<B_VEND, 256>();
          if (O_RS_POS == 3) { LD_AO }
        }
        if (s == NSEG - 1) break;
        {
          float o0[4] = {0.f, 0.f, 0.f, 0.f}, o1[4] = {0.f, 0.f, 0.f, 0.f}, o2[4] = {0.f, 0.f, 0.f, 0.f};
          mma16816(s0, one, pm[0], pm[1]);
          mma16816(s1, one, pm[2], pm[3]);
          mma1688(s2, c1, c1, pm[4]);
          mma16816(o0, vf, pm[0], pm[1]);
          mma16816(o1, vf + 4, pm[2], pm[3]);
          mma1688(o2, vf[8], vf[9], pm[4]);
          const float i0 = rcp(s0[0] + s1[0] + s2[0]), i1 = rcp(s0[1] + s1[1] + s2[1]);
          const uint32_t p0 = pack2((o0[0] + o1[0] + o2[0]) * i0, (o0[1] + o1[1] + o2[1]) * i1), p1 = pack2((o0[2] + o1[2] + o2[2]) * i0, (o0[3] + o1[3] + o2[3]) * i1);
          sta1(a1, p0, b1); sta1(a2, p1, b1);
          sta1(a3, p0, b2); sta1(a4, p1, b2);
          sts1(a0, p0); sts1(a0 + 128, p1);
          if (O_RS_POS == 2) {
#pragma unroll
            for (int j = 0; j < 16; j++) if ((O_RSM >> j) & 1) ldsm4t(ao[O_IDX(j)], la_w + O_WO + (1 + (j >> 3)) * 24576 + (4 + (j & 7)) * 2048);
          }
          if (VEND_POS == 1) bar_arrive<B_VEND, 256>();
          fence_async();
        }
      }
      uint8_t* arp;
      uint32_t t1;
      {
        bar_sync<B_WG2, 128>();
        float c9[4], ca[4], cb[4], cc[4];
        constexpr uint64_t da = mkdesc(SB0 + O_WO, 1024, 1024, 1), db = mkdesc(SB0 + O_OG, 128, 128, 0);
#define O_RUN(acc, tile, k0, k1) _Pragma("unroll") for (int k = k0; k < k1; k++) wg_ss_n8_ta1_tb1(acc, da + (tile) * 1536 + k * 128, db + (k >> 2) * 128 + (k & 3) * 16, k);
        wg_fence();
        O_RUN(c9, 3, 0, 4)
        wg_commit();
        if (w == 0) TS(14);
        O_RUN(ca, 0, 0, 4) O_RUN(cb, 1, 0, 4) O_RUN(cc, 2, 0, 4)
        wg_commit();
        SCHED_FENCE();
        arp = ar + (s >> 2) * AR_GROUP + (s & 1) * 128 + ((s >> 1) & 1) * 512;
        uint8_t* pp = arp + opaque(prod_off);
        wg_wait<1>();
        pin<4>(c9);
        if (!(EXP & 4) && (!(EXP & 8) || rank == 0)) fix_red(pp + T9_OFF, c9, sc);
        SCHED_FENCE();
        if (O_RS_POS == 1) {
#pragma unroll
          for (int j = 0; j < 16; j++) if ((O_RSM >> j) & 1) ldsm4t(ao[O_IDX(j)], la_w + O_WO + (1 + (j >> 3)) * 24576 + (4 + (j & 7)) * 2048);
        }
        mbar_wait(bar + 8 * MB_OG, par);
        wg_fence();
        O_RUN(ca, 0, 4, 12)
        wg_commit();
        bar_arrive<B_VDONE, 160>();
        if (w == 0) TS(15);
#define O_MIX(acc, j0, j1) _Pragma("unroll") for (int j = j0; j < j1; j++) { const int k = 4 + (j & 7); \
          if ((O_RSM >> j) & 1) wg_rs_n8_tb1(acc, ao[O_IDX(j) < O_RS ? O_IDX(j) : 0], db + (k >> 2) * 128 + (k & 3) * 16, 1); \
          else wg_ss_n8_ta1_tb1(acc, da + (1 + (j >> 3)) * 1536 + k * 128, db + (k >> 2) * 128 + (k & 3) * 16, 1); }
        O_MIX(cb, 0, O_B1)
        wg_commit();
        if (O_MODE != 1) {
          wg_wait<1>();
          pin<4>(ca);
          if (!(EXP & 1)) fix_red(pp + tile_off(0), ca, sc);
          SCHED_FENCE();
          if (w == 0) TS(16);
          if (O_MODE == 2) {
            wg_wait<0>();
            pin<4>(cb);
            if (!(EXP & 1)) fix_red(pp + tile_off(1), cb, sc);
          }
          wg_fence();
        }
        if (O_B1 < 8) { O_MIX(cb, O_B1, 8) wg_commit(); }
        if (O_C1 < 16) {
          O_MIX(cc, 8, O_C1)
          wg_commit();
          wg_wait<1>();
          pin<4>(cb);
          if (!(EXP & 1)) fix_red(pp + tile_off(1), cb, sc);
          SCHED_FENCE();
          wg_fence();
        }
        O_MIX(cc, (O_C1 < 16 ? O_C1 : 8), 16)
        wg_commit();
        bar_arrive<B_XGO1, 256>();
        bar_arrive<B_XGO, 256>();
        if (O_MODE != 2 && O_C1 == 16) {
          wg_wait<1>();
          if (O_MODE == 1) { pin<4>(ca); if (!(EXP & 1)) fix_red(pp + tile_off(0), ca, sc); }
          pin<4>(cb);
          if (!(EXP & 1)) fix_red(pp + tile_off(1), cb, sc);
          SCHED_FENCE();
        }
        wg_wait<0>();
        pin<4>(cc);
        fix_red(pp + tile_off(2), cc, sc);
        t1 = clk();
        if (w == 3) TS(17);
      }
      pv_x(s);
      bar_arrive<B_PFREE, 256>();
      bar_arrive<B_PFREE1, 256>();
      if (w == 0) TS(28);
#pragma unroll
      for (int k = 0; k < V_RS; k++) ldsm4t(af[k], la_w + vord(V_OWN + k) * 2048);
      {
        arm();
        const int dly = w == 0 ? POLL_D0 : POLL_DELAY - (3 - w) * POLL_STEP;
        const uint32_t need = w == 0 ? ((EXP & 4) ? 0 : (EXP & 8) ? 32 : 96) : ((EXP & 1) && w < 3) ? 0 : 32;
        const uint8_t* cp = arp + opaque(cons_off);
        uint4 y[4];
        int it = 0;
        while ((int)(clk() - t1) < dly) {}
        if (w == 3) TS(18);
        y[0] = ld_poll(cp); y[1] = ld_poll(cp + 256); y[2] = ld_poll(cp + 16384); y[3] = ld_poll(cp + 16384 + 256);
        if (EXP & 2) {} else if (EVF) { const uint64_t pol = policy_evict_first(); stg4h(op, oq0, pol); stg4h(op + 512, oq1, pol); } else { stg4(op, oq0); stg4(op + 512, oq1); }
        uint32_t p[8];
        const float isl = isc * 0.5f, bias = -(float)(need >> 3) * isl;
        while (true) {
          const uint32_t bad = ((y[0].x ^ need) | (y[0].z ^ need) | (y[1].x ^ need) | (y[1].z ^ need)) | ((y[2].x ^ need) | (y[2].z ^ need) | (y[3].x ^ need) | (y[3].z ^ need));
          const bool again = __any_sync(~0u, (bad & 127u) != 0);
          if (SPEC_DEC || !again) {
#pragma unroll
            for (int k = 0; k < 4; k++) {
              p[2 * k] = pack2(fmaf((float)(int)__funnelshift_r(y[k].x, y[k].y, 3), isl, bias), fmaf((float)(int)__funnelshift_r(y[k].z, y[k].w, 3), isl, bias));
              p[2 * k + 1] = pack2((float)(int)y[k].y * isc, (float)(int)y[k].w * isc);
            }
            if (SPEC_DEC) {
#pragma unroll
              for (int k = 0; k < 8; k++) asm volatile("" : "+r"(p[k]));
            }
          }
          if (!again) break;
          if (++it > 2000000) __trap();
          y[0] = ld_poll(cp); y[1] = ld_poll(cp + 256); y[2] = ld_poll(cp + 16384); y[3] = ld_poll(cp + 16384 + 256);
        }
        TS(19 + w);
        forward(p);
      }
    }
    if (VEND_POS == 1) bar_arrive<B_VEND, 256>();
    bar_arrive<B_VDONE, 160>();
    bar_arrive<B_XGO1, 256>();
    bar_arrive<B_XGO, 256>();
    pv_x(NSEG - 1);
    if (EVF) { const uint64_t pol = policy_evict_first(); stg4h(op, oq0, pol); stg4h(op + 512, oq1, pol); } else { stg4(op, oq0); stg4(op + 512, oq1); }
    bar_sync<B_WG2, 128>();
    if (tid == 256) { red_release(flags + FL_A + (e0 >> 10) * 8 + (NSEG - 1) * 48, 1); }
    __syncwarp();
  }
  asm volatile("barrier.cluster.arrive.relaxed.aligned;\nbarrier.cluster.wait.aligned;" ::: "memory");
  GT(layer * 4 + 1, 2);
  if (wid == 0) asm volatile("griddepcontrol.wait;" ::: "memory");
}

constexpr int P_B = 0, P_A = 131072, P_BAR = 196608, OPC_SMEM = P_BAR + 256;
#define PF_C 3
#define PF_S0 43
constexpr int OP_KR = 48;

__global__ void __launch_bounds__(384, 1)
opc_kernel(const __grid_constant__ CUtensorMap tmo, bf16* __restrict__ out, int layer,
           const bf16* __restrict__ Wq, const bf16* __restrict__ Wk, const bf16* __restrict__ Wv, const bf16* __restrict__ Wo) {
  extern __shared__ __align__(1024) uint8_t smem[];
  asm volatile("griddepcontrol.launch_dependents;");
  GT(layer * 4 + 2, 0);
  const uint32_t sb = smem_u32(smem);
  check_smem_base(sb);
  const int tid = threadIdx.x, wid = __shfl_sync(~0u, tid >> 5, 0), wg = wid >> 2, w = wid & 3, lane = tid & 31;
  const uint32_t bar = sb + P_BAR;
  uint32_t* flags = g_zero + Z_FLAGS + layer * FL_LAYER;
  float* acc = g_acc + layer * (S_TOK * DM);
  const uint64_t pol = policy_evict_first();
  if (wid == 0) {
    if (lane < 16) mbar_init(bar + 8 * lane, (lane == 8 || lane == 9) ? 8 : 1);
    fence_async();
  }
  __syncthreads();
  if (blockIdx.x < 30) {
    const int cg = blockIdx.x % 5, kg = blockIdx.x / 5;
    if (wg < 2) {
      asm volatile("setmaxnreg.inc.sync.aligned.u32 240;");
      uint32_t a[OP_KR][4];
      const uint32_t la = sb + P_B + ((lane >> 4) * 8 + (lane & 7)) * 128 + (((2 * w + ((lane >> 3) & 1)) ^ (lane & 7)) << 4);
      mbar_wait(bar + 80, 0);
#pragma unroll
      for (int k = 0; k < 32; k++) ldsm4t(a[k], la + wg * 65536 + k * 2048);
      bar_arrive<2, 288>();
      mbar_wait(bar + 88, 0);
#pragma unroll
      for (int k = 0; k < 16; k++) ldsm4t(a[32 + k], la + wg * 32768 + k * 2048);
      bar_arrive<3, 288>();
      mbar_wait(bar + 96, 0);
      float* ap = acc + (cg * 8 + wg * 4 + w) * 512 + lane * 4;
      for (int s = 0; s < NSEG; s++) {
        const int buf = s & 1;
        const uint32_t par = (s >> 1) & 1;
        float d[16];
        const uint64_t db = mkdesc(SB0 + P_B + buf * 65536, 512, 128, 0), da = mkdesc(SB0 + P_A + wg * 32768, 1024, 1024, 1);
        float* p = ap + (s & AC_MASK) * (32 * DM);
        float* pz = ap + ((s + 2) & AC_MASK) * (32 * DM) + kg * 128;
        if (kg < 4 && s + 2 < NSEG) { if (EVF) stg4h(pz, make_uint4(0, 0, 0, 0), pol); else stg4(pz, make_uint4(0, 0, 0, 0)); }
#pragma unroll
        for (int q = 0; q < 4; q++) {
          mbar_wait(bar + 8 * (buf * 4 + q), par);
          wg_fence();
#pragma unroll
          for (int k = 16 * q; k < 16 * q + 16; k++) {
            if (k < OP_KR) wg_rs_n32_tb1(d, a[k < OP_KR ? k : 0], db + k * 64, k);
            else wg_ss_n32_ta1_tb1(d, da + (k - OP_KR) * 128, db + k * 64, 1);
          }
        }
        wg_commit();
        wg_wait<0>();
        pin<16>(d);
        if (lane == 0) mbar_arrive(bar + 8 * (8 + buf));
        if (s == NSEG - 1) GT(layer * 4 + 2, 6);
        if (EVF) {
          red4fh(p, d[0], d[1], d[4], d[5], pol);
          red4fh(p + 128, d[8], d[9], d[12], d[13], pol);
          red4fh(p + 256, d[2], d[3], d[6], d[7], pol);
          red4fh(p + 384, d[10], d[11], d[14], d[15], pol);
        } else {
          red4f(p, d[0], d[1], d[4], d[5]);
          red4f(p + 128, d[8], d[9], d[12], d[13]);
          red4f(p + 256, d[2], d[3], d[6], d[7]);
          red4f(p + 384, d[10], d[11], d[14], d[15]);
        }
        bar_sync<1, 256>();
        if (tid == 0) { red_release(flags + FL_B + s * 8, 1); }
        __syncwarp();
      }
    } else {
      asm volatile("setmaxnreg.dec.sync.aligned.u32 24;");
      if (w == 0) {
        if (lane == 0) { mbar_expect(bar + 80, 131072); mbar_expect(bar + 96, 65536); mbar_expect(bar + 88, 65536); }
        __syncwarp();
        if (lane < 16) tma2d(sb + P_B + lane * 8192, &tmo, cg * 128 + (lane >> 3) * 64, kg * 1024 + (lane & 7) * 64, bar + 80);
        else if (lane < 24) tma2d(sb + P_B + lane * 8192, &tmo, cg * 128 + ((lane >> 2) & 1) * 64, kg * 1024 + 768 + (lane & 3) * 64, bar + 96);
        bar_sync<2, 288>();
        fence_async();
        if (lane < 8) tma2d(sb + P_B + lane * 8192, &tmo, cg * 128 + (lane >> 2) * 64, kg * 1024 + 512 + (lane & 3) * 64, bar + 88);
        bar_sync<3, 288>();
        for (int s = 0; s < NSEG; s++) {
          const int buf = s & 1;
          if (s >= 2) mbar_wait(bar + 8 * (8 + buf), ((s >> 1) & 1) ^ 1);
          if (s >= 2) wait_flag(flags + FL_B + (s - 2) * 8, 30);
          wait_flag(flags + FL_A + s * 48 + kg * 8, 16);
          fence_async_global();
          if (lane < 4) {
            mbar_expect(bar + 8 * (buf * 4 + lane), 16384);
            if (EVF) bulk_g2sh(sb + P_B + buf * 65536 + lane * 16384, g_ot + (size_t)(s & OT_MASK) * (HE * 64) + kg * 65536 + lane * 16384, 16384, bar + 8 * (buf * 4 + lane), pol);
            else bulk_g2s(sb + P_B + buf * 65536 + lane * 16384, g_ot + (size_t)(s & OT_MASK) * (HE * 64) + kg * 65536 + lane * 16384, 16384, bar + 8 * (buf * 4 + lane));
            if (s == NSEG - 1 && lane == 0) GTT(layer * 4 + 2, 5);
          }
          __syncwarp();
        }
      } else if (w == 1 && layer == 0) {
#pragma unroll 1
        for (int q = 4 * (4 - PF_C); q < 18; q++) {
          wait_flag(flags + FL_A + (PF_S0 + q) * 48 + kg * 8, 16);
          const int m = q >> 2;
          const uint8_t* W = m == 0 ? (const uint8_t*)Wo : m == 1 ? (const uint8_t*)Wv : m == 2 ? (const uint8_t*)Wk : m == 3 ? (const uint8_t*)Wq : (q & 1) ? g_w2 : g_w1;
          const int n = m < 4 ? 512 : (q & 1) ? 224 : 640, l0 = m < 4 ? blockIdx.x * 2048 + (q & 3) * 512 : blockIdx.x * n, lim = m < 4 ? 61440 : (q & 1) ? 6720 : 19200;
#pragma unroll 1
          for (int k = lane; k < n; k += 32) {
            if (l0 + k < lim) asm volatile("prefetch.global.L2 [%0];" :: "l"(W + (size_t)(l0 + k) * 128));
            __nanosleep(100);
          }
        }
      }
    }
  } else {
    constexpr int LD = 644;
    float* xs = (float*)smem;
    uint32_t par = 0;
    for (int task = blockIdx.x - 30; task < 2 * NSEG; task += 6, par ^= 1) {
      const int s = task >> 1, jj = task & 1;
      if (wid == 0) {
        wait_flag(flags + FL_XN + (task >> 2) * 8 + 1, 3);
        fence_async_global();
        if (lane == 0) { mbar_expect(bar, 20480); bulk_g2s(sb + 49152, g_x + task * 16 * DM, 20480, bar); }
      }
      if (wid == 1) { wait_flag(flags + FL_B + s * 8, 30); if (s == NSEG - 1 && lane == 0) GTT(layer * 4 + 2, 7); }
      __syncthreads();
      if (wid < 10) {
        float4 v[8];
#pragma unroll
        for (int k = 0; k < 8; k++) v[k] = EVF ? ldg4fh(acc + (s & AC_MASK) * (32 * DM) + (wid * 8 + k) * 256 + jj * 128 + lane * 4, pol) : __ldcg((const float4*)(acc + (s & AC_MASK) * (32 * DM) + (wid * 8 + k) * 256 + jj * 128 + lane * 4));
        float* xp = xs + (lane & 3) * 2 * LD + wid * 64 + (lane >> 2);
#pragma unroll
        for (int k = 0; k < 8; k++) { xp[k * 8] = v[k].x; xp[LD + k * 8] = v[k].y; xp[8 * LD + k * 8] = v[k].z; xp[9 * LD + k * 8] = v[k].w; }
      }
      mbar_wait(bar, par);
      __syncthreads();
#pragma unroll 1
      for (int row = wid; row < 16; row += 12) {
        const int tk = task * 16 + row;
        float v[20], sum = 0.f;
        const int pj = (lane & 24) + 2 * (lane & 3) + ((lane >> 2) & 1);
        bf16* dst = out ? out + tk * DM + lane * 2 : g_x + tk * DM + pj * 2;
#pragma unroll
        for (int k = 0; k < 10; k++) {
          const float2 u = *(const float2*)(xs + row * LD + k * 64 + lane * 2);
          const uint32_t r = *(const uint32_t*)(smem + 49152 + row * 1280 + k * 128 + pj * 4);
          v[2 * k] = u.x + bflo(r); v[2 * k + 1] = u.y + bfhi(r); sum += v[2 * k] + v[2 * k + 1];
          *(uint32_t*)(dst + k * 64) = pack2(v[2 * k], v[2 * k + 1]);
        }
        if (!out) {
#pragma unroll
          for (int o = 16; o; o >>= 1) sum += __shfl_xor_sync(~0u, sum, o);
          const float m = sum * (1.f / DM);
          float q = 0.f;
#pragma unroll
          for (int k = 0; k < 20; k++) { v[k] -= m; q += v[k] * v[k]; }
#pragma unroll
          for (int o = 16; o; o >>= 1) q += __shfl_xor_sync(~0u, q, o);
          const float rs = rsqrtf(q * (1.f / DM) + 1e-5f);
          uint8_t* xp = g_xt + (tk >> 7) * 163840 + (tk & 127) * 128 + (((lane >> 2) ^ (tk & 7)) << 4) + (lane & 3) * 4;
#pragma unroll
          for (int k = 0; k < 10; k++) *(uint32_t*)(xp + k * 16384) = pack2(v[2 * k] * rs, v[2 * k + 1] * rs);
        }
      }
      fence_async();
      __syncthreads();
      if (tid == 0 && !out) { red_release(flags + FL_LAYER + FL_T + (task >> 3) * 8, 1); }
    }
  }
  GT(layer * 4 + 2, 1);
  __syncwarp();
  asm volatile("griddepcontrol.wait;" ::: "memory");
  GT(layer * 4 + 2, 2);
}

constexpr int L_STAGE = 47104;
constexpr int L_KV = 0, L_B2 = 43008;
constexpr int L_BAR = 4 * L_STAGE;
constexpr int LA_SMEM = L_BAR + 256;
__device__ __forceinline__ float phi(float t) { return (fmaxf(t, 0.f) + 1e-6f) + ex2(fminf(t * 1.4426950408889634f, 0.f)); }
__device__ __forceinline__ void sqacc(uint32_t& h, uint32_t v) { asm("fma.rn.bf16x2 %0, %1, %1, %0;" : "+r"(h) : "r"(v)); }
__device__ __forceinline__ uint32_t phi2(float a, float b) { return pack2(phi(a), phi(b)); }
#define LA_LATE 6
#define PF_LB 1
#define PF_IL 1
#define PF_SLEEP1 400
#define PF_N0 2
#define PF_N1 0
#define PF_SLEEP 300

__global__ void __launch_bounds__(384, 1)
la_kernel(const bf16* __restrict__ Wq, const bf16* __restrict__ Wk, const bf16* __restrict__ Wv,
          const bf16* __restrict__ Wo, uint8_t* __restrict__ ar, int layer) {
  extern __shared__ __align__(1024) uint8_t smem[];
  const uint32_t sb = smem_u32(smem);
  check_smem_base(sb);
  const int tid = threadIdx.x, wid = __shfl_sync(~0u, tid >> 5, 0), wg = wid >> 2, w = wid & 3, lane = tid & 31, g = lane >> 2, i4 = lane & 3;
  const int cr = blockIdx.x & 1, hg = (blockIdx.x >> 1) & 7, tb = (blockIdx.x >> 4) * 2 + cr;
  const uint32_t bar = sb + L_BAR;
  uint32_t* flags = g_zero + Z_FLAGS + layer * FL_LAYER;
  asm volatile("griddepcontrol.launch_dependents;");
  GT(layer * 4, 0);
  if (wid == 0) {
    if (lane < 8) mbar_init(bar + 8 * lane, lane >= 4 ? (blockIdx.x < 128 ? 16 : 10) : 1);
    asm volatile("fence.mbarrier_init.release.cluster;" ::: "memory");
    fence_async();
  }
  if (blockIdx.x >= 128) {
    __syncthreads();
    const int q = blockIdx.x - 128;
    const uint8_t* src = (const uint8_t*)Wo + q * 1966080;
    if (wid == 11) {
#pragma unroll 1
      for (int it = 0; it < 48; it++) {
        const int st = it & 3;
        if (it >= 4) mbar_wait(bar + 8 * (4 + st), ((it >> 2) & 1) ^ 1);
        if (lane == 0) mbar_expect(bar + 8 * st, 40960);
        __syncwarp();
        if (lane < 4) bulk_g2s(sb + st * 40960 + lane * 10240, src + it * 40960 + lane * 10240, 10240, bar + 8 * st);
      }
    } else if (wid < 10) {
      float c[8] = {0.f, 0.f, 0.f, 0.f, 0.f, 0.f, 0.f, 0.f};
#pragma unroll 1
      for (int it = 0; it < 48; it++) {
        const int st = it & 3;
        mbar_wait(bar + 8 * st, (it >> 2) & 1);
        uint4 v[8];
#pragma unroll
        for (int k = 0; k < 8; k++) v[k] = lds4(sb + st * 40960 + k * 5120 + tid * 16);
        uint32_t h[4] = {0, 0, 0, 0};
#pragma unroll
        for (int k = 0; k < 8; k++) { sqacc(h[0], v[k].x); sqacc(h[1], v[k].y); sqacc(h[2], v[k].z); sqacc(h[3], v[k].w); }
        __syncwarp();
        if (lane == 0) mbar_arrive(bar + 8 * (4 + st));
#pragma unroll
        for (int k = 0; k < 4; k++) { c[2 * k] += bflo(h[k]); c[2 * k + 1] += bfhi(h[k]); }
      }
      float* red = (float*)(smem + 163840);
      *(float4*)(red + tid * 8) = make_float4(c[0], c[1], c[2], c[3]);
      *(float4*)(red + tid * 8 + 4) = make_float4(c[4], c[5], c[6], c[7]);
      bar_sync<1, 320>();
#pragma unroll
      for (int k = tid; k < DM; k += 320) g_nrm[q * DM + k] = (red[k] + red[DM + k]) + (red[2 * DM + k] + red[3 * DM + k]);
      asm volatile("griddepcontrol.wait;" ::: "memory");
      bar_sync<1, 320>();
      if (tid == 0) red_release(flags + FL_N, 1);
      GT(0, 2);
    }
    return;
  }
  __syncthreads();
  asm volatile("barrier.cluster.arrive.relaxed.aligned;" ::: "memory");
  if (layer == 0) asm volatile("griddepcontrol.wait;" ::: "memory");
  asm volatile("barrier.cluster.wait.aligned;" ::: "memory");
  if (wg == 2) {
    asm volatile("setmaxnreg.dec.sync.aligned.u32 40;");
    if (w == 0) {
      if (lane < 4) {
        mbar_expect(bar + 8 * lane, L_STAGE);
        bulk_g2s_mc(sb + lane * L_STAGE + 16384 + cr * 15360, g_w1 + (hg * 10 + lane) * 30720 + cr * 15360, 15360, bar + 8 * lane);
      }
      if (layer == 1) { if (LA_LATE) wait_flag(flags + FL_T + 15 * 8, LA_LATE); wait_flag(flags + FL_T + tb * 8, 8); fence_async_global(); }
      if (lane < 4) bulk_g2s(sb + lane * L_STAGE, g_xt + (tb * 10 + lane) * 16384, 16384, bar + 8 * lane);
#pragma unroll 1
      for (int kc = 4; kc < 10; kc++) {
        const int st = kc & 3;
        mbar_wait(bar + 8 * (4 + st), ((kc >> 2) & 1) ^ 1);
        if (lane == 0) {
          mbar_expect(bar + 8 * st, L_STAGE);
          bulk_g2s_mc(sb + st * L_STAGE + 16384 + cr * 15360, g_w1 + (hg * 10 + kc) * 30720 + cr * 15360, 15360, bar + 8 * st);
          bulk_g2s(sb + st * L_STAGE, g_xt + (tb * 10 + kc) * 16384, 16384, bar + 8 * st);
        }
        __syncwarp();
      }
    } else {
      const int t = tid - 288;
#pragma unroll 1
      for (int k = t; k < 768; k += 96) *(uint4*)(ar + blockIdx.x * 12288 + k * 16) = make_uint4(0, 0, 0, 0);
      if (layer == 0) {
        float sv = 0.f;
        const uint4* pv = (const uint4*)((const uint8_t*)Wv + blockIdx.x * 61440) + t;
#pragma unroll 1
        for (int k = 0; k < 40; k += 5) {
          uint4 v[5];
#pragma unroll
          for (int j = 0; j < 5; j++) v[j] = __ldg(pv + (k + j) * 96);
          if (PF_IL && k < 25) {
            asm volatile("prefetch.global.L2 [%0];" :: "l"((const uint8_t*)Wq + blockIdx.x * 61440 + (k / 5) * 12288 + t * 128));
            if (PF_IL > 1) asm volatile("prefetch.global.L2 [%0];" :: "l"((const uint8_t*)Wk + blockIdx.x * 61440 + (k / 5) * 12288 + t * 128));
          }
#pragma unroll
          for (int j = 0; j < 5; j++) {
            sv = fmaf(bflo(v[j].x), bflo(v[j].x), fmaf(bfhi(v[j].x), bfhi(v[j].x), fmaf(bflo(v[j].y), bflo(v[j].y), fmaf(bfhi(v[j].y), bfhi(v[j].y), sv))));
            sv = fmaf(bflo(v[j].z), bflo(v[j].z), fmaf(bfhi(v[j].z), bfhi(v[j].z), fmaf(bflo(v[j].w), bflo(v[j].w), fmaf(bfhi(v[j].w), bfhi(v[j].w), sv))));
          }
        }
#pragma unroll
        for (int o = 16; o; o >>= 1) sv += __shfl_xor_sync(~0u, sv, o);
        if (lane == 0) atomicAdd((float*)(g_zero + Z_NORM), sv);
      }
      if (layer == 1 && PF_LB) {
        const int l = blockIdx.x * 96 + t;
        if (l < 6720 + NLB * 640) asm volatile("prefetch.global.L2 [%0];" :: "l"(l < 6720 ? g_w2 + l * 128 : (const uint8_t*)g_x + (l - 6720) * 128));
      }
#pragma unroll 1
      for (int k = layer ? 0 : 5 * PF_IL; k < 5 * (layer ? PF_N1 : PF_N0); k++) {
        const int m = k / 5;
        const bf16* W = m == 0 ? Wq : m == 1 ? Wk : m == 2 ? Wv : Wo;
        asm volatile("prefetch.global.L2 [%0];" :: "l"((const uint8_t*)W + blockIdx.x * 61440 + (k - m * 5) * 12288 + t * 128));
        __nanosleep(layer ? PF_SLEEP1 : PF_SLEEP);
      }
      if (t == 0) GTT(layer * 4, 14);
      bar_arrive<3, 352>();
    }
  } else {
    asm volatile("setmaxnreg.inc.sync.aligned.u32 232;");
    GT(layer * 4, 4);
    uint32_t pq[5][4];
    float* kv = (float*)(g_zero + Z_KV) + layer * KV_LAYER + hg * 1920;
    {
      float d[120];
#pragma unroll 1
      for (int kc = 0; kc < 10; kc++) {
        const int st = kc & 3;
        const uint64_t da = mkdesc(SB0 + st * L_STAGE + wg * 8192, 16, 1024, 1), db = mkdesc(SB0 + st * L_STAGE + 16384, 3840, 128, 0);
        mbar_wait(bar + 8 * st, (kc >> 2) & 1);
        wg_fence();
#pragma unroll
        for (int k = 0; k < 4; k++) wg_ss_n240_ta0_tb1(d, da + 2 * k, db + k * 480, kc | k);
        wg_commit();
        if (kc > 0) { wg_wait<1>(); if (lane < 2) mbar_arrive_cl(mapa(bar + 8 * (4 + ((kc - 1) & 3)), lane)); }
      }
      wg_wait<0>();
      pin<120>(d);
      GT(layer * 4, 5);
      bar_sync<1, 256>();
      const uint32_t kb = sb + L_KV + (wg * 8 + 2 * w + ((lane >> 3) & 1)) * 2688 + (lane >> 4) * 128 + (lane & 7) * 16;
#pragma unroll
      for (int j = 0; j < 5; j++) stsm4(kb + 1280 + j * 256, pack2(d[80 + 8 * j], d[81 + 8 * j]), pack2(d[82 + 8 * j], d[83 + 8 * j]), pack2(d[84 + 8 * j], d[85 + 8 * j]), pack2(d[86 + 8 * j], d[87 + 8 * j]));
      stsm2(kb + 2560, 0x3F803F80u, 0x3F803F80u);
#pragma unroll
      for (int j = 0; j < 5; j++) stsm4(kb + j * 256, phi2(d[40 + 8 * j], d[41 + 8 * j]), phi2(d[42 + 8 * j], d[43 + 8 * j]), phi2(d[44 + 8 * j], d[45 + 8 * j]), phi2(d[46 + 8 * j], d[47 + 8 * j]));
      fence_async();
      bar_sync<1, 256>();
      float e[44];
      {
        const uint64_t da = mkdesc(SB0 + L_KV + wg * 1024, 2688, 128, 0), db = mkdesc(SB0 + L_KV + 1280, 2688, 128, 0);
        wg_fence();
#pragma unroll
        for (int k = 0; k < 8; k++) wg_ss_n88_ta1_tb1(e, da + k * 336, db + k * 336, k);
        wg_commit();
        wg_wait<0>();
        pin<44>(e);
      }
#pragma unroll
      for (int h = 0; h < 2; h++) {
        const int row = wg * 64 + 16 * w + 8 * h + g;
        const int c = row < 80 ? 2 * i4 - (row / 20) * 20 : 100;
        float* dst = kv + row * 24 + c;
#pragma unroll
        for (int j = 0; j < 10; j++)
          asm volatile("{\n.reg .pred p;\nsetp.lt.u32 p, %3, 20;\n@p red.relaxed.gpu.global.add.v2.f32 [%0], {%1,%2};\n}" :: "l"(dst + 8 * j), "f"(e[4 * j + 2 * h]), "f"(e[4 * j + 2 * h + 1]), "r"(c + 8 * j) : "memory");
        asm volatile("{\n.reg .pred p;\nsetp.ne.u32 p, %2, 0;\n@p red.relaxed.gpu.global.add.f32 [%0], %1;\n}" :: "l"(kv + row * 24 + 20), "f"(e[40 + 2 * h]), "r"((int)(row < 80 && i4 == 0)) : "memory");
      }
      bar_sync<1, 256>();
      GT(layer * 4, 6);
      if (tid == 0) { red_release(flags + FL_KV + hg * 8, 1); }
      __syncwarp();
      pin<40>(d);
#pragma unroll
      for (int k = 0; k < 5; k++) {
        pq[k][0] = phi2(d[8 * k], d[8 * k + 1]); pq[k][1] = phi2(d[8 * k + 2], d[8 * k + 3]);
        pq[k][2] = phi2(d[8 * k + 4], d[8 * k + 5]); pq[k][3] = phi2(d[8 * k + 6], d[8 * k + 7]);
      }
    }
#pragma unroll 1
    for (int k = tid; k < 1600; k += 256) sts4(sb + L_B2 + k * 16, 0, 0, 0, 0);
    GT(layer * 4, 7);
    if (wid == 0) wait_flag(flags + FL_KV + hg * 8, 16);
    GT(layer * 4, 8);
    bar_sync<1, 256>();
    if (tid < 240) {
      const int dd = tid / 3, part = tid - dd * 3, n = (dd / 20) * 20 + 8 * part;
      const float4 v0 = __ldcg((const float4*)(kv + dd * 24 + 8 * part)), v1 = __ldcg((const float4*)(kv + dd * 24 + 8 * part + 4));
      const float z = __ldcg(kv + dd * 24 + 20);
      const uint32_t a = sb + L_B2 + (dd >> 3) * 2560 + (dd & 7) * 16, zz = pack2(z, z);
      const uint32_t a0 = a + (n >> 3) * 128 + (n & 7) * 2, a1 = a + ((n + 4) >> 3) * 128 + ((n + 4) & 7) * 2;
      sts2(a0, pack2(v0.x, v0.y), pack2(v0.z, v0.w)); sts2(a0 + 1280, zz, zz);
      if (part < 2) { sts2(a1, pack2(v1.x, v1.y), pack2(v1.z, v1.w)); sts2(a1 + 1280, zz, zz); }
    }
    fence_async();
    bar_sync<1, 256>();
    {
      float o[80];
      const uint64_t db = mkdesc(SB0 + L_B2, 2560, 128, 0);
      wg_fence();
#pragma unroll
      for (int k = 0; k < 5; k++) wg_rs_n160_tb1(o, pq[k], db + k * 320, k);
      wg_commit();
      wg_wait<0>();
      pin<80>(o);
      uint8_t* op = g_oa + (tb * 2 + wg) * 81920 + hg * 10240 + w * 256 + lane * 4;
#pragma unroll
      for (int j = 0; j < 20; j++) {
        const float inv = rcp(o[40 + 2 * j] + 1e-6f);
        *(uint32_t*)(op + (j >> 1) * 1024 + (j & 1) * 128) = pack2(o[2 * j] * inv, o[2 * j + 1] * inv);
      }
      GT(layer * 4, 9);
    }
    bar_sync<3, 352>();
    if (tid == 0) { red_release(flags + FL_O + tb * 8, 1); red_add(flags + FL_X, 1); }
    GT(layer * 4, 2);
    if (wid == 7) asm volatile("griddepcontrol.wait;" ::: "memory");
  }
}

__global__ void __launch_bounds__(256) prep_kernel(const bf16* __restrict__ x, const bf16* __restrict__ wqkv, const bf16* __restrict__ wo) {
  asm volatile("griddepcontrol.launch_dependents;");
  const int b = blockIdx.x, tid = threadIdx.x, lane = tid & 31;
  if (b < 160) GT(3, 0);
  if (b < 256) {
    const int row = b * 8 + (tid >> 5);
    float v[20], s = 0.f;
#pragma unroll
    for (int k = 0; k < 10; k++) { const uint32_t u = __ldg((const uint32_t*)(x + row * DM + k * 64 + lane * 2)); v[2 * k] = bflo(u); v[2 * k + 1] = bfhi(u); s += v[2 * k] + v[2 * k + 1]; }
#pragma unroll
    for (int o = 16; o; o >>= 1) s += __shfl_xor_sync(~0u, s, o);
    const float m = s * (1.f / DM);
    float q = 0.f;
#pragma unroll
    for (int k = 0; k < 20; k++) { v[k] -= m; q += v[k] * v[k]; }
#pragma unroll
    for (int o = 16; o; o >>= 1) q += __shfl_xor_sync(~0u, q, o);
    const float r = rsqrtf(q * (1.f / DM) + 1e-5f);
#pragma unroll
    for (int k = 0; k < 10; k++)
      *(uint32_t*)(g_xt + ((row >> 7) * 10 + k) * 16384 + (row & 127) * 128 + (((lane >> 2) ^ (row & 7)) << 4) + (lane & 3) * 4) = pack2(v[2 * k] * r, v[2 * k + 1] * r);
  } else if (b < 256 + 203) {
#pragma unroll
    for (int it = 0; it < 4; it++) {
      const int u = (b - 256) * 1024 + it * 256 + tid;
      if (u < 153600) {
        const int k8 = u & 7, nb = (u >> 3) % 30, kg = (u / 240) % 80, hg = u / 19200;
        *(uint4*)(g_w1 + u * 16) = __ldg((const uint4*)(wqkv + (kg * 8 + k8) * 1920 + (nb / 10) * 640 + hg * 80 + (nb % 10) * 8));
      } else {
        const int v = u - 153600, k8 = v & 7, nb = (v >> 3) % 28, kg = (v / 224) % 80, c = (v / 17920) * 224 + nb * 8;
        if (v < 53760) *(uint4*)(g_w2 + v * 16) = c < DM ? __ldg((const uint4*)(wo + (kg * 8 + k8) * DM + c)) : make_uint4(0, 0, 0, 0);
      }
    }
  } else {
    const int t = (b - 459) * 256 + tid;
    for (int k = t; k < Z_END / 4; k += 16 * 256) ((uint4*)g_zero)[k] = make_uint4(0, 0, 0, 0);
    for (int k = t; k < 16 * DM; k += 16 * 256) { ((uint4*)g_acc)[k] = make_uint4(0, 0, 0, 0); ((uint4*)(g_acc + S_TOK * DM))[k] = make_uint4(0, 0, 0, 0); }
  }
  if (b < 160) GT(3, 2);
}

typedef CUresult (*EncodeFn)(CUtensorMap*, CUtensorMapDataType, cuuint32_t, void*, const cuuint64_t*, const cuuint64_t*, const cuuint32_t*,
                             const cuuint32_t*, CUtensorMapInterleave, CUtensorMapSwizzle, CUtensorMapL2promotion, CUtensorMapFloatOOBfill);
static void make_map(EncodeFn fn, CUtensorMap* m, const void* p, uint64_t cols, uint64_t rows, uint32_t bc, uint32_t br, CUtensorMapSwizzle sw) {
  cuuint64_t dims[2] = {cols, rows}; cuuint64_t strides[1] = {cols * 2}; cuuint32_t box[2] = {bc, br}; cuuint32_t es[2] = {1, 1};
  fn(m, CU_TENSOR_MAP_DATA_TYPE_BFLOAT16, 2, (void*)p, dims, strides, box, es, CU_TENSOR_MAP_INTERLEAVE_NONE, sw,
     CU_TENSOR_MAP_L2_PROMOTION_L2_128B, CU_TENSOR_MAP_FLOAT_OOB_FILL_NONE);
}

static void make_map_perm(EncodeFn fn, CUtensorMap* m, const void* p) {
  cuuint64_t dims[5] = {HE, 2, 2, 4, 40}; const cuuint64_t r = HE * 2; cuuint64_t strides[4] = {r, 8 * r, 2 * r, 16 * r};
  cuuint32_t box[5] = {64, 2, 2, 4, 4}; cuuint32_t es[5] = {1, 1, 1, 1, 1};
  fn(m, CU_TENSOR_MAP_DATA_TYPE_BFLOAT16, 5, (void*)p, dims, strides, box, es, CU_TENSOR_MAP_INTERLEAVE_NONE, CU_TENSOR_MAP_SWIZZLE_128B,
     CU_TENSOR_MAP_L2_PROMOTION_L2_128B, CU_TENSOR_MAP_FLOAT_OOB_FILL_NONE);
}

#define OPC_PDL 1
#define LA_PDL 1
#define REC_PDL 1
extern "C" void kernel_launch(void* const* d_in, const int* in_sizes, int n_in, void* d_out, int out_size) {
  const bf16* x = (const bf16*)d_in[0];
  const bf16* wqkv = (const bf16*)d_in[1];
  const bf16* wo_a = (const bf16*)d_in[2];
  const bf16* mem0 = (const bf16*)d_in[4];
  const bf16* Wq = (const bf16*)d_in[5];
  const bf16* Wk = (const bf16*)d_in[6];
  const bf16* Wv = (const bf16*)d_in[7];
  const bf16* Wo = (const bf16*)d_in[8];
  cudaStream_t st = cudaStreamPerThread;

  static EncodeFn enc = nullptr;
  static uint8_t* p_ar; static uint32_t* p_zero; static bf16* p_x;
  if (!enc) {
    cudaDriverEntryPointQueryResult qr;
    void* fn = nullptr;
    cudaGetDriverEntryPoint("cuTensorMapEncodeTiled", &fn, cudaEnableDefault, &qr);
    enc = (EncodeFn)fn;
    cudaFuncSetAttribute(rec_kernel, cudaFuncAttributeMaxDynamicSharedMemorySize, REC_SMEM);
    cudaFuncSetAttribute(opc_kernel, cudaFuncAttributeMaxDynamicSharedMemorySize, OPC_SMEM);
    cudaFuncSetAttribute(la_kernel, cudaFuncAttributeMaxDynamicSharedMemorySize, LA_SMEM);
    cudaGetSymbolAddress((void**)&p_ar, g_ar); p_ar = (uint8_t*)(((uintptr_t)p_ar + 32767) & ~(uintptr_t)32767);
    cudaGetSymbolAddress((void**)&p_zero, g_zero); cudaGetSymbolAddress((void**)&p_x, g_x);
  }
  CUtensorMap tmq, tmk, tmv, tmo, tmx[2];
  make_map_perm(enc, &tmq, Wq);
  make_map_perm(enc, &tmk, Wk);
  make_map_perm(enc, &tmv, Wv);
  make_map(enc, &tmo, Wo, DM, HE, 64, 64, CU_TENSOR_MAP_SWIZZLE_128B);
  make_map(enc, &tmx[0], x, DM, S_TOK, 232, 64, CU_TENSOR_MAP_SWIZZLE_NONE);
  make_map(enc, &tmx[1], p_x, DM, S_TOK, 232, 64, CU_TENSOR_MAP_SWIZZLE_NONE);

  cudaLaunchAttribute at[2];
  at[0].id = cudaLaunchAttributeProgrammaticStreamSerialization; at[0].val.programmaticStreamSerializationAllowed = 1;
  at[1].id = cudaLaunchAttributeClusterDimension; at[1].val.clusterDim.x = 3; at[1].val.clusterDim.y = 1; at[1].val.clusterDim.z = 1;
  cudaLaunchAttribute at2[2] = {at[1], at[0]};
  at2[0].val.clusterDim.x = 2;
  prep_kernel<<<475, 256, 0, st>>>(x, wqkv, wo_a);
  for (int l = 0; l < 2; l++) {
    cudaLaunchConfig_t cfg = {};
    cfg.blockDim = dim3(384); cfg.stream = st;
    cfg.gridDim = dim3(l == 0 ? 132 : 128); cfg.dynamicSmemBytes = LA_SMEM; cfg.attrs = at2; cfg.numAttrs = 1 + LA_PDL;
    cudaLaunchKernelEx(&cfg, la_kernel, Wq, Wk, Wv, Wo, p_ar + l * AR_LAYER, l);
    cfg.gridDim = dim3(96 + 3 * NLB); cfg.dynamicSmemBytes = REC_SMEM; cfg.attrs = at + 1 - REC_PDL; cfg.numAttrs = 1 + REC_PDL;
    cudaLaunchKernelEx(&cfg, rec_kernel, tmq, tmk, tmv, tmo, tmx[l], mem0, p_ar + l * AR_LAYER, p_zero + Z_FLAGS + l * FL_LAYER, l);
    cfg.gridDim = dim3(36); cfg.dynamicSmemBytes = OPC_SMEM; cfg.attrs = at; cfg.numAttrs = OPC_PDL;
    cudaLaunchKernelEx(&cfg, opc_kernel, tmo, l == 1 ? (bf16*)d_out : (bf16*)nullptr, l, Wq, Wk, Wv, Wo);
  }
}
```

```cpp
#include <cuda_runtime.h>
#include <cuda_bf16.h>
#include <cuda.h>
#include <stdint.h>

typedef __nv_bfloat16 bf16;
typedef unsigned long long u64;

constexpr int S_TOK = 2048, DM = 640, DH = 192, HE = 6144, NSEG = 64;

constexpr int AR_GROUP = 98304;
constexpr int AR_LAYER = 16 * AR_GROUP;
__device__ __align__(1024) uint8_t g_ar[2 * AR_LAYER + 32768];
__device__ __align__(1024) uint8_t g_xn[NSEG * 40960];
__device__ __align__(1024) uint8_t g_xt[S_TOK * DM * 2];
__device__ __align__(1024) uint8_t g_ot[NSEG * HE * 64];
__device__ __align__(1024) uint8_t g_oa[S_TOK * DM * 2];
__device__ __align__(1024) uint8_t g_w1[DM * 1920 * 2];
__device__ __align__(1024) uint8_t g_w2[DM * 672 * 2];
__device__ __align__(1024) float g_acc[2 * S_TOK * DM];
__device__ __align__(1024) bf16 g_x[S_TOK * DM];
constexpr int FL_A = 0, FL_B = 64 * 6 * 8, FL_KV = FL_B + 64 * 8, FL_O = FL_KV + 8 * 8, FL_T = FL_O + 16 * 8, FL_X = FL_T + 16 * 8, FL_N = FL_X + 8, FL_XN = FL_N + 8, FL_LAYER = FL_XN + 32 * 8;
constexpr int Z_FLAGS = 0, Z_NORM = 2 * FL_LAYER, Z_KV = Z_NORM + 8, KV_LAYER = 8 * 80 * 24, Z_END = Z_KV + 2 * KV_LAYER;
__device__ __align__(128) uint32_t g_zero[Z_END];
__device__ __align__(128) float g_nrm[4 * DM];
#define GT(slot, k) do {} while (0)
#define GTT(slot, k) do {} while (0)

__device__ __forceinline__ uint32_t smem_u32(const void* p) { return (uint32_t)__cvta_generic_to_shared(p); }
__device__ __forceinline__ uint32_t mapa(uint32_t a, uint32_t r) { uint32_t o; asm("mapa.shared::cluster.u32 %0, %1, %2;" : "=r"(o) : "r"(a), "r"(r)); return o; }
__device__ __forceinline__ void mbar_init(uint32_t bar, uint32_t cnt) { asm volatile("mbarrier.init.shared::cta.b64 [%0], %1;" :: "r"(bar), "r"(cnt) : "memory"); }
__device__ __forceinline__ void mbar_expect(uint32_t bar, uint32_t tx) { asm volatile("mbarrier.arrive.expect_tx.shared::cta.b64 _, [%0], %1;" :: "r"(bar), "r"(tx) : "memory"); }
__device__ __forceinline__ void mbar_arrive(uint32_t bar) { asm volatile("mbarrier.arrive.shared::cta.b64 _, [%0];" :: "r"(bar) : "memory"); }
__device__ __forceinline__ void mbar_wait(uint32_t bar, uint32_t par) {
  asm volatile("{\n.reg .pred p;\n.reg .u32 c;\nmov.u32 c, 0;\n"
               "LW:\nmbarrier.try_wait.parity.shared::cta.b64 p, [%0], %1;\n@p bra LD;\n"
               "add.u32 c, c, 1;\nsetp.lt.u32 p, c, 4000000;\n@p bra LW;\ntrap;\nLD:\n}" :: "r"(bar), "r"(par) : "memory");
}
__device__ __forceinline__ void mbar_waitf(uint32_t bar, uint32_t par) {
  asm volatile("{\n.reg .pred p, q;\n.reg .u32 c;\nmov.u32 c, 0;\n"
               "LW:\nadd.u32 c, c, 1;\nsetp.lt.u32 q, c, 1000000;\nmbarrier.try_wait.parity.shared::cta.b64 p, [%0], %1;\n"
               "and.pred q, q, !p;\n@q bra LW;\n}" :: "r"(bar), "r"(par) : "memory");
}
template <int ID, int N> __device__ __forceinline__ void bar_sync() { asm volatile("barrier.sync %0, %1;" :: "n"(ID), "n"(N) : "memory"); }
template <int ID, int N> __device__ __forceinline__ void bar_arrive() { asm volatile("barrier.arrive %0, %1;" :: "n"(ID), "n"(N) : "memory"); }
__device__ __forceinline__ void fence_async() { asm volatile("fence.proxy.async.shared::cta;" ::: "memory"); }
__device__ __forceinline__ void cluster_sync() { asm volatile("barrier.cluster.arrive.aligned;\nbarrier.cluster.wait.aligned;" ::: "memory"); }
__device__ __forceinline__ void wg_fence() { asm volatile("wgmma.fence.sync.aligned;" ::: "memory"); }
__device__ __forceinline__ void wg_commit() { asm volatile("wgmma.commit_group.sync.aligned;" ::: "memory"); }
template <int N> __device__ __forceinline__ void wg_wait() { asm volatile("wgmma.wait_group.sync.aligned %0;" :: "n"(N) : "memory"); }
template <int N> __device__ __forceinline__ void pin(float* d) {
#pragma unroll
  for (int i = 0; i < N; i++) asm volatile("" : "+f"(d[i]) :: "memory");
}
__device__ __forceinline__ constexpr uint64_t mkdesc(uint32_t addr, uint32_t lbo, uint32_t sbo, int sw) {
  return (uint64_t)((addr & 0x3FFFF) >> 4) | ((uint64_t)(lbo >> 4) << 16) | ((uint64_t)(sbo >> 4) << 32) | ((uint64_t)sw << 62);
}
constexpr uint32_t SB0 = 1024;
__device__ __forceinline__ void check_smem_base(uint32_t sb) { if ((sb & 0x3FFFF) != SB0) __trap(); }
__device__ __forceinline__ uint32_t cta_rank() { uint32_t r; asm volatile("mov.u32 %0, %%cluster_ctarank;" : "=r"(r)); return r; }
__device__ __forceinline__ uint32_t opaque(uint32_t v) { uint32_t o; asm volatile("mov.u32 %0, %1;" : "=r"(o) : "r"(v)); return o; }
__device__ __forceinline__ uint32_t pack2(float lo, float hi) { uint32_t r; asm("cvt.rn.bf16x2.f32 %0, %1, %2;" : "=r"(r) : "f"(hi), "f"(lo)); return r; }
__device__ __forceinline__ void ldsm4(uint32_t* r, uint32_t a) { asm volatile("ldmatrix.sync.aligned.m8n8.x4.shared.b16 {%0,%1,%2,%3}, [%4];" : "=r"(r[0]), "=r"(r[1]), "=r"(r[2]), "=r"(r[3]) : "r"(a) : "memory"); }
__device__ __forceinline__ void ldsm4t(uint32_t* r, uint32_t a) { asm volatile("ldmatrix.sync.aligned.m8n8.x4.trans.shared.b16 {%0,%1,%2,%3}, [%4];" : "=r"(r[0]), "=r"(r[1]), "=r"(r[2]), "=r"(r[3]) : "r"(a) : "memory"); }
__device__ __forceinline__ void ldsm1(uint32_t& r, uint32_t a) { asm volatile("ldmatrix.sync.aligned.m8n8.x1.shared.b16 {%0}, [%1];" : "=r"(r) : "r"(a) : "memory"); }
__device__ __forceinline__ void stsm4(uint32_t a, uint32_t r0, uint32_t r1, uint32_t r2, uint32_t r3) { asm volatile("stmatrix.sync.aligned.m8n8.x4.shared.b16 [%0], {%1,%2,%3,%4};" :: "r"(a), "r"(r0), "r"(r1), "r"(r2), "r"(r3) : "memory"); }
__device__ __forceinline__ void stsm1(uint32_t a, uint32_t r0) { asm volatile("stmatrix.sync.aligned.m8n8.x1.shared.b16 [%0], {%1};" :: "r"(a), "r"(r0) : "memory"); }
__device__ __forceinline__ void stsm4t(uint32_t a, uint32_t r0, uint32_t r1, uint32_t r2, uint32_t r3) { asm volatile("stmatrix.sync.aligned.m8n8.x4.trans.shared.b16 [%0], {%1,%2,%3,%4};" :: "r"(a), "r"(r0), "r"(r1), "r"(r2), "r"(r3) : "memory"); }
__device__ __forceinline__ void stsm2t(uint32_t a, uint32_t r0, uint32_t r1) { asm volatile("stmatrix.sync.aligned.m8n8.x2.trans.shared.b16 [%0], {%1,%2};" :: "r"(a), "r"(r0), "r"(r1) : "memory"); }
__device__ __forceinline__ void mma16816(float* c, const uint32_t* a, uint32_t b0, uint32_t b1) {
  asm volatile("mma.sync.aligned.m16n8k16.row.col.f32.bf16.bf16.f32 {%0,%1,%2,%3}, {%4,%5,%6,%7}, {%8,%9}, {%0,%1,%2,%3};"
               : "+f"(c[0]), "+f"(c[1]), "+f"(c[2]), "+f"(c[3]) : "r"(a[0]), "r"(a[1]), "r"(a[2]), "r"(a[3]), "r"(b0), "r"(b1));
}
__device__ __forceinline__ void mma1688(float* c, uint32_t a0, uint32_t a1, uint32_t b0) {
  asm volatile("mma.sync.aligned.m16n8k8.row.col.f32.bf16.bf16.f32 {%0,%1,%2,%3}, {%4,%5}, {%6}, {%0,%1,%2,%3};"
               : "+f"(c[0]), "+f"(c[1]), "+f"(c[2]), "+f"(c[3]) : "r"(a0), "r"(a1), "r"(b0));
}
__device__ __forceinline__ void sta1(uint32_t a, uint32_t v, uint32_t bar) { asm volatile("st.async.weak.shared::cluster.mbarrier::complete_tx::bytes.b32 [%0], %1, [%2];" :: "r"(a), "r"(v), "r"(bar) : "memory"); }
__device__ __forceinline__ void sta1p(uint32_t a, uint32_t v, uint32_t bar, bool p) { asm volatile("{\n.reg .pred p;\nsetp.ne.b32 p, %3, 0;\n@p st.async.weak.shared::cluster.mbarrier::complete_tx::bytes.b32 [%0], %1, [%2];\n}" :: "r"(a), "r"(v), "r"(bar), "r"((int)p) : "memory"); }
__device__ __forceinline__ void sta2(uint32_t a, uint32_t v0, uint32_t v1, uint32_t bar) { asm volatile("st.async.weak.shared::cluster.mbarrier::complete_tx::bytes.v2.b32 [%0], {%1,%2}, [%3];" :: "r"(a), "r"(v0), "r"(v1), "r"(bar) : "memory"); }
__device__ __forceinline__ void sta4(uint32_t a, uint32_t v0, uint32_t v1, uint32_t v2, uint32_t v3, uint32_t bar) { asm volatile("st.async.weak.shared::cluster.mbarrier::complete_tx::bytes.v4.b32 [%0], {%1,%2,%3,%4}, [%5];" :: "r"(a), "r"(v0), "r"(v1), "r"(v2), "r"(v3), "r"(bar) : "memory"); }
__device__ __forceinline__ float bflo(uint32_t v) { return __uint_as_float(v << 16); }
__device__ __forceinline__ float bfhi(uint32_t v) { return __uint_as_float(v & 0xFFFF0000u); }
__device__ __forceinline__ void sta2f(uint32_t a, float v0, float v1, uint32_t bar) { asm volatile("st.async.weak.shared::cluster.mbarrier::complete_tx::bytes.v2.f32 [%0], {%1,%2}, [%3];" :: "r"(a), "f"(v0), "f"(v1), "r"(bar) : "memory"); }
__device__ __forceinline__ void sta4f(uint32_t a, float v0, float v1, float v2, float v3, uint32_t bar) { asm volatile("st.async.weak.shared::cluster.mbarrier::complete_tx::bytes.v4.f32 [%0], {%1,%2,%3,%4}, [%5];" :: "r"(a), "f"(v0), "f"(v1), "f"(v2), "f"(v3), "r"(bar) : "memory"); }
__device__ __forceinline__ float4 lds4f(uint32_t a) { float4 v; asm volatile("ld.shared.v4.f32 {%0,%1,%2,%3}, [%4];" : "=f"(v.x), "=f"(v.y), "=f"(v.z), "=f"(v.w) : "r"(a) : "memory"); return v; }
__device__ __forceinline__ float2 lds2f(uint32_t a) { float2 v; asm volatile("ld.shared.v2.f32 {%0,%1}, [%2];" : "=f"(v.x), "=f"(v.y) : "r"(a) : "memory"); return v; }
__device__ __forceinline__ uint4 lds4(uint32_t a) { uint4 v; asm volatile("ld.shared.v4.u32 {%0,%1,%2,%3}, [%4];" : "=r"(v.x), "=r"(v.y), "=r"(v.z), "=r"(v.w) : "r"(a) : "memory"); return v; }
__device__ __forceinline__ uint32_t lds1(uint32_t a) { uint32_t v; asm volatile("ld.shared.u32 %0, [%1];" : "=r"(v) : "r"(a) : "memory"); return v; }
__device__ __forceinline__ void stsm2(uint32_t a, uint32_t r0, uint32_t r1) { asm volatile("stmatrix.sync.aligned.m8n8.x2.shared.b16 [%0], {%1,%2};" :: "r"(a), "r"(r0), "r"(r1) : "memory"); }
__device__ __forceinline__ float rcp(float x) { float y; asm("rcp.approx.ftz.f32 %0, %1;" : "=f"(y) : "f"(x)); return y; }
__device__ __forceinline__ void sts4(uint32_t a, uint32_t v0, uint32_t v1, uint32_t v2, uint32_t v3) { asm volatile("st.shared.v4.u32 [%0], {%1,%2,%3,%4};" :: "r"(a), "r"(v0), "r"(v1), "r"(v2), "r"(v3) : "memory"); }
__device__ __forceinline__ void bulk_s2c(uint32_t dst, uint32_t src, uint32_t bytes, uint32_t bar) {
  asm volatile("cp.async.bulk.shared::cluster.shared::cta.mbarrier::complete_tx::bytes [%0], [%1], %2, [%3];" :: "r"(dst), "r"(src), "r"(bytes), "r"(bar) : "memory");
}
__device__ __forceinline__ void stg4(void* p, uint4 v) { asm volatile("st.global.v4.u32 [%0], {%1,%2,%3,%4};" :: "l"(p), "r"(v.x), "r"(v.y), "r"(v.z), "r"(v.w) : "memory"); }
__device__ __forceinline__ void red_add(uint32_t* p, uint32_t v) { asm volatile("red.relaxed.gpu.global.add.u32 [%0], %1;" :: "l"(p), "r"(v) : "memory"); }
__device__ __forceinline__ void red_release(uint32_t* p, uint32_t v) { asm volatile("red.release.gpu.global.add.u32 [%0], %1;" :: "l"(p), "r"(v) : "memory"); }
__device__ __forceinline__ void fence_async_global() { asm volatile("fence.proxy.async.global;" ::: "memory"); }
__device__ __forceinline__ uint64_t policy_evict_first() { uint64_t p; asm("createpolicy.fractional.L2::evict_first.b64 %0, 1.0;" : "=l"(p)); return p; }
__device__ __forceinline__ void stg4h(void* p, uint4 v, uint64_t pol) { asm volatile("st.global.L2::cache_hint.v4.u32 [%0], {%1,%2,%3,%4}, %5;" :: "l"(p), "r"(v.x), "r"(v.y), "r"(v.z), "r"(v.w), "l"(pol) : "memory"); }
__device__ __forceinline__ void red4fh(float* p, float a, float b, float c, float d, uint64_t pol) { asm volatile("red.relaxed.gpu.global.add.L2::cache_hint.v4.f32 [%0], {%1,%2,%3,%4}, %5;" :: "l"(p), "f"(a), "f"(b), "f"(c), "f"(d), "l"(pol) : "memory"); }
__device__ __forceinline__ float4 ldg4fh(const float* p, uint64_t pol) { float4 v; asm volatile("ld.global.cg.L2::cache_hint.v4.f32 {%0,%1,%2,%3}, [%4], %5;" : "=f"(v.x), "=f"(v.y), "=f"(v.z), "=f"(v.w) : "l"(p), "l"(pol) : "memory"); return v; }
__device__ __forceinline__ void bulk_g2sh(uint32_t dst, const void* src, uint32_t bytes, uint32_t bar, uint64_t pol) {
  asm volatile("cp.async.bulk.shared::cluster.global.mbarrier::complete_tx::bytes.L2::cache_hint [%0], [%1], %2, [%3], %4;" :: "r"(dst), "l"(src), "r"(bytes), "r"(bar), "l"(pol) : "memory");
}
#define OT_MASK 63
#define AC_MASK 63
#define EVF 1
__device__ __forceinline__ void red4f(float* p, float a, float b, float c, float d) { asm volatile("red.relaxed.gpu.global.add.v4.f32 [%0], {%1,%2,%3,%4};" :: "l"(p), "f"(a), "f"(b), "f"(c), "f"(d) : "memory"); }
__device__ __forceinline__ void wait_flag(const uint32_t* p, uint32_t target) {
  uint32_t v; int it = 0;
  while (true) {
    asm volatile("ld.acquire.gpu.global.u32 %0, [%1];" : "=r"(v) : "l"(p) : "memory");
    if (__all_sync(~0u, v >= target)) break;
    if (++it > 4000000) __trap();
    __nanosleep(20);
  }
}
__device__ __forceinline__ void sts2(uint32_t a, uint32_t v0, uint32_t v1) { asm volatile("st.shared.v2.u32 [%0], {%1,%2};" :: "r"(a), "r"(v0), "r"(v1) : "memory"); }
__device__ __forceinline__ float sqrt_approx(float x) { float y; asm("sqrt.approx.f32 %0, %1;" : "=f"(y) : "f"(x)); return y; }
__device__ __forceinline__ void bulk_s2c_elect(uint32_t d1, uint32_t b1, uint32_t d2, uint32_t b2, uint32_t src) {
  asm volatile("{\n.reg .pred p;\nelect.sync _|p, 0xffffffff;\n"
               "@p cp.async.bulk.shared::cluster.shared::cta.mbarrier::complete_tx::bytes [%0], [%4], 1024, [%1];\n"
               "@p cp.async.bulk.shared::cluster.shared::cta.mbarrier::complete_tx::bytes [%2], [%4], 1024, [%3];\n}"
               :: "r"(d1), "r"(b1), "r"(d2), "r"(b2), "r"(src) : "memory");
}
__device__ __forceinline__ void mbar_arrive_elect(uint32_t bar) { asm volatile("{\n.reg .pred p;\nelect.sync _|p, 0xffffffff;\n@p mbarrier.arrive.shared::cta.b64 _, [%0];\n}" :: "r"(bar) : "memory"); }
__device__ __forceinline__ void cp16(uint32_t dst, const void* src) { asm volatile("cp.async.cg.shared.global [%0], [%1], 16;" :: "r"(dst), "l"(src) : "memory"); }
__device__ __forceinline__ void sts1(uint32_t a, uint32_t v) { asm volatile("st.shared.u32 [%0], %1;" :: "r"(a), "r"(v) : "memory"); }
__device__ __forceinline__ void bulk_g2s(uint32_t dst, const void* src, uint32_t bytes, uint32_t bar) {
  asm volatile("cp.async.bulk.shared::cluster.global.mbarrier::complete_tx::bytes [%0], [%1], %2, [%3];" :: "r"(dst), "l"(src), "r"(bytes), "r"(bar) : "memory");
}
__device__ __forceinline__ void bulk_g2s_mc(uint32_t dst, const void* src, uint32_t bytes, uint32_t bar) {
  asm volatile("cp.async.bulk.shared::cluster.global.mbarrier::complete_tx::bytes.multicast::cluster [%0], [%1], %2, [%3], %4;" :: "r"(dst), "l"(src), "r"(bytes), "r"(bar), "h"((uint16_t)3) : "memory");
}
__device__ __forceinline__ void mbar_arrive_cl(uint32_t bar) { asm volatile("mbarrier.arrive.shared::cluster.b64 _, [%0];" :: "r"(bar) : "memory"); }
__device__ __forceinline__ void tma2d(uint32_t dst, const CUtensorMap* m, int c0, int c1, uint32_t bar) {
  asm volatile("cp.async.bulk.tensor.2d.shared::cluster.global.mbarrier::complete_tx::bytes [%0], [%1, {%3, %4}], [%2];" :: "r"(dst), "l"((uint64_t)m), "r"(bar), "r"(c0), "r"(c1) : "memory");
}
__device__ __forceinline__ void tma5d(uint32_t dst, const CUtensorMap* m, int c0, int c4, uint32_t bar) {
  asm volatile("cp.async.bulk.tensor.5d.shared::cluster.global.mbarrier::complete_tx::bytes [%0], [%1, {%3, %5, %5, %5, %4}], [%2];" :: "r"(dst), "l"((uint64_t)m), "r"(bar), "r"(c0), "r"(c4), "r"(0) : "memory");
}
__device__ __forceinline__ void red64(void* p, uint32_t lo, uint32_t hi) { asm volatile("{\n.reg .b64 t;\nmov.b64 t, {%1,%2};\nred.relaxed.gpu.global.add.u64 [%0], t;\n}" :: "l"(p), "r"(lo), "r"(hi) : "memory"); }
__device__ __forceinline__ uint4 ld_poll(const void* p) {
  uint4 v;
  asm volatile("{\n.reg .b64 a, b;\nld.relaxed.gpu.global.v2.b64 {a, b}, [%4];\nmov.b64 {%0,%1}, a;\nmov.b64 {%2,%3}, b;\n}" : "=r"(v.x), "=r"(v.y), "=r"(v.z), "=r"(v.w) : "l"(p) : "memory");
  return v;
}
__device__ __forceinline__ uint32_t clk() { uint32_t c; asm volatile("mov.u32 %0, %%clock;" : "=r"(c) :: "memory"); return c; }
#define SCHED_FENCE() asm volatile("pmevent 0;" ::: "memory")
__device__ __forceinline__ float ex2(float x) { float y; asm("ex2.approx.ftz.f32 %0, %1;" : "=f"(y) : "f"(x)); return y; }

__device__ __forceinline__ void wg_ss_n240_ta0_tb1(float* d, uint64_t a, uint64_t b, int sc) {
  asm volatile("{\n.reg .pred p;\nsetp.ne.b32 p, %122, 0;\nwgmma.mma_async.sync.aligned.m64n240k16.f32.bf16.bf16 {%0, %1, %2, %3, %4, %5, %6, %7, %8, %9, %10, %11, %12, %13, %14, %15, %16, %17, %18, %19, %20, %21, %22, %23, %24, %25, %26, %27, %28, %29, %30, %31, %32, %33, %34, %35, %36, %37, %38, %39, %40, %41, %42, %43, %44, %45, %46, %47, %48, %49, %50, %51, %52, %53, %54, %55, %56, %57, %58, %59, %60, %61, %62, %63, %64, %65, %66, %67, %68, %69, %70, %71, %72, %73, %74, %75, %76, %77, %78, %79, %80, %81, %82, %83, %84, %85, %86, %87, %88, %89, %90, %91, %92, %93, %94, %95, %96, %97, %98, %99, %100, %101, %102, %103, %104, %105, %106, %107, %108, %109, %110, %111, %112, %113, %114, %115, %116, %117, %118, %119}, %120, %121, p, 1, 1, 0, 1;\n}\n"
    : "+f"(d[0]), "+f"(d[1]), "+f"(d[2]), "+f"(d[3]), "+f"(d[4]), "+f"(d[5]), "+f"(d[6]), "+f"(d[7]), "+f"(d[8]), "+f"(d[9]), "+f"(d[10]), "+f"(d[11]), "+f"(d[12]), "+f"(d[13]), "+f"(d[14]), "+f"(d[15]), "+f"(d[16]), "+f"(d[17]), "+f"(d[18]), "+f"(d[19]), "+f"(d[20]), "+f"(d[21]), "+f"(d[22]), "+f"(d[23]), "+f"(d[24]), "+f"(d[25]), "+f"(d[26]), "+f"(d[27]), "+f"(d[28]), "+f"(d[29]), "+f"(d[30]), "+f"(d[31]), "+f"(d[32]), "+f"(d[33]), "+f"(d[34]), "+f"(d[35]), "+f"(d[36]), "+f"(d[37]), "+f"(d[38]), "+f"(d[39]), "+f"(d[40]), "+f"(d[41]), "+f"(d[42]), "+f"(d[43]), "+f"(d[44]), "+f"(d[45]), "+f"(d[46]), "+f"(d[47]), "+f"(d[48]), "+f"(d[49]), "+f"(d[50]), "+f"(d[51]), "+f"(d[52]), "+f"(d[53]), "+f"(d[54]), "+f"(d[55]), "+f"(d[56]), "+f"(d[57]), "+f"(d[58]), "+f"(d[59]), "+f"(d[60]), "+f"(d[61]), "+f"(d[62]), "+f"(d[63]), "+f"(d[64]), "+f"(d[65]), "+f"(d[66]), "+f"(d[67]), "+f"(d[68]), "+f"(d[69]), "+f"(d[70]), "+f"(d[71]), "+f"(d[72]), "+f"(d[73]), "+f"(d[74]), "+f"(d[75]), "+f"(d[76]), "+f"(d[77]), "+f"(d[78]), "+f"(d[79]), "+f"(d[80]), "+f"(d[81]), "+f"(d[82]), "+f"(d[83]), "+f"(d[84]), "+f"(d[85]), "+f"(d[86]), "+f"(d[87]), "+f"(d[88]), "+f"(d[89]), "+f"(d[90]), "+f"(d[91]), "+f"(d[92]), "+f"(d[93]), "+f"(d[94]), "+f"(d[95]), "+f"(d[96]), "+f"(d[97]), "+f"(d[98]), "+f"(d[99]), "+f"(d[100]), "+f"(d[101]), "+f"(d[102]), "+f"(d[103]), "+f"(d[104]), "+f"(d[105]), "+f"(d[106]), "+f"(d[107]), "+f"(d[108]), "+f"(d[109]), "+f"(d[110]), "+f"(d[111]), "+f"(d[112]), "+f"(d[113]), "+f"(d[114]), "+f"(d[115]), "+f"(d[116]), "+f"(d[117]), "+f"(d[118]), "+f"(d[119])
    : "l"(a), "l"(b), "r"(sc));
}
__device__ __forceinline__ void wg_ss_n88_ta1_tb1(float* d, uint64_t a, uint64_t b, int sc) {
  asm volatile("{\n.reg .pred p;\nsetp.ne.b32 p, %46, 0;\nwgmma.mma_async.sync.aligned.m64n88k16.f32.bf16.bf16 {%0, %1, %2, %3, %4, %5, %6, %7, %8, %9, %10, %11, %12, %13, %14, %15, %16, %17, %18, %19, %20, %21, %22, %23, %24, %25, %26, %27, %28, %29, %30, %31, %32, %33, %34, %35, %36, %37, %38, %39, %40, %41, %42, %43}, %44, %45, p, 1, 1, 1, 1;\n}\n"
    : "+f"(d[0]), "+f"(d[1]), "+f"(d[2]), "+f"(d[3]), "+f"(d[4]), "+f"(d[5]), "+f"(d[6]), "+f"(d[7]), "+f"(d[8]), "+f"(d[9]), "+f"(d[10]), "+f"(d[11]), "+f"(d[12]), "+f"(d[13]), "+f"(d[14]), "+f"(d[15]), "+f"(d[16]), "+f"(d[17]), "+f"(d[18]), "+f"(d[19]), "+f"(d[20]), "+f"(d[21]), "+f"(d[22]), "+f"(d[23]), "+f"(d[24]), "+f"(d[25]), "+f"(d[26]), "+f"(d[27]), "+f"(d[28]), "+f"(d[29]), "+f"(d[30]), "+f"(d[31]), "+f"(d[32]), "+f"(d[33]), "+f"(d[34]), "+f"(d[35]), "+f"(d[36]), "+f"(d[37]), "+f"(d[38]), "+f"(d[39]), "+f"(d[40]), "+f"(d[41]), "+f"(d[42]), "+f"(d[43])
    : "l"(a), "l"(b), "r"(sc));
}
__device__ __forceinline__ void wg_rs_n160_tb1(float* d, const uint32_t* a, uint64_t b, int sc) {
  asm volatile("{\n.reg .pred p;\nsetp.ne.b32 p, %85, 0;\nwgmma.mma_async.sync.aligned.m64n160k16.f32.bf16.bf16 {%0, %1, %2, %3, %4, %5, %6, %7, %8, %9, %10, %11, %12, %13, %14, %15, %16, %17, %18, %19, %20, %21, %22, %23, %24, %25, %26, %27, %28, %29, %30, %31, %32, %33, %34, %35, %36, %37, %38, %39, %40, %41, %42, %43, %44, %45, %46, %47, %48, %49, %50, %51, %52, %53, %54, %55, %56, %57, %58, %59, %60, %61, %62, %63, %64, %65, %66, %67, %68, %69, %70, %71, %72, %73, %74, %75, %76, %77, %78, %79}, {%80, %81, %82, %83}, %84, p, 1, 1, 1;\n}\n"
    : "+f"(d[0]), "+f"(d[1]), "+f"(d[2]), "+f"(d[3]), "+f"(d[4]), "+f"(d[5]), "+f"(d[6]), "+f"(d[7]), "+f"(d[8]), "+f"(d[9]), "+f"(d[10]), "+f"(d[11]), "+f"(d[12]), "+f"(d[13]), "+f"(d[14]), "+f"(d[15]), "+f"(d[16]), "+f"(d[17]), "+f"(d[18]), "+f"(d[19]), "+f"(d[20]), "+f"(d[21]), "+f"(d[22]), "+f"(d[23]), "+f"(d[24]), "+f"(d[25]), "+f"(d[26]), "+f"(d[27]), "+f"(d[28]), "+f"(d[29]), "+f"(d[30]), "+f"(d[31]), "+f"(d[32]), "+f"(d[33]), "+f"(d[34]), "+f"(d[35]), "+f"(d[36]), "+f"(d[37]), "+f"(d[38]), "+f"(d[39]), "+f"(d[40]), "+f"(d[41]), "+f"(d[42]), "+f"(d[43]), "+f"(d[44]), "+f"(d[45]), "+f"(d[46]), "+f"(d[47]), "+f"(d[48]), "+f"(d[49]), "+f"(d[50]), "+f"(d[51]), "+f"(d[52]), "+f"(d[53]), "+f"(d[54]), "+f"(d[55]), "+f"(d[56]), "+f"(d[57]), "+f"(d[58]), "+f"(d[59]), "+f"(d[60]), "+f"(d[61]), "+f"(d[62]), "+f"(d[63]), "+f"(d[64]), "+f"(d[65]), "+f"(d[66]), "+f"(d[67]), "+f"(d[68]), "+f"(d[69]), "+f"(d[70]), "+f"(d[71]), "+f"(d[72]), "+f"(d[73]), "+f"(d[74]), "+f"(d[75]), "+f"(d[76]), "+f"(d[77]), "+f"(d[78]), "+f"(d[79])
    : "r"(a[0]), "r"(a[1]), "r"(a[2]), "r"(a[3]), "l"(b), "r"(sc));
}
__device__ __forceinline__ void wg_ss_n112_ta0_tb1(float* d, uint64_t a, uint64_t b, int sc) {
  asm volatile("{\n.reg .pred p;\nsetp.ne.b32 p, %58, 0;\nwgmma.mma_async.sync.aligned.m64n112k16.f32.bf16.bf16 {%0, %1, %2, %3, %4, %5, %6, %7, %8, %9, %10, %11, %12, %13, %14, %15, %16, %17, %18, %19, %20, %21, %22, %23, %24, %25, %26, %27, %28, %29, %30, %31, %32, %33, %34, %35, %36, %37, %38, %39, %40, %41, %42, %43, %44, %45, %46, %47, %48, %49, %50, %51, %52, %53, %54, %55}, %56, %57, p, 1, 1, 0, 1;\n}\n"
    : "+f"(d[0]), "+f"(d[1]), "+f"(d[2]), "+f"(d[3]), "+f"(d[4]), "+f"(d[5]), "+f"(d[6]), "+f"(d[7]), "+f"(d[8]), "+f"(d[9]), "+f"(d[10]), "+f"(d[11]), "+f"(d[12]), "+f"(d[13]), "+f"(d[14]), "+f"(d[15]), "+f"(d[16]), "+f"(d[17]), "+f"(d[18]), "+f"(d[19]), "+f"(d[20]), "+f"(d[21]), "+f"(d[22]), "+f"(d[23]), "+f"(d[24]), "+f"(d[25]), "+f"(d[26]), "+f"(d[27]), "+f"(d[28]), "+f"(d[29]), "+f"(d[30]), "+f"(d[31]), "+f"(d[32]), "+f"(d[33]), "+f"(d[34]), "+f"(d[35]), "+f"(d[36]), "+f"(d[37]), "+f"(d[38]), "+f"(d[39]), "+f"(d[40]), "+f"(d[41]), "+f"(d[42]), "+f"(d[43]), "+f"(d[44]), "+f"(d[45]), "+f"(d[46]), "+f"(d[47]), "+f"(d[48]), "+f"(d[49]), "+f"(d[50]), "+f"(d[51]), "+f"(d[52]), "+f"(d[53]), "+f"(d[54]), "+f"(d[55])
    : "l"(a), "l"(b), "r"(sc));
}
__device__ __forceinline__ void wg_rs_n32_tb1(float* d, const uint32_t* a, uint64_t b, int sc) {
  asm volatile("{\n.reg .pred p;\nsetp.ne.b32 p, %21, 0;\nwgmma.mma_async.sync.aligned.m64n32k16.f32.bf16.bf16 {%0, %1, %2, %3, %4, %5, %6, %7, %8, %9, %10, %11, %12, %13, %14, %15}, {%16, %17, %18, %19}, %20, p, 1, 1, 1;\n}\n"
    : "+f"(d[0]), "+f"(d[1]), "+f"(d[2]), "+f"(d[3]), "+f"(d[4]), "+f"(d[5]), "+f"(d[6]), "+f"(d[7]), "+f"(d[8]), "+f"(d[9]), "+f"(d[10]), "+f"(d[11]), "+f"(d[12]), "+f"(d[13]), "+f"(d[14]), "+f"(d[15])
    : "r"(a[0]), "r"(a[1]), "r"(a[2]), "r"(a[3]), "l"(b), "r"(sc));
}
__device__ __forceinline__ void wg_ss_n32_ta1_tb1(float* d, uint64_t a, uint64_t b, int sc) {
  asm volatile("{\n.reg .pred p;\nsetp.ne.b32 p, %18, 0;\nwgmma.mma_async.sync.aligned.m64n32k16.f32.bf16.bf16 {%0, %1, %2, %3, %4, %5, %6, %7, %8, %9, %10, %11, %12, %13, %14, %15}, %16, %17, p, 1, 1, 1, 1;\n}\n"
    : "+f"(d[0]), "+f"(d[1]), "+f"(d[2]), "+f"(d[3]), "+f"(d[4]), "+f"(d[5]), "+f"(d[6]), "+f"(d[7]), "+f"(d[8]), "+f"(d[9]), "+f"(d[10]), "+f"(d[11]), "+f"(d[12]), "+f"(d[13]), "+f"(d[14]), "+f"(d[15])
    : "l"(a), "l"(b), "r"(sc));
}
__device__ __forceinline__ void wg_rs_n32_tb0(float* d, const uint32_t* a, uint64_t b, int sc) {
  asm volatile("{\n.reg .pred p;\nsetp.ne.b32 p, %21, 0;\nwgmma.mma_async.sync.aligned.m64n32k16.f32.bf16.bf16 {%0, %1, %2, %3, %4, %5, %6, %7, %8, %9, %10, %11, %12, %13, %14, %15}, {%16, %17, %18, %19}, %20, p, 1, 1, 0;\n}\n"
    : "+f"(d[0]), "+f"(d[1]), "+f"(d[2]), "+f"(d[3]), "+f"(d[4]), "+f"(d[5]), "+f"(d[6]), "+f"(d[7]), "+f"(d[8]), "+f"(d[9]), "+f"(d[10]), "+f"(d[11]), "+f"(d[12]), "+f"(d[13]), "+f"(d[14]), "+f"(d[15])
    : "r"(a[0]), "r"(a[1]), "r"(a[2]), "r"(a[3]), "l"(b), "r"(sc));
}
__device__ __forceinline__ void wg_rs_n40_tb0(float* d, const uint32_t* a, uint64_t b, int sc) {
  asm volatile("{\n.reg .pred p;\nsetp.ne.b32 p, %25, 0;\nwgmma.mma_async.sync.aligned.m64n40k16.f32.bf16.bf16 {%0, %1, %2, %3, %4, %5, %6, %7, %8, %9, %10, %11, %12, %13, %14, %15, %16, %17, %18, %19}, {%20, %21, %22, %23}, %24, p, 1, 1, 0;\n}\n"
    : "+f"(d[0]), "+f"(d[1]), "+f"(d[2]), "+f"(d[3]), "+f"(d[4]), "+f"(d[5]), "+f"(d[6]), "+f"(d[7]), "+f"(d[8]), "+f"(d[9]), "+f"(d[10]), "+f"(d[11]), "+f"(d[12]), "+f"(d[13]), "+f"(d[14]), "+f"(d[15]), "+f"(d[16]), "+f"(d[17]), "+f"(d[18]), "+f"(d[19])
    : "r"(a[0]), "r"(a[1]), "r"(a[2]), "r"(a[3]), "l"(b), "r"(sc));
}
__device__ __forceinline__ void wg_rs_n8_tb1(float* d, const uint32_t* a, uint64_t b, int sc) {
  asm volatile("{\n.reg .pred p;\nsetp.ne.b32 p, %9, 0;\nwgmma.mma_async.sync.aligned.m64n8k16.f32.bf16.bf16 {%0, %1, %2, %3}, {%4, %5, %6, %7}, %8, p, 1, 1, 1;\n}\n"
    : "+f"(d[0]), "+f"(d[1]), "+f"(d[2]), "+f"(d[3])
    : "r"(a[0]), "r"(a[1]), "r"(a[2]), "r"(a[3]), "l"(b), "r"(sc));
}
__device__ __forceinline__ void wg_ss_n40_ta0_tb0(float* d, uint64_t a, uint64_t b, int sc) {
  asm volatile("{\n.reg .pred p;\nsetp.ne.b32 p, %22, 0;\nwgmma.mma_async.sync.aligned.m64n40k16.f32.bf16.bf16 {%0, %1, %2, %3, %4, %5, %6, %7, %8, %9, %10, %11, %12, %13, %14, %15, %16, %17, %18, %19}, %20, %21, p, 1, 1, 0, 0;\n}\n"
    : "+f"(d[0]), "+f"(d[1]), "+f"(d[2]), "+f"(d[3]), "+f"(d[4]), "+f"(d[5]), "+f"(d[6]), "+f"(d[7]), "+f"(d[8]), "+f"(d[9]), "+f"(d[10]), "+f"(d[11]), "+f"(d[12]), "+f"(d[13]), "+f"(d[14]), "+f"(d[15]), "+f"(d[16]), "+f"(d[17]), "+f"(d[18]), "+f"(d[19])
    : "l"(a), "l"(b), "r"(sc));
}
__device__ __forceinline__ void wg_ss_n40_ta1_tb0(float* d, uint64_t a, uint64_t b, int sc) {
  asm volatile("{\n.reg .pred p;\nsetp.ne.b32 p, %22, 0;\nwgmma.mma_async.sync.aligned.m64n40k16.f32.bf16.bf16 {%0, %1, %2, %3, %4, %5, %6, %7, %8, %9, %10, %11, %12, %13, %14, %15, %16, %17, %18, %19}, %20, %21, p, 1, 1, 1, 0;\n}\n"
    : "+f"(d[0]), "+f"(d[1]), "+f"(d[2]), "+f"(d[3]), "+f"(d[4]), "+f"(d[5]), "+f"(d[6]), "+f"(d[7]), "+f"(d[8]), "+f"(d[9]), "+f"(d[10]), "+f"(d[11]), "+f"(d[12]), "+f"(d[13]), "+f"(d[14]), "+f"(d[15]), "+f"(d[16]), "+f"(d[17]), "+f"(d[18]), "+f"(d[19])
    : "l"(a), "l"(b), "r"(sc));
}
__device__ __forceinline__ void wg_ss_n8_ta1_tb1(float* d, uint64_t a, uint64_t b, int sc) {
  asm volatile("{\n.reg .pred p;\nsetp.ne.b32 p, %6, 0;\nwgmma.mma_async.sync.aligned.m64n8k16.f32.bf16.bf16 {%0, %1, %2, %3}, %4, %5, p, 1, 1, 1, 1;\n}\n"
    : "+f"(d[0]), "+f"(d[1]), "+f"(d[2]), "+f"(d[3])
    : "l"(a), "l"(b), "r"(sc));
}

constexpr int O_WV = 0, O_WO = 81920, O_H = 163840, O_QK = 215040, O_SM = 228352, O_MISC = 229632;
constexpr int O_QM = O_QK + 1024, O_K = O_QK + 3072, O_OG = O_QK + 8192;
constexpr int SM_SLOT = 640;
constexpr int O_MAXS = O_MISC;
constexpr int O_BAR = O_MISC + 64;
constexpr int MB_XF = 0, MB_ML = 2, MB_MR = 4, MB_PF = 6, MB_SM = 7, MB_SX = 8, MB_OG = 9, MB_W = 10, MB_WC = 30;
constexpr int O_PROF = O_BAR + 8 * 40;
constexpr int REC_SMEM = O_PROF + 128;
constexpr int B_VOWN = 0, B_QK = 1, B_VGO = 2, B_ML0 = 3, B_PM = 4, B_PX = 5, B_XGO = 6, B_ML1 = 7, B_WG2 = 8, B_VHALF = 9, B_VDONE = 10,
              B_MR = 11, B_SSENT = 12, B_SLD = 13, B_VEND = 14, B_XGO1 = 15;
#define POLL_A 400
#define POLL_B 500
#define POLL_C 600
#define OX_T 0
#define POLL_D0 300
#define TS0(idx) do {} while (0)
#define TS(idx) do {} while (0)
#define SLD_POS 0
#define W_OPEN 16
#define W_WIN 3
#define TRIG_LATE 1
#define XP_END 40
#define F_ORD 0
#define VEND_POS 2
#define SPEC_DEC 0
#define T9_POS 2
#define PARV 0
#define NB_MEM 6
#define PF_MODE 0
#define PF_FENCE 0
#define LATE_NORM 1
#define F_FEN 1
#define O_B1 5
#define O_C1 16
#define O_MODE 0
#define AR_MAP 1
#define EXP 0
#define FILL_B 4096
#define MP_D 3
#define MP_CH 4
#define MP_F 0
#define ML_N0 1
#define MR_N0 3
#define O_RSM 0x2AA0
#define O_RS __builtin_popcount(O_RSM)
#define O_IDX(j) __builtin_popcount(O_RSM & ((1 << (j)) - 1))
#define O_RS_POS 0
#define V_N1 2
#define V_N2 0
#define V_N3 4
#define V_OWN 6
#define V_S1 9
#define V_K1 (V_OWN + V_RS + V_S1)
#define V_K2 ((V_K1 > 20 ? V_K1 : 20) + V_S2)
#define V_S2 3
constexpr int V_RS = V_N1 + V_N2 + V_N3;
constexpr float SCL = 0.07216878364870322f;
constexpr float L2E = 1.4426950408889634f;
__device__ __forceinline__ constexpr int vord(int i) { return i < 4 ? 36 + i : i - 4; }
__device__ __forceinline__ constexpr uint32_t hoff(int k) { return ((k >> 2) * 5120 + (k & 3) * 32) >> 4; }

__device__ __forceinline__ constexpr int ar_chunk(int T) { return AR_MAP == 0 ? (T >> 2) * 8 + (T & 3) : T == 9 ? 19 : (T % 3) * 8 + T / 3; }
__device__ __forceinline__ void fix_red(uint8_t* p, const float* a, float2 sc) {
  int v0 = __float2int_rn(a[0] * sc.x), v1 = __float2int_rn(a[1] * sc.y), v2 = __float2int_rn(a[2] * sc.x), v3 = __float2int_rn(a[3] * sc.y);
  red64(p, ((uint32_t)v0 << 7) | 1u, ((uint32_t)v2 << 3) + (uint32_t)(v0 >> 25));
  red64(p + 1024, ((uint32_t)v1 << 7) | 1u, ((uint32_t)v3 << 3) + (uint32_t)(v1 >> 25));
}
__device__ __forceinline__ float max10(const float* t) {
  float m = fmaxf(fmaxf(fmaxf(t[0], t[1]), fmaxf(t[2], t[3])), fmaxf(fmaxf(t[4], t[5]), fmaxf(t[6], t[7])));
  m = fmaxf(m, fmaxf(t[8], t[9]));
  m = fmaxf(m, __shfl_xor_sync(~0u, m, 1));
  return fmaxf(m, __shfl_xor_sync(~0u, m, 2));
}
#define ACC2(k, p, u, v) { t[k] = bflo(p) + bflo(u) + bflo(v); t[k + 1] = bfhi(p) + bfhi(u) + bfhi(v); }

#define LBT 0
#define NLB 5
constexpr int LB_STAGE = 36864, LB_ST = 6 * LB_STAGE;
__device__ __forceinline__ void lb_role(const uint32_t sb, const CUtensorMap* tmx, uint32_t* __restrict__ flags, int layer) {
  const int tid = threadIdx.x, wid = __shfl_sync(~0u, tid >> 5, 0), wg = wid >> 2, w = wid & 3, lane = tid & 31, g = lane >> 2, i4 = lane & 3;
  const int cl = blockIdx.x / 3, rank = blockIdx.x - cl * 3;
  const uint32_t bar = sb + O_BAR;
  asm volatile("griddepcontrol.launch_dependents;");
  if (wid == 8) {
    if (lane < 14) mbar_init(bar + 8 * lane, lane >= 6 && lane < 12 ? 8 : 1);
    asm volatile("fence.mbarrier_init.release.cluster;" ::: "memory");
    fence_async();
  }
  __syncthreads();
  asm volatile("barrier.cluster.arrive.relaxed.aligned;" ::: "memory");
  if (wid == 8) {
    int st = 0; uint32_t ph = 1;
    const uint8_t* wsrc = g_w2 + rank * 286720;
    if (lane < 6) { mbar_expect(bar + 8 * lane, LB_STAGE); bulk_g2s(sb + lane * LB_STAGE + 8192, wsrc + lane * 28672, 28672, bar + 8 * lane); }
    if (layer == 1) wait_flag(flags + FL_T + (lane & 15) * 8, 8);
#pragma unroll 1
    for (int tile = cl; tile < 32; tile += NLB) {
      wait_flag(flags + FL_O + (tile >> 1) * 8, 8);
      if (tile == cl + LBT * NLB && lane == 0) GTT(layer * 4 + 1, 11);
      fence_async_global();
#pragma unroll 1
      for (int kc = 0; kc < 10; kc++) {
        const bool pre = tile == cl && kc < 6;
        mbar_wait(bar + 8 * (6 + st), ph);
        if (lane == 0) {
          if (!pre) { mbar_expect(bar + 8 * st, LB_STAGE); bulk_g2s(sb + st * LB_STAGE + 8192, wsrc + kc * 28672, 28672, bar + 8 * st); }
          bulk_g2s(sb + st * LB_STAGE, g_oa + tile * 81920 + kc * 8192, 8192, bar + 8 * st);
        }
        __syncwarp();
        if (++st == 6) { st = 0; ph ^= 1; }
      }
      mbar_wait(bar + 8 * (6 + st), ph);
      if (lane == 0) { mbar_expect(bar + 8 * st, 64 * 464); tma2d(sb + st * LB_STAGE, tmx, rank * 224, tile * 64, bar + 8 * st); }
      __syncwarp();
      if (++st == 6) { st = 0; ph ^= 1; }
    }
    asm volatile("barrier.cluster.wait.aligned;" ::: "memory");
  } else if (wg < 2) {
    asm volatile("barrier.cluster.wait.aligned;" ::: "memory");
    const int u = 2 * rank + wg, nb = u == 5 ? 5 : 7;
    int st = 0; uint32_t ph = 0, it = 0;
#pragma unroll 1
    for (int tile = cl; tile < 32; tile += NLB, it++) {
      const int row0 = tile * 64 + 16 * w + g;
      float d[56];
      if (tid == 0) mbar_expect(bar + 8 * (12 + (it & 1)), 3072);
#pragma unroll 1
      for (int kc = 0; kc < 10; kc++) {
        const uint64_t da = mkdesc(SB0 + st * LB_STAGE, 1024, 128, 0), db = mkdesc(SB0 + st * LB_STAGE + 8192 + wg * 1792, 3584, 128, 0);
        mbar_wait(bar + 8 * st, ph);
        if (it == LBT && kc == 0) GT(layer * 4 + 1, 12);
        wg_fence();
#pragma unroll
        for (int k = 0; k < 4; k++) wg_ss_n112_ta0_tb1(d, da + k * 128, db + k * 448, kc | k);
        wg_commit();
        wg_wait<1>();
        if (kc > 0 && lane == 0) mbar_arrive(bar + 8 * (6 + (st == 0 ? 5 : st - 1)));
        if (++st == 6) { st = 0; ph ^= 1; }
      }
      wg_wait<0>();
      pin<56>(d);
      if (it == LBT) GT(layer * 4 + 1, 13);
      if (lane == 0) mbar_arrive(bar + 8 * (6 + (st == 0 ? 5 : st - 1)));
      mbar_wait(bar + 8 * st, ph);
      {
        const uint32_t x0 = sb + st * LB_STAGE + (16 * w + g) * 464 + wg * 224 + (layer ? 8 : 4) * i4, x1 = x0 + (layer ? 4 : 16);
#pragma unroll
        for (int j = 0; j < 28; j++) {
          const uint32_t v = lds1(((j & 2) ? x1 : x0) + (j >> 2) * 32 + (j & 1) * 3712);
          d[2 * j] += bflo(v); d[2 * j + 1] += bfhi(v);
        }
      }
      fence_async();
      __syncwarp();
      if (lane == 0) mbar_arrive(bar + 8 * (6 + st));
      if (++st == 6) { st = 0; ph ^= 1; }
      const float cnt = nb * 16.f;
      const uint32_t so = LB_ST + (it & 1) * 3072 + (16 * w + g) * 48;
#pragma unroll
      for (int h = 0; h < 2; h++) {
        float sum = 0.f;
#pragma unroll
        for (int j = 0; j < 14; j++) sum += d[4 * j + 2 * h] + d[4 * j + 2 * h + 1];
        sum += __shfl_xor_sync(~0u, sum, 1); sum += __shfl_xor_sync(~0u, sum, 2);
        const float mean = sum * rcp(cnt);
        float q = 0.f, q2 = 0.f;
#pragma unroll
        for (int j = 0; j < 14; j++) {
          const float a = d[4 * j + 2 * h] - mean, b = d[4 * j + 2 * h + 1] - mean;
          if (j < 10) q = fmaf(a, a, fmaf(b, b, q)); else q2 = fmaf(a, a, fmaf(b, b, q2));
        }
        if (nb == 7) q += q2;
        q += __shfl_xor_sync(~0u, q, 1); q += __shfl_xor_sync(~0u, q, 2);
        if (i4 < 3) { const uint32_t b = mapa(sb, i4); sta2f(b + so + h * 384 + u * 8, sum, q, b + O_BAR + 8 * (12 + (it & 1))); }
      }
      mbar_wait(bar + 8 * (12 + (it & 1)), (it >> 1) & 1);
      if (it == LBT) GT(layer * 4 + 1, 14);
#pragma unroll
      for (int h = 0; h < 2; h++) {
        const float4 x = lds4f(sb + so + h * 384), y = lds4f(sb + so + h * 384 + 16), z = lds4f(sb + so + h * 384 + 32);
        const float mu = (((x.x + x.z) + (y.x + y.z)) + (z.x + z.z)) * (1.f / DM);
        const float e0 = x.x * (1.f / 112.f) - mu, e1 = x.z * (1.f / 112.f) - mu, e2 = y.x * (1.f / 112.f) - mu, e3 = y.z * (1.f / 112.f) - mu;
        const float e4 = z.x * (1.f / 112.f) - mu, e5 = z.z * (1.f / 80.f) - mu;
        const float q = (((x.y + x.w) + (y.y + y.w)) + (z.y + z.w)) + 112.f * ((e0 * e0 + e1 * e1) + (e2 * e2 + e3 * e3) + e4 * e4) + 80.f * e5 * e5;
        const float rs = rsqrtf(q * (1.f / DM) + 1e-5f), sh = -mu * rs;
        const int tk = row0 + 8 * h;
        uint8_t* xp = g_xn + (tk >> 5) * 40960 + (tk & 31) * 128 + (i4 & 1) * 8;
#pragma unroll
        for (int j = 0; j < 7; j++) {
          if (j < nb) {
            const int b16 = u * 7 + j;
            const float* a = d + 8 * j + 2 * h;
            *(uint2*)(xp + (b16 >> 2) * 4096 + (((2 * (b16 & 3) + (i4 >> 1)) ^ g) << 4)) =
                make_uint2(pack2(fmaf(a[0], rs, sh), fmaf(a[1], rs, sh)), pack2(fmaf(a[4], rs, sh), fmaf(a[5], rs, sh)));
          }
        }
      }
      if (it == LBT) GT(layer * 4 + 1, 15);
      bar_arrive<1, 288>();
      bar_sync<2, 288>();
#pragma unroll
      for (int j = 0; j < 14; j++) {
        const float* a = d + 8 * (j >> 1) + 2 * (j & 1);
        if ((j >> 1) < nb) *(uint2*)(g_x + (row0 + 8 * (j & 1)) * DM + u * 112 + 4 * i4 + 16 * (j >> 1)) = make_uint2(pack2(a[0], a[1]), pack2(a[4], a[5]));
      }
      bar_arrive<3, 288>();
    }
  } else {
    asm volatile("barrier.cluster.wait.aligned;" ::: "memory");
    if (wid == 9) {
#pragma unroll 1
      for (int tile = cl; tile < 32; tile += NLB) {
        bar_sync<1, 288>();
        if (tile != cl) bar_arrive<2, 288>();
        if (lane == 0) { red_release(flags + FL_XN + tile * 8, 1); if (tile == cl + LBT * NLB) GTT(layer * 4 + 1, 9); }
        __syncwarp();
        if (tile == cl) bar_arrive<2, 288>();
        bar_sync<3, 288>();
        if (lane == 0) red_release(flags + FL_XN + tile * 8 + 1, 1);
        __syncwarp();
      }
    }
  }
  asm volatile("barrier.cluster.arrive.relaxed.aligned;\nbarrier.cluster.wait.aligned;" ::: "memory");
  GT(layer * 4 + 1, 10);
}

__global__ void __launch_bounds__(384, 1)
rec_kernel(const __grid_constant__ CUtensorMap tmq, const __grid_constant__ CUtensorMap tmk,
           const __grid_constant__ CUtensorMap tmv, const __grid_constant__ CUtensorMap tmo,
           const __grid_constant__ CUtensorMap tmx, const bf16* __restrict__ mem0, uint8_t* __restrict__ ar, uint32_t* __restrict__ flags, int layer) {
  extern __shared__ __align__(1024) uint8_t smem[];
  const uint32_t sb = smem_u32(smem);
  check_smem_base(sb);
  GT(layer * 4 + 1, 0);
  if (blockIdx.x < 3 * NLB) { lb_role(sb, &tmx, flags, layer); return; }
  const int bid = blockIdx.x - 3 * NLB;
  const int tid = threadIdx.x, wid = __shfl_sync(~0u, tid >> 5, 0), wg = wid >> 2, w = wid & 3;
  const int lane = __shfl_sync(~0u, tid & 31, tid & 31);
  const int head = bid / 3, rank = bid - head * 3;
  const int e0 = bid * 64;
  const uint32_t bar = sb + O_BAR;
  const uint32_t sb1 = mapa(sb, rank == 2 ? 0 : rank + 1), sb2 = mapa(sb, rank == 0 ? 2 : rank - 1);
  auto chunk_of = [&](int p) { const int c = 3 * rank + p; return p == 9 ? 9 : c >= 9 ? c - 9 : c; };

  auto load_piece = [&](int i) {
    if (lane == 0) mbar_expect(bar + 8 * (MB_W + i), 16384);
    __syncwarp();
    if (lane < 2) {
      if (i < 15) {
        const int m = i < 10 ? i & 1 : 0, p = (i < 10 ? i >> 1 : i - 10) * 2 + lane;
        tma5d(sb + m * 81920 + p * 8192, i >= 10 ? &tmv : m ? &tmk : &tmq, e0, chunk_of(p) * 4, bar + 8 * (MB_W + i));
      } else {
        const int p = (i - 15) * 2 + lane, k = p / 3, j = rank + p - 3 * k;
        tma2d(sb + O_WO + p * 8192, &tmo, p == 9 ? 576 : (rank * 3 + k) * 64, head * DH + (j >= 3 ? j - 3 : j) * 64, bar + 8 * (MB_W + i));
      }
    }
  };
  if (wid == 9) {
    mbar_init(bar + 8 * lane, lane == MB_ML ? ML_N0 : lane == MB_ML + 1 && ML_N0 < 4 ? 4 - ML_N0 : (lane >= MB_WC || lane == MB_PF) ? 4 : 1);
    if (lane < 8) mbar_init(bar + 8 * (32 + lane), 4);
    asm volatile("fence.mbarrier_init.release.cluster;" ::: "memory");
    fence_async();
    __syncwarp();
#pragma unroll 1
    for (int i = 0; i < W_WIN; i++) load_piece(i);
  }
  __syncthreads();
  asm volatile("barrier.cluster.arrive.relaxed.aligned;" ::: "memory");

  if (wg < 2) {
    asm volatile("setmaxnreg.inc.sync.aligned.u32 208;");
    uint32_t a[40][4];
    const uint32_t swz = (lane & 7) * 128 + (((2 * w + ((lane >> 3) & 1)) ^ (lane & 7)) << 4);
    const uint32_t st_x = __shfl_sync(~0u, sb + O_QK + wg * 5120 + (lane >> 4) * 2048 + swz, lane);
    {
      const uint32_t la = sb + wg * 81920 + (lane >> 4) * 1024 + swz;
#pragma unroll
      for (int p = 0; p < 5; p++) {
        mbar_wait(bar + 8 * (MB_W + 2 * p + wg), 0);
#pragma unroll
        for (int k = 0; k < 8; k++) ldsm4t(a[p * 8 + k], la + (p * 8 + k) * 2048);
        fence_async();
        __syncwarp();
        mbar_arrive_elect(bar + 8 * (MB_WC + wg * 5 + p));
      }
    }
    GT(layer * 4 + 1, 5);
    asm volatile("barrier.cluster.wait.aligned;" ::: "memory");
    const uint32_t ld_m = __shfl_sync(~0u, sb + O_H + (lane & 7) * 128 + (((lane >> 3) ^ (lane & 7)) << 4), lane);

    for (int s = 0; s < NSEG; s++) {
      const uint32_t par = PARV ? ((s ^ (lane >> 5)) & 1) : (s & 1);
      if (wid == 4) TS0(0);
      if (wid == 0) TS(30);
      {
        float ax[16];
        constexpr uint64_t db = mkdesc(SB0 + O_H + 1024, 16, 1024, 1);
        mbar_waitf(bar + 8 * MB_XF, par);
        wg_fence();
#pragma unroll
        for (int k = 0; k < 20; k++) wg_rs_n32_tb0(ax, a[vord(k)], db + hoff(vord(k)), k);
        mbar_waitf(bar + 8 * (MB_XF + 1), par);
        if (PF_MODE == 2) mbar_waitf(bar + 8 * MB_PF, par ^ 1);
        wg_fence();
#pragma unroll
        for (int k = 20; k < XP_END; k++) wg_rs_n32_tb0(ax, a[vord(k)], db + hoff(vord(k)), 1);
        wg_commit();
        if (PF_MODE == 0) mbar_waitf(bar + 8 * MB_PF, par ^ 1);
        if (PF_MODE == 1 && s > 0) bar_sync<B_ML0, 384>();
        if (wid == 6 && lane == 0) { mbar_expect(bar + 8 * MB_SM, 2 * SM_SLOT + 48 + 48); mbar_expect(bar + 8 * MB_SX, 2 * 2176); }
        wg_wait<0>();
        pin<16>(ax);
        if (w == 0) TS(1 + 22 * wg);
        stsm4t(st_x, pack2(ax[0], ax[1]), pack2(ax[2], ax[3]), pack2(ax[4], ax[5]), pack2(ax[6], ax[7]));
        stsm4t(st_x + 4096, pack2(ax[8], ax[9]), pack2(ax[10], ax[11]), pack2(ax[12], ax[13]), pack2(ax[14], ax[15]));
        if (V_OWN > 0) bar_arrive<B_VOWN, 384>();
      }
      {
        float c[MP_CH][4];
#pragma unroll
        for (int k = 0; k < MP_CH; k++) c[k][0] = c[k][1] = c[k][2] = c[k][3] = 0.f;
        uint32_t b[MP_D][2][4];
        const uint32_t ld_m2 = opaque(ld_m ^ 64);
        SCHED_FENCE();
#define MORD(j) ((j) == 0 ? 9 : (j) < 4 ? (j) - 1 : 3 + ((j) - 4) / 2 + 3 * ((j) & 1))
#pragma unroll
        for (int j = 0; j < 10 + MP_D - 1; j++) {
          if (j < 10) {
            if (j == 0) { if (NB_MEM & 1) bar_sync<B_ML0, 256 + 32 * ML_N0>(); else mbar_waitf(bar + 8 * MB_ML, par); if (wid == 0) TS(2); }
            if (ML_N0 < 4 && j == ML_N0) { if (NB_MEM & 2) bar_sync<B_ML1, 256 + 32 * (4 - ML_N0)>(); else mbar_waitf(bar + 8 * (MB_ML + 1), par); if (wid == 0) TS(3); }
            if (j == 4) { if (NB_MEM & 4) bar_sync<B_MR, 288>(); else mbar_waitf(bar + 8 * MB_MR, par); if (wid == 0) TS(4); }
            if (j == 4 + 2 * MR_N0) { mbar_waitf(bar + 8 * (MB_MR + 1), par); if (wid == 0) TS(5); }
            ldsm4(b[j % MP_D][0], ld_m + MORD(j) * 5120);
            ldsm4(b[j % MP_D][1], ld_m2 + MORD(j) * 5120);
            if ((MP_F >> j) & 1) SCHED_FENCE();
          }
          const int u = j - (MP_D - 1);
          if (u >= 0) {
#pragma unroll
            for (int k = 0; k < 4; k++) mma16816(c[(4 * u + k) % MP_CH], a[4 * MORD(u) + k], b[u % MP_D][k >> 1][(k & 1) * 2], b[u % MP_D][k >> 1][(k & 1) * 2 + 1]);
          }
        }
        SCHED_FENCE();
        bar_arrive<B_VGO, 384>();
        SCHED_FENCE();
#pragma unroll
        for (int k = 0; k < 4; k++) c[0][k] = MP_CH == 4 ? (c[0][k] + c[1][k]) + (c[2][k] + c[MP_CH - 1][k]) : (c[1][k] + c[2][k]) + c[0][k];
        stsm2t(st_x + 1024 - wg * 3072, pack2(c[0][0], c[0][1]), pack2(c[0][2], c[0][3]));
        fence_async();
      }
      if (wg == 0) {
        bar_sync<B_QK, 256>();
        float sv[20];
        {
          constexpr uint64_t da = mkdesc(SB0 + O_QK, 16, 1024, 1), db = mkdesc(SB0 + O_K, 16, 2048, 1);
          wg_fence();
#pragma unroll
          for (int k = 0; k < 4; k++) wg_ss_n40_ta0_tb0(sv, da + 2 * k, db + 2 * k, k);
          wg_commit();
        }
        if (w == 0) TS(6);
        SCHED_FENCE();
        const uint32_t ln = opaque(lane);
        uint32_t m0, m1, m2, m3, m4;
        {
          const uint32_t a1 = opaque(sb1 + O_SM + SM_SLOT + ln * 16), a2 = opaque(sb2 + O_SM + ln * 16);
          const uint32_t a3 = opaque(sb1 + O_SM + SM_SLOT + 512 + ln * 4), a4 = opaque(sb2 + O_SM + 512 + ln * 4);
          const uint32_t b1 = opaque(sb1 + O_BAR + 8 * MB_SM), b2 = opaque(sb2 + O_BAR + 8 * MB_SM);
          const uint32_t bt = opaque(mapa(sb, min(ln, 2u)) + O_BAR + 8 * MB_SM), at = opaque(bt + (O_MAXS + 48 - O_BAR - 8 * MB_SM));
          SCHED_FENCE();
          wg_wait<0>();
          pin<20>(sv);
          m0 = pack2(sv[2], sv[3]); m1 = pack2(sv[6], sv[7]); m2 = pack2(sv[10], sv[11]); m3 = pack2(sv[14], sv[15]); m4 = pack2(sv[18], sv[19]);
          if (w == 0) {
            sta4(a1, m0, m1, m2, m3, b1);
            sta4(a2, m0, m1, m2, m3, b2);
            sta1(a3, m4, b1);
            sta1(a4, m4, b2);
          }
          sta1p(at, 0u, bt, ln < 3);
          bar_arrive<B_SSENT, 256>();
          SCHED_FENCE();
        }
        const uint32_t p0 = pack2(sv[0], sv[1]), p1 = pack2(sv[4], sv[5]), p2 = pack2(sv[8], sv[9]), p3 = pack2(sv[12], sv[13]), p4 = pack2(sv[16], sv[17]);
        const uint32_t ox = O_K + w * 2048 + ln * 16, ox2 = O_K + 8192 + ln * 4;
        {
          const uint32_t a1 = opaque(sb1 + ox + 512), a2 = opaque(sb2 + ox), b1 = opaque(sb1 + O_BAR + 8 * MB_SX), b2 = opaque(sb2 + O_BAR + 8 * MB_SX);
          if (w == 0) {
            TS(7);
            const uint32_t om = opaque(sb + O_SM + ln * 16), om2 = opaque(sb + O_SM + 512 + ln * 4);
            const uint32_t pa0 = ld_m + (O_QM - O_H), pa1 = (ld_m ^ 64) + (O_QM - O_H);
            float t[10] = {bflo(m0), bfhi(m0), bflo(m1), bfhi(m1), bflo(m2), bfhi(m2), bflo(m3), bfhi(m3), bflo(m4), bfhi(m4)};
            pin<10>(t);
            SCHED_FENCE();
            mbar_waitf(bar + 8 * MB_SM, par);
            const uint4 u = lds4(om), v = lds4(om + SM_SLOT);
            const uint32_t u4 = lds1(om2), v4 = lds1(om2 + SM_SLOT);
            sta4(a1, p0, p1, p2, p3, b1);
            sta4(a2, p0, p1, p2, p3, b2);
            if (SLD_POS == 0) bar_arrive<B_SLD, 256>();
            SCHED_FENCE();
#define ACC3(k, u, v) { t[k] += bflo(u) + bflo(v); t[k + 1] += bfhi(u) + bfhi(v); }
            ACC3(0, u.x, v.x) ACC3(2, u.y, v.y) ACC3(4, u.z, v.z) ACC3(6, u.w, v.w) ACC3(8, u4, v4)
            TS(8);
            const float mm = max10(t) * (SCL * L2E);
            if (SLD_POS == 1) { SCHED_FENCE(); bar_arrive<B_SLD, 256>(); SCHED_FENCE(); }
#pragma unroll
            for (int k = 0; k < 10; k++) t[k] = ex2(fmaf(t[k], SCL * L2E, -mm));
            stsm4(pa0, pack2(t[0], t[1]), pack2(t[2], t[3]), pack2(t[4], t[5]), pack2(t[6], t[7]));
            stsm1(pa1, pack2(t[8], t[9]));
            bar_arrive<B_PM, 160>();
            TS(9);
          } else {
            const uint32_t a3 = opaque(sb1 + ox2 + 128), a4 = opaque(sb2 + ox2);
            SCHED_FENCE();
            mbar_waitf(bar + 8 * MB_SM, par);
            sta4(a1, p0, p1, p2, p3, b1);
            sta4(a2, p0, p1, p2, p3, b2);
            if (w == 3) { sta1(a3, p4, b1); sta1(a4, p4, b2); }
            bar_arrive<B_SLD, 256>();
          }
        }
        mbar_waitf(bar + 8 * MB_SX, par);
        bar_sync<B_VEND, 256>();
        {
          float t[10];
          const uint4 u = lds4(sb + ox), v = lds4(sb + ox + 512);
          const uint32_t u4 = lds1(sb + ox2), v4 = lds1(sb + ox2 + 128);
          SCHED_FENCE();
          ACC2(0, p0, u.x, v.x) ACC2(2, p1, u.y, v.y) ACC2(4, p2, u.z, v.z) ACC2(6, p3, u.w, v.w) ACC2(8, p4, u4, v4)
          const int dq = 8 * w + (ln >> 2) - 2 * (ln & 3);
#pragma unroll
          for (int k = 1; k < 5; k++) {
            if (8 * (k - 1) > dq) t[2 * k] = -1e9f / SCL;
            if (8 * (k - 1) + 1 > dq) t[2 * k + 1] = -1e9f / SCL;
          }
          const float mm = max10(t) * (SCL * L2E);
#pragma unroll
          for (int k = 0; k < 10; k++) t[k] = ex2(fmaf(t[k], SCL * L2E, -mm));
          float sum = ((t[0] + t[1]) + (t[2] + t[3])) + ((t[4] + t[5]) + (t[6] + t[7])) + (t[8] + t[9]);
          sum += __shfl_xor_sync(~0u, sum, 1);
          sum += __shfl_xor_sync(~0u, sum, 2);
          const float inv = rcp(sum);
          const int rr = 2 * w + (ln & 1);
          const uint32_t pa = sb + O_QK + ((ln >> 1) & 3) * 2048 + rr * 128;
          stsm4(pa + (((ln >> 3) ^ rr) << 4), pack2(t[0] * inv, t[1] * inv), pack2(t[2] * inv, t[3] * inv), pack2(t[4] * inv, t[5] * inv), pack2(t[6] * inv, t[7] * inv));
          stsm2(pa + (((4 + ((ln >> 3) & 1)) ^ rr) << 4), pack2(t[8] * inv, t[9] * inv), 0u);
          fence_async();
        }
        bar_arrive<B_PX, 256>();
        if (w == 0) TS(10);
        bar_sync<B_XGO, 256>();
      } else {
        bar_arrive<B_QK, 256>();
        const int ln = opaque(lane);
        if (w == 2) {
          bar_sync<B_VHALF, 192>();
          if (ln == 0 && s > 0) { red_release(flags + FL_A + (e0 >> 10) * 8 + (s - 1) * 48, 1); }
          __syncwarp();
        }
        if (w == 3) {
          const int l = bid * 2 + ln, s2 = s + 2;
          if (ln < 2 && l < 160 && s2 < NSEG - 1) {
            const int tile = l >> 4;
            const uint8_t* p = ar + (s2 >> 2) * AR_GROUP + (s2 & 1) * 128 + ((s2 >> 1) & 1) * 512 + ar_chunk(tile) * 4096 +
                               ((l >> 3) & 1) * 16384 + (l & 1) * 256 + ((l >> 1) & 3) * 1024;
            asm volatile("prefetch.global.L2 [%0];" :: "l"(p));
          }
        }
        if (w == 0) {
          const bool more = s + 1 < NSEG;
          if (ln < 2 && more) mbar_expect(bar + 8 * (MB_XF + ln), FILL_B * 5);
          const uint8_t* src = g_xn + (s + 1) * 40960 + chunk_of(ln) * 4096;
          if ((s & 1) && more) { wait_flag(flags + FL_XN + ((s + 1) >> 1) * 8, 3); fence_async_global(); }
          bar_sync<B_VHALF, 192>();
          if ((ln < 4 || ln == 9) && more) bulk_g2s(sb + O_H + ln * 5120 + 1024, src, FILL_B, bar + 8 * MB_XF);
          bar_sync<B_VDONE, 160>();
          if (ln >= 4 && ln < 9 && more) bulk_g2s(sb + O_H + ln * 5120 + 1024, src, FILL_B, bar + 8 * (MB_XF + 1));
        }
        bar_sync<B_XGO1, 256>();
      }
    }
  } else {
    asm volatile("setmaxnreg.dec.sync.aligned.u32 88;");
    asm volatile("barrier.cluster.wait.aligned;" ::: "memory");

    const int g = lane >> 2, i4 = lane & 3;
    const int myT = w == 0 ? 9 : rank * 3 + w - 1, myP = w == 0 ? 9 : w - 1;
    const int tok = 2 * ((lane >> 1) & 3) + ((lane >> 3) & 1);
    const uint32_t fw_off = sb + O_H + myP * 5120 + tok * 128 + (((2 * (lane >> 4) + (lane & 1)) ^ tok) << 4);
    const uint32_t prod_off = (w >> 1) * 16384 + (w & 1) * 2048 + ((g >> 1) & 1) * 256 + (i4 * 2 + (g >> 2)) * 16 + (g & 1) * 8;
    const uint32_t cons_off = ar_chunk(myT) * 4096 + (lane >> 3) * 1024 + (lane & 7) * 16;
    auto tile_off = [&](int k) { return AR_MAP == 0 ? ar_chunk(rank * 3 + k) * 4096 : (k * 8 + rank) * 4096; };
    constexpr uint32_t T9_OFF = ar_chunk(9) * 4096;

    uint32_t mx;
    auto forward = [&](const uint32_t* p) {
      const uint32_t c = O_H + myP * 5120, bo = O_BAR + 8 * (MB_MR + (w > MR_N0));
      sts4(fw_off, p[0], p[1], p[2], p[3]);
      sts4(fw_off ^ 64, p[4], p[5], p[6], p[7]);
      fence_async();
      __syncwarp();
      if (w < ML_N0) { if (NB_MEM & 1) bar_arrive<B_ML0, 256 + 32 * ML_N0>(); else mbar_arrive_elect(bar + 8 * MB_ML); }
      else { if (NB_MEM & 2) bar_arrive<B_ML1, 256 + 32 * (4 - ML_N0)>(); else mbar_arrive_elect(bar + 8 * (MB_ML + 1)); }
      if (w > 0) bulk_s2c_elect(sb1 + c + 6 * 5120, sb1 + bo, sb2 + c + 3 * 5120, sb2 + bo, sb + c);
      SCHED_FENCE();
      mx = 0;
#pragma unroll
      for (int k = 0; k < 8; k++) mx = __vmaxu2(mx, p[k] & 0x7FFF7FFFu);
    };
    auto send_max = [&]() {
      mx = max(mx & 0xFFFFu, mx >> 16);
      mx = __reduce_max_sync(~0u, mx);
      { const uint32_t b = mapa(sb, min(lane, 2)); sta1p(b + O_MAXS + (rank * 4 + w) * 4, mx << 16, b + O_BAR + 8 * MB_SM, lane < 3); }
    };
    auto arm = [&]() { if (lane == 0 && w < (MR_N0 < 3 ? 3 : 2)) mbar_expect(bar + 8 * (w == 0 ? MB_OG : MB_MR - 1 + w), w == 0 ? 2048 : w == 1 ? 2048 * MR_N0 : 2048 * (3 - MR_N0)); };
    {
      arm();
      const uint32_t* mp = (const uint32_t*)(mem0 + tok * DM + myT * 64 + 16 * (lane >> 4) + 4 * (lane & 1));
      const uint32_t p[8] = {mp[0], mp[4], mp[1], mp[5], mp[16], mp[20], mp[17], mp[21]};
      forward(p);
    }
    if (w == 1) {
#pragma unroll 1
      for (int i = W_WIN; i < 20; i++) {
        if (i <= W_OPEN) mbar_wait(bar + 8 * (MB_W + i - W_WIN), 0);
        if (i >= 10) mbar_wait(bar + 8 * (MB_WC + i - 10), 0);
        load_piece(i);
      }
    }
    if (w == 0) {
      if (lane < 2) mbar_expect(bar + 8 * (MB_XF + lane), 20480);
      wait_flag(flags + FL_XN, 3);
      fence_async_global();
      if (lane < 10) bulk_g2s(sb + O_H + lane * 5120 + 1024, g_xn + chunk_of(lane) * 4096, 4096, bar + 8 * (MB_XF + (lane >= 4 && lane < 9)));
      if (!TRIG_LATE) asm volatile("griddepcontrol.launch_dependents;");
      if (lane == 0) GTT(layer * 4 + 1, 4);
    }
    if (w == 2) {
      wait_flag(flags + FL_X, 128);
      wait_flag(g_zero + Z_FLAGS + FL_N, 4);
      const float sq = __ldcg((const float*)(g_zero + Z_NORM));
      float mx = 0.f;
#pragma unroll
      for (int k = 0; k < 5; k++) {
        const float4* p = (const float4*)g_nrm + k * 32 + lane;
        const float4 x = __ldcg(p), y = __ldcg(p + 160), z = __ldcg(p + 320), u = __ldcg(p + 480);
        mx = fmaxf(fmaxf(mx, fmaxf((x.x + y.x) + (z.x + u.x), (x.y + y.y) + (z.y + u.y))), fmaxf((x.z + y.z) + (z.z + u.z), (x.w + y.w) + (z.w + u.w)));
      }
#pragma unroll
      for (int o = 16; o; o >>= 1) mx = fmaxf(mx, __shfl_xor_sync(~0u, mx, o));
      sts1(sb + O_MAXS + 52, __float_as_uint(sqrt_approx(sq) * sqrt_approx(mx) * (25.2982213f * 1.1f)));
    }
    bar_sync<B_WG2, 128>();
    const float cbound = __uint_as_float(lds1(sb + O_MAXS + 52));
#pragma unroll 1
    for (int i = 10; i < 15; i++) mbar_wait(bar + 8 * (MB_W + i), 0);
    if (tid == 256) GTT(layer * 4 + 1, 7);

    const uint32_t la_w = sb + O_WV + ((lane >> 4) * 8 + (lane & 7)) * 128 + (((2 * w + ((lane >> 3) & 1)) ^ (lane & 7)) << 4);
    uint32_t af[V_RS][4];
#pragma unroll
    for (int k = 0; k < V_RS; k++) ldsm4t(af[k], la_w + vord(V_OWN + k) * 2048);
    uint32_t vf[10];
    uint4 oq0, oq1;
    uint8_t* op;
    auto pv_x = [&](int s) {
      float ox[16];
      const uint32_t vz[4] = {vf[8], vf[9], 0u, 0u};
      constexpr uint64_t dp = mkdesc(SB0 + O_QK, 16, 2048, 1);
      bar_sync<B_PX, 256>();
      wg_fence();
      wg_rs_n32_tb0(ox, vf, dp, 0);
      wg_rs_n32_tb0(ox, vf + 4, dp + 2, 1);
      wg_rs_n32_tb0(ox, vz, dp + 4, 1);
      wg_commit();
      const uint32_t ln = opaque(lane);
      op = g_ot + (size_t)(s & OT_MASK) * (HE * 64) + (e0 + 16 * w) * 64 + (ln & 3) * 128 + (ln >> 2) * 16;
      wg_wait<0>();
      pin<16>(ox);
      oq0 = make_uint4(pack2(ox[0], ox[1]), pack2(ox[4], ox[5]), pack2(ox[8], ox[9]), pack2(ox[12], ox[13]));
      oq1 = make_uint4(pack2(ox[2], ox[3]), pack2(ox[6], ox[7]), pack2(ox[10], ox[11]), pack2(ox[14], ox[15]));
    };
    for (int s = 0;; s++) {
      const uint32_t par = PARV ? ((s ^ (lane >> 5)) & 1) : (s & 1);
      float sc1, isc, sum0, sum1;
      float2 sc;
      uint32_t ao[O_RS > 0 ? O_RS : 1][4];
      {
        float av[20];
        constexpr uint64_t da = mkdesc(SB0 + O_WV, 1024, 1024, 1), db = mkdesc(SB0 + O_H, 16, 1024, 1);
#define V_RUN_RS(k0, k1) wg_fence(); _Pragma("unroll") for (int k = k0; k < k1; k++) wg_rs_n40_tb0(av, af[k], db + hoff(vord(V_OWN + k)), V_OWN + k);
#define V_RUN_SS(k0, k1) wg_fence(); _Pragma("unroll") for (int k = k0; k < k1; k++) wg_ss_n40_ta1_tb0(av, da + vord(k) * 128, db + hoff(vord(k)), k);
        if (V_OWN > 0) {
          bar_sync<B_VOWN, 384>();
          V_RUN_SS(0, V_OWN)
          if (w == 0) TS(29);
          SCHED_FENCE();
        }
        if ((NB_MEM & 4) && w == 0) { mbar_waitf(bar + 8 * MB_MR, par); bar_arrive<B_MR, 288>(); SCHED_FENCE(); }
        send_max();
        bar_sync<B_VGO, 384>();
        V_RUN_RS(0, V_N1)
        if (w == 0) TS(11);
        bar_sync<B_SSENT, 256>();
        V_RUN_SS(V_OWN + V_RS, V_K1)
        V_RUN_RS(V_N1 + V_N2, V_RS)
        const uint32_t ln = opaque(lane);
        const uint32_t amx = opaque(sb + O_MAXS + 4 * min(ln, 11u));
        SCHED_FENCE();
        mbar_waitf(bar + 8 * MB_SM, par);
        const uint32_t mxl = lds1(amx);
        if (s == 0) {
#pragma unroll 1
          for (int i = 15; i < 20; i++) mbar_wait(bar + 8 * (MB_W + i), 0);
          if (TRIG_LATE) asm volatile("griddepcontrol.launch_dependents;"); if (tid == 256) GTT(layer * 4 + 1, 8); }
        bar_sync<B_SLD, 256>();
        V_RUN_SS(V_K1, 20)
        wg_commit();
        V_RUN_SS((V_K1 > 20 ? V_K1 : 20), V_K2)
        wg_commit();
        wg_wait<1>();
        bar_arrive<B_VHALF, 192>();
        V_RUN_SS(V_K2, 40)
        wg_commit();
        SCHED_FENCE();
        if (w == 0) TS(12);
        {
          const float bnd = cbound * fmaxf(1.f, __uint_as_float(__reduce_max_sync(~0u, mxl)));
          const uint32_t eb = min(max(__float_as_uint(bnd) >> 23, 31u), 254u);
          sc1 = __uint_as_float(opaque((280u - eb) << 23));
          isc = __uint_as_float(opaque((eb - 29u) << 23));
        }
        const uint32_t pa = sb + O_QM + (ln & 7) * 128;
        const uint32_t pa0 = opaque(pa + (((ln >> 3) ^ (ln & 7)) << 4)), pa1 = opaque(pa0 ^ 64);
        const uint32_t o = O_OG + w * 256 + ln * 4;
        const uint32_t a0 = opaque(sb + o), a1 = opaque(sb1 + o + 4096), a2 = opaque(sb1 + o + 4096 + 128), a3 = opaque(sb2 + o + 2048), a4 = opaque(sb2 + o + 2048 + 128);
        const uint32_t b1 = opaque(sb1 + O_BAR + 8 * MB_OG), b2 = opaque(sb2 + O_BAR + 8 * MB_OG);
        const uint32_t c1 = opaque(0x3F803F80u);
        const uint32_t one[4] = {c1, c1, c1, c1};
        uint32_t pm[5];
        float s0[4] = {0.f, 0.f, 0.f, 0.f}, s1[4] = {0.f, 0.f, 0.f, 0.f}, s2[4] = {0.f, 0.f, 0.f, 0.f};
#define LD_AO _Pragma("unroll") for (int j = 0; j < 16; j++) if ((O_RSM >> j) & 1) ldsm4t(ao[O_IDX(j)], la_w + O_WO + (1 + (j >> 3)) * 24576 + (4 + (j & 7)) * 2048);
        if (VEND_POS == 2) bar_arrive<B_VEND, 256>();
        SCHED_FENCE();
        if (F_ORD == 0) {
          bar_sync<B_PM, 160>();
          ldsm4(pm, pa0);
          ldsm1(pm[4], pa1);
          if (VEND_POS == 0) bar_arrive<B_VEND, 256>();
          if (O_RS_POS == 4) { LD_AO }
          if (F_FEN & 1) SCHED_FENCE();
        }
        wg_wait<0>();
        pin<20>(av);
        if (VEND_POS == 3) { bar_arrive<B_VEND, 256>(); SCHED_FENCE(); }
        if (w == 0) TS(13);
        if (O_RS_POS == 0) { LD_AO }
#pragma unroll
        for (int k = 0; k < 10; k++) vf[k] = pack2(av[2 * k], av[2 * k + 1]);
        if (F_ORD == 1) {
          SCHED_FENCE();
          bar_sync<B_PM, 160>();
          ldsm4(pm, pa0);
          ldsm1(pm[4], pa1);
          if (VEND_POS == 0) bar_arrive<B_VEND, 256>();
          if (O_RS_POS == 3) { LD_AO }
        }
        {
          float o0[4] = {0.f, 0.f, 0.f, 0.f}, o1[4] = {0.f, 0.f, 0.f, 0.f}, o2[4] = {0.f, 0.f, 0.f, 0.f};
          mma16816(o0, vf, pm[0], pm[1]);
          mma16816(o1, vf + 4, pm[2], pm[3]);
          mma1688(o2, vf[8], vf[9], pm[4]);
          mma16816(s0, one, pm[0], pm[1]);
          mma16816(s1, one, pm[2], pm[3]);
          mma1688(s2, c1, c1, pm[4]);
          if (O_RS_POS == 5) { LD_AO }
          if (F_FEN & 2) SCHED_FENCE();
          if (O_RS_POS == 6) { LD_AO SCHED_FENCE(); }
          const uint32_t p0 = pack2(o0[0] + o1[0] + o2[0], o0[1] + o1[1] + o2[1]), p1 = pack2(o0[2] + o1[2] + o2[2], o0[3] + o1[3] + o2[3]);
          sta1(a1, p0, b1); sta1(a2, p1, b1);
          sta1(a3, p0, b2); sta1(a4, p1, b2);
          sts1(a0, p0); sts1(a0 + 128, p1);
          if (O_RS_POS == 2) {
#pragma unroll
            for (int j = 0; j < 16; j++) if ((O_RSM >> j) & 1) ldsm4t(ao[O_IDX(j)], la_w + O_WO + (1 + (j >> 3)) * 24576 + (4 + (j & 7)) * 2048);
          }
          if (VEND_POS == 1) bar_arrive<B_VEND, 256>();
          sum0 = s0[0] + s1[0] + s2[0]; sum1 = s0[1] + s1[1] + s2[1];
          fence_async();
          if (O_RS_POS == 7) { LD_AO }
        }
      }
      if (s == NSEG - 1) break;
      uint8_t* arp;
      uint32_t t1;
      {
        bar_sync<B_WG2, 128>();
        float c9[4], ca[4], cb[4], cc[4];
        constexpr uint64_t da = mkdesc(SB0 + O_WO, 1024, 1024, 1), db = mkdesc(SB0 + O_OG, 128, 128, 0);
#define O_RUN(acc, tile, k0, k1) _Pragma("unroll") for (int k = k0; k < k1; k++) wg_ss_n8_ta1_tb1(acc, da + (tile) * 1536 + k * 128, db + (k >> 2) * 128 + (k & 3) * 16, k);
        wg_fence();
        O_RUN(c9, 3, 0, 4)
        wg_commit();
        if (w == 0) TS(14);
        uint8_t* pp;
#define T9_RED { wg_wait<1>(); pin<4>(c9); if (!(EXP & 4) && (!(EXP & 8) || rank == 0)) fix_red(pp + T9_OFF, c9, sc); SCHED_FENCE(); }
#define PP_SET { SCHED_FENCE(); arp = ar + (s >> 2) * AR_GROUP + (s & 1) * 128 + ((s >> 1) & 1) * 512; pp = arp + opaque(prod_off); \
          sc = LATE_NORM ? make_float2(sc1 * rcp(sum0), sc1 * rcp(sum1)) : make_float2(sc1, sc1); }
        if (T9_POS == 2) {
          O_RUN(ca, 0, 0, 4) O_RUN(cb, 1, 0, 2)
          wg_commit();
          PP_SET
          T9_RED
          wg_fence();
          O_RUN(cb, 1, 2, 4) O_RUN(cc, 2, 0, 4)
        } else {
          O_RUN(ca, 0, 0, 4) O_RUN(cb, 1, 0, 4) O_RUN(cc, 2, 0, 4)
          wg_commit();
          PP_SET
        }
        if (T9_POS == 0) T9_RED
        if (O_RS_POS == 1) { LD_AO }
        mbar_waitf(bar + 8 * MB_OG, par);
        wg_fence();
        O_RUN(ca, 0, 4, 12)
        wg_commit();
        if (T9_POS == 1) { T9_RED wg_fence(); }
        bar_arrive<B_VDONE, 160>();
        if (w == 0) TS(15);
#define O_MIX(acc, j0, j1) _Pragma("unroll") for (int j = j0; j < j1; j++) { const int k = 4 + (j & 7); \
          if ((O_RSM >> j) & 1) wg_rs_n8_tb1(acc, ao[O_IDX(j) < O_RS ? O_IDX(j) : 0], db + (k >> 2) * 128 + (k & 3) * 16, 1); \
          else wg_ss_n8_ta1_tb1(acc, da + (1 + (j >> 3)) * 1536 + k * 128, db + (k >> 2) * 128 + (k & 3) * 16, 1); }
        O_MIX(cb, 0, O_B1)
        wg_commit();
        if (O_MODE != 1) {
          wg_wait<1>();
          pin<4>(ca);
          if (!(EXP & 1)) fix_red(pp + tile_off(0), ca, sc);
          SCHED_FENCE();
          if (w == 0) TS(16);
          if (O_MODE == 2) {
            wg_wait<0>();
            pin<4>(cb);
            if (!(EXP & 1)) fix_red(pp + tile_off(1), cb, sc);
          }
          wg_fence();
        }
        if (O_B1 < 8) { O_MIX(cb, O_B1, 8) wg_commit(); }
        if (O_C1 < 16) {
          O_MIX(cc, 8, O_C1)
          wg_commit();
          wg_wait<1>();
          pin<4>(cb);
          if (!(EXP & 1)) fix_red(pp + tile_off(1), cb, sc);
          SCHED_FENCE();
          wg_fence();
        }
        O_MIX(cc, (O_C1 < 16 ? O_C1 : 8), 16)
        wg_commit();
        bar_arrive<B_XGO1, 256>();
        bar_arrive<B_XGO, 256>();
        if (O_MODE != 2 && O_C1 == 16) {
          wg_wait<1>();
          if (O_MODE == 1) { pin<4>(ca); if (!(EXP & 1)) fix_red(pp + tile_off(0), ca, sc); }
          pin<4>(cb);
          if (!(EXP & 1)) fix_red(pp + tile_off(1), cb, sc);
          SCHED_FENCE();
        }
        wg_wait<0>();
        pin<4>(cc);
        fix_red(pp + tile_off(2), cc, sc);
        t1 = clk();
        if (w == 3) TS(17);
      }
      pv_x(s);
      if (PF_MODE == 1) bar_arrive<B_ML0, 384>(); else mbar_arrive_elect(bar + 8 * MB_PF);
      if (PF_FENCE) SCHED_FENCE();
      if (w == 0) TS(28);
#pragma unroll
      for (int k = 0; k < V_RS; k++) ldsm4t(af[k], la_w + vord(V_OWN + k) * 2048);
      {
        arm();
        const int dly = w == 0 ? POLL_D0 : w == 1 ? POLL_A : w == 2 ? POLL_B : POLL_C;
        const uint32_t need = w == 0 ? ((EXP & 4) ? 0 : (EXP & 8) ? 32 : 96) : ((EXP & 1) && w < 3) ? 0 : 32;
        const uint8_t* cp = arp + opaque(cons_off);
        uint4 y[4];
        int it = 0;
        while ((int)(clk() - t1) < dly) {}
        if (w == 3) TS(18);
        y[0] = ld_poll(cp); y[1] = ld_poll(cp + 256); y[2] = ld_poll(cp + 16384); y[3] = ld_poll(cp + 16384 + 256);
        if (OX_T > 0) { while ((int)(clk() - t1) < OX_T) {} }
        if ((EXP & 2) || OX_T < 0) {} else if (EVF) { const uint64_t pol = policy_evict_first(); stg4h(op, oq0, pol); stg4h(op + 512, oq1, pol); } else { stg4(op, oq0); stg4(op + 512, oq1); }
        uint32_t p[8];
        const float isl = isc * 0.5f, bias = -(float)(need >> 3) * isl;
        while (true) {
          const uint32_t bad = ((y[0].x ^ need) | (y[0].z ^ need) | (y[1].x ^ need) | (y[1].z ^ need)) | ((y[2].x ^ need) | (y[2].z ^ need) | (y[3].x ^ need) | (y[3].z ^ need));
          const bool again = __any_sync(~0u, (bad & 127u) != 0);
          if (SPEC_DEC || !again) {
#pragma unroll
            for (int k = 0; k < 4; k++) {
              p[2 * k] = pack2(fmaf((float)(int)__funnelshift_r(y[k].x, y[k].y, 3), isl, bias), fmaf((float)(int)__funnelshift_r(y[k].z, y[k].w, 3), isl, bias));
              p[2 * k + 1] = pack2((float)(int)y[k].y * isc, (float)(int)y[k].w * isc);
            }
            if (SPEC_DEC) {
#pragma unroll
              for (int k = 0; k < 8; k++) asm volatile("" : "+r"(p[k]));
            }
          }
          if (!again) break;
          if (++it > 2000000) __trap();
          y[0] = ld_poll(cp); y[1] = ld_poll(cp + 256); y[2] = ld_poll(cp + 16384); y[3] = ld_poll(cp + 16384 + 256);
        }
        TS(19 + w);
        forward(p);
        if (OX_T < 0) { const uint64_t pol = policy_evict_first(); stg4h(op, oq0, pol); stg4h(op + 512, oq1, pol); }
      }
    }
    bar_arrive<B_VDONE, 160>();
    bar_arrive<B_XGO1, 256>();
    bar_arrive<B_XGO, 256>();
    pv_x(NSEG - 1);
    mbar_wait(bar + 8 * MB_OG, 1);
    if (EVF) { const uint64_t pol = policy_evict_first(); stg4h(op, oq0, pol); stg4h(op + 512, oq1, pol); } else { stg4(op, oq0); stg4(op + 512, oq1); }
    bar_sync<B_WG2, 128>();
    if (tid == 256) { red_release(flags + FL_A + (e0 >> 10) * 8 + (NSEG - 1) * 48, 1); }
    __syncwarp();
  }
  asm volatile("barrier.cluster.arrive.relaxed.aligned;\nbarrier.cluster.wait.aligned;" ::: "memory");
  GT(layer * 4 + 1, 2);
  if (wid == 0) asm volatile("griddepcontrol.wait;" ::: "memory");
}

constexpr int P_B = 0, P_A = 131072, P_BAR = 196608, OPC_SMEM = P_BAR + 256;
#define PF_C 3
#define PF_S0 43
constexpr int OP_KR = 48;

__global__ void __launch_bounds__(384, 1)
opc_kernel(const __grid_constant__ CUtensorMap tmo, bf16* __restrict__ out, int layer,
           const bf16* __restrict__ Wq, const bf16* __restrict__ Wk, const bf16* __restrict__ Wv, const bf16* __restrict__ Wo) {
  extern __shared__ __align__(1024) uint8_t smem[];
  asm volatile("griddepcontrol.launch_dependents;");
  GT(layer * 4 + 2, 0);
  const uint32_t sb = smem_u32(smem);
  check_smem_base(sb);
  const int tid = threadIdx.x, wid = __shfl_sync(~0u, tid >> 5, 0), wg = wid >> 2, w = wid & 3, lane = tid & 31;
  const uint32_t bar = sb + P_BAR;
  uint32_t* flags = g_zero + Z_FLAGS + layer * FL_LAYER;
  float* acc = g_acc + layer * (S_TOK * DM);
  const uint64_t pol = policy_evict_first();
  if (wid == 0) {
    if (lane < 16) mbar_init(bar + 8 * lane, (lane == 8 || lane == 9) ? 8 : 1);
    fence_async();
  }
  __syncthreads();
  if (blockIdx.x < 30) {
    const int cg = blockIdx.x % 5, kg = blockIdx.x / 5;
    if (wg < 2) {
      asm volatile("setmaxnreg.inc.sync.aligned.u32 240;");
      uint32_t a[OP_KR][4];
      const uint32_t la = sb + P_B + ((lane >> 4) * 8 + (lane & 7)) * 128 + (((2 * w + ((lane >> 3) & 1)) ^ (lane & 7)) << 4);
      mbar_wait(bar + 80, 0);
#pragma unroll
      for (int k = 0; k < 32; k++) ldsm4t(a[k], la + wg * 65536 + k * 2048);
      bar_arrive<2, 288>();
      mbar_wait(bar + 88, 0);
#pragma unroll
      for (int k = 0; k < 16; k++) ldsm4t(a[32 + k], la + wg * 32768 + k * 2048);
      bar_arrive<3, 288>();
      mbar_wait(bar + 96, 0);
      float* ap = acc + (cg * 8 + wg * 4 + w) * 512 + lane * 4;
      for (int s = 0; s < NSEG; s++) {
        const int buf = s & 1;
        const uint32_t par = (s >> 1) & 1;
        float d[16];
        const uint64_t db = mkdesc(SB0 + P_B + buf * 65536, 512, 128, 0), da = mkdesc(SB0 + P_A + wg * 32768, 1024, 1024, 1);
        float* p = ap + (s & AC_MASK) * (32 * DM);
        float* pz = ap + ((s + 2) & AC_MASK) * (32 * DM) + kg * 128;
        if (kg < 4 && s + 2 < NSEG) { if (EVF) stg4h(pz, make_uint4(0, 0, 0, 0), pol); else stg4(pz, make_uint4(0, 0, 0, 0)); }
#pragma unroll
        for (int q = 0; q < 4; q++) {
          mbar_wait(bar + 8 * (buf * 4 + q), par);
          wg_fence();
#pragma unroll
          for (int k = 16 * q; k < 16 * q + 16; k++) {
            if (k < OP_KR) wg_rs_n32_tb1(d, a[k < OP_KR ? k : 0], db + k * 64, k);
            else wg_ss_n32_ta1_tb1(d, da + (k - OP_KR) * 128, db + k * 64, 1);
          }
        }
        wg_commit();
        wg_wait<0>();
        pin<16>(d);
        if (lane == 0) mbar_arrive(bar + 8 * (8 + buf));
        if (s == NSEG - 1) GT(layer * 4 + 2, 6);
        if (EVF) {
          red4fh(p, d[0], d[1], d[4], d[5], pol);
          red4fh(p + 128, d[8], d[9], d[12], d[13], pol);
          red4fh(p + 256, d[2], d[3], d[6], d[7], pol);
          red4fh(p + 384, d[10], d[11], d[14], d[15], pol);
        } else {
          red4f(p, d[0], d[1], d[4], d[5]);
          red4f(p + 128, d[8], d[9], d[12], d[13]);
          red4f(p + 256, d[2], d[3], d[6], d[7]);
          red4f(p + 384, d[10], d[11], d[14], d[15]);
        }
        bar_sync<1, 256>();
        if (tid == 0) { red_release(flags + FL_B + s * 8, 1); }
        __syncwarp();
      }
    } else {
      asm volatile("setmaxnreg.dec.sync.aligned.u32 24;");
      if (w == 0) {
        if (lane == 0) { mbar_expect(bar + 80, 131072); mbar_expect(bar + 96, 65536); mbar_expect(bar + 88, 65536); }
        __syncwarp();
        if (lane < 16) tma2d(sb + P_B + lane * 8192, &tmo, cg * 128 + (lane >> 3) * 64, kg * 1024 + (lane & 7) * 64, bar + 80);
        else if (lane < 24) tma2d(sb + P_B + lane * 8192, &tmo, cg * 128 + ((lane >> 2) & 1) * 64, kg * 1024 + 768 + (lane & 3) * 64, bar + 96);
        bar_sync<2, 288>();
        fence_async();
        if (lane < 8) tma2d(sb + P_B + lane * 8192, &tmo, cg * 128 + (lane >> 2) * 64, kg * 1024 + 512 + (lane & 3) * 64, bar + 88);
        bar_sync<3, 288>();
        for (int s = 0; s < NSEG; s++) {
          const int buf = s & 1;
          if (s >= 2) mbar_wait(bar + 8 * (8 + buf), ((s >> 1) & 1) ^ 1);
          if (s >= 2) wait_flag(flags + FL_B + (s - 2) * 8, 30);
          wait_flag(flags + FL_A + s * 48 + kg * 8, 16);
          fence_async_global();
          if (lane < 4) {
            mbar_expect(bar + 8 * (buf * 4 + lane), 16384);
            if (EVF) bulk_g2sh(sb + P_B + buf * 65536 + lane * 16384, g_ot + (size_t)(s & OT_MASK) * (HE * 64) + kg * 65536 + lane * 16384, 16384, bar + 8 * (buf * 4 + lane), pol);
            else bulk_g2s(sb + P_B + buf * 65536 + lane * 16384, g_ot + (size_t)(s & OT_MASK) * (HE * 64) + kg * 65536 + lane * 16384, 16384, bar + 8 * (buf * 4 + lane));
            if (s == NSEG - 1 && lane == 0) GTT(layer * 4 + 2, 5);
          }
          __syncwarp();
        }
      } else if (w == 1 && layer == 0) {
#pragma unroll 1
        for (int q = 4 * (4 - PF_C); q < 18; q++) {
          wait_flag(flags + FL_A + (PF_S0 + q) * 48 + kg * 8, 16);
          const int m = q >> 2;
          const uint8_t* W = m == 0 ? (const uint8_t*)Wo : m == 1 ? (const uint8_t*)Wv : m == 2 ? (const uint8_t*)Wk : m == 3 ? (const uint8_t*)Wq : (q & 1) ? g_w2 : g_w1;
          const int n = m < 4 ? 512 : (q & 1) ? 224 : 640, l0 = m < 4 ? blockIdx.x * 2048 + (q & 3) * 512 : blockIdx.x * n, lim = m < 4 ? 61440 : (q & 1) ? 6720 : 19200;
#pragma unroll 1
          for (int k = lane; k < n; k += 32) {
            if (l0 + k < lim) asm volatile("prefetch.global.L2 [%0];" :: "l"(W + (size_t)(l0 + k) * 128));
            __nanosleep(100);
          }
        }
      }
    }
  } else {
    constexpr int LD = 644;
    float* xs = (float*)smem;
    uint32_t par = 0;
    for (int task = blockIdx.x - 30; task < 2 * NSEG; task += 6, par ^= 1) {
      const int s = task >> 1, jj = task & 1;
      if (wid == 0) {
        wait_flag(flags + FL_XN + (task >> 2) * 8 + 1, 3);
        fence_async_global();
        if (lane == 0) { mbar_expect(bar, 20480); bulk_g2s(sb + 49152, g_x + task * 16 * DM, 20480, bar); }
      }
      if (wid == 1) { wait_flag(flags + FL_B + s * 8, 30); if (s == NSEG - 1 && lane == 0) GTT(layer * 4 + 2, 7); }
      __syncthreads();
      if (wid < 10) {
        float4 v[8];
#pragma unroll
        for (int k = 0; k < 8; k++) v[k] = EVF ? ldg4fh(acc + (s & AC_MASK) * (32 * DM) + (wid * 8 + k) * 256 + jj * 128 + lane * 4, pol) : __ldcg((const float4*)(acc + (s & AC_MASK) * (32 * DM) + (wid * 8 + k) * 256 + jj * 128 + lane * 4));
        float* xp = xs + (lane & 3) * 2 * LD + wid * 64 + (lane >> 2);
#pragma unroll
        for (int k = 0; k < 8; k++) { xp[k * 8] = v[k].x; xp[LD + k * 8] = v[k].y; xp[8 * LD + k * 8] = v[k].z; xp[9 * LD + k * 8] = v[k].w; }
      }
      mbar_wait(bar, par);
      __syncthreads();
#pragma unroll 1
      for (int row = wid; row < 16; row += 12) {
        const int tk = task * 16 + row;
        float v[20], sum = 0.f;
        const int pj = (lane & 24) + 2 * (lane & 3) + ((lane >> 2) & 1);
        bf16* dst = out ? out + tk * DM + lane * 2 : g_x + tk * DM + pj * 2;
#pragma unroll
        for (int k = 0; k < 10; k++) {
          const float2 u = *(const float2*)(xs + row * LD + k * 64 + lane * 2);
          const uint32_t r = *(const uint32_t*)(smem + 49152 + row * 1280 + k * 128 + pj * 4);
          v[2 * k] = u.x + bflo(r); v[2 * k + 1] = u.y + bfhi(r); sum += v[2 * k] + v[2 * k + 1];
          *(uint32_t*)(dst + k * 64) = pack2(v[2 * k], v[2 * k + 1]);
        }
        if (!out) {
#pragma unroll
          for (int o = 16; o; o >>= 1) sum += __shfl_xor_sync(~0u, sum, o);
          const float m = sum * (1.f / DM);
          float q = 0.f;
#pragma unroll
          for (int k = 0; k < 20; k++) { v[k] -= m; q += v[k] * v[k]; }
#pragma unroll
          for (int o = 16; o; o >>= 1) q += __shfl_xor_sync(~0u, q, o);
          const float rs = rsqrtf(q * (1.f / DM) + 1e-5f);
          uint8_t* xp = g_xt + (tk >> 7) * 163840 + (tk & 127) * 128 + (((lane >> 2) ^ (tk & 7)) << 4) + (lane & 3) * 4;
#pragma unroll
          for (int k = 0; k < 10; k++) *(uint32_t*)(xp + k * 16384) = pack2(v[2 * k] * rs, v[2 * k + 1] * rs);
        }
      }
      fence_async();
      __syncthreads();
      if (tid == 0 && !out) { red_release(flags + FL_LAYER + FL_T + (task >> 3) * 8, 1); }
    }
  }
  GT(layer * 4 + 2, 1);
  __syncwarp();
  asm volatile("griddepcontrol.wait;" ::: "memory");
  GT(layer * 4 + 2, 2);
}

constexpr int L_STAGE = 47104;
constexpr int L_KV = 0, L_B2 = 43008;
constexpr int L_BAR = 4 * L_STAGE;
constexpr int LA_SMEM = L_BAR + 256;
__device__ __forceinline__ float phi(float t) { return (fmaxf(t, 0.f) + 1e-6f) + ex2(fminf(t * 1.4426950408889634f, 0.f)); }
__device__ __forceinline__ void sqacc(uint32_t& h, uint32_t v) { asm("fma.rn.bf16x2 %0, %1, %1, %0;" : "+r"(h) : "r"(v)); }
__device__ __forceinline__ uint32_t phi2(float a, float b) { return pack2(phi(a), phi(b)); }
#define LA_LATE 6
#define PF_LB 1
#define PF_IL 1
#define PF_SLEEP1 400
#define PF_N0 2
#define PF_N1 0
#define PF_SLEEP 300

__global__ void __launch_bounds__(384, 1)
la_kernel(const bf16* __restrict__ Wq, const bf16* __restrict__ Wk, const bf16* __restrict__ Wv,
          const bf16* __restrict__ Wo, uint8_t* __restrict__ ar, int layer) {
  extern __shared__ __align__(1024) uint8_t smem[];
  const uint32_t sb = smem_u32(smem);
  check_smem_base(sb);
  const int tid = threadIdx.x, wid = __shfl_sync(~0u, tid >> 5, 0), wg = wid >> 2, w = wid & 3, lane = tid & 31, g = lane >> 2, i4 = lane & 3;
  const int cr = blockIdx.x & 1, hg = (blockIdx.x >> 1) & 7, tb = (blockIdx.x >> 4) * 2 + cr;
  const uint32_t bar = sb + L_BAR;
  uint32_t* flags = g_zero + Z_FLAGS + layer * FL_LAYER;
  asm volatile("griddepcontrol.launch_dependents;");
  GT(layer * 4, 0);
  if (wid == 0) {
    if (lane < 8) mbar_init(bar + 8 * lane, lane >= 4 ? (blockIdx.x < 128 ? 16 : 10) : 1);
    asm volatile("fence.mbarrier_init.release.cluster;" ::: "memory");
    fence_async();
  }
  if (blockIdx.x >= 128) {
    __syncthreads();
    const int q = blockIdx.x - 128;
    const uint8_t* src = (const uint8_t*)Wo + q * 1966080;
    if (wid == 11) {
#pragma unroll 1
      for (int it = 0; it < 48; it++) {
        const int st = it & 3;
        if (it >= 4) mbar_wait(bar + 8 * (4 + st), ((it >> 2) & 1) ^ 1);
        if (lane == 0) mbar_expect(bar + 8 * st, 40960);
        __syncwarp();
        if (lane < 4) bulk_g2s(sb + st * 40960 + lane * 10240, src + it * 40960 + lane * 10240, 10240, bar + 8 * st);
      }
    } else if (wid < 10) {
      float c[8] = {0.f, 0.f, 0.f, 0.f, 0.f, 0.f, 0.f, 0.f};
#pragma unroll 1
      for (int it = 0; it < 48; it++) {
        const int st = it & 3;
        mbar_wait(bar + 8 * st, (it >> 2) & 1);
        uint4 v[8];
#pragma unroll
        for (int k = 0; k < 8; k++) v[k] = lds4(sb + st * 40960 + k * 5120 + tid * 16);
        uint32_t h[4] = {0, 0, 0, 0};
#pragma unroll
        for (int k = 0; k < 8; k++) { sqacc(h[0], v[k].x); sqacc(h[1], v[k].y); sqacc(h[2], v[k].z); sqacc(h[3], v[k].w); }
        __syncwarp();
        if (lane == 0) mbar_arrive(bar + 8 * (4 + st));
#pragma unroll
        for (int k = 0; k < 4; k++) { c[2 * k] += bflo(h[k]); c[2 * k + 1] += bfhi(h[k]); }
      }
      float* red = (float*)(smem + 163840);
      *(float4*)(red + tid * 8) = make_float4(c[0], c[1], c[2], c[3]);
      *(float4*)(red + tid * 8 + 4) = make_float4(c[4], c[5], c[6], c[7]);
      bar_sync<1, 320>();
#pragma unroll
      for (int k = tid; k < DM; k += 320) g_nrm[q * DM + k] = (red[k] + red[DM + k]) + (red[2 * DM + k] + red[3 * DM + k]);
      asm volatile("griddepcontrol.wait;" ::: "memory");
      bar_sync<1, 320>();
      if (tid == 0) red_release(flags + FL_N, 1);
      GT(0, 2);
    }
    return;
  }
  __syncthreads();
  asm volatile("barrier.cluster.arrive.relaxed.aligned;" ::: "memory");
  if (layer == 0) asm volatile("griddepcontrol.wait;" ::: "memory");
  asm volatile("barrier.cluster.wait.aligned;" ::: "memory");
  if (wg == 2) {
    asm volatile("setmaxnreg.dec.sync.aligned.u32 40;");
    if (w == 0) {
      if (lane < 4) {
        mbar_expect(bar + 8 * lane, L_STAGE);
        bulk_g2s_mc(sb + lane * L_STAGE + 16384 + cr * 15360, g_w1 + (hg * 10 + lane) * 30720 + cr * 15360, 15360, bar + 8 * lane);
      }
      if (layer == 1) { if (LA_LATE) wait_flag(flags + FL_T + 15 * 8, LA_LATE); wait_flag(flags + FL_T + tb * 8, 8); fence_async_global(); }
      if (lane < 4) bulk_g2s(sb + lane * L_STAGE, g_xt + (tb * 10 + lane) * 16384, 16384, bar + 8 * lane);
#pragma unroll 1
      for (int kc = 4; kc < 10; kc++) {
        const int st = kc & 3;
        mbar_wait(bar + 8 * (4 + st), ((kc >> 2) & 1) ^ 1);
        if (lane == 0) {
          mbar_expect(bar + 8 * st, L_STAGE);
          bulk_g2s_mc(sb + st * L_STAGE + 16384 + cr * 15360, g_w1 + (hg * 10 + kc) * 30720 + cr * 15360, 15360, bar + 8 * st);
          bulk_g2s(sb + st * L_STAGE, g_xt + (tb * 10 + kc) * 16384, 16384, bar + 8 * st);
        }
        __syncwarp();
      }
    } else {
      const int t = tid - 288;
#pragma unroll 1
      for (int k = t; k < 768; k += 96) *(uint4*)(ar + blockIdx.x * 12288 + k * 16) = make_uint4(0, 0, 0, 0);
      if (layer == 0) {
        float sv = 0.f;
        const uint4* pv = (const uint4*)((const uint8_t*)Wv + blockIdx.x * 61440) + t;
#pragma unroll 1
        for (int k = 0; k < 40; k += 5) {
          uint4 v[5];
#pragma unroll
          for (int j = 0; j < 5; j++) v[j] = __ldg(pv + (k + j) * 96);
          if (PF_IL && k < 25) {
            asm volatile("prefetch.global.L2 [%0];" :: "l"((const uint8_t*)Wq + blockIdx.x * 61440 + (k / 5) * 12288 + t * 128));
            if (PF_IL > 1) asm volatile("prefetch.global.L2 [%0];" :: "l"((const uint8_t*)Wk + blockIdx.x * 61440 + (k / 5) * 12288 + t * 128));
          }
#pragma unroll
          for (int j = 0; j < 5; j++) {
            sv = fmaf(bflo(v[j].x), bflo(v[j].x), fmaf(bfhi(v[j].x), bfhi(v[j].x), fmaf(bflo(v[j].y), bflo(v[j].y), fmaf(bfhi(v[j].y), bfhi(v[j].y), sv))));
            sv = fmaf(bflo(v[j].z), bflo(v[j].z), fmaf(bfhi(v[j].z), bfhi(v[j].z), fmaf(bflo(v[j].w), bflo(v[j].w), fmaf(bfhi(v[j].w), bfhi(v[j].w), sv))));
          }
        }
#pragma unroll
        for (int o = 16; o; o >>= 1) sv += __shfl_xor_sync(~0u, sv, o);
        if (lane == 0) atomicAdd((float*)(g_zero + Z_NORM), sv);
      }
      if (layer == 1 && PF_LB) {
        const int l = blockIdx.x * 96 + t;
        if (l < 6720 + NLB * 640) asm volatile("prefetch.global.L2 [%0];" :: "l"(l < 6720 ? g_w2 + l * 128 : (const uint8_t*)g_x + (l - 6720) * 128));
      }
#pragma unroll 1
      for (int k = layer ? 0 : 5 * PF_IL; k < 5 * (layer ? PF_N1 : PF_N0); k++) {
        const int m = k / 5;
        const bf16* W = m == 0 ? Wq : m == 1 ? Wk : m == 2 ? Wv : Wo;
        asm volatile("prefetch.global.L2 [%0];" :: "l"((const uint8_t*)W + blockIdx.x * 61440 + (k - m * 5) * 12288 + t * 128));
        __nanosleep(layer ? PF_SLEEP1 : PF_SLEEP);
      }
      if (t == 0) GTT(layer * 4, 14);
      bar_arrive<3, 352>();
    }
  } else {
    asm volatile("setmaxnreg.inc.sync.aligned.u32 232;");
    GT(layer * 4, 4);
    uint32_t pq[5][4];
    float* kv = (float*)(g_zero + Z_KV) + layer * KV_LAYER + hg * 1920;
    {
      float d[120];
#pragma unroll 1
      for (int kc = 0; kc < 10; kc++) {
        const int st = kc & 3;
        const uint64_t da = mkdesc(SB0 + st * L_STAGE + wg * 8192, 16, 1024, 1), db = mkdesc(SB0 + st * L_STAGE + 16384, 3840, 128, 0);
        mbar_wait(bar + 8 * st, (kc >> 2) & 1);
        wg_fence();
#pragma unroll
        for (int k = 0; k < 4; k++) wg_ss_n240_ta0_tb1(d, da + 2 * k, db + k * 480, kc | k);
        wg_commit();
        if (kc > 0) { wg_wait<1>(); if (lane < 2) mbar_arrive_cl(mapa(bar + 8 * (4 + ((kc - 1) & 3)), lane)); }
      }
      wg_wait<0>();
      pin<120>(d);
      GT(layer * 4, 5);
      bar_sync<1, 256>();
      const uint32_t kb = sb + L_KV + (wg * 8 + 2 * w + ((lane >> 3) & 1)) * 2688 + (lane >> 4) * 128 + (lane & 7) * 16;
#pragma unroll
      for (int j = 0; j < 5; j++) stsm4(kb + 1280 + j * 256, pack2(d[80 + 8 * j], d[81 + 8 * j]), pack2(d[82 + 8 * j], d[83 + 8 * j]), pack2(d[84 + 8 * j], d[85 + 8 * j]), pack2(d[86 + 8 * j], d[87 + 8 * j]));
      stsm2(kb + 2560, 0x3F803F80u, 0x3F803F80u);
#pragma unroll
      for (int j = 0; j < 5; j++) stsm4(kb + j * 256, phi2(d[40 + 8 * j], d[41 + 8 * j]), phi2(d[42 + 8 * j], d[43 + 8 * j]), phi2(d[44 + 8 * j], d[45 + 8 * j]), phi2(d[46 + 8 * j], d[47 + 8 * j]));
      fence_async();
      bar_sync<1, 256>();
      float e[44];
      {
        const uint64_t da = mkdesc(SB0 + L_KV + wg * 1024, 2688, 128, 0), db = mkdesc(SB0 + L_KV + 1280, 2688, 128, 0);
        wg_fence();
#pragma unroll
        for (int k = 0; k < 8; k++) wg_ss_n88_ta1_tb1(e, da + k * 336, db + k * 336, k);
        wg_commit();
        wg_wait<0>();
        pin<44>(e);
      }
#pragma unroll
      for (int h = 0; h < 2; h++) {
        const int row = wg * 64 + 16 * w + 8 * h + g;
        const int c = row < 80 ? 2 * i4 - (row / 20) * 20 : 100;
        float* dst = kv + row * 24 + c;
#pragma unroll
        for (int j = 0; j < 10; j++)
          asm volatile("{\n.reg .pred p;\nsetp.lt.u32 p, %3, 20;\n@p red.relaxed.gpu.global.add.v2.f32 [%0], {%1,%2};\n}" :: "l"(dst + 8 * j), "f"(e[4 * j + 2 * h]), "f"(e[4 * j + 2 * h + 1]), "r"(c + 8 * j) : "memory");
        asm volatile("{\n.reg .pred p;\nsetp.ne.u32 p, %2, 0;\n@p red.relaxed.gpu.global.add.f32 [%0], %1;\n}" :: "l"(kv + row * 24 + 20), "f"(e[40 + 2 * h]), "r"((int)(row < 80 && i4 == 0)) : "memory");
      }
      bar_sync<1, 256>();
      GT(layer * 4, 6);
      if (tid == 0) { red_release(flags + FL_KV + hg * 8, 1); }
      __syncwarp();
      pin<40>(d);
#pragma unroll
      for (int k = 0; k < 5; k++) {
        pq[k][0] = phi2(d[8 * k], d[8 * k + 1]); pq[k][1] = phi2(d[8 * k + 2], d[8 * k + 3]);
        pq[k][2] = phi2(d[8 * k + 4], d[8 * k + 5]); pq[k][3] = phi2(d[8 * k + 6], d[8 * k + 7]);
      }
    }
#pragma unroll 1
    for (int k = tid; k < 1600; k += 256) sts4(sb + L_B2 + k * 16, 0, 0, 0, 0);
    GT(layer * 4, 7);
    if (wid == 0) wait_flag(flags + FL_KV + hg * 8, 16);
    GT(layer * 4, 8);
    bar_sync<1, 256>();
    if (tid < 240) {
      const int dd = tid / 3, part = tid - dd * 3, n = (dd / 20) * 20 + 8 * part;
      const float4 v0 = __ldcg((const float4*)(kv + dd * 24 + 8 * part)), v1 = __ldcg((const float4*)(kv + dd * 24 + 8 * part + 4));
      const float z = __ldcg(kv + dd * 24 + 20);
      const uint32_t a = sb + L_B2 + (dd >> 3) * 2560 + (dd & 7) * 16, zz = pack2(z, z);
      const uint32_t a0 = a + (n >> 3) * 128 + (n & 7) * 2, a1 = a + ((n + 4) >> 3) * 128 + ((n + 4) & 7) * 2;
      sts2(a0, pack2(v0.x, v0.y), pack2(v0.z, v0.w)); sts2(a0 + 1280, zz, zz);
      if (part < 2) { sts2(a1, pack2(v1.x, v1.y), pack2(v1.z, v1.w)); sts2(a1 + 1280, zz, zz); }
    }
    fence_async();
    bar_sync<1, 256>();
    {
      float o[80];
      const uint64_t db = mkdesc(SB0 + L_B2, 2560, 128, 0);
      wg_fence();
#pragma unroll
      for (int k = 0; k < 5; k++) wg_rs_n160_tb1(o, pq[k], db + k * 320, k);
      wg_commit();
      wg_wait<0>();
      pin<80>(o);
      uint8_t* op = g_oa + (tb * 2 + wg) * 81920 + hg * 10240 + w * 256 + lane * 4;
#pragma unroll
      for (int j = 0; j < 20; j++) {
        const float inv = rcp(o[40 + 2 * j] + 1e-6f);
        *(uint32_t*)(op + (j >> 1) * 1024 + (j & 1) * 128) = pack2(o[2 * j] * inv, o[2 * j + 1] * inv);
      }
      GT(layer * 4, 9);
    }
    bar_sync<3, 352>();
    if (tid == 0) { red_release(flags + FL_O + tb * 8, 1); red_add(flags + FL_X, 1); }
    GT(layer * 4, 2);
    if (wid == 7) asm volatile("griddepcontrol.wait;" ::: "memory");
  }
}

__global__ void __launch_bounds__(256) prep_kernel(const bf16* __restrict__ x, const bf16* __restrict__ wqkv, const bf16* __restrict__ wo) {
  asm volatile("griddepcontrol.launch_dependents;");
  const int b = blockIdx.x, tid = threadIdx.x, lane = tid & 31;
  if (b < 160) GT(3, 0);
  if (b < 256) {
    const int row = b * 8 + (tid >> 5);
    float v[20], s = 0.f;
#pragma unroll
    for (int k = 0; k < 10; k++) { const uint32_t u = __ldg((const uint32_t*)(x + row * DM + k * 64 + lane * 2)); v[2 * k] = bflo(u); v[2 * k + 1] = bfhi(u); s += v[2 * k] + v[2 * k + 1]; }
#pragma unroll
    for (int o = 16; o; o >>= 1) s += __shfl_xor_sync(~0u, s, o);
    const float m = s * (1.f / DM);
    float q = 0.f;
#pragma unroll
    for (int k = 0; k < 20; k++) { v[k] -= m; q += v[k] * v[k]; }
#pragma unroll
    for (int o = 16; o; o >>= 1) q += __shfl_xor_sync(~0u, q, o);
    const float r = rsqrtf(q * (1.f / DM) + 1e-5f);
#pragma unroll
    for (int k = 0; k < 10; k++)
      *(uint32_t*)(g_xt + ((row >> 7) * 10 + k) * 16384 + (row & 127) * 128 + (((lane >> 2) ^ (row & 7)) << 4) + (lane & 3) * 4) = pack2(v[2 * k] * r, v[2 * k + 1] * r);
  } else if (b < 256 + 203) {
#pragma unroll
    for (int it = 0; it < 4; it++) {
      const int u = (b - 256) * 1024 + it * 256 + tid;
      if (u < 153600) {
        const int k8 = u & 7, nb = (u >> 3) % 30, kg = (u / 240) % 80, hg = u / 19200;
        *(uint4*)(g_w1 + u * 16) = __ldg((const uint4*)(wqkv + (kg * 8 + k8) * 1920 + (nb / 10) * 640 + hg * 80 + (nb % 10) * 8));
      } else {
        const int v = u - 153600, k8 = v & 7, nb = (v >> 3) % 28, kg = (v / 224) % 80, c = (v / 17920) * 224 + nb * 8;
        if (v < 53760) *(uint4*)(g_w2 + v * 16) = c < DM ? __ldg((const uint4*)(wo + (kg * 8 + k8) * DM + c)) : make_uint4(0, 0, 0, 0);
      }
    }
  } else {
    const int t = (b - 459) * 256 + tid;
    for (int k = t; k < Z_END / 4; k += 16 * 256) ((uint4*)g_zero)[k] = make_uint4(0, 0, 0, 0);
    for (int k = t; k < 16 * DM; k += 16 * 256) { ((uint4*)g_acc)[k] = make_uint4(0, 0, 0, 0); ((uint4*)(g_acc + S_TOK * DM))[k] = make_uint4(0, 0, 0, 0); }
  }
  if (b < 160) GT(3, 2);
}

typedef CUresult (*EncodeFn)(CUtensorMap*, CUtensorMapDataType, cuuint32_t, void*, const cuuint64_t*, const cuuint64_t*, const cuuint32_t*,
                             const cuuint32_t*, CUtensorMapInterleave, CUtensorMapSwizzle, CUtensorMapL2promotion, CUtensorMapFloatOOBfill);
static void make_map(EncodeFn fn, CUtensorMap* m, const void* p, uint64_t cols, uint64_t rows, uint32_t bc, uint32_t br, CUtensorMapSwizzle sw) {
  cuuint64_t dims[2] = {cols, rows}; cuuint64_t strides[1] = {cols * 2}; cuuint32_t box[2] = {bc, br}; cuuint32_t es[2] = {1, 1};
  fn(m, CU_TENSOR_MAP_DATA_TYPE_BFLOAT16, 2, (void*)p, dims, strides, box, es, CU_TENSOR_MAP_INTERLEAVE_NONE, sw,
     CU_TENSOR_MAP_L2_PROMOTION_L2_128B, CU_TENSOR_MAP_FLOAT_OOB_FILL_NONE);
}

static void make_map_perm(EncodeFn fn, CUtensorMap* m, const void* p) {
  cuuint64_t dims[5] = {HE, 2, 2, 4, 40}; const cuuint64_t r = HE * 2; cuuint64_t strides[4] = {r, 8 * r, 2 * r, 16 * r};
  cuuint32_t box[5] = {64, 2, 2, 4, 4}; cuuint32_t es[5] = {1, 1, 1, 1, 1};
  fn(m, CU_TENSOR_MAP_DATA_TYPE_BFLOAT16, 5, (void*)p, dims, strides, box, es, CU_TENSOR_MAP_INTERLEAVE_NONE, CU_TENSOR_MAP_SWIZZLE_128B,
     CU_TENSOR_MAP_L2_PROMOTION_L2_128B, CU_TENSOR_MAP_FLOAT_OOB_FILL_NONE);
}

#define OPC_PDL 1
#define LA_PDL 1
#define REC_PDL 1
extern "C" void kernel_launch(void* const* d_in, const int* in_sizes, int n_in, void* d_out, int out_size) {
  const bf16* x = (const bf16*)d_in[0];
  const bf16* wqkv = (const bf16*)d_in[1];
  const bf16* wo_a = (const bf16*)d_in[2];
  const bf16* mem0 = (const bf16*)d_in[4];
  const bf16* Wq = (const bf16*)d_in[5];
  const bf16* Wk = (const bf16*)d_in[6];
  const bf16* Wv = (const bf16*)d_in[7];
  const bf16* Wo = (const bf16*)d_in[8];
  cudaStream_t st = cudaStreamPerThread;

  static EncodeFn enc = nullptr;
  static uint8_t* p_ar; static uint32_t* p_zero; static bf16* p_x;
  if (!enc) {
    cudaDriverEntryPointQueryResult qr;
    void* fn = nullptr;
    cudaGetDriverEntryPoint("cuTensorMapEncodeTiled", &fn, cudaEnableDefault, &qr);
    enc = (EncodeFn)fn;
    cudaFuncSetAttribute(rec_kernel, cudaFuncAttributeMaxDynamicSharedMemorySize, REC_SMEM);
    cudaFuncSetAttribute(opc_kernel, cudaFuncAttributeMaxDynamicSharedMemorySize, OPC_SMEM);
    cudaFuncSetAttribute(la_kernel, cudaFuncAttributeMaxDynamicSharedMemorySize, LA_SMEM);
    cudaGetSymbolAddress((void**)&p_ar, g_ar); p_ar = (uint8_t*)(((uintptr_t)p_ar + 32767) & ~(uintptr_t)32767);
    cudaGetSymbolAddress((void**)&p_zero, g_zero); cudaGetSymbolAddress((void**)&p_x, g_x);
  }
  CUtensorMap tmq, tmk, tmv, tmo, tmx[2];
  make_map_perm(enc, &tmq, Wq);
  make_map_perm(enc, &tmk, Wk);
  make_map_perm(enc, &tmv, Wv);
  make_map(enc, &tmo, Wo, DM, HE, 64, 64, CU_TENSOR_MAP_SWIZZLE_128B);
  make_map(enc, &tmx[0], x, DM, S_TOK, 232, 64, CU_TENSOR_MAP_SWIZZLE_NONE);
  make_map(enc, &tmx[1], p_x, DM, S_TOK, 232, 64, CU_TENSOR_MAP_SWIZZLE_NONE);

  cudaLaunchAttribute at[2];
  at[0].id = cudaLaunchAttributeProgrammaticStreamSerialization; at[0].val.programmaticStreamSerializationAllowed = 1;
  at[1].id = cudaLaunchAttributeClusterDimension; at[1].val.clusterDim.x = 3; at[1].val.clusterDim.y = 1; at[1].val.clusterDim.z = 1;
  cudaLaunchAttribute at2[2] = {at[1], at[0]};
  at2[0].val.clusterDim.x = 2;
  prep_kernel<<<475, 256, 0, st>>>(x, wqkv, wo_a);
  for (int l = 0; l < 2; l++) {
    cudaLaunchConfig_t cfg = {};
    cfg.blockDim = dim3(384); cfg.stream = st;
    cfg.gridDim = dim3(l == 0 ? 132 : 128); cfg.dynamicSmemBytes = LA_SMEM; cfg.attrs = at2; cfg.numAttrs = 1 + LA_PDL;
    cudaLaunchKernelEx(&cfg, la_kernel, Wq, Wk, Wv, Wo, p_ar + l * AR_LAYER, l);
    cfg.gridDim = dim3(96 + 3 * NLB); cfg.dynamicSmemBytes = REC_SMEM; cfg.attrs = at + 1 - REC_PDL; cfg.numAttrs = 1 + REC_PDL;
    cudaLaunchKernelEx(&cfg, rec_kernel, tmq, tmk, tmv, tmo, tmx[l], mem0, p_ar + l * AR_LAYER, p_zero + Z_FLAGS + l * FL_LAYER, l);
    cfg.gridDim = dim3(36); cfg.dynamicSmemBytes = OPC_SMEM; cfg.attrs = at; cfg.numAttrs = OPC_PDL;
    cudaLaunchKernelEx(&cfg, opc_kernel, tmo, l == 1 ? (bf16*)d_out : (bf16*)nullptr, l, Wq, Wk, Wv, Wo);
  }
}
```

```cpp
#include <cuda_runtime.h>
#include <cuda_bf16.h>
#include <cuda.h>
#include <stdint.h>

typedef __nv_bfloat16 bf16;
typedef unsigned long long u64;

constexpr int S_TOK = 2048, DM = 640, DH = 192, HE = 6144, NSEG = 64;

constexpr int AR_GROUP = 98304;
constexpr int AR_LAYER = 16 * AR_GROUP;
__device__ __align__(1024) uint8_t g_ar[2 * AR_LAYER + 32768];
__device__ __align__(1024) uint8_t g_xn[NSEG * 40960];
__device__ __align__(1024) uint8_t g_xt[S_TOK * DM * 2];
__device__ __align__(1024) uint8_t g_ot[NSEG * HE * 64];
__device__ __align__(1024) uint8_t g_oa[S_TOK * DM * 2];
__device__ __align__(1024) uint8_t g_w1[DM * 1920 * 2];
__device__ __align__(1024) uint8_t g_w2[DM * 672 * 2];
__device__ __align__(1024) float g_acc[2 * S_TOK * DM];
__device__ __align__(1024) bf16 g_x[S_TOK * DM];
constexpr int FL_A = 0, FL_B = 64 * 6 * 8, FL_KV = FL_B + 64 * 8, FL_O = FL_KV + 8 * 8, FL_T = FL_O + 16 * 8, FL_X = FL_T + 16 * 8, FL_N = FL_X + 8, FL_XN = FL_N + 8, FL_LAYER = FL_XN + 32 * 8;
constexpr int Z_FLAGS = 0, Z_NORM = 2 * FL_LAYER, Z_KV = Z_NORM + 8, KV_LAYER = 8 * 80 * 24, Z_END = Z_KV + 2 * KV_LAYER;
__device__ __align__(128) uint32_t g_zero[Z_END];
__device__ __align__(128) float g_nrm[4 * DM];
#define GT(slot, k) do {} while (0)
#define GTT(slot, k) do {} while (0)

__device__ __forceinline__ uint32_t smem_u32(const void* p) { return (uint32_t)__cvta_generic_to_shared(p); }
__device__ __forceinline__ uint32_t mapa(uint32_t a, uint32_t r) { uint32_t o; asm("mapa.shared::cluster.u32 %0, %1, %2;" : "=r"(o) : "r"(a), "r"(r)); return o; }
__device__ __forceinline__ void mbar_init(uint32_t bar, uint32_t cnt) { asm volatile("mbarrier.init.shared::cta.b64 [%0], %1;" :: "r"(bar), "r"(cnt) : "memory"); }
__device__ __forceinline__ void mbar_expect(uint32_t bar, uint32_t tx) { asm volatile("mbarrier.arrive.expect_tx.shared::cta.b64 _, [%0], %1;" :: "r"(bar), "r"(tx) : "memory"); }
__device__ __forceinline__ void mbar_arrive(uint32_t bar) { asm volatile("mbarrier.arrive.shared::cta.b64 _, [%0];" :: "r"(bar) : "memory"); }
__device__ __forceinline__ void mbar_wait(uint32_t bar, uint32_t par) {
  asm volatile("{\n.reg .pred p;\n.reg .u32 c;\nmov.u32 c, 0;\n"
               "LW:\nmbarrier.try_wait.parity.shared::cta.b64 p, [%0], %1;\n@p bra LD;\n"
               "add.u32 c, c, 1;\nsetp.lt.u32 p, c, 4000000;\n@p bra LW;\ntrap;\nLD:\n}" :: "r"(bar), "r"(par) : "memory");
}
__device__ __forceinline__ void mbar_waitf(uint32_t bar, uint32_t par) {
  asm volatile("{\n.reg .pred p, q;\n.reg .u32 c;\nmov.u32 c, 0;\n"
               "LW:\nadd.u32 c, c, 1;\nsetp.lt.u32 q, c, 1000000;\nmbarrier.try_wait.parity.shared::cta.b64 p, [%0], %1;\n"
               "and.pred q, q, !p;\n@q bra LW;\n}" :: "r"(bar), "r"(par) : "memory");
}
template <int ID, int N> __device__ __forceinline__ void bar_sync() { asm volatile("barrier.sync %0, %1;" :: "n"(ID), "n"(N) : "memory"); }
template <int ID, int N> __device__ __forceinline__ void bar_arrive() { asm volatile("barrier.arrive %0, %1;" :: "n"(ID), "n"(N) : "memory"); }
__device__ __forceinline__ void fence_async() { asm volatile("fence.proxy.async.shared::cta;" ::: "memory"); }
__device__ __forceinline__ void cluster_sync() { asm volatile("barrier.cluster.arrive.aligned;\nbarrier.cluster.wait.aligned;" ::: "memory"); }
__device__ __forceinline__ void wg_fence() { asm volatile("wgmma.fence.sync.aligned;" ::: "memory"); }
__device__ __forceinline__ void wg_commit() { asm volatile("wgmma.commit_group.sync.aligned;" ::: "memory"); }
template <int N> __device__ __forceinline__ void wg_wait() { asm volatile("wgmma.wait_group.sync.aligned %0;" :: "n"(N) : "memory"); }
template <int N> __device__ __forceinline__ void pin(float* d) {
#pragma unroll
  for (int i = 0; i < N; i++) asm volatile("" : "+f"(d[i]) :: "memory");
}
__device__ __forceinline__ constexpr uint64_t mkdesc(uint32_t addr, uint32_t lbo, uint32_t sbo, int sw) {
  return (uint64_t)((addr & 0x3FFFF) >> 4) | ((uint64_t)(lbo >> 4) << 16) | ((uint64_t)(sbo >> 4) << 32) | ((uint64_t)sw << 62);
}
constexpr uint32_t SB0 = 1024;
__device__ __forceinline__ void check_smem_base(uint32_t sb) { if ((sb & 0x3FFFF) != SB0) __trap(); }
__device__ __forceinline__ uint32_t cta_rank() { uint32_t r; asm volatile("mov.u32 %0, %%cluster_ctarank;" : "=r"(r)); return r; }
__device__ __forceinline__ uint32_t opaque(uint32_t v) { uint32_t o; asm volatile("mov.u32 %0, %1;" : "=r"(o) : "r"(v)); return o; }
__device__ __forceinline__ uint32_t pack2(float lo, float hi) { uint32_t r; asm("cvt.rn.bf16x2.f32 %0, %1, %2;" : "=r"(r) : "f"(hi), "f"(lo)); return r; }
__device__ __forceinline__ void ldsm4(uint32_t* r, uint32_t a) { asm volatile("ldmatrix.sync.aligned.m8n8.x4.shared.b16 {%0,%1,%2,%3}, [%4];" : "=r"(r[0]), "=r"(r[1]), "=r"(r[2]), "=r"(r[3]) : "r"(a) : "memory"); }
__device__ __forceinline__ void ldsm4t(uint32_t* r, uint32_t a) { asm volatile("ldmatrix.sync.aligned.m8n8.x4.trans.shared.b16 {%0,%1,%2,%3}, [%4];" : "=r"(r[0]), "=r"(r[1]), "=r"(r[2]), "=r"(r[3]) : "r"(a) : "memory"); }
__device__ __forceinline__ void ldsm1(uint32_t& r, uint32_t a) { asm volatile("ldmatrix.sync.aligned.m8n8.x1.shared.b16 {%0}, [%1];" : "=r"(r) : "r"(a) : "memory"); }
__device__ __forceinline__ void stsm4(uint32_t a, uint32_t r0, uint32_t r1, uint32_t r2, uint32_t r3) { asm volatile("stmatrix.sync.aligned.m8n8.x4.shared.b16 [%0], {%1,%2,%3,%4};" :: "r"(a), "r"(r0), "r"(r1), "r"(r2), "r"(r3) : "memory"); }
__device__ __forceinline__ void stsm1(uint32_t a, uint32_t r0) { asm volatile("stmatrix.sync.aligned.m8n8.x1.shared.b16 [%0], {%1};" :: "r"(a), "r"(r0) : "memory"); }
__device__ __forceinline__ void stsm4t(uint32_t a, uint32_t r0, uint32_t r1, uint32_t r2, uint32_t r3) { asm volatile("stmatrix.sync.aligned.m8n8.x4.trans.shared.b16 [%0], {%1,%2,%3,%4};" :: "r"(a), "r"(r0), "r"(r1), "r"(r2), "r"(r3) : "memory"); }
__device__ __forceinline__ void stsm2t(uint32_t a, uint32_t r0, uint32_t r1) { asm volatile("stmatrix.sync.aligned.m8n8.x2.trans.shared.b16 [%0], {%1,%2};" :: "r"(a), "r"(r0), "r"(r1) : "memory"); }
__device__ __forceinline__ void mma16816(float* c, const uint32_t* a, uint32_t b0, uint32_t b1) {
  asm volatile("mma.sync.aligned.m16n8k16.row.col.f32.bf16.bf16.f32 {%0,%1,%2,%3}, {%4,%5,%6,%7}, {%8,%9}, {%0,%1,%2,%3};"
               : "+f"(c[0]), "+f"(c[1]), "+f"(c[2]), "+f"(c[3]) : "r"(a[0]), "r"(a[1]), "r"(a[2]), "r"(a[3]), "r"(b0), "r"(b1));
}
__device__ __forceinline__ void mma1688(float* c, uint32_t a0, uint32_t a1, uint32_t b0) {
  asm volatile("mma.sync.aligned.m16n8k8.row.col.f32.bf16.bf16.f32 {%0,%1,%2,%3}, {%4,%5}, {%6}, {%0,%1,%2,%3};"
               : "+f"(c[0]), "+f"(c[1]), "+f"(c[2]), "+f"(c[3]) : "r"(a0), "r"(a1), "r"(b0));
}
__device__ __forceinline__ void sta1(uint32_t a, uint32_t v, uint32_t bar) { asm volatile("st.async.weak.shared::cluster.mbarrier::complete_tx::bytes.b32 [%0], %1, [%2];" :: "r"(a), "r"(v), "r"(bar) : "memory"); }
__device__ __forceinline__ void sta1p(uint32_t a, uint32_t v, uint32_t bar, bool p) { asm volatile("{\n.reg .pred p;\nsetp.ne.b32 p, %3, 0;\n@p st.async.weak.shared::cluster.mbarrier::complete_tx::bytes.b32 [%0], %1, [%2];\n}" :: "r"(a), "r"(v), "r"(bar), "r"((int)p) : "memory"); }
__device__ __forceinline__ void sta2(uint32_t a, uint32_t v0, uint32_t v1, uint32_t bar) { asm volatile("st.async.weak.shared::cluster.mbarrier::complete_tx::bytes.v2.b32 [%0], {%1,%2}, [%3];" :: "r"(a), "r"(v0), "r"(v1), "r"(bar) : "memory"); }
__device__ __forceinline__ void sta4(uint32_t a, uint32_t v0, uint32_t v1, uint32_t v2, uint32_t v3, uint32_t bar) { asm volatile("st.async.weak.shared::cluster.mbarrier::complete_tx::bytes.v4.b32 [%0], {%1,%2,%3,%4}, [%5];" :: "r"(a), "r"(v0), "r"(v1), "r"(v2), "r"(v3), "r"(bar) : "memory"); }
__device__ __forceinline__ float bflo(uint32_t v) { return __uint_as_float(v << 16); }
__device__ __forceinline__ float bfhi(uint32_t v) { return __uint_as_float(v & 0xFFFF0000u); }
__device__ __forceinline__ void sta2f(uint32_t a, float v0, float v1, uint32_t bar) { asm volatile("st.async.weak.shared::cluster.mbarrier::complete_tx::bytes.v2.f32 [%0], {%1,%2}, [%3];" :: "r"(a), "f"(v0), "f"(v1), "r"(bar) : "memory"); }
__device__ __forceinline__ void sta4f(uint32_t a, float v0, float v1, float v2, float v3, uint32_t bar) { asm volatile("st.async.weak.shared::cluster.mbarrier::complete_tx::bytes.v4.f32 [%0], {%1,%2,%3,%4}, [%5];" :: "r"(a), "f"(v0), "f"(v1), "f"(v2), "f"(v3), "r"(bar) : "memory"); }
__device__ __forceinline__ float4 lds4f(uint32_t a) { float4 v; asm volatile("ld.shared.v4.f32 {%0,%1,%2,%3}, [%4];" : "=f"(v.x), "=f"(v.y), "=f"(v.z), "=f"(v.w) : "r"(a) : "memory"); return v; }
__device__ __forceinline__ float2 lds2f(uint32_t a) { float2 v; asm volatile("ld.shared.v2.f32 {%0,%1}, [%2];" : "=f"(v.x), "=f"(v.y) : "r"(a) : "memory"); return v; }
__device__ __forceinline__ uint4 lds4(uint32_t a) { uint4 v; asm volatile("ld.shared.v4.u32 {%0,%1,%2,%3}, [%4];" : "=r"(v.x), "=r"(v.y), "=r"(v.z), "=r"(v.w) : "r"(a) : "memory"); return v; }
__device__ __forceinline__ uint32_t lds1(uint32_t a) { uint32_t v; asm volatile("ld.shared.u32 %0, [%1];" : "=r"(v) : "r"(a) : "memory"); return v; }
__device__ __forceinline__ void stsm2(uint32_t a, uint32_t r0, uint32_t r1) { asm volatile("stmatrix.sync.aligned.m8n8.x2.shared.b16 [%0], {%1,%2};" :: "r"(a), "r"(r0), "r"(r1) : "memory"); }
__device__ __forceinline__ float rcp(float x) { float y; asm("rcp.approx.ftz.f32 %0, %1;" : "=f"(y) : "f"(x)); return y; }
__device__ __forceinline__ void sts4(uint32_t a, uint32_t v0, uint32_t v1, uint32_t v2, uint32_t v3) { asm volatile("st.shared.v4.u32 [%0], {%1,%2,%3,%4};" :: "r"(a), "r"(v0), "r"(v1), "r"(v2), "r"(v3) : "memory"); }
__device__ __forceinline__ void bulk_s2c(uint32_t dst, uint32_t src, uint32_t bytes, uint32_t bar) {
  asm volatile("cp.async.bulk.shared::cluster.shared::cta.mbarrier::complete_tx::bytes [%0], [%1], %2, [%3];" :: "r"(dst), "r"(src), "r"(bytes), "r"(bar) : "memory");
}
__device__ __forceinline__ void stg4(void* p, uint4 v) { asm volatile("st.global.v4.u32 [%0], {%1,%2,%3,%4};" :: "l"(p), "r"(v.x), "r"(v.y), "r"(v.z), "r"(v.w) : "memory"); }
__device__ __forceinline__ void red_add(uint32_t* p, uint32_t v) { asm volatile("red.relaxed.gpu.global.add.u32 [%0], %1;" :: "l"(p), "r"(v) : "memory"); }
__device__ __forceinline__ void red_release(uint32_t* p, uint32_t v) { asm volatile("red.release.gpu.global.add.u32 [%0], %1;" :: "l"(p), "r"(v) : "memory"); }
__device__ __forceinline__ void fence_async_global() { asm volatile("fence.proxy.async.global;" ::: "memory"); }
__device__ __forceinline__ uint64_t policy_evict_first() { uint64_t p; asm("createpolicy.fractional.L2::evict_first.b64 %0, 1.0;" : "=l"(p)); return p; }
__device__ __forceinline__ void stg4h(void* p, uint4 v, uint64_t pol) { asm volatile("st.global.L2::cache_hint.v4.u32 [%0], {%1,%2,%3,%4}, %5;" :: "l"(p), "r"(v.x), "r"(v.y), "r"(v.z), "r"(v.w), "l"(pol) : "memory"); }
__device__ __forceinline__ void red4fh(float* p, float a, float b, float c, float d, uint64_t pol) { asm volatile("red.relaxed.gpu.global.add.L2::cache_hint.v4.f32 [%0], {%1,%2,%3,%4}, %5;" :: "l"(p), "f"(a), "f"(b), "f"(c), "f"(d), "l"(pol) : "memory"); }
__device__ __forceinline__ float4 ldg4fh(const float* p, uint64_t pol) { float4 v; asm volatile("ld.global.cg.L2::cache_hint.v4.f32 {%0,%1,%2,%3}, [%4], %5;" : "=f"(v.x), "=f"(v.y), "=f"(v.z), "=f"(v.w) : "l"(p), "l"(pol) : "memory"); return v; }
__device__ __forceinline__ void bulk_g2sh(uint32_t dst, const void* src, uint32_t bytes, uint32_t bar, uint64_t pol) {
  asm volatile("cp.async.bulk.shared::cluster.global.mbarrier::complete_tx::bytes.L2::cache_hint [%0], [%1], %2, [%3], %4;" :: "r"(dst), "l"(src), "r"(bytes), "r"(bar), "l"(pol) : "memory");
}
#define OT_MASK 63
#define AC_MASK 63
#define EVF 1
__device__ __forceinline__ void red4f(float* p, float a, float b, float c, float d) { asm volatile("red.relaxed.gpu.global.add.v4.f32 [%0], {%1,%2,%3,%4};" :: "l"(p), "f"(a), "f"(b), "f"(c), "f"(d) : "memory"); }
__device__ __forceinline__ void wait_flag(const uint32_t* p, uint32_t target) {
  uint32_t v; int it = 0;
  while (true) {
    asm volatile("ld.acquire.gpu.global.u32 %0, [%1];" : "=r"(v) : "l"(p) : "memory");
    if (__all_sync(~0u, v >= target)) break;
    if (++it > 4000000) __trap();
    __nanosleep(20);
  }
}
__device__ __forceinline__ void sts2(uint32_t a, uint32_t v0, uint32_t v1) { asm volatile("st.shared.v2.u32 [%0], {%1,%2};" :: "r"(a), "r"(v0), "r"(v1) : "memory"); }
__device__ __forceinline__ float sqrt_approx(float x) { float y; asm("sqrt.approx.f32 %0, %1;" : "=f"(y) : "f"(x)); return y; }
__device__ __forceinline__ void bulk_s2c_elect(uint32_t d1, uint32_t b1, uint32_t d2, uint32_t b2, uint32_t src) {
  asm volatile("{\n.reg .pred p;\nelect.sync _|p, 0xffffffff;\n"
               "@p cp.async.bulk.shared::cluster.shared::cta.mbarrier::complete_tx::bytes [%0], [%4], 1024, [%1];\n"
               "@p cp.async.bulk.shared::cluster.shared::cta.mbarrier::complete_tx::bytes [%2], [%4], 1024, [%3];\n}"
               :: "r"(d1), "r"(b1), "r"(d2), "r"(b2), "r"(src) : "memory");
}
__device__ __forceinline__ void mbar_arrive_elect(uint32_t bar) { asm volatile("{\n.reg .pred p;\nelect.sync _|p, 0xffffffff;\n@p mbarrier.arrive.shared::cta.b64 _, [%0];\n}" :: "r"(bar) : "memory"); }
__device__ __forceinline__ void cp16(uint32_t dst, const void* src) { asm volatile("cp.async.cg.shared.global [%0], [%1], 16;" :: "r"(dst), "l"(src) : "memory"); }
__device__ __forceinline__ void sts1(uint32_t a, uint32_t v) { asm volatile("st.shared.u32 [%0], %1;" :: "r"(a), "r"(v) : "memory"); }
__device__ __forceinline__ void bulk_g2s(uint32_t dst, const void* src, uint32_t bytes, uint32_t bar) {
  asm volatile("cp.async.bulk.shared::cluster.global.mbarrier::complete_tx::bytes [%0], [%1], %2, [%3];" :: "r"(dst), "l"(src), "r"(bytes), "r"(bar) : "memory");
}
__device__ __forceinline__ void bulk_g2s_mc(uint32_t dst, const void* src, uint32_t bytes, uint32_t bar) {
  asm volatile("cp.async.bulk.shared::cluster.global.mbarrier::complete_tx::bytes.multicast::cluster [%0], [%1], %2, [%3], %4;" :: "r"(dst), "l"(src), "r"(bytes), "r"(bar), "h"((uint16_t)3) : "memory");
}
__device__ __forceinline__ void mbar_arrive_cl(uint32_t bar) { asm volatile("mbarrier.arrive.shared::cluster.b64 _, [%0];" :: "r"(bar) : "memory"); }
__device__ __forceinline__ void tma2d(uint32_t dst, const CUtensorMap* m, int c0, int c1, uint32_t bar) {
  asm volatile("cp.async.bulk.tensor.2d.shared::cluster.global.mbarrier::complete_tx::bytes [%0], [%1, {%3, %4}], [%2];" :: "r"(dst), "l"((uint64_t)m), "r"(bar), "r"(c0), "r"(c1) : "memory");
}
__device__ __forceinline__ void tma5d(uint32_t dst, const CUtensorMap* m, int c0, int c4, uint32_t bar) {
  asm volatile("cp.async.bulk.tensor.5d.shared::cluster.global.mbarrier::complete_tx::bytes [%0], [%1, {%3, %5, %5, %5, %4}], [%2];" :: "r"(dst), "l"((uint64_t)m), "r"(bar), "r"(c0), "r"(c4), "r"(0) : "memory");
}
__device__ __forceinline__ void red64(void* p, uint32_t lo, uint32_t hi) { asm volatile("{\n.reg .b64 t;\nmov.b64 t, {%1,%2};\nred.relaxed.gpu.global.add.u64 [%0], t;\n}" :: "l"(p), "r"(lo), "r"(hi) : "memory"); }
__device__ __forceinline__ uint4 ld_poll(const void* p) {
  uint4 v;
  asm volatile("{\n.reg .b64 a, b;\nld.relaxed.gpu.global.v2.b64 {a, b}, [%4];\nmov.b64 {%0,%1}, a;\nmov.b64 {%2,%3}, b;\n}" : "=r"(v.x), "=r"(v.y), "=r"(v.z), "=r"(v.w) : "l"(p) : "memory");
  return v;
}
__device__ __forceinline__ uint32_t clk() { uint32_t c; asm volatile("mov.u32 %0, %%clock;" : "=r"(c) :: "memory"); return c; }
#define SCHED_FENCE() asm volatile("pmevent 0;" ::: "memory")
__device__ __forceinline__ float ex2(float x) { float y; asm("ex2.approx.ftz.f32 %0, %1;" : "=f"(y) : "f"(x)); return y; }

__device__ __forceinline__ void wg_ss_n240_ta0_tb1(float* d, uint64_t a, uint64_t b, int sc) {
  asm volatile("{\n.reg .pred p;\nsetp.ne.b32 p, %122, 0;\nwgmma.mma_async.sync.aligned.m64n240k16.f32.bf16.bf16 {%0, %1, %2, %3, %4, %5, %6, %7, %8, %9, %10, %11, %12, %13, %14, %15, %16, %17, %18, %19, %20, %21, %22, %23, %24, %25, %26, %27, %28, %29, %30, %31, %32, %33, %34, %35, %36, %37, %38, %39, %40, %41, %42, %43, %44, %45, %46, %47, %48, %49, %50, %51, %52, %53, %54, %55, %56, %57, %58, %59, %60, %61, %62, %63, %64, %65, %66, %67, %68, %69, %70, %71, %72, %73, %74, %75, %76, %77, %78, %79, %80, %81, %82, %83, %84, %85, %86, %87, %88, %89, %90, %91, %92, %93, %94, %95, %96, %97, %98, %99, %100, %101, %102, %103, %104, %105, %106, %107, %108, %109, %110, %111, %112, %113, %114, %115, %116, %117, %118, %119}, %120, %121, p, 1, 1, 0, 1;\n}\n"
    : "+f"(d[0]), "+f"(d[1]), "+f"(d[2]), "+f"(d[3]), "+f"(d[4]), "+f"(d[5]), "+f"(d[6]), "+f"(d[7]), "+f"(d[8]), "+f"(d[9]), "+f"(d[10]), "+f"(d[11]), "+f"(d[12]), "+f"(d[13]), "+f"(d[14]), "+f"(d[15]), "+f"(d[16]), "+f"(d[17]), "+f"(d[18]), "+f"(d[19]), "+f"(d[20]), "+f"(d[21]), "+f"(d[22]), "+f"(d[23]), "+f"(d[24]), "+f"(d[25]), "+f"(d[26]), "+f"(d[27]), "+f"(d[28]), "+f"(d[29]), "+f"(d[30]), "+f"(d[31]), "+f"(d[32]), "+f"(d[33]), "+f"(d[34]), "+f"(d[35]), "+f"(d[36]), "+f"(d[37]), "+f"(d[38]), "+f"(d[39]), "+f"(d[40]), "+f"(d[41]), "+f"(d[42]), "+f"(d[43]), "+f"(d[44]), "+f"(d[45]), "+f"(d[46]), "+f"(d[47]), "+f"(d[48]), "+f"(d[49]), "+f"(d[50]), "+f"(d[51]), "+f"(d[52]), "+f"(d[53]), "+f"(d[54]), "+f"(d[55]), "+f"(d[56]), "+f"(d[57]), "+f"(d[58]), "+f"(d[59]), "+f"(d[60]), "+f"(d[61]), "+f"(d[62]), "+f"(d[63]), "+f"(d[64]), "+f"(d[65]), "+f"(d[66]), "+f"(d[67]), "+f"(d[68]), "+f"(d[69]), "+f"(d[70]), "+f"(d[71]), "+f"(d[72]), "+f"(d[73]), "+f"(d[74]), "+f"(d[75]), "+f"(d[76]), "+f"(d[77]), "+f"(d[78]), "+f"(d[79]), "+f"(d[80]), "+f"(d[81]), "+f"(d[82]), "+f"(d[83]), "+f"(d[84]), "+f"(d[85]), "+f"(d[86]), "+f"(d[87]), "+f"(d[88]), "+f"(d[89]), "+f"(d[90]), "+f"(d[91]), "+f"(d[92]), "+f"(d[93]), "+f"(d[94]), "+f"(d[95]), "+f"(d[96]), "+f"(d[97]), "+f"(d[98]), "+f"(d[99]), "+f"(d[100]), "+f"(d[101]), "+f"(d[102]), "+f"(d[103]), "+f"(d[104]), "+f"(d[105]), "+f"(d[106]), "+f"(d[107]), "+f"(d[108]), "+f"(d[109]), "+f"(d[110]), "+f"(d[111]), "+f"(d[112]), "+f"(d[113]), "+f"(d[114]), "+f"(d[115]), "+f"(d[116]), "+f"(d[117]), "+f"(d[118]), "+f"(d[119])
    : "l"(a), "l"(b), "r"(sc));
}
__device__ __forceinline__ void wg_ss_n88_ta1_tb1(float* d, uint64_t a, uint64_t b, int sc) {
  asm volatile("{\n.reg .pred p;\nsetp.ne.b32 p, %46, 0;\nwgmma.mma_async.sync.aligned.m64n88k16.f32.bf16.bf16 {%0, %1, %2, %3, %4, %5, %6, %7, %8, %9, %10, %11, %12, %13, %14, %15, %16, %17, %18, %19, %20, %21, %22, %23, %24, %25, %26, %27, %28, %29, %30, %31, %32, %33, %34, %35, %36, %37, %38, %39, %40, %41, %42, %43}, %44, %45, p, 1, 1, 1, 1;\n}\n"
    : "+f"(d[0]), "+f"(d[1]), "+f"(d[2]), "+f"(d[3]), "+f"(d[4]), "+f"(d[5]), "+f"(d[6]), "+f"(d[7]), "+f"(d[8]), "+f"(d[9]), "+f"(d[10]), "+f"(d[11]), "+f"(d[12]), "+f"(d[13]), "+f"(d[14]), "+f"(d[15]), "+f"(d[16]), "+f"(d[17]), "+f"(d[18]), "+f"(d[19]), "+f"(d[20]), "+f"(d[21]), "+f"(d[22]), "+f"(d[23]), "+f"(d[24]), "+f"(d[25]), "+f"(d[26]), "+f"(d[27]), "+f"(d[28]), "+f"(d[29]), "+f"(d[30]), "+f"(d[31]), "+f"(d[32]), "+f"(d[33]), "+f"(d[34]), "+f"(d[35]), "+f"(d[36]), "+f"(d[37]), "+f"(d[38]), "+f"(d[39]), "+f"(d[40]), "+f"(d[41]), "+f"(d[42]), "+f"(d[43])
    : "l"(a), "l"(b), "r"(sc));
}
__device__ __forceinline__ void wg_rs_n160_tb1(float* d, const uint32_t* a, uint64_t b, int sc) {
  asm volatile("{\n.reg .pred p;\nsetp.ne.b32 p, %85, 0;\nwgmma.mma_async.sync.aligned.m64n160k16.f32.bf16.bf16 {%0, %1, %2, %3, %4, %5, %6, %7, %8, %9, %10, %11, %12, %13, %14, %15, %16, %17, %18, %19, %20, %21, %22, %23, %24, %25, %26, %27, %28, %29, %30, %31, %32, %33, %34, %35, %36, %37, %38, %39, %40, %41, %42, %43, %44, %45, %46, %47, %48, %49, %50, %51, %52, %53, %54, %55, %56, %57, %58, %59, %60, %61, %62, %63, %64, %65, %66, %67, %68, %69, %70, %71, %72, %73, %74, %75, %76, %77, %78, %79}, {%80, %81, %82, %83}, %84, p, 1, 1, 1;\n}\n"
    : "+f"(d[0]), "+f"(d[1]), "+f"(d[2]), "+f"(d[3]), "+f"(d[4]), "+f"(d[5]), "+f"(d[6]), "+f"(d[7]), "+f"(d[8]), "+f"(d[9]), "+f"(d[10]), "+f"(d[11]), "+f"(d[12]), "+f"(d[13]), "+f"(d[14]), "+f"(d[15]), "+f"(d[16]), "+f"(d[17]), "+f"(d[18]), "+f"(d[19]), "+f"(d[20]), "+f"(d[21]), "+f"(d[22]), "+f"(d[23]), "+f"(d[24]), "+f"(d[25]), "+f"(d[26]), "+f"(d[27]), "+f"(d[28]), "+f"(d[29]), "+f"(d[30]), "+f"(d[31]), "+f"(d[32]), "+f"(d[33]), "+f"(d[34]), "+f"(d[35]), "+f"(d[36]), "+f"(d[37]), "+f"(d[38]), "+f"(d[39]), "+f"(d[40]), "+f"(d[41]), "+f"(d[42]), "+f"(d[43]), "+f"(d[44]), "+f"(d[45]), "+f"(d[46]), "+f"(d[47]), "+f"(d[48]), "+f"(d[49]), "+f"(d[50]), "+f"(d[51]), "+f"(d[52]), "+f"(d[53]), "+f"(d[54]), "+f"(d[55]), "+f"(d[56]), "+f"(d[57]), "+f"(d[58]), "+f"(d[59]), "+f"(d[60]), "+f"(d[61]), "+f"(d[62]), "+f"(d[63]), "+f"(d[64]), "+f"(d[65]), "+f"(d[66]), "+f"(d[67]), "+f"(d[68]), "+f"(d[69]), "+f"(d[70]), "+f"(d[71]), "+f"(d[72]), "+f"(d[73]), "+f"(d[74]), "+f"(d[75]), "+f"(d[76]), "+f"(d[77]), "+f"(d[78]), "+f"(d[79])
    : "r"(a[0]), "r"(a[1]), "r"(a[2]), "r"(a[3]), "l"(b), "r"(sc));
}
__device__ __forceinline__ void wg_ss_n112_ta0_tb1(float* d, uint64_t a, uint64_t b, int sc) {
  asm volatile("{\n.reg .pred p;\nsetp.ne.b32 p, %58, 0;\nwgmma.mma_async.sync.aligned.m64n112k16.f32.bf16.bf16 {%0, %1, %2, %3, %4, %5, %6, %7, %8, %9, %10, %11, %12, %13, %14, %15, %16, %17, %18, %19, %20, %21, %22, %23, %24, %25, %26, %27, %28, %29, %30, %31, %32, %33, %34, %35, %36, %37, %38, %39, %40, %41, %42, %43, %44, %45, %46, %47, %48, %49, %50, %51, %52, %53, %54, %55}, %56, %57, p, 1, 1, 0, 1;\n}\n"
    : "+f"(d[0]), "+f"(d[1]), "+f"(d[2]), "+f"(d[3]), "+f"(d[4]), "+f"(d[5]), "+f"(d[6]), "+f"(d[7]), "+f"(d[8]), "+f"(d[9]), "+f"(d[10]), "+f"(d[11]), "+f"(d[12]), "+f"(d[13]), "+f"(d[14]), "+f"(d[15]), "+f"(d[16]), "+f"(d[17]), "+f"(d[18]), "+f"(d[19]), "+f"(d[20]), "+f"(d[21]), "+f"(d[22]), "+f"(d[23]), "+f"(d[24]), "+f"(d[25]), "+f"(d[26]), "+f"(d[27]), "+f"(d[28]), "+f"(d[29]), "+f"(d[30]), "+f"(d[31]), "+f"(d[32]), "+f"(d[33]), "+f"(d[34]), "+f"(d[35]), "+f"(d[36]), "+f"(d[37]), "+f"(d[38]), "+f"(d[39]), "+f"(d[40]), "+f"(d[41]), "+f"(d[42]), "+f"(d[43]), "+f"(d[44]), "+f"(d[45]), "+f"(d[46]), "+f"(d[47]), "+f"(d[48]), "+f"(d[49]), "+f"(d[50]), "+f"(d[51]), "+f"(d[52]), "+f"(d[53]), "+f"(d[54]), "+f"(d[55])
    : "l"(a), "l"(b), "r"(sc));
}
__device__ __forceinline__ void wg_rs_n32_tb1(float* d, const uint32_t* a, uint64_t b, int sc) {
  asm volatile("{\n.reg .pred p;\nsetp.ne.b32 p, %21, 0;\nwgmma.mma_async.sync.aligned.m64n32k16.f32.bf16.bf16 {%0, %1, %2, %3, %4, %5, %6, %7, %8, %9, %10, %11, %12, %13, %14, %15}, {%16, %17, %18, %19}, %20, p, 1, 1, 1;\n}\n"
    : "+f"(d[0]), "+f"(d[1]), "+f"(d[2]), "+f"(d[3]), "+f"(d[4]), "+f"(d[5]), "+f"(d[6]), "+f"(d[7]), "+f"(d[8]), "+f"(d[9]), "+f"(d[10]), "+f"(d[11]), "+f"(d[12]), "+f"(d[13]), "+f"(d[14]), "+f"(d[15])
    : "r"(a[0]), "r"(a[1]), "r"(a[2]), "r"(a[3]), "l"(b), "r"(sc));
}
__device__ __forceinline__ void wg_ss_n32_ta1_tb1(float* d, uint64_t a, uint64_t b, int sc) {
  asm volatile("{\n.reg .pred p;\nsetp.ne.b32 p, %18, 0;\nwgmma.mma_async.sync.aligned.m64n32k16.f32.bf16.bf16 {%0, %1, %2, %3, %4, %5, %6, %7, %8, %9, %10, %11, %12, %13, %14, %15}, %16, %17, p, 1, 1, 1, 1;\n}\n"
    : "+f"(d[0]), "+f"(d[1]), "+f"(d[2]), "+f"(d[3]), "+f"(d[4]), "+f"(d[5]), "+f"(d[6]), "+f"(d[7]), "+f"(d[8]), "+f"(d[9]), "+f"(d[10]), "+f"(d[11]), "+f"(d[12]), "+f"(d[13]), "+f"(d[14]), "+f"(d[15])
    : "l"(a), "l"(b), "r"(sc));
}
__device__ __forceinline__ void wg_rs_n32_tb0(float* d, const uint32_t* a, uint64_t b, int sc) {
  asm volatile("{\n.reg .pred p;\nsetp.ne.b32 p, %21, 0;\nwgmma.mma_async.sync.aligned.m64n32k16.f32.bf16.bf16 {%0, %1, %2, %3, %4, %5, %6, %7, %8, %9, %10, %11, %12, %13, %14, %15}, {%16, %17, %18, %19}, %20, p, 1, 1, 0;\n}\n"
    : "+f"(d[0]), "+f"(d[1]), "+f"(d[2]), "+f"(d[3]), "+f"(d[4]), "+f"(d[5]), "+f"(d[6]), "+f"(d[7]), "+f"(d[8]), "+f"(d[9]), "+f"(d[10]), "+f"(d[11]), "+f"(d[12]), "+f"(d[13]), "+f"(d[14]), "+f"(d[15])
    : "r"(a[0]), "r"(a[1]), "r"(a[2]), "r"(a[3]), "l"(b), "r"(sc));
}
__device__ __forceinline__ void wg_rs_n40_tb0(float* d, const uint32_t* a, uint64_t b, int sc) {
  asm volatile("{\n.reg .pred p;\nsetp.ne.b32 p, %25, 0;\nwgmma.mma_async.sync.aligned.m64n40k16.f32.bf16.bf16 {%0, %1, %2, %3, %4, %5, %6, %7, %8, %9, %10, %11, %12, %13, %14, %15, %16, %17, %18, %19}, {%20, %21, %22, %23}, %24, p, 1, 1, 0;\n}\n"
    : "+f"(d[0]), "+f"(d[1]), "+f"(d[2]), "+f"(d[3]), "+f"(d[4]), "+f"(d[5]), "+f"(d[6]), "+f"(d[7]), "+f"(d[8]), "+f"(d[9]), "+f"(d[10]), "+f"(d[11]), "+f"(d[12]), "+f"(d[13]), "+f"(d[14]), "+f"(d[15]), "+f"(d[16]), "+f"(d[17]), "+f"(d[18]), "+f"(d[19])
    : "r"(a[0]), "r"(a[1]), "r"(a[2]), "r"(a[3]), "l"(b), "r"(sc));
}
__device__ __forceinline__ void wg_rs_n8_tb1(float* d, const uint32_t* a, uint64_t b, int sc) {
  asm volatile("{\n.reg .pred p;\nsetp.ne.b32 p, %9, 0;\nwgmma.mma_async.sync.aligned.m64n8k16.f32.bf16.bf16 {%0, %1, %2, %3}, {%4, %5, %6, %7}, %8, p, 1, 1, 1;\n}\n"
    : "+f"(d[0]), "+f"(d[1]), "+f"(d[2]), "+f"(d[3])
    : "r"(a[0]), "r"(a[1]), "r"(a[2]), "r"(a[3]), "l"(b), "r"(sc));
}
__device__ __forceinline__ void wg_ss_n40_ta0_tb0(float* d, uint64_t a, uint64_t b, int sc) {
  asm volatile("{\n.reg .pred p;\nsetp.ne.b32 p, %22, 0;\nwgmma.mma_async.sync.aligned.m64n40k16.f32.bf16.bf16 {%0, %1, %2, %3, %4, %5, %6, %7, %8, %9, %10, %11, %12, %13, %14, %15, %16, %17, %18, %19}, %20, %21, p, 1, 1, 0, 0;\n}\n"
    : "+f"(d[0]), "+f"(d[1]), "+f"(d[2]), "+f"(d[3]), "+f"(d[4]), "+f"(d[5]), "+f"(d[6]), "+f"(d[7]), "+f"(d[8]), "+f"(d[9]), "+f"(d[10]), "+f"(d[11]), "+f"(d[12]), "+f"(d[13]), "+f"(d[14]), "+f"(d[15]), "+f"(d[16]), "+f"(d[17]), "+f"(d[18]), "+f"(d[19])
    : "l"(a), "l"(b), "r"(sc));
}
__device__ __forceinline__ void wg_ss_n40_ta1_tb0(float* d, uint64_t a, uint64_t b, int sc) {
  asm volatile("{\n.reg .pred p;\nsetp.ne.b32 p, %22, 0;\nwgmma.mma_async.sync.aligned.m64n40k16.f32.bf16.bf16 {%0, %1, %2, %3, %4, %5, %6, %7, %8, %9, %10, %11, %12, %13, %14, %15, %16, %17, %18, %19}, %20, %21, p, 1, 1, 1, 0;\n}\n"
    : "+f"(d[0]), "+f"(d[1]), "+f"(d[2]), "+f"(d[3]), "+f"(d[4]), "+f"(d[5]), "+f"(d[6]), "+f"(d[7]), "+f"(d[8]), "+f"(d[9]), "+f"(d[10]), "+f"(d[11]), "+f"(d[12]), "+f"(d[13]), "+f"(d[14]), "+f"(d[15]), "+f"(d[16]), "+f"(d[17]), "+f"(d[18]), "+f"(d[19])
    : "l"(a), "l"(b), "r"(sc));
}
__device__ __forceinline__ void wg_ss_n8_ta1_tb1(float* d, uint64_t a, uint64_t b, int sc) {
  asm volatile("{\n.reg .pred p;\nsetp.ne.b32 p, %6, 0;\nwgmma.mma_async.sync.aligned.m64n8k16.f32.bf16.bf16 {%0, %1, %2, %3}, %4, %5, p, 1, 1, 1, 1;\n}\n"
    : "+f"(d[0]), "+f"(d[1]), "+f"(d[2]), "+f"(d[3])
    : "l"(a), "l"(b), "r"(sc));
}

constexpr int O_WV = 0, O_WO = 81920, O_H = 163840, O_QK = 215040, O_SM = 228352, O_MISC = 229632;
constexpr int O_QM = O_QK + 1024, O_K = O_QK + 3072, O_OG = O_QK + 8192;
constexpr int SM_SLOT = 640;
constexpr int O_MAXS = O_MISC;
constexpr int O_BAR = O_MISC + 64;
constexpr int MB_XF = 0, MB_ML = 2, MB_MR = 4, MB_PF = 6, MB_SM = 7, MB_SX = 8, MB_OG = 9, MB_W = 10, MB_WC = 30;
constexpr int O_PROF = O_BAR + 8 * 40;
constexpr int REC_SMEM = O_PROF + 128;
constexpr int B_VOWN = 0, B_QK = 1, B_VGO = 2, B_ML0 = 3, B_PM = 4, B_PX = 5, B_XGO = 6, B_ML1 = 7, B_WG2 = 8, B_VHALF = 9, B_VDONE = 10,
              B_MR = 11, B_SSENT = 12, B_SLD = 13, B_VEND = 14, B_XGO1 = 15;
#define POLL_A 400
#define POLL_B 500
#define POLL_C 600
#define OX_W 0
#define OX_T 0
#define POLL_D0 300
#define TS0(idx) do {} while (0)
#define TS(idx) do {} while (0)
#define SLD_POS 0
#define W_OPEN 16
#define W_WIN 3
#define TRIG_LATE 1
#define XP_END 40
#define F_ORD 0
#define VEND_POS 2
#define SPEC_DEC 0
#define T9_POS 2
#define PARV 0
#define NB_MEM 6
#define PF_MODE 0
#define PF_FENCE 0
#define LATE_NORM 1
#define F_FEN 1
#define SM_MODE 2
#define SX_MODE 2
#define PERSIST 1
#define O_B1 5
#define O_C1 16
#define O_MODE 0
#define AR_MAP 1
#define EXP 0
#define FILL_B 4096
#define MP_D 3
#define MP_CH 4
#define MP_F 0
#define ML_N0 1
#define MR_N0 3
#define O_RSM 0x2AA0
#define O_RS __builtin_popcount(O_RSM)
#define O_IDX(j) __builtin_popcount(O_RSM & ((1 << (j)) - 1))
#define O_RS_POS 0
#define V_N1 0
#define V_N2 0
#define V_N3 3
#define V_OWN 6
#define V_S1 9
#define V_K1 (V_OWN + V_RS + V_S1)
#define V_K2 ((V_K1 > 20 ? V_K1 : 20) + V_S2)
#define V_S2 3
constexpr int V_RS = V_N1 + V_N2 + V_N3;
constexpr float SCL = 0.07216878364870322f;
constexpr float L2E = 1.4426950408889634f;
__device__ __forceinline__ constexpr int vord(int i) { return i < 4 ? 36 + i : i - 4; }
__device__ __forceinline__ constexpr uint32_t hoff(int k) { return ((k >> 2) * 5120 + (k & 3) * 32) >> 4; }

__device__ __forceinline__ constexpr int ar_chunk(int T) { return AR_MAP == 0 ? (T >> 2) * 8 + (T & 3) : T == 9 ? 19 : (T % 3) * 8 + T / 3; }
__device__ __forceinline__ void fix_red(uint8_t* p, const float* a, float2 sc) {
  int v0 = __float2int_rn(a[0] * sc.x), v1 = __float2int_rn(a[1] * sc.y), v2 = __float2int_rn(a[2] * sc.x), v3 = __float2int_rn(a[3] * sc.y);
  red64(p, ((uint32_t)v0 << 7) | 1u, ((uint32_t)v2 << 3) + (uint32_t)(v0 >> 25));
  red64(p + 1024, ((uint32_t)v1 << 7) | 1u, ((uint32_t)v3 << 3) + (uint32_t)(v1 >> 25));
}
__device__ __forceinline__ float lmax10(const float* t) {
  return fmaxf(fmaxf(fmaxf(fmaxf(t[0], t[1]), fmaxf(t[2], t[3])), fmaxf(fmaxf(t[4], t[5]), fmaxf(t[6], t[7]))), fmaxf(t[8], t[9]));
}
__device__ __forceinline__ float max10(const float* t) {
  float m = fmaxf(fmaxf(fmaxf(t[0], t[1]), fmaxf(t[2], t[3])), fmaxf(fmaxf(t[4], t[5]), fmaxf(t[6], t[7])));
  m = fmaxf(m, fmaxf(t[8], t[9]));
  m = fmaxf(m, __shfl_xor_sync(~0u, m, 1));
  return fmaxf(m, __shfl_xor_sync(~0u, m, 2));
}
#define ACC2(k, p, u, v) { t[k] = bflo(p) + bflo(u) + bflo(v); t[k + 1] = bfhi(p) + bfhi(u) + bfhi(v); }

#define LBT 0
#define NLB 5
constexpr int LB_STAGE = 36864, LB_ST = 6 * LB_STAGE;
__device__ __forceinline__ void lb_role(const uint32_t sb, const CUtensorMap* tmx, uint32_t* __restrict__ flags, int layer) {
  const int tid = threadIdx.x, wid = __shfl_sync(~0u, tid >> 5, 0), wg = wid >> 2, w = wid & 3, lane = tid & 31, g = lane >> 2, i4 = lane & 3;
  const int cl = blockIdx.x / 3, rank = blockIdx.x - cl * 3;
  const uint32_t bar = sb + O_BAR;
  asm volatile("griddepcontrol.launch_dependents;");
  if (wid == 8) {
    if (lane < 14) mbar_init(bar + 8 * lane, lane >= 6 && lane < 12 ? 8 : 1);
    asm volatile("fence.mbarrier_init.release.cluster;" ::: "memory");
    fence_async();
  }
  __syncthreads();
  asm volatile("barrier.cluster.arrive.relaxed.aligned;" ::: "memory");
  if (wid == 8) {
    int st = 0; uint32_t ph = 1;
    const uint8_t* wsrc = g_w2 + rank * 286720;
    if (lane < 6) { mbar_expect(bar + 8 * lane, LB_STAGE); bulk_g2s(sb + lane * LB_STAGE + 8192, wsrc + lane * 28672, 28672, bar + 8 * lane); }
    if (layer == 1) wait_flag(flags + FL_T + (lane & 15) * 8, 8);
#pragma unroll 1
    for (int tile = cl; tile < 32; tile += NLB) {
      wait_flag(flags + FL_O + (tile >> 1) * 8, 8);
      if (tile == cl + LBT * NLB && lane == 0) GTT(layer * 4 + 1, 11);
      fence_async_global();
#pragma unroll 1
      for (int kc = 0; kc < 10; kc++) {
        const bool pre = tile == cl && kc < 6;
        mbar_wait(bar + 8 * (6 + st), ph);
        if (lane == 0) {
          if (!pre) { mbar_expect(bar + 8 * st, LB_STAGE); bulk_g2s(sb + st * LB_STAGE + 8192, wsrc + kc * 28672, 28672, bar + 8 * st); }
          bulk_g2s(sb + st * LB_STAGE, g_oa + tile * 81920 + kc * 8192, 8192, bar + 8 * st);
        }
        __syncwarp();
        if (++st == 6) { st = 0; ph ^= 1; }
      }
      mbar_wait(bar + 8 * (6 + st), ph);
      if (lane == 0) { mbar_expect(bar + 8 * st, 64 * 464); tma2d(sb + st * LB_STAGE, tmx, rank * 224, tile * 64, bar + 8 * st); }
      __syncwarp();
      if (++st == 6) { st = 0; ph ^= 1; }
    }
    asm volatile("barrier.cluster.wait.aligned;" ::: "memory");
  } else if (wg < 2) {
    asm volatile("barrier.cluster.wait.aligned;" ::: "memory");
    const int u = 2 * rank + wg, nb = u == 5 ? 5 : 7;
    int st = 0; uint32_t ph = 0, it = 0;
#pragma unroll 1
    for (int tile = cl; tile < 32; tile += NLB, it++) {
      const int row0 = tile * 64 + 16 * w + g;
      float d[56];
      if (tid == 0) mbar_expect(bar + 8 * (12 + (it & 1)), 3072);
#pragma unroll 1
      for (int kc = 0; kc < 10; kc++) {
        const uint64_t da = mkdesc(SB0 + st * LB_STAGE, 1024, 128, 0), db = mkdesc(SB0 + st * LB_STAGE + 8192 + wg * 1792, 3584, 128, 0);
        mbar_wait(bar + 8 * st, ph);
        if (it == LBT && kc == 0) GT(layer * 4 + 1, 12);
        wg_fence();
#pragma unroll
        for (int k = 0; k < 4; k++) wg_ss_n112_ta0_tb1(d, da + k * 128, db + k * 448, kc | k);
        wg_commit();
        wg_wait<1>();
        if (kc > 0 && lane == 0) mbar_arrive(bar + 8 * (6 + (st == 0 ? 5 : st - 1)));
        if (++st == 6) { st = 0; ph ^= 1; }
      }
      wg_wait<0>();
      pin<56>(d);
      if (it == LBT) GT(layer * 4 + 1, 13);
      if (lane == 0) mbar_arrive(bar + 8 * (6 + (st == 0 ? 5 : st - 1)));
      mbar_wait(bar + 8 * st, ph);
      {
        const uint32_t x0 = sb + st * LB_STAGE + (16 * w + g) * 464 + wg * 224 + (layer ? 8 : 4) * i4, x1 = x0 + (layer ? 4 : 16);
#pragma unroll
        for (int j = 0; j < 28; j++) {
          const uint32_t v = lds1(((j & 2) ? x1 : x0) + (j >> 2) * 32 + (j & 1) * 3712);
          d[2 * j] += bflo(v); d[2 * j + 1] += bfhi(v);
        }
      }
      fence_async();
      __syncwarp();
      if (lane == 0) mbar_arrive(bar + 8 * (6 + st));
      if (++st == 6) { st = 0; ph ^= 1; }
      const float cnt = nb * 16.f;
      const uint32_t so = LB_ST + (it & 1) * 3072 + (16 * w + g) * 48;
#pragma unroll
      for (int h = 0; h < 2; h++) {
        float sum = 0.f;
#pragma unroll
        for (int j = 0; j < 14; j++) sum += d[4 * j + 2 * h] + d[4 * j + 2 * h + 1];
        sum += __shfl_xor_sync(~0u, sum, 1); sum += __shfl_xor_sync(~0u, sum, 2);
        const float mean = sum * rcp(cnt);
        float q = 0.f, q2 = 0.f;
#pragma unroll
        for (int j = 0; j < 14; j++) {
          const float a = d[4 * j + 2 * h] - mean, b = d[4 * j + 2 * h + 1] - mean;
          if (j < 10) q = fmaf(a, a, fmaf(b, b, q)); else q2 = fmaf(a, a, fmaf(b, b, q2));
        }
        if (nb == 7) q += q2;
        q += __shfl_xor_sync(~0u, q, 1); q += __shfl_xor_sync(~0u, q, 2);
        if (i4 < 3) { const uint32_t b = mapa(sb, i4); sta2f(b + so + h * 384 + u * 8, sum, q, b + O_BAR + 8 * (12 + (it & 1))); }
      }
      mbar_wait(bar + 8 * (12 + (it & 1)), (it >> 1) & 1);
      if (it == LBT) GT(layer * 4 + 1, 14);
#pragma unroll
      for (int h = 0; h < 2; h++) {
        const float4 x = lds4f(sb + so + h * 384), y = lds4f(sb + so + h * 384 + 16), z = lds4f(sb + so + h * 384 + 32);
        const float mu = (((x.x + x.z) + (y.x + y.z)) + (z.x + z.z)) * (1.f / DM);
        const float e0 = x.x * (1.f / 112.f) - mu, e1 = x.z * (1.f / 112.f) - mu, e2 = y.x * (1.f / 112.f) - mu, e3 = y.z * (1.f / 112.f) - mu;
        const float e4 = z.x * (1.f / 112.f) - mu, e5 = z.z * (1.f / 80.f) - mu;
        const float q = (((x.y + x.w) + (y.y + y.w)) + (z.y + z.w)) + 112.f * ((e0 * e0 + e1 * e1) + (e2 * e2 + e3 * e3) + e4 * e4) + 80.f * e5 * e5;
        const float rs = rsqrtf(q * (1.f / DM) + 1e-5f), sh = -mu * rs;
        const int tk = row0 + 8 * h;
        uint8_t* xp = g_xn + (tk >> 5) * 40960 + (tk & 31) * 128 + (i4 & 1) * 8;
#pragma unroll
        for (int j = 0; j < 7; j++) {
          if (j < nb) {
            const int b16 = u * 7 + j;
            const float* a = d + 8 * j + 2 * h;
            *(uint2*)(xp + (b16 >> 2) * 4096 + (((2 * (b16 & 3) + (i4 >> 1)) ^ g) << 4)) =
                make_uint2(pack2(fmaf(a[0], rs, sh), fmaf(a[1], rs, sh)), pack2(fmaf(a[4], rs, sh), fmaf(a[5], rs, sh)));
          }
        }
      }
      if (it == LBT) GT(layer * 4 + 1, 15);
      bar_arrive<1, 288>();
      bar_sync<2, 288>();
#pragma unroll
      for (int j = 0; j < 14; j++) {
        const float* a = d + 8 * (j >> 1) + 2 * (j & 1);
        if ((j >> 1) < nb) *(uint2*)(g_x + (row0 + 8 * (j & 1)) * DM + u * 112 + 4 * i4 + 16 * (j >> 1)) = make_uint2(pack2(a[0], a[1]), pack2(a[4], a[5]));
      }
      bar_arrive<3, 288>();
    }
  } else {
    asm volatile("barrier.cluster.wait.aligned;" ::: "memory");
    if (wid == 9) {
#pragma unroll 1
      for (int tile = cl; tile < 32; tile += NLB) {
        bar_sync<1, 288>();
        if (tile != cl) bar_arrive<2, 288>();
        if (lane == 0) { red_release(flags + FL_XN + tile * 8, 1); if (tile == cl + LBT * NLB) GTT(layer * 4 + 1, 9); }
        __syncwarp();
        if (tile == cl) bar_arrive<2, 288>();
        bar_sync<3, 288>();
        if (lane == 0) red_release(flags + FL_XN + tile * 8 + 1, 1);
        __syncwarp();
      }
    }
  }
  asm volatile("barrier.cluster.arrive.relaxed.aligned;\nbarrier.cluster.wait.aligned;" ::: "memory");
  GT(layer * 4 + 1, 10);
}

__global__ void __launch_bounds__(384, 1)
rec_kernel(const __grid_constant__ CUtensorMap tmq, const __grid_constant__ CUtensorMap tmk,
           const __grid_constant__ CUtensorMap tmv, const __grid_constant__ CUtensorMap tmo,
           const __grid_constant__ CUtensorMap tmx, const bf16* __restrict__ mem0, uint8_t* __restrict__ ar, uint32_t* __restrict__ flags, int layer) {
  extern __shared__ __align__(1024) uint8_t smem[];
  const uint32_t sb = smem_u32(smem);
  check_smem_base(sb);
  GT(layer * 4 + 1, 0);
  if (blockIdx.x < 3 * NLB) { lb_role(sb, &tmx, flags, layer); return; }
  const int bid = blockIdx.x - 3 * NLB;
  const int tid = threadIdx.x, wid = __shfl_sync(~0u, tid >> 5, 0), wg = wid >> 2, w = wid & 3;
  const int lane = __shfl_sync(~0u, tid & 31, tid & 31);
  const int head = bid / 3, rank = bid - head * 3;
  const int e0 = bid * 64;
  const uint32_t bar = sb + O_BAR;
  const uint32_t sb1 = mapa(sb, rank == 2 ? 0 : rank + 1), sb2 = mapa(sb, rank == 0 ? 2 : rank - 1);
  auto chunk_of = [&](int p) { const int c = 3 * rank + p; return p == 9 ? 9 : c >= 9 ? c - 9 : c; };

  auto load_piece = [&](int i) {
    if (lane == 0) mbar_expect(bar + 8 * (MB_W + i), 16384);
    __syncwarp();
    if (lane < 2) {
      if (i < 15) {
        const int m = i < 10 ? i & 1 : 0, p = (i < 10 ? i >> 1 : i - 10) * 2 + lane;
        tma5d(sb + m * 81920 + p * 8192, i >= 10 ? &tmv : m ? &tmk : &tmq, e0, chunk_of(p) * 4, bar + 8 * (MB_W + i));
      } else {
        const int p = (i - 15) * 2 + lane, k = p / 3, j = rank + p - 3 * k;
        tma2d(sb + O_WO + p * 8192, &tmo, p == 9 ? 576 : (rank * 3 + k) * 64, head * DH + (j >= 3 ? j - 3 : j) * 64, bar + 8 * (MB_W + i));
      }
    }
  };
  if (wid == 9) {
    mbar_init(bar + 8 * lane, lane == MB_ML ? ML_N0 : lane == MB_ML + 1 && ML_N0 < 4 ? 4 - ML_N0 : (lane >= MB_WC || lane == MB_PF) ? 4 : 1);
    if (lane < 8) mbar_init(bar + 8 * (32 + lane), 4);
    asm volatile("fence.mbarrier_init.release.cluster;" ::: "memory");
    fence_async();
    __syncwarp();
#pragma unroll 1
    for (int i = 0; i < W_WIN; i++) load_piece(i);
  }
  __syncthreads();
  asm volatile("barrier.cluster.arrive.relaxed.aligned;" ::: "memory");

  if (wg < 2) {
    asm volatile("setmaxnreg.inc.sync.aligned.u32 208;");
    uint32_t a[40][4];
    const uint32_t swz = (lane & 7) * 128 + (((2 * w + ((lane >> 3) & 1)) ^ (lane & 7)) << 4);
    const uint32_t st_x = __shfl_sync(~0u, sb + O_QK + wg * 5120 + (lane >> 4) * 2048 + swz, lane);
    {
      const uint32_t la = sb + wg * 81920 + (lane >> 4) * 1024 + swz;
#pragma unroll
      for (int p = 0; p < 5; p++) {
        mbar_wait(bar + 8 * (MB_W + 2 * p + wg), 0);
#pragma unroll
        for (int k = 0; k < 8; k++) ldsm4t(a[p * 8 + k], la + (p * 8 + k) * 2048);
        fence_async();
        __syncwarp();
        mbar_arrive_elect(bar + 8 * (MB_WC + wg * 5 + p));
      }
    }
    GT(layer * 4 + 1, 5);
    asm volatile("barrier.cluster.wait.aligned;" ::: "memory");
    const uint32_t ld_m = __shfl_sync(~0u, sb + O_H + (lane & 7) * 128 + (((lane >> 3) ^ (lane & 7)) << 4), lane);

    for (int s = 0; s < NSEG; s++) {
      const uint32_t par = PARV ? ((s ^ (lane >> 5)) & 1) : (s & 1);
      if (wid == 4) TS0(0);
      if (wid == 0) TS(30);
      {
        float ax[16];
        constexpr uint64_t db = mkdesc(SB0 + O_H + 1024, 16, 1024, 1);
        mbar_waitf(bar + 8 * MB_XF, par);
        wg_fence();
#pragma unroll
        for (int k = 0; k < 20; k++) wg_rs_n32_tb0(ax, a[vord(k)], db + hoff(vord(k)), k);
        mbar_waitf(bar + 8 * (MB_XF + 1), par);
        if (PF_MODE == 2) mbar_waitf(bar + 8 * MB_PF, par ^ 1);
        wg_fence();
#pragma unroll
        for (int k = 20; k < XP_END; k++) wg_rs_n32_tb0(ax, a[vord(k)], db + hoff(vord(k)), 1);
        wg_commit();
        if (PF_MODE == 0) mbar_waitf(bar + 8 * MB_PF, par ^ 1);
        if (PF_MODE == 1 && s > 0) bar_sync<B_ML0, 384>();
        if (wid == 6 && lane == 0) { mbar_expect(bar + 8 * MB_SM, 2 * SM_SLOT + 48 + 48); mbar_expect(bar + 8 * MB_SX, 2 * 2176); }
        wg_wait<0>();
        pin<16>(ax);
        if (w == 0) TS(1 + 22 * wg);
        stsm4t(st_x, pack2(ax[0], ax[1]), pack2(ax[2], ax[3]), pack2(ax[4], ax[5]), pack2(ax[6], ax[7]));
        stsm4t(st_x + 4096, pack2(ax[8], ax[9]), pack2(ax[10], ax[11]), pack2(ax[12], ax[13]), pack2(ax[14], ax[15]));
        if (V_OWN > 0) bar_arrive<B_VOWN, 384>();
      }
      {
        float c[MP_CH][4];
#pragma unroll
        for (int k = 0; k < MP_CH; k++) c[k][0] = c[k][1] = c[k][2] = c[k][3] = 0.f;
        uint32_t b[MP_D][2][4];
        const uint32_t ld_m2 = opaque(ld_m ^ 64);
        SCHED_FENCE();
#define MORD(j) ((j) == 0 ? 9 : (j) < 4 ? (j) - 1 : 3 + ((j) - 4) / 2 + 3 * ((j) & 1))
#pragma unroll
        for (int j = 0; j < 10 + MP_D - 1; j++) {
          if (j < 10) {
            if (j == 0) { if (NB_MEM & 1) bar_sync<B_ML0, 256 + 32 * ML_N0>(); else mbar_waitf(bar + 8 * MB_ML, par); if (wid == 0) TS(2); }
            if (ML_N0 < 4 && j == ML_N0) { if (NB_MEM & 2) bar_sync<B_ML1, 256 + 32 * (4 - ML_N0)>(); else mbar_waitf(bar + 8 * (MB_ML + 1), par); if (wid == 0) TS(3); }
            if (j == 4) { if (NB_MEM & 4) bar_sync<B_MR, 288>(); else mbar_waitf(bar + 8 * MB_MR, par); if (wid == 0) TS(4); }
            if (j == 4 + 2 * MR_N0) { mbar_waitf(bar + 8 * (MB_MR + 1), par); if (wid == 0) TS(5); }
            ldsm4(b[j % MP_D][0], ld_m + MORD(j) * 5120);
            ldsm4(b[j % MP_D][1], ld_m2 + MORD(j) * 5120);
            if ((MP_F >> j) & 1) SCHED_FENCE();
          }
          const int u = j - (MP_D - 1);
          if (u >= 0) {
#pragma unroll
            for (int k = 0; k < 4; k++) mma16816(c[(4 * u + k) % MP_CH], a[4 * MORD(u) + k], b[u % MP_D][k >> 1][(k & 1) * 2], b[u % MP_D][k >> 1][(k & 1) * 2 + 1]);
          }
        }
        SCHED_FENCE();
        bar_arrive<B_VGO, 384>();
        if (wid == 0) TS(31);
        SCHED_FENCE();
#pragma unroll
        for (int k = 0; k < 4; k++) c[0][k] = MP_CH == 4 ? (c[0][k] + c[1][k]) + (c[2][k] + c[MP_CH - 1][k]) : (c[1][k] + c[2][k]) + c[0][k];
        stsm2t(st_x + 1024 - wg * 3072, pack2(c[0][0], c[0][1]), pack2(c[0][2], c[0][3]));
        fence_async();
      }
      if (wg == 0) {
        bar_sync<B_QK, 256>();
        float sv[20];
        {
          constexpr uint64_t da = mkdesc(SB0 + O_QK, 16, 1024, 1), db = mkdesc(SB0 + O_K, 16, 2048, 1);
          wg_fence();
#pragma unroll
          for (int k = 0; k < 4; k++) wg_ss_n40_ta0_tb0(sv, da + 2 * k, db + 2 * k, k);
          wg_commit();
        }
        if (w == 0) TS(6);
        SCHED_FENCE();
        const uint32_t ln = opaque(lane);
        uint32_t m0, m1, m2, m3, m4;
        {
          const uint32_t a1 = opaque(sb1 + O_SM + SM_SLOT + ln * 16), a2 = opaque(sb2 + O_SM + ln * 16);
          const uint32_t a3 = opaque(sb1 + O_SM + SM_SLOT + 512 + ln * 4), a4 = opaque(sb2 + O_SM + 512 + ln * 4);
          const uint32_t b1 = opaque(sb1 + O_BAR + 8 * MB_SM), b2 = opaque(sb2 + O_BAR + 8 * MB_SM);
          const uint32_t bt = opaque(mapa(sb, min(ln, 2u)) + O_BAR + 8 * MB_SM), at = opaque(bt + (O_MAXS + 48 - O_BAR - 8 * MB_SM));
          SCHED_FENCE();
          wg_wait<0>();
          pin<20>(sv);
          m0 = pack2(sv[2], sv[3]); m1 = pack2(sv[6], sv[7]); m2 = pack2(sv[10], sv[11]); m3 = pack2(sv[14], sv[15]); m4 = pack2(sv[18], sv[19]);
          if (w == 0) {
            sta4(a1, m0, m1, m2, m3, b1);
            sta4(a2, m0, m1, m2, m3, b2);
            sta1(a3, m4, b1);
            sta1(a4, m4, b2);
          }
          sta1p(at, 0u, bt, ln < 3);
          bar_arrive<B_SSENT, 256>();
          SCHED_FENCE();
        }
        const uint32_t p0 = pack2(sv[0], sv[1]), p1 = pack2(sv[4], sv[5]), p2 = pack2(sv[8], sv[9]), p3 = pack2(sv[12], sv[13]), p4 = pack2(sv[16], sv[17]);
        const uint32_t ox = O_K + w * 2048 + ln * 16, ox2 = O_K + 8192 + ln * 4;
        {
          const uint32_t a1 = opaque(sb1 + ox + 512), a2 = opaque(sb2 + ox), b1 = opaque(sb1 + O_BAR + 8 * MB_SX), b2 = opaque(sb2 + O_BAR + 8 * MB_SX);
          if (w == 0) {
            TS(7);
            const uint32_t om = opaque(sb + O_SM + ln * 16), om2 = opaque(sb + O_SM + 512 + ln * 4);
            const uint32_t pa0 = ld_m + (O_QM - O_H), pa1 = (ld_m ^ 64) + (O_QM - O_H);
            float t[10] = {bflo(m0), bfhi(m0), bflo(m1), bfhi(m1), bflo(m2), bfhi(m2), bflo(m3), bfhi(m3), bflo(m4), bfhi(m4)};
            pin<10>(t);
            SCHED_FENCE();
            mbar_waitf(bar + 8 * MB_SM, par);
            const uint4 u = lds4(om), v = lds4(om + SM_SLOT);
            const uint32_t u4 = lds1(om2), v4 = lds1(om2 + SM_SLOT);
            sta4(a1, p0, p1, p2, p3, b1);
            sta4(a2, p0, p1, p2, p3, b2);
            if (SLD_POS == 0) bar_arrive<B_SLD, 256>();
            SCHED_FENCE();
#define ACC3(k, u, v) { t[k] += bflo(u) + bflo(v); t[k + 1] += bfhi(u) + bfhi(v); }
            ACC3(0, u.x, v.x) ACC3(2, u.y, v.y) ACC3(4, u.z, v.z) ACC3(6, u.w, v.w) ACC3(8, u4, v4)
            TS(8);
            const float ml = lmax10(t) * (SCL * L2E);
            const float m1 = __shfl_xor_sync(~0u, ml, 1), m2 = __shfl_xor_sync(~0u, ml, 2), m3 = __shfl_xor_sync(~0u, ml, 3);
            SCHED_FENCE();
#pragma unroll
            for (int k = 0; k < 10; k++) t[k] = ex2(fmaf(t[k], SCL * L2E, -ml));
            pin<10>(t);
            SCHED_FENCE();
            const float f = ex2(ml - fmaxf(fmaxf(ml, m1), fmaxf(m2, m3)));
#pragma unroll
            for (int k = 0; k < 10; k++) t[k] *= f;
            stsm4(pa0, pack2(t[0], t[1]), pack2(t[2], t[3]), pack2(t[4], t[5]), pack2(t[6], t[7]));
            stsm1(pa1, pack2(t[8], t[9]));
            bar_arrive<B_PM, 160>();
            TS(9);
          } else {
            const uint32_t a3 = opaque(sb1 + ox2 + 128), a4 = opaque(sb2 + ox2);
            SCHED_FENCE();
            mbar_waitf(bar + 8 * MB_SM, par);
            sta4(a1, p0, p1, p2, p3, b1);
            sta4(a2, p0, p1, p2, p3, b2);
            if (w == 3) { sta1(a3, p4, b1); sta1(a4, p4, b2); }
            bar_arrive<B_SLD, 256>();
          }
        }
        {
          float t[10] = {bflo(p0), bfhi(p0), bflo(p1), bfhi(p1), bflo(p2), bfhi(p2), bflo(p3), bfhi(p3), bflo(p4), bfhi(p4)};
          const int dq = 8 * w + (ln >> 2) - 2 * (ln & 3);
#pragma unroll
          for (int k = 1; k < 5; k++) {
            if (8 * (k - 1) > dq) t[2 * k] = -1e9f / SCL;
            if (8 * (k - 1) + 1 > dq) t[2 * k + 1] = -1e9f / SCL;
          }
          const int rr = 2 * w + (ln & 1);
          const uint32_t pa = sb + O_QK + ((ln >> 1) & 3) * 2048 + rr * 128;
          const uint32_t pa0 = opaque(pa + (((ln >> 3) ^ rr) << 4)), pa1 = opaque(pa0 ^ 64), l0 = opaque(sb + ox), l1 = opaque(sb + ox2);
          pin<10>(t);
          SCHED_FENCE();
          mbar_waitf(bar + 8 * MB_SX, par);
          bar_sync<B_VEND, 256>();
          const uint4 u = lds4(l0), v = lds4(l0 + 512);
          uint32_t u4 = 0, v4 = 0;
          if (w == 3) { u4 = lds1(l1); v4 = lds1(l1 + 128); }
          ACC3(0, u.x, v.x) ACC3(2, u.y, v.y) ACC3(4, u.z, v.z) ACC3(6, u.w, v.w) ACC3(8, u4, v4)
          const float ml = lmax10(t) * (SCL * L2E);
          const float m1 = __shfl_xor_sync(~0u, ml, 1), m2 = __shfl_xor_sync(~0u, ml, 2), m3 = __shfl_xor_sync(~0u, ml, 3);
          SCHED_FENCE();
#pragma unroll
          for (int k = 0; k < 10; k++) t[k] = ex2(fmaf(t[k], SCL * L2E, -ml));
          float sum = ((t[0] + t[1]) + (t[2] + t[3])) + ((t[4] + t[5]) + (t[6] + t[7])) + (t[8] + t[9]);
          pin<1>(&sum);
          SCHED_FENCE();
          const float f = ex2(ml - fmaxf(fmaxf(ml, m1), fmaxf(m2, m3)));
          sum *= f;
          const float s1 = __shfl_xor_sync(~0u, sum, 1), s2 = __shfl_xor_sync(~0u, sum, 2), s3 = __shfl_xor_sync(~0u, sum, 3);
          const float inv = f * rcp((sum + s1) + (s2 + s3));
          stsm4(pa0, pack2(t[0] * inv, t[1] * inv), pack2(t[2] * inv, t[3] * inv), pack2(t[4] * inv, t[5] * inv), pack2(t[6] * inv, t[7] * inv));
          stsm2(pa1, pack2(t[8] * inv, t[9] * inv), 0u);
          fence_async();
        }
        bar_arrive<B_PX, 256>();
        if (w == 0) TS(10);
        bar_sync<B_XGO, 256>();
      } else {
        bar_arrive<B_QK, 256>();
        const int ln = opaque(lane);
        if (w == 2) {
          bar_sync<B_VHALF, 192>();
          if (ln == 0 && s > 0) { red_release(flags + FL_A + (e0 >> 10) * 8 + (s - 1) * 48, 1); }
          __syncwarp();
        }
        if (w == 3) {
          const int l = bid * 2 + ln, s2 = s + 2;
          if (ln < 2 && l < 160 && s2 < NSEG - 1) {
            const int tile = l >> 4;
            const uint8_t* p = ar + (s2 >> 2) * AR_GROUP + (s2 & 1) * 128 + ((s2 >> 1) & 1) * 512 + ar_chunk(tile) * 4096 +
                               ((l >> 3) & 1) * 16384 + (l & 1) * 256 + ((l >> 1) & 3) * 1024;
            asm volatile("prefetch.global.L2 [%0];" :: "l"(p));
          }
        }
        if (w == 0) {
          const bool more = s + 1 < NSEG;
          if (ln < 2 && more) mbar_expect(bar + 8 * (MB_XF + ln), FILL_B * 5);
          const uint8_t* src = g_xn + (s + 1) * 40960 + chunk_of(ln) * 4096;
          if ((s & 1) && more) { wait_flag(flags + FL_XN + ((s + 1) >> 1) * 8, 3); fence_async_global(); }
          bar_sync<B_VHALF, 192>();
          if ((ln < 4 || ln == 9) && more) bulk_g2s(sb + O_H + ln * 5120 + 1024, src, FILL_B, bar + 8 * MB_XF);
          bar_sync<B_VDONE, 160>();
          if (ln >= 4 && ln < 9 && more) bulk_g2s(sb + O_H + ln * 5120 + 1024, src, FILL_B, bar + 8 * (MB_XF + 1));
        }
        bar_sync<B_XGO1, 256>();
      }
    }
  } else {
    asm volatile("setmaxnreg.dec.sync.aligned.u32 88;");
    asm volatile("barrier.cluster.wait.aligned;" ::: "memory");

    const int g = lane >> 2, i4 = lane & 3;
    const int myT = w == 0 ? 9 : rank * 3 + w - 1, myP = w == 0 ? 9 : w - 1;
    const int tok = 2 * ((lane >> 1) & 3) + ((lane >> 3) & 1);
    const uint32_t fw_off = sb + O_H + myP * 5120 + tok * 128 + (((2 * (lane >> 4) + (lane & 1)) ^ tok) << 4);
    const uint32_t prod_off = (w >> 1) * 16384 + (w & 1) * 2048 + ((g >> 1) & 1) * 256 + (i4 * 2 + (g >> 2)) * 16 + (g & 1) * 8;
    const uint32_t cons_off = ar_chunk(myT) * 4096 + (lane >> 3) * 1024 + (lane & 7) * 16;
    auto tile_off = [&](int k) { return AR_MAP == 0 ? ar_chunk(rank * 3 + k) * 4096 : (k * 8 + rank) * 4096; };
    constexpr uint32_t T9_OFF = ar_chunk(9) * 4096;

    uint32_t mx;
    auto forward = [&](const uint32_t* p) {
      const uint32_t c = O_H + myP * 5120, bo = O_BAR + 8 * (MB_MR + (w > MR_N0));
      sts4(fw_off, p[0], p[1], p[2], p[3]);
      sts4(fw_off ^ 64, p[4], p[5], p[6], p[7]);
      fence_async();
      __syncwarp();
      if (w < ML_N0) { if (NB_MEM & 1) bar_arrive<B_ML0, 256 + 32 * ML_N0>(); else mbar_arrive_elect(bar + 8 * MB_ML); }
      else { if (NB_MEM & 2) bar_arrive<B_ML1, 256 + 32 * (4 - ML_N0)>(); else mbar_arrive_elect(bar + 8 * (MB_ML + 1)); }
      if (w > 0) bulk_s2c_elect(sb1 + c + 6 * 5120, sb1 + bo, sb2 + c + 3 * 5120, sb2 + bo, sb + c);
      SCHED_FENCE();
      mx = 0;
#pragma unroll
      for (int k = 0; k < 8; k++) mx = __vmaxu2(mx, p[k] & 0x7FFF7FFFu);
    };
    auto send_max = [&]() {
      mx = max(mx & 0xFFFFu, mx >> 16);
      mx = __reduce_max_sync(~0u, mx);
      { const uint32_t b = mapa(sb, min(lane, 2)); sta1p(b + O_MAXS + (rank * 4 + w) * 4, mx << 16, b + O_BAR + 8 * MB_SM, lane < 3); }
    };
    auto arm = [&]() { if (lane == 0 && w < (MR_N0 < 3 ? 3 : 2)) mbar_expect(bar + 8 * (w == 0 ? MB_OG : MB_MR - 1 + w), w == 0 ? 2048 : w == 1 ? 2048 * MR_N0 : 2048 * (3 - MR_N0)); };
    {
      arm();
      const uint32_t* mp = (const uint32_t*)(mem0 + tok * DM + myT * 64 + 16 * (lane >> 4) + 4 * (lane & 1));
      const uint32_t p[8] = {mp[0], mp[4], mp[1], mp[5], mp[16], mp[20], mp[17], mp[21]};
      forward(p);
    }
    if (w == 1) {
#pragma unroll 1
      for (int i = W_WIN; i < 20; i++) {
        if (i <= W_OPEN) mbar_wait(bar + 8 * (MB_W + i - W_WIN), 0);
        if (i >= 10) mbar_wait(bar + 8 * (MB_WC + i - 10), 0);
        load_piece(i);
      }
    }
    if (w == 0) {
      if (lane < 2) mbar_expect(bar + 8 * (MB_XF + lane), 20480);
      wait_flag(flags + FL_XN, 3);
      fence_async_global();
      if (lane < 10) bulk_g2s(sb + O_H + lane * 5120 + 1024, g_xn + chunk_of(lane) * 4096, 4096, bar + 8 * (MB_XF + (lane >= 4 && lane < 9)));
      if (!TRIG_LATE) asm volatile("griddepcontrol.launch_dependents;");
      if (lane == 0) GTT(layer * 4 + 1, 4);
    }
    if (w == 2) {
      wait_flag(flags + FL_X, 128);
      wait_flag(g_zero + Z_FLAGS + FL_N, 4);
      const float sq = __ldcg((const float*)(g_zero + Z_NORM));
      float mx = 0.f;
#pragma unroll
      for (int k = 0; k < 5; k++) {
        const float4* p = (const float4*)g_nrm + k * 32 + lane;
        const float4 x = __ldcg(p), y = __ldcg(p + 160), z = __ldcg(p + 320), u = __ldcg(p + 480);
        mx = fmaxf(fmaxf(mx, fmaxf((x.x + y.x) + (z.x + u.x), (x.y + y.y) + (z.y + u.y))), fmaxf((x.z + y.z) + (z.z + u.z), (x.w + y.w) + (z.w + u.w)));
      }
#pragma unroll
      for (int o = 16; o; o >>= 1) mx = fmaxf(mx, __shfl_xor_sync(~0u, mx, o));
      sts1(sb + O_MAXS + 52, __float_as_uint(sqrt_approx(sq) * sqrt_approx(mx) * (25.2982213f * 1.1f)));
    }
    bar_sync<B_WG2, 128>();
    const float cbound = __uint_as_float(lds1(sb + O_MAXS + 52));
#pragma unroll 1
    for (int i = 10; i < 15; i++) mbar_wait(bar + 8 * (MB_W + i), 0);
    if (tid == 256) GTT(layer * 4 + 1, 7);

    const uint32_t la_w = sb + O_WV + ((lane >> 4) * 8 + (lane & 7)) * 128 + (((2 * w + ((lane >> 3) & 1)) ^ (lane & 7)) << 4);
    uint32_t af[V_RS][4];
#pragma unroll
    for (int k = 0; k < V_RS; k++) ldsm4t(af[k], la_w + vord(V_OWN + k) * 2048);
#define LD_AO0 _Pragma("unroll") for (int j = 0; j < 16; j++) if ((O_RSM >> j) & 1) ldsm4t(ao[O_IDX(j)], la_w + O_WO + (1 + (j >> 3)) * 24576 + (4 + (j & 7)) * 2048);
#define LD_AO LD_AO0
    uint32_t vf[10];
    uint4 oq0 = make_uint4(0, 0, 0, 0), oq1 = oq0;
    uint8_t* op = nullptr;
    auto pv_x = [&](int s) {
      float ox[16];
      const uint32_t vz[4] = {vf[8], vf[9], 0u, 0u};
      constexpr uint64_t dp = mkdesc(SB0 + O_QK, 16, 2048, 1);
      bar_sync<B_PX, 256>();
      wg_fence();
      wg_rs_n32_tb0(ox, vf, dp, 0);
      wg_rs_n32_tb0(ox, vf + 4, dp + 2, 1);
      wg_rs_n32_tb0(ox, vz, dp + 4, 1);
      wg_commit();
      const uint32_t ln = opaque(lane);
      op = g_ot + (size_t)(s & OT_MASK) * (HE * 64) + (e0 + 16 * w) * 64 + (ln & 3) * 128 + (ln >> 2) * 16;
      wg_wait<0>();
      pin<16>(ox);
      oq0 = make_uint4(pack2(ox[0], ox[1]), pack2(ox[4], ox[5]), pack2(ox[8], ox[9]), pack2(ox[12], ox[13]));
      oq1 = make_uint4(pack2(ox[2], ox[3]), pack2(ox[6], ox[7]), pack2(ox[10], ox[11]), pack2(ox[14], ox[15]));
    };
    for (int s = 0;; s++) {
      const uint32_t par = PARV ? ((s ^ (lane >> 5)) & 1) : (s & 1);
      float sc1, isc, sum0, sum1;
      float2 sc;
#if !(PERSIST & 2)
      uint32_t ao[O_RS > 0 ? O_RS : 1][4];
#endif
      {
        float av[20];
        constexpr uint64_t da = mkdesc(SB0 + O_WV, 1024, 1024, 1), db = mkdesc(SB0 + O_H, 16, 1024, 1);
#define V_RUN_RS(k0, k1) wg_fence(); _Pragma("unroll") for (int k = k0; k < k1; k++) wg_rs_n40_tb0(av, af[k], db + hoff(vord(V_OWN + k)), V_OWN + k);
#define V_RUN_SS(k0, k1) wg_fence(); _Pragma("unroll") for (int k = k0; k < k1; k++) wg_ss_n40_ta1_tb0(av, da + vord(k) * 128, db + hoff(vord(k)), k);
        if (V_OWN > 0) {
          bar_sync<B_VOWN, 384>();
          V_RUN_SS(0, V_OWN)
          if (w == 0) TS(29);
          SCHED_FENCE();
        }
        if ((NB_MEM & 4) && w == 0) { mbar_waitf(bar + 8 * MB_MR, par); bar_arrive<B_MR, 288>(); SCHED_FENCE(); }
        send_max();
        if (OX_T == -4 && s > 0) { const uint64_t pol = policy_evict_first(); stg4h(op, oq0, pol); stg4h(op + 512, oq1, pol); }
        bar_sync<B_VGO, 384>();
        if (OX_T == -3 && s > 0) { if (OX_W) { const uint32_t t2 = clk(); while ((int)(clk() - t2) < OX_W) {} } const uint64_t pol = policy_evict_first(); stg4h(op, oq0, pol); stg4h(op + 512, oq1, pol); }
        V_RUN_RS(0, V_N1)
        if (w == 0) TS(11);
        bar_sync<B_SSENT, 256>();
        V_RUN_SS(V_OWN + V_RS, V_K1)
        V_RUN_RS(V_N1 + V_N2, V_RS)
        const uint32_t ln = opaque(lane);
        const uint32_t amx = opaque(sb + O_MAXS + 4 * min(ln, 11u));
        SCHED_FENCE();
        mbar_waitf(bar + 8 * MB_SM, par);
        const uint32_t mxl = lds1(amx);
        if (s == 0) {
#pragma unroll 1
          for (int i = 15; i < 20; i++) mbar_wait(bar + 8 * (MB_W + i), 0);
          if (TRIG_LATE) asm volatile("griddepcontrol.launch_dependents;"); if (tid == 256) GTT(layer * 4 + 1, 8); }
        bar_sync<B_SLD, 256>();
        V_RUN_SS(V_K1, 20)
        wg_commit();
        V_RUN_SS((V_K1 > 20 ? V_K1 : 20), V_K2)
        wg_commit();
        wg_wait<1>();
        bar_arrive<B_VHALF, 192>();
        V_RUN_SS(V_K2, 40)
        wg_commit();
        SCHED_FENCE();
        if (w == 0) TS(12);
        {
          const float bnd = cbound * fmaxf(1.f, __uint_as_float(__reduce_max_sync(~0u, mxl)));
          const uint32_t eb = min(max(__float_as_uint(bnd) >> 23, 31u), 254u);
          sc1 = __uint_as_float(opaque((280u - eb) << 23));
          isc = __uint_as_float(opaque((eb - 29u) << 23));
        }
        const uint32_t pa = sb + O_QM + (ln & 7) * 128;
        const uint32_t pa0 = opaque(pa + (((ln >> 3) ^ (ln & 7)) << 4)), pa1 = opaque(pa0 ^ 64);
        const uint32_t o = O_OG + w * 256 + ln * 4;
        const uint32_t a0 = opaque(sb + o), a1 = opaque(sb1 + o + 4096), a2 = opaque(sb1 + o + 4096 + 128), a3 = opaque(sb2 + o + 2048), a4 = opaque(sb2 + o + 2048 + 128);
        const uint32_t b1 = opaque(sb1 + O_BAR + 8 * MB_OG), b2 = opaque(sb2 + O_BAR + 8 * MB_OG);
        const uint32_t c1 = opaque(0x3F803F80u);
        const uint32_t one[4] = {c1, c1, c1, c1};
        uint32_t pm[5];
        float s0[4] = {0.f, 0.f, 0.f, 0.f}, s1[4] = {0.f, 0.f, 0.f, 0.f}, s2[4] = {0.f, 0.f, 0.f, 0.f};
        if (VEND_POS == 2) bar_arrive<B_VEND, 256>();
        SCHED_FENCE();
        if (F_ORD == 0) {
          bar_sync<B_PM, 160>();
          ldsm4(pm, pa0);
          ldsm1(pm[4], pa1);
          if (VEND_POS == 0) bar_arrive<B_VEND, 256>();
          if (O_RS_POS == 4) { LD_AO }
          if (F_FEN & 1) SCHED_FENCE();
        }
        wg_wait<0>();
        pin<20>(av);
        if (VEND_POS == 3) { bar_arrive<B_VEND, 256>(); SCHED_FENCE(); }
        if (w == 0) TS(13);
        if (O_RS_POS == 0) { LD_AO }
#pragma unroll
        for (int k = 0; k < 10; k++) vf[k] = pack2(av[2 * k], av[2 * k + 1]);
        if (F_ORD == 1) {
          SCHED_FENCE();
          bar_sync<B_PM, 160>();
          ldsm4(pm, pa0);
          ldsm1(pm[4], pa1);
          if (VEND_POS == 0) bar_arrive<B_VEND, 256>();
          if (O_RS_POS == 3) { LD_AO }
        }
        {
          float o0[4] = {0.f, 0.f, 0.f, 0.f}, o1[4] = {0.f, 0.f, 0.f, 0.f}, o2[4] = {0.f, 0.f, 0.f, 0.f};
          mma16816(o0, vf, pm[0], pm[1]);
          mma16816(o1, vf + 4, pm[2], pm[3]);
          mma1688(o2, vf[8], vf[9], pm[4]);
          mma16816(s0, one, pm[0], pm[1]);
          mma16816(s1, one, pm[2], pm[3]);
          mma1688(s2, c1, c1, pm[4]);
          if (O_RS_POS == 5) { LD_AO }
          if (F_FEN & 2) SCHED_FENCE();
          if (O_RS_POS == 6) { LD_AO SCHED_FENCE(); }
          const uint32_t p0 = pack2(o0[0] + o1[0] + o2[0], o0[1] + o1[1] + o2[1]), p1 = pack2(o0[2] + o1[2] + o2[2], o0[3] + o1[3] + o2[3]);
          sta1(a1, p0, b1); sta1(a2, p1, b1);
          sta1(a3, p0, b2); sta1(a4, p1, b2);
          sts1(a0, p0); sts1(a0 + 128, p1);
          if (O_RS_POS == 2) {
            LD_AO
          }
          if (VEND_POS == 1) bar_arrive<B_VEND, 256>();
          sum0 = s0[0] + s1[0] + s2[0]; sum1 = s0[1] + s1[1] + s2[1];
          fence_async();
          if (O_RS_POS == 7) { LD_AO }
        }
      }
      if (s == NSEG - 1) break;
      uint8_t* arp;
      uint32_t t1;
      {
        bar_sync<B_WG2, 128>();
        float c9[4], ca[4], cb[4], cc[4];
        constexpr uint64_t da = mkdesc(SB0 + O_WO, 1024, 1024, 1), db = mkdesc(SB0 + O_OG, 128, 128, 0);
#define O_RUN(acc, tile, k0, k1) _Pragma("unroll") for (int k = k0; k < k1; k++) wg_ss_n8_ta1_tb1(acc, da + (tile) * 1536 + k * 128, db + (k >> 2) * 128 + (k & 3) * 16, k);
        wg_fence();
        O_RUN(c9, 3, 0, 4)
        wg_commit();
        if (w == 0) TS(14);
        uint8_t* pp;
#define T9_RED { wg_wait<1>(); pin<4>(c9); if (!(EXP & 4) && (!(EXP & 8) || rank == 0)) fix_red(pp + T9_OFF, c9, sc); SCHED_FENCE(); }
#define PP_SET { SCHED_FENCE(); arp = ar + (s >> 2) * AR_GROUP + (s & 1) * 128 + ((s >> 1) & 1) * 512; pp = arp + opaque(prod_off); \
          sc = LATE_NORM ? make_float2(sc1 * rcp(sum0), sc1 * rcp(sum1)) : make_float2(sc1, sc1); }
        if (T9_POS == 2) {
          O_RUN(ca, 0, 0, 4) O_RUN(cb, 1, 0, 2)
          wg_commit();
          PP_SET
          T9_RED
          wg_fence();
          O_RUN(cb, 1, 2, 4) O_RUN(cc, 2, 0, 4)
        } else {
          O_RUN(ca, 0, 0, 4) O_RUN(cb, 1, 0, 4) O_RUN(cc, 2, 0, 4)
          wg_commit();
          PP_SET
        }
        if (T9_POS == 0) T9_RED
        if (O_RS_POS == 1) { LD_AO }
        mbar_waitf(bar + 8 * MB_OG, par);
        wg_fence();
        O_RUN(ca, 0, 4, 12)
        wg_commit();
        if (T9_POS == 1) { T9_RED wg_fence(); }
        bar_arrive<B_VDONE, 160>();
        if (w == 0) TS(15);
#define O_MIX(acc, j0, j1) _Pragma("unroll") for (int j = j0; j < j1; j++) { const int k = 4 + (j & 7); \
          if ((O_RSM >> j) & 1) wg_rs_n8_tb1(acc, ao[O_IDX(j) < O_RS ? O_IDX(j) : 0], db + (k >> 2) * 128 + (k & 3) * 16, 1); \
          else wg_ss_n8_ta1_tb1(acc, da + (1 + (j >> 3)) * 1536 + k * 128, db + (k >> 2) * 128 + (k & 3) * 16, 1); }
        O_MIX(cb, 0, O_B1)
        wg_commit();
        if (O_MODE != 1) {
          wg_wait<1>();
          pin<4>(ca);
          if (!(EXP & 1)) fix_red(pp + tile_off(0), ca, sc);
          SCHED_FENCE();
          if (w == 0) TS(16);
          if (O_MODE == 2) {
            wg_wait<0>();
            pin<4>(cb);
            if (!(EXP & 1)) fix_red(pp + tile_off(1), cb, sc);
          }
          wg_fence();
        }
        if (O_B1 < 8) { O_MIX(cb, O_B1, 8) wg_commit(); }
        if (O_C1 < 16) {
          O_MIX(cc, 8, O_C1)
          wg_commit();
          wg_wait<1>();
          pin<4>(cb);
          if (!(EXP & 1)) fix_red(pp + tile_off(1), cb, sc);
          SCHED_FENCE();
          wg_fence();
        }
        O_MIX(cc, (O_C1 < 16 ? O_C1 : 8), 16)
        wg_commit();
        bar_arrive<B_XGO1, 256>();
        bar_arrive<B_XGO, 256>();
        if (O_MODE != 2 && O_C1 == 16) {
          wg_wait<1>();
          if (O_MODE == 1) { pin<4>(ca); if (!(EXP & 1)) fix_red(pp + tile_off(0), ca, sc); }
          pin<4>(cb);
          if (!(EXP & 1)) fix_red(pp + tile_off(1), cb, sc);
          SCHED_FENCE();
        }
        wg_wait<0>();
        pin<4>(cc);
        fix_red(pp + tile_off(2), cc, sc);
        t1 = clk();
        if (w == 3) TS(17);
      }
      pv_x(s);
      if (PF_MODE == 1) bar_arrive<B_ML0, 384>(); else mbar_arrive_elect(bar + 8 * MB_PF);
      if (PF_FENCE) SCHED_FENCE();
      if (OX_T == -2) { const uint64_t pol = policy_evict_first(); stg4h(op, oq0, pol); stg4h(op + 512, oq1, pol); }
      if (w == 0) TS(28);
      if (!(PERSIST & 1)) {
#pragma unroll
        for (int k = 0; k < V_RS; k++) ldsm4t(af[k], la_w + vord(V_OWN + k) * 2048);
      }
      {
        arm();
        const int dly = w == 0 ? POLL_D0 : w == 1 ? POLL_A : w == 2 ? POLL_B : POLL_C;
        const uint32_t need = w == 0 ? ((EXP & 4) ? 0 : (EXP & 8) ? 32 : 96) : ((EXP & 1) && w < 3) ? 0 : 32;
        const uint8_t* cp = arp + opaque(cons_off);
        uint4 y[4];
        int it = 0;
        while ((int)(clk() - t1) < dly) {}
        if (w == 3) TS(18);
        y[0] = ld_poll(cp); y[1] = ld_poll(cp + 256); y[2] = ld_poll(cp + 16384); y[3] = ld_poll(cp + 16384 + 256);
        if (OX_T > 0) { while ((int)(clk() - t1) < OX_T) {} }
        if ((EXP & 2) || OX_T < 0) {} else if (EVF) { const uint64_t pol = policy_evict_first(); stg4h(op, oq0, pol); stg4h(op + 512, oq1, pol); } else { stg4(op, oq0); stg4(op + 512, oq1); }
        uint32_t p[8];
        const float isl = isc * 0.5f, bias = -(float)(need >> 3) * isl;
        while (true) {
          const uint32_t bad = ((y[0].x ^ need) | (y[0].z ^ need) | (y[1].x ^ need) | (y[1].z ^ need)) | ((y[2].x ^ need) | (y[2].z ^ need) | (y[3].x ^ need) | (y[3].z ^ need));
          const bool again = __any_sync(~0u, (bad & 127u) != 0);
          if (SPEC_DEC || !again) {
#pragma unroll
            for (int k = 0; k < 4; k++) {
              p[2 * k] = pack2(fmaf((float)(int)__funnelshift_r(y[k].x, y[k].y, 3), isl, bias), fmaf((float)(int)__funnelshift_r(y[k].z, y[k].w, 3), isl, bias));
              p[2 * k + 1] = pack2((float)(int)y[k].y * isc, (float)(int)y[k].w * isc);
            }
            if (SPEC_DEC) {
#pragma unroll
              for (int k = 0; k < 8; k++) asm volatile("" : "+r"(p[k]));
            }
          }
          if (!again) break;
          if (++it > 2000000) __trap();
          y[0] = ld_poll(cp); y[1] = ld_poll(cp + 256); y[2] = ld_poll(cp + 16384); y[3] = ld_poll(cp + 16384 + 256);
        }
        TS(19 + w);
        forward(p);
        if (OX_T == -1) { const uint64_t pol = policy_evict_first(); stg4h(op, oq0, pol); stg4h(op + 512, oq1, pol); }
      }
    }
    bar_arrive<B_VDONE, 160>();
    bar_arrive<B_XGO1, 256>();
    bar_arrive<B_XGO, 256>();
    pv_x(NSEG - 1);
    mbar_wait(bar + 8 * MB_OG, 1);
    if (EVF) { const uint64_t pol = policy_evict_first(); stg4h(op, oq0, pol); stg4h(op + 512, oq1, pol); } else { stg4(op, oq0); stg4(op + 512, oq1); }
    bar_sync<B_WG2, 128>();
    if (tid == 256) { red_release(flags + FL_A + (e0 >> 10) * 8 + (NSEG - 1) * 48, 1); }
    __syncwarp();
  }
  asm volatile("barrier.cluster.arrive.relaxed.aligned;\nbarrier.cluster.wait.aligned;" ::: "memory");
  GT(layer * 4 + 1, 2);
  if (wid == 0) asm volatile("griddepcontrol.wait;" ::: "memory");
}

constexpr int P_B = 0, P_A = 131072, P_BAR = 196608, OPC_SMEM = P_BAR + 256;
#define PF_C 3
#define PF_S0 43
constexpr int OP_KR = 48;

__global__ void __launch_bounds__(384, 1)
opc_kernel(const __grid_constant__ CUtensorMap tmo, bf16* __restrict__ out, int layer,
           const bf16* __restrict__ Wq, const bf16* __restrict__ Wk, const bf16* __restrict__ Wv, const bf16* __restrict__ Wo) {
  extern __shared__ __align__(1024) uint8_t smem[];
  asm volatile("griddepcontrol.launch_dependents;");
  GT(layer * 4 + 2, 0);
  const uint32_t sb = smem_u32(smem);
  check_smem_base(sb);
  const int tid = threadIdx.x, wid = __shfl_sync(~0u, tid >> 5, 0), wg = wid >> 2, w = wid & 3, lane = tid & 31;
  const uint32_t bar = sb + P_BAR;
  uint32_t* flags = g_zero + Z_FLAGS + layer * FL_LAYER;
  float* acc = g_acc + layer * (S_TOK * DM);
  const uint64_t pol = policy_evict_first();
  if (wid == 0) {
    if (lane < 16) mbar_init(bar + 8 * lane, (lane == 8 || lane == 9) ? 8 : 1);
    fence_async();
  }
  __syncthreads();
  if (blockIdx.x < 30) {
    const int cg = blockIdx.x % 5, kg = blockIdx.x / 5;
    if (wg < 2) {
      asm volatile("setmaxnreg.inc.sync.aligned.u32 240;");
      uint32_t a[OP_KR][4];
      const uint32_t la = sb + P_B + ((lane >> 4) * 8 + (lane & 7)) * 128 + (((2 * w + ((lane >> 3) & 1)) ^ (lane & 7)) << 4);
      mbar_wait(bar + 80, 0);
#pragma unroll
      for (int k = 0; k < 32; k++) ldsm4t(a[k], la + wg * 65536 + k * 2048);
      bar_arrive<2, 288>();
      mbar_wait(bar + 88, 0);
#pragma unroll
      for (int k = 0; k < 16; k++) ldsm4t(a[32 + k], la + wg * 32768 + k * 2048);
      bar_arrive<3, 288>();
      mbar_wait(bar + 96, 0);
      float* ap = acc + (cg * 8 + wg * 4 + w) * 512 + lane * 4;
      for (int s = 0; s < NSEG; s++) {
        const int buf = s & 1;
        const uint32_t par = (s >> 1) & 1;
        float d[16];
        const uint64_t db = mkdesc(SB0 + P_B + buf * 65536, 512, 128, 0), da = mkdesc(SB0 + P_A + wg * 32768, 1024, 1024, 1);
        float* p = ap + (s & AC_MASK) * (32 * DM);
        float* pz = ap + ((s + 2) & AC_MASK) * (32 * DM) + kg * 128;
        if (kg < 4 && s + 2 < NSEG) { if (EVF) stg4h(pz, make_uint4(0, 0, 0, 0), pol); else stg4(pz, make_uint4(0, 0, 0, 0)); }
#pragma unroll
        for (int q = 0; q < 4; q++) {
          mbar_wait(bar + 8 * (buf * 4 + q), par);
          wg_fence();
#pragma unroll
          for (int k = 16 * q; k < 16 * q + 16; k++) {
            if (k < OP_KR) wg_rs_n32_tb1(d, a[k < OP_KR ? k : 0], db + k * 64, k);
            else wg_ss_n32_ta1_tb1(d, da + (k - OP_KR) * 128, db + k * 64, 1);
          }
        }
        wg_commit();
        wg_wait<0>();
        pin<16>(d);
        if (lane == 0) mbar_arrive(bar + 8 * (8 + buf));
        if (s == NSEG - 1) GT(layer * 4 + 2, 6);
        if (EVF) {
          red4fh(p, d[0], d[1], d[4], d[5], pol);
          red4fh(p + 128, d[8], d[9], d[12], d[13], pol);
          red4fh(p + 256, d[2], d[3], d[6], d[7], pol);
          red4fh(p + 384, d[10], d[11], d[14], d[15], pol);
        } else {
          red4f(p, d[0], d[1], d[4], d[5]);
          red4f(p + 128, d[8], d[9], d[12], d[13]);
          red4f(p + 256, d[2], d[3], d[6], d[7]);
          red4f(p + 384, d[10], d[11], d[14], d[15]);
        }
        bar_sync<1, 256>();
        if (tid == 0) { red_release(flags + FL_B + s * 8, 1); }
        __syncwarp();
      }
    } else {
      asm volatile("setmaxnreg.dec.sync.aligned.u32 24;");
      if (w == 0) {
        if (lane == 0) { mbar_expect(bar + 80, 131072); mbar_expect(bar + 96, 65536); mbar_expect(bar + 88, 65536); }
        __syncwarp();
        if (lane < 16) tma2d(sb + P_B + lane * 8192, &tmo, cg * 128 + (lane >> 3) * 64, kg * 1024 + (lane & 7) * 64, bar + 80);
        else if (lane < 24) tma2d(sb + P_B + lane * 8192, &tmo, cg * 128 + ((lane >> 2) & 1) * 64, kg * 1024 + 768 + (lane & 3) * 64, bar + 96);
        bar_sync<2, 288>();
        fence_async();
        if (lane < 8) tma2d(sb + P_B + lane * 8192, &tmo, cg * 128 + (lane >> 2) * 64, kg * 1024 + 512 + (lane & 3) * 64, bar + 88);
        bar_sync<3, 288>();
        for (int s = 0; s < NSEG; s++) {
          const int buf = s & 1;
          if (s >= 2) mbar_wait(bar + 8 * (8 + buf), ((s >> 1) & 1) ^ 1);
          if (s >= 2) wait_flag(flags + FL_B + (s - 2) * 8, 30);
          wait_flag(flags + FL_A + s * 48 + kg * 8, 16);
          fence_async_global();
          if (lane < 4) {
            mbar_expect(bar + 8 * (buf * 4 + lane), 16384);
            if (EVF) bulk_g2sh(sb + P_B + buf * 65536 + lane * 16384, g_ot + (size_t)(s & OT_MASK) * (HE * 64) + kg * 65536 + lane * 16384, 16384, bar + 8 * (buf * 4 + lane), pol);
            else bulk_g2s(sb + P_B + buf * 65536 + lane * 16384, g_ot + (size_t)(s & OT_MASK) * (HE * 64) + kg * 65536 + lane * 16384, 16384, bar + 8 * (buf * 4 + lane));
            if (s == NSEG - 1 && lane == 0) GTT(layer * 4 + 2, 5);
          }
          __syncwarp();
        }
      } else if (w == 1 && layer == 0) {
#pragma unroll 1
        for (int q = 4 * (4 - PF_C); q < 18; q++) {
          wait_flag(flags + FL_A + (PF_S0 + q) * 48 + kg * 8, 16);
          const int m = q >> 2;
          const uint8_t* W = m == 0 ? (const uint8_t*)Wo : m == 1 ? (const uint8_t*)Wv : m == 2 ? (const uint8_t*)Wk : m == 3 ? (const uint8_t*)Wq : (q & 1) ? g_w2 : g_w1;
          const int n = m < 4 ? 512 : (q & 1) ? 224 : 640, l0 = m < 4 ? blockIdx.x * 2048 + (q & 3) * 512 : blockIdx.x * n, lim = m < 4 ? 61440 : (q & 1) ? 6720 : 19200;
#pragma unroll 1
          for (int k = lane; k < n; k += 32) {
            if (l0 + k < lim) asm volatile("prefetch.global.L2 [%0];" :: "l"(W + (size_t)(l0 + k) * 128));
            __nanosleep(100);
          }
        }
      }
    }
  } else {
    constexpr int LD = 644;
    float* xs = (float*)smem;
    uint32_t par = 0;
    for (int task = blockIdx.x - 30; task < 2 * NSEG; task += 6, par ^= 1) {
      const int s = task >> 1, jj = task & 1;
      if (wid == 0) {
        wait_flag(flags + FL_XN + (task >> 2) * 8 + 1, 3);
        fence_async_global();
        if (lane == 0) { mbar_expect(bar, 20480); bulk_g2s(sb + 49152, g_x + task * 16 * DM, 20480, bar); }
      }
      if (wid == 1) { wait_flag(flags + FL_B + s * 8, 30); if (s == NSEG - 1 && lane == 0) GTT(layer * 4 + 2, 7); }
      __syncthreads();
      if (wid < 10) {
        float4 v[8];
#pragma unroll
        for (int k = 0; k < 8; k++) v[k] = EVF ? ldg4fh(acc + (s & AC_MASK) * (32 * DM) + (wid * 8 + k) * 256 + jj * 128 + lane * 4, pol) : __ldcg((const float4*)(acc + (s & AC_MASK) * (32 * DM) + (wid * 8 + k) * 256 + jj * 128 + lane * 4));
        float* xp = xs + (lane & 3) * 2 * LD + wid * 64 + (lane >> 2);
#pragma unroll
        for (int k = 0; k < 8; k++) { xp[k * 8] = v[k].x; xp[LD + k * 8] = v[k].y; xp[8 * LD + k * 8] = v[k].z; xp[9 * LD + k * 8] = v[k].w; }
      }
      mbar_wait(bar, par);
      __syncthreads();
#pragma unroll 1
      for (int row = wid; row < 16; row += 12) {
        const int tk = task * 16 + row;
        float v[20], sum = 0.f;
        const int pj = (lane & 24) + 2 * (lane & 3) + ((lane >> 2) & 1);
        bf16* dst = out ? out + tk * DM + lane * 2 : g_x + tk * DM + pj * 2;
#pragma unroll
        for (int k = 0; k < 10; k++) {
          const float2 u = *(const float2*)(xs + row * LD + k * 64 + lane * 2);
          const uint32_t r = *(const uint32_t*)(smem + 49152 + row * 1280 + k * 128 + pj * 4);
          v[2 * k] = u.x + bflo(r); v[2 * k + 1] = u.y + bfhi(r); sum += v[2 * k] + v[2 * k + 1];
          *(uint32_t*)(dst + k * 64) = pack2(v[2 * k], v[2 * k + 1]);
        }
        if (!out) {
#pragma unroll
          for (int o = 16; o; o >>= 1) sum += __shfl_xor_sync(~0u, sum, o);
          const float m = sum * (1.f / DM);
          float q = 0.f;
#pragma unroll
          for (int k = 0; k < 20; k++) { v[k] -= m; q += v[k] * v[k]; }
#pragma unroll
          for (int o = 16; o; o >>= 1) q += __shfl_xor_sync(~0u, q, o);
          const float rs = rsqrtf(q * (1.f / DM) + 1e-5f);
          uint8_t* xp = g_xt + (tk >> 7) * 163840 + (tk & 127) * 128 + (((lane >> 2) ^ (tk & 7)) << 4) + (lane & 3) * 4;
#pragma unroll
          for (int k = 0; k < 10; k++) *(uint32_t*)(xp + k * 16384) = pack2(v[2 * k] * rs, v[2 * k + 1] * rs);
        }
      }
      fence_async();
      __syncthreads();
      if (tid == 0 && !out) { red_release(flags + FL_LAYER + FL_T + (task >> 3) * 8, 1); }
    }
  }
  GT(layer * 4 + 2, 1);
  __syncwarp();
  asm volatile("griddepcontrol.wait;" ::: "memory");
  GT(layer * 4 + 2, 2);
}

constexpr int L_STAGE = 47104;
constexpr int L_KV = 0, L_B2 = 43008;
constexpr int L_BAR = 4 * L_STAGE;
constexpr int LA_SMEM = L_BAR + 256;
__device__ __forceinline__ float phi(float t) { return (fmaxf(t, 0.f) + 1e-6f) + ex2(fminf(t * 1.4426950408889634f, 0.f)); }
__device__ __forceinline__ void sqacc(uint32_t& h, uint32_t v) { asm("fma.rn.bf16x2 %0, %1, %1, %0;" : "+r"(h) : "r"(v)); }
__device__ __forceinline__ uint32_t phi2(float a, float b) { return pack2(phi(a), phi(b)); }
#define LA_LATE 6
#define PF_LB 1
#define PF_IL 1
#define PF_SLEEP1 400
#define PF_N0 2
#define PF_N1 0
#define PF_SLEEP 300

__global__ void __launch_bounds__(384, 1)
la_kernel(const bf16* __restrict__ Wq, const bf16* __restrict__ Wk, const bf16* __restrict__ Wv,
          const bf16* __restrict__ Wo, uint8_t* __restrict__ ar, int layer) {
  extern __shared__ __align__(1024) uint8_t smem[];
  const uint32_t sb = smem_u32(smem);
  check_smem_base(sb);
  const int tid = threadIdx.x, wid = __shfl_sync(~0u, tid >> 5, 0), wg = wid >> 2, w = wid & 3, lane = tid & 31, g = lane >> 2, i4 = lane & 3;
  const int cr = blockIdx.x & 1, hg = (blockIdx.x >> 1) & 7, tb = (blockIdx.x >> 4) * 2 + cr;
  const uint32_t bar = sb + L_BAR;
  uint32_t* flags = g_zero + Z_FLAGS + layer * FL_LAYER;
  asm volatile("griddepcontrol.launch_dependents;");
  GT(layer * 4, 0);
  if (wid == 0) {
    if (lane < 8) mbar_init(bar + 8 * lane, lane >= 4 ? (blockIdx.x < 128 ? 16 : 10) : 1);
    asm volatile("fence.mbarrier_init.release.cluster;" ::: "memory");
    fence_async();
  }
  if (blockIdx.x >= 128) {
    __syncthreads();
    const int q = blockIdx.x - 128;
    const uint8_t* src = (const uint8_t*)Wo + q * 1966080;
    if (wid == 11) {
#pragma unroll 1
      for (int it = 0; it < 48; it++) {
        const int st = it & 3;
        if (it >= 4) mbar_wait(bar + 8 * (4 + st), ((it >> 2) & 1) ^ 1);
        if (lane == 0) mbar_expect(bar + 8 * st, 40960);
        __syncwarp();
        if (lane < 4) bulk_g2s(sb + st * 40960 + lane * 10240, src + it * 40960 + lane * 10240, 10240, bar + 8 * st);
      }
    } else if (wid < 10) {
      float c[8] = {0.f, 0.f, 0.f, 0.f, 0.f, 0.f, 0.f, 0.f};
#pragma unroll 1
      for (int it = 0; it < 48; it++) {
        const int st = it & 3;
        mbar_wait(bar + 8 * st, (it >> 2) & 1);
        uint4 v[8];
#pragma unroll
        for (int k = 0; k < 8; k++) v[k] = lds4(sb + st * 40960 + k * 5120 + tid * 16);
        uint32_t h[4] = {0, 0, 0, 0};
#pragma unroll
        for (int k = 0; k < 8; k++) { sqacc(h[0], v[k].x); sqacc(h[1], v[k].y); sqacc(h[2], v[k].z); sqacc(h[3], v[k].w); }
        __syncwarp();
        if (lane == 0) mbar_arrive(bar + 8 * (4 + st));
#pragma unroll
        for (int k = 0; k < 4; k++) { c[2 * k] += bflo(h[k]); c[2 * k + 1] += bfhi(h[k]); }
      }
      float* red = (float*)(smem + 163840);
      *(float4*)(red + tid * 8) = make_float4(c[0], c[1], c[2], c[3]);
      *(float4*)(red + tid * 8 + 4) = make_float4(c[4], c[5], c[6], c[7]);
      bar_sync<1, 320>();
#pragma unroll
      for (int k = tid; k < DM; k += 320) g_nrm[q * DM + k] = (red[k] + red[DM + k]) + (red[2 * DM + k] + red[3 * DM + k]);
      asm volatile("griddepcontrol.wait;" ::: "memory");
      bar_sync<1, 320>();
      if (tid == 0) red_release(flags + FL_N, 1);
      GT(0, 2);
    }
    return;
  }
  __syncthreads();
  asm volatile("barrier.cluster.arrive.relaxed.aligned;" ::: "memory");
  if (layer == 0) asm volatile("griddepcontrol.wait;" ::: "memory");
  asm volatile("barrier.cluster.wait.aligned;" ::: "memory");
  if (wg == 2) {
    asm volatile("setmaxnreg.dec.sync.aligned.u32 40;");
    if (w == 0) {
      if (lane < 4) {
        mbar_expect(bar + 8 * lane, L_STAGE);
        bulk_g2s_mc(sb + lane * L_STAGE + 16384 + cr * 15360, g_w1 + (hg * 10 + lane) * 30720 + cr * 15360, 15360, bar + 8 * lane);
      }
      if (layer == 1) { if (LA_LATE) wait_flag(flags + FL_T + 15 * 8, LA_LATE); wait_flag(flags + FL_T + tb * 8, 8); fence_async_global(); }
      if (lane < 4) bulk_g2s(sb + lane * L_STAGE, g_xt + (tb * 10 + lane) * 16384, 16384, bar + 8 * lane);
#pragma unroll 1
      for (int kc = 4; kc < 10; kc++) {
        const int st = kc & 3;
        mbar_wait(bar + 8 * (4 + st), ((kc >> 2) & 1) ^ 1);
        if (lane == 0) {
          mbar_expect(bar + 8 * st, L_STAGE);
          bulk_g2s_mc(sb + st * L_STAGE + 16384 + cr * 15360, g_w1 + (hg * 10 + kc) * 30720 + cr * 15360, 15360, bar + 8 * st);
          bulk_g2s(sb + st * L_STAGE, g_xt + (tb * 10 + kc) * 16384, 16384, bar + 8 * st);
        }
        __syncwarp();
      }
    } else {
      const int t = tid - 288;
#pragma unroll 1
      for (int k = t; k < 768; k += 96) *(uint4*)(ar + blockIdx.x * 12288 + k * 16) = make_uint4(0, 0, 0, 0);
      if (layer == 0) {
        float sv = 0.f;
        const uint4* pv = (const uint4*)((const uint8_t*)Wv + blockIdx.x * 61440) + t;
#pragma unroll 1
        for (int k = 0; k < 40; k += 5) {
          uint4 v[5];
#pragma unroll
          for (int j = 0; j < 5; j++) v[j] = __ldg(pv + (k + j) * 96);
          if (PF_IL && k < 25) {
            asm volatile("prefetch.global.L2 [%0];" :: "l"((const uint8_t*)Wq + blockIdx.x * 61440 + (k / 5) * 12288 + t * 128));
            if (PF_IL > 1) asm volatile("prefetch.global.L2 [%0];" :: "l"((const uint8_t*)Wk + blockIdx.x * 61440 + (k / 5) * 12288 + t * 128));
          }
#pragma unroll
          for (int j = 0; j < 5; j++) {
            sv = fmaf(bflo(v[j].x), bflo(v[j].x), fmaf(bfhi(v[j].x), bfhi(v[j].x), fmaf(bflo(v[j].y), bflo(v[j].y), fmaf(bfhi(v[j].y), bfhi(v[j].y), sv))));
            sv = fmaf(bflo(v[j].z), bflo(v[j].z), fmaf(bfhi(v[j].z), bfhi(v[j].z), fmaf(bflo(v[j].w), bflo(v[j].w), fmaf(bfhi(v[j].w), bfhi(v[j].w), sv))));
          }
        }
#pragma unroll
        for (int o = 16; o; o >>= 1) sv += __shfl_xor_sync(~0u, sv, o);
        if (lane == 0) atomicAdd((float*)(g_zero + Z_NORM), sv);
      }
      if (layer == 1 && PF_LB) {
        const int l = blockIdx.x * 96 + t;
        if (l < 6720 + NLB * 640) asm volatile("prefetch.global.L2 [%0];" :: "l"(l < 6720 ? g_w2 + l * 128 : (const uint8_t*)g_x + (l - 6720) * 128));
      }
#pragma unroll 1
      for (int k = layer ? 0 : 5 * PF_IL; k < 5 * (layer ? PF_N1 : PF_N0); k++) {
        const int m = k / 5;
        const bf16* W = m == 0 ? Wq : m == 1 ? Wk : m == 2 ? Wv : Wo;
        asm volatile("prefetch.global.L2 [%0];" :: "l"((const uint8_t*)W + blockIdx.x * 61440 + (k - m * 5) * 12288 + t * 128));
        __nanosleep(layer ? PF_SLEEP1 : PF_SLEEP);
      }
      if (t == 0) GTT(layer * 4, 14);
      bar_arrive<3, 352>();
    }
  } else {
    asm volatile("setmaxnreg.inc.sync.aligned.u32 232;");
    GT(layer * 4, 4);
    uint32_t pq[5][4];
    float* kv = (float*)(g_zero + Z_KV) + layer * KV_LAYER + hg * 1920;
    {
      float d[120];
#pragma unroll 1
      for (int kc = 0; kc < 10; kc++) {
        const int st = kc & 3;
        const uint64_t da = mkdesc(SB0 + st * L_STAGE + wg * 8192, 16, 1024, 1), db = mkdesc(SB0 + st * L_STAGE + 16384, 3840, 128, 0);
        mbar_wait(bar + 8 * st, (kc >> 2) & 1);
        wg_fence();
#pragma unroll
        for (int k = 0; k < 4; k++) wg_ss_n240_ta0_tb1(d, da + 2 * k, db + k * 480, kc | k);
        wg_commit();
        if (kc > 0) { wg_wait<1>(); if (lane < 2) mbar_arrive_cl(mapa(bar + 8 * (4 + ((kc - 1) & 3)), lane)); }
      }
      wg_wait<0>();
      pin<120>(d);
      GT(layer * 4, 5);
      bar_sync<1, 256>();
      const uint32_t kb = sb + L_KV + (wg * 8 + 2 * w + ((lane >> 3) & 1)) * 2688 + (lane >> 4) * 128 + (lane & 7) * 16;
#pragma unroll
      for (int j = 0; j < 5; j++) stsm4(kb + 1280 + j * 256, pack2(d[80 + 8 * j], d[81 + 8 * j]), pack2(d[82 + 8 * j], d[83 + 8 * j]), pack2(d[84 + 8 * j], d[85 + 8 * j]), pack2(d[86 + 8 * j], d[87 + 8 * j]));
      stsm2(kb + 2560, 0x3F803F80u, 0x3F803F80u);
#pragma unroll
      for (int j = 0; j < 5; j++) stsm4(kb + j * 256, phi2(d[40 + 8 * j], d[41 + 8 * j]), phi2(d[42 + 8 * j], d[43 + 8 * j]), phi2(d[44 + 8 * j], d[45 + 8 * j]), phi2(d[46 + 8 * j], d[47 + 8 * j]));
      fence_async();
      bar_sync<1, 256>();
      float e[44];
      {
        const uint64_t da = mkdesc(SB0 + L_KV + wg * 1024, 2688, 128, 0), db = mkdesc(SB0 + L_KV + 1280, 2688, 128, 0);
        wg_fence();
#pragma unroll
        for (int k = 0; k < 8; k++) wg_ss_n88_ta1_tb1(e, da + k * 336, db + k * 336, k);
        wg_commit();
        wg_wait<0>();
        pin<44>(e);
      }
#pragma unroll
      for (int h = 0; h < 2; h++) {
        const int row = wg * 64 + 16 * w + 8 * h + g;
        const int c = row < 80 ? 2 * i4 - (row / 20) * 20 : 100;
        float* dst = kv + row * 24 + c;
#pragma unroll
        for (int j = 0; j < 10; j++)
          asm volatile("{\n.reg .pred p;\nsetp.lt.u32 p, %3, 20;\n@p red.relaxed.gpu.global.add.v2.f32 [%0], {%1,%2};\n}" :: "l"(dst + 8 * j), "f"(e[4 * j + 2 * h]), "f"(e[4 * j + 2 * h + 1]), "r"(c + 8 * j) : "memory");
        asm volatile("{\n.reg .pred p;\nsetp.ne.u32 p, %2, 0;\n@p red.relaxed.gpu.global.add.f32 [%0], %1;\n}" :: "l"(kv + row * 24 + 20), "f"(e[40 + 2 * h]), "r"((int)(row < 80 && i4 == 0)) : "memory");
      }
      bar_sync<1, 256>();
      GT(layer * 4, 6);
      if (tid == 0) { red_release(flags + FL_KV + hg * 8, 1); }
      __syncwarp();
      pin<40>(d);
#pragma unroll
      for (int k = 0; k < 5; k++) {
        pq[k][0] = phi2(d[8 * k], d[8 * k + 1]); pq[k][1] = phi2(d[8 * k + 2], d[8 * k + 3]);
        pq[k][2] = phi2(d[8 * k + 4], d[8 * k + 5]); pq[k][3] = phi2(d[8 * k + 6], d[8 * k + 7]);
      }
    }
#pragma unroll 1
    for (int k = tid; k < 1600; k += 256) sts4(sb + L_B2 + k * 16, 0, 0, 0, 0);
    GT(layer * 4, 7);
    if (wid == 0) wait_flag(flags + FL_KV + hg * 8, 16);
    GT(layer * 4, 8);
    bar_sync<1, 256>();
    if (tid < 240) {
      const int dd = tid / 3, part = tid - dd * 3, n = (dd / 20) * 20 + 8 * part;
      const float4 v0 = __ldcg((const float4*)(kv + dd * 24 + 8 * part)), v1 = __ldcg((const float4*)(kv + dd * 24 + 8 * part + 4));
      const float z = __ldcg(kv + dd * 24 + 20);
      const uint32_t a = sb + L_B2 + (dd >> 3) * 2560 + (dd & 7) * 16, zz = pack2(z, z);
      const uint32_t a0 = a + (n >> 3) * 128 + (n & 7) * 2, a1 = a + ((n + 4) >> 3) * 128 + ((n + 4) & 7) * 2;
      sts2(a0, pack2(v0.x, v0.y), pack2(v0.z, v0.w)); sts2(a0 + 1280, zz, zz);
      if (part < 2) { sts2(a1, pack2(v1.x, v1.y), pack2(v1.z, v1.w)); sts2(a1 + 1280, zz, zz); }
    }
    fence_async();
    bar_sync<1, 256>();
    {
      float o[80];
      const uint64_t db = mkdesc(SB0 + L_B2, 2560, 128, 0);
      wg_fence();
#pragma unroll
      for (int k = 0; k < 5; k++) wg_rs_n160_tb1(o, pq[k], db + k * 320, k);
      wg_commit();
      wg_wait<0>();
      pin<80>(o);
      uint8_t* op = g_oa + (tb * 2 + wg) * 81920 + hg * 10240 + w * 256 + lane * 4;
#pragma unroll
      for (int j = 0; j < 20; j++) {
        const float inv = rcp(o[40 + 2 * j] + 1e-6f);
        *(uint32_t*)(op + (j >> 1) * 1024 + (j & 1) * 128) = pack2(o[2 * j] * inv, o[2 * j + 1] * inv);
      }
      GT(layer * 4, 9);
    }
    bar_sync<3, 352>();
    if (tid == 0) { red_release(flags + FL_O + tb * 8, 1); red_add(flags + FL_X, 1); }
    GT(layer * 4, 2);
    if (wid == 7) asm volatile("griddepcontrol.wait;" ::: "memory");
  }
}

__global__ void __launch_bounds__(256) prep_kernel(const bf16* __restrict__ x, const bf16* __restrict__ wqkv, const bf16* __restrict__ wo) {
  asm volatile("griddepcontrol.launch_dependents;");
  const int b = blockIdx.x, tid = threadIdx.x, lane = tid & 31;
  if (b < 160) GT(3, 0);
  if (b < 256) {
    const int row = b * 8 + (tid >> 5);
    float v[20], s = 0.f;
#pragma unroll
    for (int k = 0; k < 10; k++) { const uint32_t u = __ldg((const uint32_t*)(x + row * DM + k * 64 + lane * 2)); v[2 * k] = bflo(u); v[2 * k + 1] = bfhi(u); s += v[2 * k] + v[2 * k + 1]; }
#pragma unroll
    for (int o = 16; o; o >>= 1) s += __shfl_xor_sync(~0u, s, o);
    const float m = s * (1.f / DM);
    float q = 0.f;
#pragma unroll
    for (int k = 0; k < 20; k++) { v[k] -= m; q += v[k] * v[k]; }
#pragma unroll
    for (int o = 16; o; o >>= 1) q += __shfl_xor_sync(~0u, q, o);
    const float r = rsqrtf(q * (1.f / DM) + 1e-5f);
#pragma unroll
    for (int k = 0; k < 10; k++)
      *(uint32_t*)(g_xt + ((row >> 7) * 10 + k) * 16384 + (row & 127) * 128 + (((lane >> 2) ^ (row & 7)) << 4) + (lane & 3) * 4) = pack2(v[2 * k] * r, v[2 * k + 1] * r);
  } else if (b < 256 + 203) {
#pragma unroll
    for (int it = 0; it < 4; it++) {
      const int u = (b - 256) * 1024 + it * 256 + tid;
      if (u < 153600) {
        const int k8 = u & 7, nb = (u >> 3) % 30, kg = (u / 240) % 80, hg = u / 19200;
        *(uint4*)(g_w1 + u * 16) = __ldg((const uint4*)(wqkv + (kg * 8 + k8) * 1920 + (nb / 10) * 640 + hg * 80 + (nb % 10) * 8));
      } else {
        const int v = u - 153600, k8 = v & 7, nb = (v >> 3) % 28, kg = (v / 224) % 80, c = (v / 17920) * 224 + nb * 8;
        if (v < 53760) *(uint4*)(g_w2 + v * 16) = c < DM ? __ldg((const uint4*)(wo + (kg * 8 + k8) * DM + c)) : make_uint4(0, 0, 0, 0);
      }
    }
  } else {
    const int t = (b - 459) * 256 + tid;
    for (int k = t; k < Z_END / 4; k += 16 * 256) ((uint4*)g_zero)[k] = make_uint4(0, 0, 0, 0);
    for (int k = t; k < 16 * DM; k += 16 * 256) { ((uint4*)g_acc)[k] = make_uint4(0, 0, 0, 0); ((uint4*)(g_acc + S_TOK * DM))[k] = make_uint4(0, 0, 0, 0); }
  }
  if (b < 160) GT(3, 2);
}

typedef CUresult (*EncodeFn)(CUtensorMap*, CUtensorMapDataType, cuuint32_t, void*, const cuuint64_t*, const cuuint64_t*, const cuuint32_t*,
                             const cuuint32_t*, CUtensorMapInterleave, CUtensorMapSwizzle, CUtensorMapL2promotion, CUtensorMapFloatOOBfill);
static void make_map(EncodeFn fn, CUtensorMap* m, const void* p, uint64_t cols, uint64_t rows, uint32_t bc, uint32_t br, CUtensorMapSwizzle sw) {
  cuuint64_t dims[2] = {cols, rows}; cuuint64_t strides[1] = {cols * 2}; cuuint32_t box[2] = {bc, br}; cuuint32_t es[2] = {1, 1};
  fn(m, CU_TENSOR_MAP_DATA_TYPE_BFLOAT16, 2, (void*)p, dims, strides, box, es, CU_TENSOR_MAP_INTERLEAVE_NONE, sw,
     CU_TENSOR_MAP_L2_PROMOTION_L2_128B, CU_TENSOR_MAP_FLOAT_OOB_FILL_NONE);
}

static void make_map_perm(EncodeFn fn, CUtensorMap* m, const void* p) {
  cuuint64_t dims[5] = {HE, 2, 2, 4, 40}; const cuuint64_t r = HE * 2; cuuint64_t strides[4] = {r, 8 * r, 2 * r, 16 * r};
  cuuint32_t box[5] = {64, 2, 2, 4, 4}; cuuint32_t es[5] = {1, 1, 1, 1, 1};
  fn(m, CU_TENSOR_MAP_DATA_TYPE_BFLOAT16, 5, (void*)p, dims, strides, box, es, CU_TENSOR_MAP_INTERLEAVE_NONE, CU_TENSOR_MAP_SWIZZLE_128B,
     CU_TENSOR_MAP_L2_PROMOTION_L2_128B, CU_TENSOR_MAP_FLOAT_OOB_FILL_NONE);
}

#define OPC_PDL 1
#define LA_PDL 1
#define REC_PDL 1
extern "C" void kernel_launch(void* const* d_in, const int* in_sizes, int n_in, void* d_out, int out_size) {
  const bf16* x = (const bf16*)d_in[0];
  const bf16* wqkv = (const bf16*)d_in[1];
  const bf16* wo_a = (const bf16*)d_in[2];
  const bf16* mem0 = (const bf16*)d_in[4];
  const bf16* Wq = (const bf16*)d_in[5];
  const bf16* Wk = (const bf16*)d_in[6];
  const bf16* Wv = (const bf16*)d_in[7];
  const bf16* Wo = (const bf16*)d_in[8];
  cudaStream_t st = cudaStreamPerThread;

  static EncodeFn enc = nullptr;
  static uint8_t* p_ar; static uint32_t* p_zero; static bf16* p_x;
  if (!enc) {
    cudaDriverEntryPointQueryResult qr;
    void* fn = nullptr;
    cudaGetDriverEntryPoint("cuTensorMapEncodeTiled", &fn, cudaEnableDefault, &qr);
    enc = (EncodeFn)fn;
    cudaFuncSetAttribute(rec_kernel, cudaFuncAttributeMaxDynamicSharedMemorySize, REC_SMEM);
    cudaFuncSetAttribute(opc_kernel, cudaFuncAttributeMaxDynamicSharedMemorySize, OPC_SMEM);
    cudaFuncSetAttribute(la_kernel, cudaFuncAttributeMaxDynamicSharedMemorySize, LA_SMEM);
    cudaGetSymbolAddress((void**)&p_ar, g_ar); p_ar = (uint8_t*)(((uintptr_t)p_ar + 32767) & ~(uintptr_t)32767);
    cudaGetSymbolAddress((void**)&p_zero, g_zero); cudaGetSymbolAddress((void**)&p_x, g_x);
  }
  CUtensorMap tmq, tmk, tmv, tmo, tmx[2];
  make_map_perm(enc, &tmq, Wq);
  make_map_perm(enc, &tmk, Wk);
  make_map_perm(enc, &tmv, Wv);
  make_map(enc, &tmo, Wo, DM, HE, 64, 64, CU_TENSOR_MAP_SWIZZLE_128B);
  make_map(enc, &tmx[0], x, DM, S_TOK, 232, 64, CU_TENSOR_MAP_SWIZZLE_NONE);
  make_map(enc, &tmx[1], p_x, DM, S_TOK, 232, 64, CU_TENSOR_MAP_SWIZZLE_NONE);

  cudaLaunchAttribute at[2];
  at[0].id = cudaLaunchAttributeProgrammaticStreamSerialization; at[0].val.programmaticStreamSerializationAllowed = 1;
  at[1].id = cudaLaunchAttributeClusterDimension; at[1].val.clusterDim.x = 3; at[1].val.clusterDim.y = 1; at[1].val.clusterDim.z = 1;
  cudaLaunchAttribute at2[2] = {at[1], at[0]};
  at2[0].val.clusterDim.x = 2;
  prep_kernel<<<475, 256, 0, st>>>(x, wqkv, wo_a);
  for (int l = 0; l < 2; l++) {
    cudaLaunchConfig_t cfg = {};
    cfg.blockDim = dim3(384); cfg.stream = st;
    cfg.gridDim = dim3(l == 0 ? 132 : 128); cfg.dynamicSmemBytes = LA_SMEM; cfg.attrs = at2; cfg.numAttrs = 1 + LA_PDL;
    cudaLaunchKernelEx(&cfg, la_kernel, Wq, Wk, Wv, Wo, p_ar + l * AR_LAYER, l);
    cfg.gridDim = dim3(96 + 3 * NLB); cfg.dynamicSmemBytes = REC_SMEM; cfg.attrs = at + 1 - REC_PDL; cfg.numAttrs = 1 + REC_PDL;
    cudaLaunchKernelEx(&cfg, rec_kernel, tmq, tmk, tmv, tmo, tmx[l], mem0, p_ar + l * AR_LAYER, p_zero + Z_FLAGS + l * FL_LAYER, l);
    cfg.gridDim = dim3(36); cfg.dynamicSmemBytes = OPC_SMEM; cfg.attrs = at; cfg.numAttrs = OPC_PDL;
    cudaLaunchKernelEx(&cfg, opc_kernel, tmo, l == 1 ? (bf16*)d_out : (bf16*)nullptr, l, Wq, Wk, Wv, Wo);
  }
}
```

```cpp
#include <cuda_runtime.h>
#include <cuda_bf16.h>
#include <cuda.h>
#include <stdint.h>

typedef __nv_bfloat16 bf16;
typedef unsigned long long u64;

constexpr int S_TOK = 2048, DM = 640, DH = 192, HE = 6144, NSEG = 64;

constexpr int AR_GROUP = 98304;
constexpr int AR_LAYER = 16 * AR_GROUP;
__device__ __align__(1024) uint8_t g_ar[2 * AR_LAYER + 32768];
__device__ __align__(1024) uint8_t g_xn[NSEG * 40960];
__device__ __align__(1024) uint8_t g_xt[S_TOK * DM * 2];
__device__ __align__(1024) uint8_t g_ot[NSEG * HE * 64];
__device__ __align__(1024) uint8_t g_oa[S_TOK * DM * 2];
__device__ __align__(1024) uint8_t g_w1[DM * 1920 * 2];
__device__ __align__(1024) uint8_t g_w2[DM * 672 * 2];
__device__ __align__(1024) float g_acc[2 * S_TOK * DM];
__device__ __align__(1024) bf16 g_x[S_TOK * DM];
constexpr int FL_A = 0, FL_B = 64 * 6 * 8, FL_KV = FL_B + 64 * 8, FL_O = FL_KV + 8 * 8, FL_T = FL_O + 16 * 8, FL_X = FL_T + 16 * 8, FL_N = FL_X + 8, FL_R = FL_N + 8, FL_XN = FL_R + 8, FL_LAYER = FL_XN + 32 * 8;
constexpr int Z_FLAGS = 0, Z_NORM = 2 * FL_LAYER, Z_KV = Z_NORM + 8, KV_LAYER = 8 * 80 * 24, Z_END = Z_KV + 2 * KV_LAYER;
__device__ __align__(128) uint32_t g_zero[Z_END];
__device__ __align__(128) float g_nrm[4 * DM];
#define GT(slot, k) do {} while (0)
#define GTT(slot, k) do {} while (0)

__device__ __forceinline__ uint32_t smem_u32(const void* p) { return (uint32_t)__cvta_generic_to_shared(p); }
__device__ __forceinline__ uint32_t mapa(uint32_t a, uint32_t r) { uint32_t o; asm("mapa.shared::cluster.u32 %0, %1, %2;" : "=r"(o) : "r"(a), "r"(r)); return o; }
__device__ __forceinline__ void mbar_init(uint32_t bar, uint32_t cnt) { asm volatile("mbarrier.init.shared::cta.b64 [%0], %1;" :: "r"(bar), "r"(cnt) : "memory"); }
__device__ __forceinline__ void mbar_expect(uint32_t bar, uint32_t tx) { asm volatile("mbarrier.arrive.expect_tx.shared::cta.b64 _, [%0], %1;" :: "r"(bar), "r"(tx) : "memory"); }
__device__ __forceinline__ void mbar_arrive(uint32_t bar) { asm volatile("mbarrier.arrive.shared::cta.b64 _, [%0];" :: "r"(bar) : "memory"); }
__device__ __forceinline__ void mbar_wait(uint32_t bar, uint32_t par) {
  asm volatile("{\n.reg .pred p;\n.reg .u32 c;\nmov.u32 c, 0;\n"
               "LW:\nmbarrier.try_wait.parity.shared::cta.b64 p, [%0], %1;\n@p bra LD;\n"
               "add.u32 c, c, 1;\nsetp.lt.u32 p, c, 4000000;\n@p bra LW;\ntrap;\nLD:\n}" :: "r"(bar), "r"(par) : "memory");
}
__device__ __forceinline__ void mbar_waitf(uint32_t bar, uint32_t par) {
  asm volatile("{\n.reg .pred p, q;\n.reg .u32 c;\nmov.u32 c, 0;\n"
               "LW:\nadd.u32 c, c, 1;\nsetp.lt.u32 q, c, 1000000;\nmbarrier.try_wait.parity.shared::cta.b64 p, [%0], %1;\n"
               "and.pred q, q, !p;\n@q bra LW;\n}" :: "r"(bar), "r"(par) : "memory");
}
template <int ID, int N> __device__ __forceinline__ void bar_sync() { asm volatile("barrier.sync %0, %1;" :: "n"(ID), "n"(N) : "memory"); }
template <int ID, int N> __device__ __forceinline__ void bar_arrive() { asm volatile("barrier.arrive %0, %1;" :: "n"(ID), "n"(N) : "memory"); }
__device__ __forceinline__ void fence_async() { asm volatile("fence.proxy.async.shared::cta;" ::: "memory"); }
__device__ __forceinline__ void cluster_sync() { asm volatile("barrier.cluster.arrive.aligned;\nbarrier.cluster.wait.aligned;" ::: "memory"); }
__device__ __forceinline__ void wg_fence() { asm volatile("wgmma.fence.sync.aligned;" ::: "memory"); }
__device__ __forceinline__ void wg_commit() { asm volatile("wgmma.commit_group.sync.aligned;" ::: "memory"); }
template <int N> __device__ __forceinline__ void wg_wait() { asm volatile("wgmma.wait_group.sync.aligned %0;" :: "n"(N) : "memory"); }
template <int N> __device__ __forceinline__ void pin(float* d) {
#pragma unroll
  for (int i = 0; i < N; i++) asm volatile("" : "+f"(d[i]) :: "memory");
}
__device__ __forceinline__ constexpr uint64_t mkdesc(uint32_t addr, uint32_t lbo, uint32_t sbo, int sw) {
  return (uint64_t)((addr & 0x3FFFF) >> 4) | ((uint64_t)(lbo >> 4) << 16) | ((uint64_t)(sbo >> 4) << 32) | ((uint64_t)sw << 62);
}
constexpr uint32_t SB0 = 1024;
__device__ __forceinline__ void check_smem_base(uint32_t sb) { if ((sb & 0x3FFFF) != SB0) __trap(); }
__device__ __forceinline__ uint32_t cta_rank() { uint32_t r; asm volatile("mov.u32 %0, %%cluster_ctarank;" : "=r"(r)); return r; }
__device__ __forceinline__ uint32_t opaque(uint32_t v) { uint32_t o; asm volatile("mov.u32 %0, %1;" : "=r"(o) : "r"(v)); return o; }
__device__ __forceinline__ uint32_t pack2(float lo, float hi) { uint32_t r; asm("cvt.rn.bf16x2.f32 %0, %1, %2;" : "=r"(r) : "f"(hi), "f"(lo)); return r; }
__device__ __forceinline__ void ldsm4(uint32_t* r, uint32_t a) { asm volatile("ldmatrix.sync.aligned.m8n8.x4.shared.b16 {%0,%1,%2,%3}, [%4];" : "=r"(r[0]), "=r"(r[1]), "=r"(r[2]), "=r"(r[3]) : "r"(a) : "memory"); }
__device__ __forceinline__ void ldsm4t(uint32_t* r, uint32_t a) { asm volatile("ldmatrix.sync.aligned.m8n8.x4.trans.shared.b16 {%0,%1,%2,%3}, [%4];" : "=r"(r[0]), "=r"(r[1]), "=r"(r[2]), "=r"(r[3]) : "r"(a) : "memory"); }
__device__ __forceinline__ void ldsm1(uint32_t& r, uint32_t a) { asm volatile("ldmatrix.sync.aligned.m8n8.x1.shared.b16 {%0}, [%1];" : "=r"(r) : "r"(a) : "memory"); }
__device__ __forceinline__ void stsm4(uint32_t a, uint32_t r0, uint32_t r1, uint32_t r2, uint32_t r3) { asm volatile("stmatrix.sync.aligned.m8n8.x4.shared.b16 [%0], {%1,%2,%3,%4};" :: "r"(a), "r"(r0), "r"(r1), "r"(r2), "r"(r3) : "memory"); }
__device__ __forceinline__ void stsm1(uint32_t a, uint32_t r0) { asm volatile("stmatrix.sync.aligned.m8n8.x1.shared.b16 [%0], {%1};" :: "r"(a), "r"(r0) : "memory"); }
__device__ __forceinline__ void stsm4t(uint32_t a, uint32_t r0, uint32_t r1, uint32_t r2, uint32_t r3) { asm volatile("stmatrix.sync.aligned.m8n8.x4.trans.shared.b16 [%0], {%1,%2,%3,%4};" :: "r"(a), "r"(r0), "r"(r1), "r"(r2), "r"(r3) : "memory"); }
__device__ __forceinline__ void stsm2t(uint32_t a, uint32_t r0, uint32_t r1) { asm volatile("stmatrix.sync.aligned.m8n8.x2.trans.shared.b16 [%0], {%1,%2};" :: "r"(a), "r"(r0), "r"(r1) : "memory"); }
__device__ __forceinline__ void mma16816(float* c, const uint32_t* a, uint32_t b0, uint32_t b1) {
  asm volatile("mma.sync.aligned.m16n8k16.row.col.f32.bf16.bf16.f32 {%0,%1,%2,%3}, {%4,%5,%6,%7}, {%8,%9}, {%0,%1,%2,%3};"
               : "+f"(c[0]), "+f"(c[1]), "+f"(c[2]), "+f"(c[3]) : "r"(a[0]), "r"(a[1]), "r"(a[2]), "r"(a[3]), "r"(b0), "r"(b1));
}
__device__ __forceinline__ void mma1688(float* c, uint32_t a0, uint32_t a1, uint32_t b0) {
  asm volatile("mma.sync.aligned.m16n8k8.row.col.f32.bf16.bf16.f32 {%0,%1,%2,%3}, {%4,%5}, {%6}, {%0,%1,%2,%3};"
               : "+f"(c[0]), "+f"(c[1]), "+f"(c[2]), "+f"(c[3]) : "r"(a0), "r"(a1), "r"(b0));
}
__device__ __forceinline__ void sta1(uint32_t a, uint32_t v, uint32_t bar) { asm volatile("st.async.weak.shared::cluster.mbarrier::complete_tx::bytes.b32 [%0], %1, [%2];" :: "r"(a), "r"(v), "r"(bar) : "memory"); }
__device__ __forceinline__ void sta1p(uint32_t a, uint32_t v, uint32_t bar, bool p) { asm volatile("{\n.reg .pred p;\nsetp.ne.b32 p, %3, 0;\n@p st.async.weak.shared::cluster.mbarrier::complete_tx::bytes.b32 [%0], %1, [%2];\n}" :: "r"(a), "r"(v), "r"(bar), "r"((int)p) : "memory"); }
__device__ __forceinline__ void sta2(uint32_t a, uint32_t v0, uint32_t v1, uint32_t bar) { asm volatile("st.async.weak.shared::cluster.mbarrier::complete_tx::bytes.v2.b32 [%0], {%1,%2}, [%3];" :: "r"(a), "r"(v0), "r"(v1), "r"(bar) : "memory"); }
__device__ __forceinline__ void sta4(uint32_t a, uint32_t v0, uint32_t v1, uint32_t v2, uint32_t v3, uint32_t bar) { asm volatile("st.async.weak.shared::cluster.mbarrier::complete_tx::bytes.v4.b32 [%0], {%1,%2,%3,%4}, [%5];" :: "r"(a), "r"(v0), "r"(v1), "r"(v2), "r"(v3), "r"(bar) : "memory"); }
__device__ __forceinline__ float bflo(uint32_t v) { return __uint_as_float(v << 16); }
__device__ __forceinline__ float bfhi(uint32_t v) { return __uint_as_float(v & 0xFFFF0000u); }
__device__ __forceinline__ void sta2f(uint32_t a, float v0, float v1, uint32_t bar) { asm volatile("st.async.weak.shared::cluster.mbarrier::complete_tx::bytes.v2.f32 [%0], {%1,%2}, [%3];" :: "r"(a), "f"(v0), "f"(v1), "r"(bar) : "memory"); }
__device__ __forceinline__ void sta4f(uint32_t a, float v0, float v1, float v2, float v3, uint32_t bar) { asm volatile("st.async.weak.shared::cluster.mbarrier::complete_tx::bytes.v4.f32 [%0], {%1,%2,%3,%4}, [%5];" :: "r"(a), "f"(v0), "f"(v1), "f"(v2), "f"(v3), "r"(bar) : "memory"); }
__device__ __forceinline__ float4 lds4f(uint32_t a) { float4 v; asm volatile("ld.shared.v4.f32 {%0,%1,%2,%3}, [%4];" : "=f"(v.x), "=f"(v.y), "=f"(v.z), "=f"(v.w) : "r"(a) : "memory"); return v; }
__device__ __forceinline__ float2 lds2f(uint32_t a) { float2 v; asm volatile("ld.shared.v2.f32 {%0,%1}, [%2];" : "=f"(v.x), "=f"(v.y) : "r"(a) : "memory"); return v; }
__device__ __forceinline__ uint4 lds4(uint32_t a) { uint4 v; asm volatile("ld.shared.v4.u32 {%0,%1,%2,%3}, [%4];" : "=r"(v.x), "=r"(v.y), "=r"(v.z), "=r"(v.w) : "r"(a) : "memory"); return v; }
__device__ __forceinline__ uint32_t lds1(uint32_t a) { uint32_t v; asm volatile("ld.shared.u32 %0, [%1];" : "=r"(v) : "r"(a) : "memory"); return v; }
__device__ __forceinline__ void stsm2(uint32_t a, uint32_t r0, uint32_t r1) { asm volatile("stmatrix.sync.aligned.m8n8.x2.shared.b16 [%0], {%1,%2};" :: "r"(a), "r"(r0), "r"(r1) : "memory"); }
__device__ __forceinline__ float rcp(float x) { float y; asm("rcp.approx.ftz.f32 %0, %1;" : "=f"(y) : "f"(x)); return y; }
__device__ __forceinline__ void sts4(uint32_t a, uint32_t v0, uint32_t v1, uint32_t v2, uint32_t v3) { asm volatile("st.shared.v4.u32 [%0], {%1,%2,%3,%4};" :: "r"(a), "r"(v0), "r"(v1), "r"(v2), "r"(v3) : "memory"); }
__device__ __forceinline__ void bulk_s2c(uint32_t dst, uint32_t src, uint32_t bytes, uint32_t bar) {
  asm volatile("cp.async.bulk.shared::cluster.shared::cta.mbarrier::complete_tx::bytes [%0], [%1], %2, [%3];" :: "r"(dst), "r"(src), "r"(bytes), "r"(bar) : "memory");
}
__device__ __forceinline__ void stg4(void* p, uint4 v) { asm volatile("st.global.v4.u32 [%0], {%1,%2,%3,%4};" :: "l"(p), "r"(v.x), "r"(v.y), "r"(v.z), "r"(v.w) : "memory"); }
__device__ __forceinline__ void red_add(uint32_t* p, uint32_t v) { asm volatile("red.relaxed.gpu.global.add.u32 [%0], %1;" :: "l"(p), "r"(v) : "memory"); }
__device__ __forceinline__ void red_release(uint32_t* p, uint32_t v) { asm volatile("red.release.gpu.global.add.u32 [%0], %1;" :: "l"(p), "r"(v) : "memory"); }
__device__ __forceinline__ void fence_async_global() { asm volatile("fence.proxy.async.global;" ::: "memory"); }
__device__ __forceinline__ uint64_t policy_evict_first() { uint64_t p; asm("createpolicy.fractional.L2::evict_first.b64 %0, 1.0;" : "=l"(p)); return p; }
__device__ __forceinline__ void stg4h(void* p, uint4 v, uint64_t pol) { asm volatile("st.global.L2::cache_hint.v4.u32 [%0], {%1,%2,%3,%4}, %5;" :: "l"(p), "r"(v.x), "r"(v.y), "r"(v.z), "r"(v.w), "l"(pol) : "memory"); }
__device__ __forceinline__ void red4fh(float* p, float a, float b, float c, float d, uint64_t pol) { asm volatile("red.relaxed.gpu.global.add.L2::cache_hint.v4.f32 [%0], {%1,%2,%3,%4}, %5;" :: "l"(p), "f"(a), "f"(b), "f"(c), "f"(d), "l"(pol) : "memory"); }
__device__ __forceinline__ float4 ldg4fh(const float* p, uint64_t pol) { float4 v; asm volatile("ld.global.cg.L2::cache_hint.v4.f32 {%0,%1,%2,%3}, [%4], %5;" : "=f"(v.x), "=f"(v.y), "=f"(v.z), "=f"(v.w) : "l"(p), "l"(pol) : "memory"); return v; }
__device__ __forceinline__ void bulk_g2sh(uint32_t dst, const void* src, uint32_t bytes, uint32_t bar, uint64_t pol) {
  asm volatile("cp.async.bulk.shared::cluster.global.mbarrier::complete_tx::bytes.L2::cache_hint [%0], [%1], %2, [%3], %4;" :: "r"(dst), "l"(src), "r"(bytes), "r"(bar), "l"(pol) : "memory");
}
#define OT_MASK 63
#define AC_MASK 63
#define EVF 1
__device__ __forceinline__ void red4f(float* p, float a, float b, float c, float d) { asm volatile("red.relaxed.gpu.global.add.v4.f32 [%0], {%1,%2,%3,%4};" :: "l"(p), "f"(a), "f"(b), "f"(c), "f"(d) : "memory"); }
template <int SLEEP = 20>
__device__ __forceinline__ void wait_flag(const uint32_t* p, uint32_t target) {
  uint32_t v; int it = 0;
  while (true) {
    asm volatile("ld.acquire.gpu.global.u32 %0, [%1];" : "=r"(v) : "l"(p) : "memory");
    if (__all_sync(~0u, v >= target)) break;
    if (++it > 4000000) __trap();
    __nanosleep(SLEEP);
  }
}
__device__ __forceinline__ void sts2(uint32_t a, uint32_t v0, uint32_t v1) { asm volatile("st.shared.v2.u32 [%0], {%1,%2};" :: "r"(a), "r"(v0), "r"(v1) : "memory"); }
__device__ __forceinline__ float sqrt_approx(float x) { float y; asm("sqrt.approx.f32 %0, %1;" : "=f"(y) : "f"(x)); return y; }
template <int BYTES> __device__ __forceinline__ void bulk_s2c_elect(uint32_t d1, uint32_t b1, uint32_t d2, uint32_t b2, uint32_t src) {
  asm volatile("{\n.reg .pred p;\nelect.sync _|p, 0xffffffff;\n"
               "@p cp.async.bulk.shared::cluster.shared::cta.mbarrier::complete_tx::bytes [%0], [%4], %5, [%1];\n"
               "@p cp.async.bulk.shared::cluster.shared::cta.mbarrier::complete_tx::bytes [%2], [%4], %5, [%3];\n}"
               :: "r"(d1), "r"(b1), "r"(d2), "r"(b2), "r"(src), "n"(BYTES) : "memory");
}
__device__ __forceinline__ void mbar_arrive_elect(uint32_t bar) { asm volatile("{\n.reg .pred p;\nelect.sync _|p, 0xffffffff;\n@p mbarrier.arrive.shared::cta.b64 _, [%0];\n}" :: "r"(bar) : "memory"); }
__device__ __forceinline__ void cp16(uint32_t dst, const void* src) { asm volatile("cp.async.cg.shared.global [%0], [%1], 16;" :: "r"(dst), "l"(src) : "memory"); }
__device__ __forceinline__ void sts1(uint32_t a, uint32_t v) { asm volatile("st.shared.u32 [%0], %1;" :: "r"(a), "r"(v) : "memory"); }
__device__ __forceinline__ void bulk_g2s(uint32_t dst, const void* src, uint32_t bytes, uint32_t bar) {
  asm volatile("cp.async.bulk.shared::cluster.global.mbarrier::complete_tx::bytes [%0], [%1], %2, [%3];" :: "r"(dst), "l"(src), "r"(bytes), "r"(bar) : "memory");
}
__device__ __forceinline__ void bulk_g2s_mc(uint32_t dst, const void* src, uint32_t bytes, uint32_t bar) {
  asm volatile("cp.async.bulk.shared::cluster.global.mbarrier::complete_tx::bytes.multicast::cluster [%0], [%1], %2, [%3], %4;" :: "r"(dst), "l"(src), "r"(bytes), "r"(bar), "h"((uint16_t)3) : "memory");
}
__device__ __forceinline__ void mbar_arrive_cl(uint32_t bar) { asm volatile("mbarrier.arrive.shared::cluster.b64 _, [%0];" :: "r"(bar) : "memory"); }
__device__ __forceinline__ void tma2d(uint32_t dst, const CUtensorMap* m, int c0, int c1, uint32_t bar) {
  asm volatile("cp.async.bulk.tensor.2d.shared::cluster.global.mbarrier::complete_tx::bytes [%0], [%1, {%3, %4}], [%2];" :: "r"(dst), "l"((uint64_t)m), "r"(bar), "r"(c0), "r"(c1) : "memory");
}
__device__ __forceinline__ void tma5d(uint32_t dst, const CUtensorMap* m, int c0, int c4, uint32_t bar) {
  asm volatile("cp.async.bulk.tensor.5d.shared::cluster.global.mbarrier::complete_tx::bytes [%0], [%1, {%3, %5, %5, %5, %4}], [%2];" :: "r"(dst), "l"((uint64_t)m), "r"(bar), "r"(c0), "r"(c4), "r"(0) : "memory");
}
__device__ __forceinline__ void red64(void* p, uint32_t lo, uint32_t hi) { asm volatile("{\n.reg .b64 t;\nmov.b64 t, {%1,%2};\nred.relaxed.gpu.global.add.u64 [%0], t;\n}" :: "l"(p), "r"(lo), "r"(hi) : "memory"); }
__device__ __forceinline__ uint4 ld_poll(const void* p) {
  uint4 v;
  asm volatile("{\n.reg .b64 a, b;\nld.relaxed.gpu.global.v2.b64 {a, b}, [%4];\nmov.b64 {%0,%1}, a;\nmov.b64 {%2,%3}, b;\n}" : "=r"(v.x), "=r"(v.y), "=r"(v.z), "=r"(v.w) : "l"(p) : "memory");
  return v;
}
__device__ __forceinline__ uint32_t clk() { uint32_t c; asm volatile("mov.u32 %0, %%clock;" : "=r"(c) :: "memory"); return c; }
#define SCHED_FENCE() asm volatile("pmevent 0;" ::: "memory")
__device__ __forceinline__ float ex2(float x) { float y; asm("ex2.approx.ftz.f32 %0, %1;" : "=f"(y) : "f"(x)); return y; }

__device__ __forceinline__ void wg_ss_n240_ta0_tb1(float* d, uint64_t a, uint64_t b, int sc) {
  asm volatile("{\n.reg .pred p;\nsetp.ne.b32 p, %122, 0;\nwgmma.mma_async.sync.aligned.m64n240k16.f32.bf16.bf16 {%0, %1, %2, %3, %4, %5, %6, %7, %8, %9, %10, %11, %12, %13, %14, %15, %16, %17, %18, %19, %20, %21, %22, %23, %24, %25, %26, %27, %28, %29, %30, %31, %32, %33, %34, %35, %36, %37, %38, %39, %40, %41, %42, %43, %44, %45, %46, %47, %48, %49, %50, %51, %52, %53, %54, %55, %56, %57, %58, %59, %60, %61, %62, %63, %64, %65, %66, %67, %68, %69, %70, %71, %72, %73, %74, %75, %76, %77, %78, %79, %80, %81, %82, %83, %84, %85, %86, %87, %88, %89, %90, %91, %92, %93, %94, %95, %96, %97, %98, %99, %100, %101, %102, %103, %104, %105, %106, %107, %108, %109, %110, %111, %112, %113, %114, %115, %116, %117, %118, %119}, %120, %121, p, 1, 1, 0, 1;\n}\n"
    : "+f"(d[0]), "+f"(d[1]), "+f"(d[2]), "+f"(d[3]), "+f"(d[4]), "+f"(d[5]), "+f"(d[6]), "+f"(d[7]), "+f"(d[8]), "+f"(d[9]), "+f"(d[10]), "+f"(d[11]), "+f"(d[12]), "+f"(d[13]), "+f"(d[14]), "+f"(d[15]), "+f"(d[16]), "+f"(d[17]), "+f"(d[18]), "+f"(d[19]), "+f"(d[20]), "+f"(d[21]), "+f"(d[22]), "+f"(d[23]), "+f"(d[24]), "+f"(d[25]), "+f"(d[26]), "+f"(d[27]), "+f"(d[28]), "+f"(d[29]), "+f"(d[30]), "+f"(d[31]), "+f"(d[32]), "+f"(d[33]), "+f"(d[34]), "+f"(d[35]), "+f"(d[36]), "+f"(d[37]), "+f"(d[38]), "+f"(d[39]), "+f"(d[40]), "+f"(d[41]), "+f"(d[42]), "+f"(d[43]), "+f"(d[44]), "+f"(d[45]), "+f"(d[46]), "+f"(d[47]), "+f"(d[48]), "+f"(d[49]), "+f"(d[50]), "+f"(d[51]), "+f"(d[52]), "+f"(d[53]), "+f"(d[54]), "+f"(d[55]), "+f"(d[56]), "+f"(d[57]), "+f"(d[58]), "+f"(d[59]), "+f"(d[60]), "+f"(d[61]), "+f"(d[62]), "+f"(d[63]), "+f"(d[64]), "+f"(d[65]), "+f"(d[66]), "+f"(d[67]), "+f"(d[68]), "+f"(d[69]), "+f"(d[70]), "+f"(d[71]), "+f"(d[72]), "+f"(d[73]), "+f"(d[74]), "+f"(d[75]), "+f"(d[76]), "+f"(d[77]), "+f"(d[78]), "+f"(d[79]), "+f"(d[80]), "+f"(d[81]), "+f"(d[82]), "+f"(d[83]), "+f"(d[84]), "+f"(d[85]), "+f"(d[86]), "+f"(d[87]), "+f"(d[88]), "+f"(d[89]), "+f"(d[90]), "+f"(d[91]), "+f"(d[92]), "+f"(d[93]), "+f"(d[94]), "+f"(d[95]), "+f"(d[96]), "+f"(d[97]), "+f"(d[98]), "+f"(d[99]), "+f"(d[100]), "+f"(d[101]), "+f"(d[102]), "+f"(d[103]), "+f"(d[104]), "+f"(d[105]), "+f"(d[106]), "+f"(d[107]), "+f"(d[108]), "+f"(d[109]), "+f"(d[110]), "+f"(d[111]), "+f"(d[112]), "+f"(d[113]), "+f"(d[114]), "+f"(d[115]), "+f"(d[116]), "+f"(d[117]), "+f"(d[118]), "+f"(d[119])
    : "l"(a), "l"(b), "r"(sc));
}
__device__ __forceinline__ void wg_ss_n88_ta1_tb1(float* d, uint64_t a, uint64_t b, int sc) {
  asm volatile("{\n.reg .pred p;\nsetp.ne.b32 p, %46, 0;\nwgmma.mma_async.sync.aligned.m64n88k16.f32.bf16.bf16 {%0, %1, %2, %3, %4, %5, %6, %7, %8, %9, %10, %11, %12, %13, %14, %15, %16, %17, %18, %19, %20, %21, %22, %23, %24, %25, %26, %27, %28, %29, %30, %31, %32, %33, %34, %35, %36, %37, %38, %39, %40, %41, %42, %43}, %44, %45, p, 1, 1, 1, 1;\n}\n"
    : "+f"(d[0]), "+f"(d[1]), "+f"(d[2]), "+f"(d[3]), "+f"(d[4]), "+f"(d[5]), "+f"(d[6]), "+f"(d[7]), "+f"(d[8]), "+f"(d[9]), "+f"(d[10]), "+f"(d[11]), "+f"(d[12]), "+f"(d[13]), "+f"(d[14]), "+f"(d[15]), "+f"(d[16]), "+f"(d[17]), "+f"(d[18]), "+f"(d[19]), "+f"(d[20]), "+f"(d[21]), "+f"(d[22]), "+f"(d[23]), "+f"(d[24]), "+f"(d[25]), "+f"(d[26]), "+f"(d[27]), "+f"(d[28]), "+f"(d[29]), "+f"(d[30]), "+f"(d[31]), "+f"(d[32]), "+f"(d[33]), "+f"(d[34]), "+f"(d[35]), "+f"(d[36]), "+f"(d[37]), "+f"(d[38]), "+f"(d[39]), "+f"(d[40]), "+f"(d[41]), "+f"(d[42]), "+f"(d[43])
    : "l"(a), "l"(b), "r"(sc));
}
__device__ __forceinline__ void wg_rs_n160_tb1(float* d, const uint32_t* a, uint64_t b, int sc) {
  asm volatile("{\n.reg .pred p;\nsetp.ne.b32 p, %85, 0;\nwgmma.mma_async.sync.aligned.m64n160k16.f32.bf16.bf16 {%0, %1, %2, %3, %4, %5, %6, %7, %8, %9, %10, %11, %12, %13, %14, %15, %16, %17, %18, %19, %20, %21, %22, %23, %24, %25, %26, %27, %28, %29, %30, %31, %32, %33, %34, %35, %36, %37, %38, %39, %40, %41, %42, %43, %44, %45, %46, %47, %48, %49, %50, %51, %52, %53, %54, %55, %56, %57, %58, %59, %60, %61, %62, %63, %64, %65, %66, %67, %68, %69, %70, %71, %72, %73, %74, %75, %76, %77, %78, %79}, {%80, %81, %82, %83}, %84, p, 1, 1, 1;\n}\n"
    : "+f"(d[0]), "+f"(d[1]), "+f"(d[2]), "+f"(d[3]), "+f"(d[4]), "+f"(d[5]), "+f"(d[6]), "+f"(d[7]), "+f"(d[8]), "+f"(d[9]), "+f"(d[10]), "+f"(d[11]), "+f"(d[12]), "+f"(d[13]), "+f"(d[14]), "+f"(d[15]), "+f"(d[16]), "+f"(d[17]), "+f"(d[18]), "+f"(d[19]), "+f"(d[20]), "+f"(d[21]), "+f"(d[22]), "+f"(d[23]), "+f"(d[24]), "+f"(d[25]), "+f"(d[26]), "+f"(d[27]), "+f"(d[28]), "+f"(d[29]), "+f"(d[30]), "+f"(d[31]), "+f"(d[32]), "+f"(d[33]), "+f"(d[34]), "+f"(d[35]), "+f"(d[36]), "+f"(d[37]), "+f"(d[38]), "+f"(d[39]), "+f"(d[40]), "+f"(d[41]), "+f"(d[42]), "+f"(d[43]), "+f"(d[44]), "+f"(d[45]), "+f"(d[46]), "+f"(d[47]), "+f"(d[48]), "+f"(d[49]), "+f"(d[50]), "+f"(d[51]), "+f"(d[52]), "+f"(d[53]), "+f"(d[54]), "+f"(d[55]), "+f"(d[56]), "+f"(d[57]), "+f"(d[58]), "+f"(d[59]), "+f"(d[60]), "+f"(d[61]), "+f"(d[62]), "+f"(d[63]), "+f"(d[64]), "+f"(d[65]), "+f"(d[66]), "+f"(d[67]), "+f"(d[68]), "+f"(d[69]), "+f"(d[70]), "+f"(d[71]), "+f"(d[72]), "+f"(d[73]), "+f"(d[74]), "+f"(d[75]), "+f"(d[76]), "+f"(d[77]), "+f"(d[78]), "+f"(d[79])
    : "r"(a[0]), "r"(a[1]), "r"(a[2]), "r"(a[3]), "l"(b), "r"(sc));
}
__device__ __forceinline__ void wg_ss_n112_ta0_tb1(float* d, uint64_t a, uint64_t b, int sc) {
  asm volatile("{\n.reg .pred p;\nsetp.ne.b32 p, %58, 0;\nwgmma.mma_async.sync.aligned.m64n112k16.f32.bf16.bf16 {%0, %1, %2, %3, %4, %5, %6, %7, %8, %9, %10, %11, %12, %13, %14, %15, %16, %17, %18, %19, %20, %21, %22, %23, %24, %25, %26, %27, %28, %29, %30, %31, %32, %33, %34, %35, %36, %37, %38, %39, %40, %41, %42, %43, %44, %45, %46, %47, %48, %49, %50, %51, %52, %53, %54, %55}, %56, %57, p, 1, 1, 0, 1;\n}\n"
    : "+f"(d[0]), "+f"(d[1]), "+f"(d[2]), "+f"(d[3]), "+f"(d[4]), "+f"(d[5]), "+f"(d[6]), "+f"(d[7]), "+f"(d[8]), "+f"(d[9]), "+f"(d[10]), "+f"(d[11]), "+f"(d[12]), "+f"(d[13]), "+f"(d[14]), "+f"(d[15]), "+f"(d[16]), "+f"(d[17]), "+f"(d[18]), "+f"(d[19]), "+f"(d[20]), "+f"(d[21]), "+f"(d[22]), "+f"(d[23]), "+f"(d[24]), "+f"(d[25]), "+f"(d[26]), "+f"(d[27]), "+f"(d[28]), "+f"(d[29]), "+f"(d[30]), "+f"(d[31]), "+f"(d[32]), "+f"(d[33]), "+f"(d[34]), "+f"(d[35]), "+f"(d[36]), "+f"(d[37]), "+f"(d[38]), "+f"(d[39]), "+f"(d[40]), "+f"(d[41]), "+f"(d[42]), "+f"(d[43]), "+f"(d[44]), "+f"(d[45]), "+f"(d[46]), "+f"(d[47]), "+f"(d[48]), "+f"(d[49]), "+f"(d[50]), "+f"(d[51]), "+f"(d[52]), "+f"(d[53]), "+f"(d[54]), "+f"(d[55])
    : "l"(a), "l"(b), "r"(sc));
}
__device__ __forceinline__ void wg_rs_n32_tb1(float* d, const uint32_t* a, uint64_t b, int sc) {
  asm volatile("{\n.reg .pred p;\nsetp.ne.b32 p, %21, 0;\nwgmma.mma_async.sync.aligned.m64n32k16.f32.bf16.bf16 {%0, %1, %2, %3, %4, %5, %6, %7, %8, %9, %10, %11, %12, %13, %14, %15}, {%16, %17, %18, %19}, %20, p, 1, 1, 1;\n}\n"
    : "+f"(d[0]), "+f"(d[1]), "+f"(d[2]), "+f"(d[3]), "+f"(d[4]), "+f"(d[5]), "+f"(d[6]), "+f"(d[7]), "+f"(d[8]), "+f"(d[9]), "+f"(d[10]), "+f"(d[11]), "+f"(d[12]), "+f"(d[13]), "+f"(d[14]), "+f"(d[15])
    : "r"(a[0]), "r"(a[1]), "r"(a[2]), "r"(a[3]), "l"(b), "r"(sc));
}
__device__ __forceinline__ void wg_ss_n32_ta1_tb1(float* d, uint64_t a, uint64_t b, int sc) {
  asm volatile("{\n.reg .pred p;\nsetp.ne.b32 p, %18, 0;\nwgmma.mma_async.sync.aligned.m64n32k16.f32.bf16.bf16 {%0, %1, %2, %3, %4, %5, %6, %7, %8, %9, %10, %11, %12, %13, %14, %15}, %16, %17, p, 1, 1, 1, 1;\n}\n"
    : "+f"(d[0]), "+f"(d[1]), "+f"(d[2]), "+f"(d[3]), "+f"(d[4]), "+f"(d[5]), "+f"(d[6]), "+f"(d[7]), "+f"(d[8]), "+f"(d[9]), "+f"(d[10]), "+f"(d[11]), "+f"(d[12]), "+f"(d[13]), "+f"(d[14]), "+f"(d[15])
    : "l"(a), "l"(b), "r"(sc));
}
__device__ __forceinline__ void wg_rs_n32_tb0(float* d, const uint32_t* a, uint64_t b, int sc) {
  asm volatile("{\n.reg .pred p;\nsetp.ne.b32 p, %21, 0;\nwgmma.mma_async.sync.aligned.m64n32k16.f32.bf16.bf16 {%0, %1, %2, %3, %4, %5, %6, %7, %8, %9, %10, %11, %12, %13, %14, %15}, {%16, %17, %18, %19}, %20, p, 1, 1, 0;\n}\n"
    : "+f"(d[0]), "+f"(d[1]), "+f"(d[2]), "+f"(d[3]), "+f"(d[4]), "+f"(d[5]), "+f"(d[6]), "+f"(d[7]), "+f"(d[8]), "+f"(d[9]), "+f"(d[10]), "+f"(d[11]), "+f"(d[12]), "+f"(d[13]), "+f"(d[14]), "+f"(d[15])
    : "r"(a[0]), "r"(a[1]), "r"(a[2]), "r"(a[3]), "l"(b), "r"(sc));
}
__device__ __forceinline__ void wg_rs_n40_tb0(float* d, const uint32_t* a, uint64_t b, int sc) {
  asm volatile("{\n.reg .pred p;\nsetp.ne.b32 p, %25, 0;\nwgmma.mma_async.sync.aligned.m64n40k16.f32.bf16.bf16 {%0, %1, %2, %3, %4, %5, %6, %7, %8, %9, %10, %11, %12, %13, %14, %15, %16, %17, %18, %19}, {%20, %21, %22, %23}, %24, p, 1, 1, 0;\n}\n"
    : "+f"(d[0]), "+f"(d[1]), "+f"(d[2]), "+f"(d[3]), "+f"(d[4]), "+f"(d[5]), "+f"(d[6]), "+f"(d[7]), "+f"(d[8]), "+f"(d[9]), "+f"(d[10]), "+f"(d[11]), "+f"(d[12]), "+f"(d[13]), "+f"(d[14]), "+f"(d[15]), "+f"(d[16]), "+f"(d[17]), "+f"(d[18]), "+f"(d[19])
    : "r"(a[0]), "r"(a[1]), "r"(a[2]), "r"(a[3]), "l"(b), "r"(sc));
}
__device__ __forceinline__ void wg_rs_n8_tb1(float* d, const uint32_t* a, uint64_t b, int sc) {
  asm volatile("{\n.reg .pred p;\nsetp.ne.b32 p, %9, 0;\nwgmma.mma_async.sync.aligned.m64n8k16.f32.bf16.bf16 {%0, %1, %2, %3}, {%4, %5, %6, %7}, %8, p, 1, 1, 1;\n}\n"
    : "+f"(d[0]), "+f"(d[1]), "+f"(d[2]), "+f"(d[3])
    : "r"(a[0]), "r"(a[1]), "r"(a[2]), "r"(a[3]), "l"(b), "r"(sc));
}
__device__ __forceinline__ void wg_ss_n40_ta0_tb0(float* d, uint64_t a, uint64_t b, int sc) {
  asm volatile("{\n.reg .pred p;\nsetp.ne.b32 p, %22, 0;\nwgmma.mma_async.sync.aligned.m64n40k16.f32.bf16.bf16 {%0, %1, %2, %3, %4, %5, %6, %7, %8, %9, %10, %11, %12, %13, %14, %15, %16, %17, %18, %19}, %20, %21, p, 1, 1, 0, 0;\n}\n"
    : "+f"(d[0]), "+f"(d[1]), "+f"(d[2]), "+f"(d[3]), "+f"(d[4]), "+f"(d[5]), "+f"(d[6]), "+f"(d[7]), "+f"(d[8]), "+f"(d[9]), "+f"(d[10]), "+f"(d[11]), "+f"(d[12]), "+f"(d[13]), "+f"(d[14]), "+f"(d[15]), "+f"(d[16]), "+f"(d[17]), "+f"(d[18]), "+f"(d[19])
    : "l"(a), "l"(b), "r"(sc));
}
__device__ __forceinline__ void wg_ss_n40_ta1_tb0(float* d, uint64_t a, uint64_t b, int sc) {
  asm volatile("{\n.reg .pred p;\nsetp.ne.b32 p, %22, 0;\nwgmma.mma_async.sync.aligned.m64n40k16.f32.bf16.bf16 {%0, %1, %2, %3, %4, %5, %6, %7, %8, %9, %10, %11, %12, %13, %14, %15, %16, %17, %18, %19}, %20, %21, p, 1, 1, 1, 0;\n}\n"
    : "+f"(d[0]), "+f"(d[1]), "+f"(d[2]), "+f"(d[3]), "+f"(d[4]), "+f"(d[5]), "+f"(d[6]), "+f"(d[7]), "+f"(d[8]), "+f"(d[9]), "+f"(d[10]), "+f"(d[11]), "+f"(d[12]), "+f"(d[13]), "+f"(d[14]), "+f"(d[15]), "+f"(d[16]), "+f"(d[17]), "+f"(d[18]), "+f"(d[19])
    : "l"(a), "l"(b), "r"(sc));
}
__device__ __forceinline__ void wg_ss_n8_ta1_tb1(float* d, uint64_t a, uint64_t b, int sc) {
  asm volatile("{\n.reg .pred p;\nsetp.ne.b32 p, %6, 0;\nwgmma.mma_async.sync.aligned.m64n8k16.f32.bf16.bf16 {%0, %1, %2, %3}, %4, %5, p, 1, 1, 1, 1;\n}\n"
    : "+f"(d[0]), "+f"(d[1]), "+f"(d[2]), "+f"(d[3])
    : "l"(a), "l"(b), "r"(sc));
}

constexpr int O_WV = 0, O_WO = 81920, O_H = 163840, O_QK = 215040, O_SM = 228352, O_MISC = 229632;
constexpr int O_QM = O_QK + 1024, O_K = O_QK + 3072, O_OG = O_QK + 8192;
constexpr int SM_SLOT = 640;
constexpr int O_MAXS = O_MISC;
constexpr int O_BAR = O_MISC + 64;
constexpr int MB_XF = 0, MB_ML = 2, MB_MR = 4, MB_PF = 6, MB_SM = 7, MB_SX = 8, MB_OG = 9, MB_W = 10, MB_WC = 30;
constexpr int O_PROF = O_BAR + 8 * 40;
constexpr int O_STG = O_PROF + 128;
constexpr int REC_SMEM = O_STG + 2176;
constexpr int B_VOWN = 0, B_QK = 1, B_VGO = 2, B_ML0 = 3, B_PM = 4, B_PX = 5, B_XGO = 6, B_ML1 = 7, B_WG2 = 8, B_VHALF = 9, B_VDONE = 10,
              B_MR = 11, B_SSENT = 12, B_SLD = 13, B_VEND = 14, B_XGO1 = 15;
#define POLL_A 400
#define POLL_B 500
#define POLL_C 600
#define OX_W 0
#define OX_T 0
#define POLL_D0 300
#define TS0(idx) do {} while (0)
#define TS(idx) do {} while (0)
#define SLD_POS 0
#define W_OPEN 16
#define PSL 200
#define W_WIN 4
#define TRIG_LATE 1
#define XP_END 40
#define F_ORD 0
#define VEND_POS 2
#define SPEC_DEC 0
#define T9_POS 2
#define PARV 0
#define NB_MEM 6
#define PF_MODE 0
#define PF_FENCE 0
#define LATE_NORM 1
#define F_FEN 1
#define SM_MODE 2
#define SX_MODE 2
#define PERSIST 1
#define SX_BULK 0
#define SLD_N (SX_BULK ? 160 : 256)
#define O_B1 5
#define O_C1 16
#define O_MODE 0
#define AR_MAP 1
#define EXP 0
#define FILL_B 4096
#define MP_D 3
#define MP_CH 4
#define MP_F 0
#define ML_N0 1
#define MR_N0 3
#define O_RSM 0x2AA0
#define O_RS __builtin_popcount(O_RSM)
#define O_IDX(j) __builtin_popcount(O_RSM & ((1 << (j)) - 1))
#define O_RS_POS 0
#define V_N1 0
#define V_N2 0
#define V_N3 3
#define V_OWN 6
#define V_S1 9
#define V_K1 (V_OWN + V_RS + V_S1)
#define V_K2 ((V_K1 > 20 ? V_K1 : 20) + V_S2)
#define V_S2 3
constexpr int V_RS = V_N1 + V_N2 + V_N3;
constexpr float SCL = 0.07216878364870322f;
constexpr float L2E = 1.4426950408889634f;
__device__ __forceinline__ constexpr int vord(int i) { return i < 4 ? 36 + i : i - 4; }
__device__ __forceinline__ constexpr uint32_t hoff(int k) { return ((k >> 2) * 5120 + (k & 3) * 32) >> 4; }

__device__ __forceinline__ constexpr int ar_chunk(int T) { return AR_MAP == 0 ? (T >> 2) * 8 + (T & 3) : T == 9 ? 19 : (T % 3) * 8 + T / 3; }
__device__ __forceinline__ void fix_red(uint8_t* p, const float* a, float2 sc) {
  int v0 = __float2int_rn(a[0] * sc.x), v1 = __float2int_rn(a[1] * sc.y), v2 = __float2int_rn(a[2] * sc.x), v3 = __float2int_rn(a[3] * sc.y);
  red64(p, ((uint32_t)v0 << 7) | 1u, ((uint32_t)v2 << 3) + (uint32_t)(v0 >> 25));
  red64(p + 1024, ((uint32_t)v1 << 7) | 1u, ((uint32_t)v3 << 3) + (uint32_t)(v1 >> 25));
}
__device__ __forceinline__ float lmax10(const float* t) {
  return fmaxf(fmaxf(fmaxf(fmaxf(t[0], t[1]), fmaxf(t[2], t[3])), fmaxf(fmaxf(t[4], t[5]), fmaxf(t[6], t[7]))), fmaxf(t[8], t[9]));
}
__device__ __forceinline__ float max10(const float* t) {
  float m = fmaxf(fmaxf(fmaxf(t[0], t[1]), fmaxf(t[2], t[3])), fmaxf(fmaxf(t[4], t[5]), fmaxf(t[6], t[7])));
  m = fmaxf(m, fmaxf(t[8], t[9]));
  m = fmaxf(m, __shfl_xor_sync(~0u, m, 1));
  return fmaxf(m, __shfl_xor_sync(~0u, m, 2));
}
#define ACC2(k, p, u, v) { t[k] = bflo(p) + bflo(u) + bflo(v); t[k + 1] = bfhi(p) + bfhi(u) + bfhi(v); }

#define LBT 0
#define NLB 2
constexpr int LB_STAGE = 36864, LB_ST = 6 * LB_STAGE;
__device__ __forceinline__ void lb_role(const uint32_t sb, const CUtensorMap* tmx, uint32_t* __restrict__ flags, int layer) {
  const int tid = threadIdx.x, wid = __shfl_sync(~0u, tid >> 5, 0), wg = wid >> 2, w = wid & 3, lane = tid & 31, g = lane >> 2, i4 = lane & 3;
  const int cl = blockIdx.x / 3, rank = blockIdx.x - cl * 3;
  const uint32_t bar = sb + O_BAR;
  asm volatile("griddepcontrol.launch_dependents;");
  if (wid == 8) {
    if (lane < 14) mbar_init(bar + 8 * lane, lane >= 6 && lane < 12 ? 8 : 1);
    asm volatile("fence.mbarrier_init.release.cluster;" ::: "memory");
    fence_async();
  }
  __syncthreads();
  asm volatile("barrier.cluster.arrive.relaxed.aligned;" ::: "memory");
  if (wid == 8) {
    int st = 0; uint32_t ph = 1;
    const uint8_t* wsrc = g_w2 + rank * 286720;
    if (lane < 6) { mbar_expect(bar + 8 * lane, LB_STAGE); bulk_g2s(sb + lane * LB_STAGE + 8192, wsrc + lane * 28672, 28672, bar + 8 * lane); }
    if (layer == 1) wait_flag(flags + FL_R, 6);
#pragma unroll 1
    for (int tile = cl; tile < 32; tile += NLB) {
      wait_flag(flags + FL_O + (tile >> 1) * 8, 8);
      if (tile == cl + LBT * NLB && lane == 0) GTT(layer * 4 + 1, 11);
      fence_async_global();
#pragma unroll 1
      for (int kc = 0; kc < 10; kc++) {
        const bool pre = tile == cl && kc < 6;
        mbar_wait(bar + 8 * (6 + st), ph);
        if (lane == 0) {
          if (!pre) { mbar_expect(bar + 8 * st, LB_STAGE); bulk_g2s(sb + st * LB_STAGE + 8192, wsrc + kc * 28672, 28672, bar + 8 * st); }
          bulk_g2s(sb + st * LB_STAGE, g_oa + tile * 81920 + kc * 8192, 8192, bar + 8 * st);
        }
        __syncwarp();
        if (++st == 6) { st = 0; ph ^= 1; }
      }
      mbar_wait(bar + 8 * (6 + st), ph);
      if (lane == 0) { mbar_expect(bar + 8 * st, 64 * 464); tma2d(sb + st * LB_STAGE, tmx, rank * 224, tile * 64, bar + 8 * st); }
      __syncwarp();
      if (++st == 6) { st = 0; ph ^= 1; }
    }
    asm volatile("barrier.cluster.wait.aligned;" ::: "memory");
  } else if (wg < 2) {
    asm volatile("barrier.cluster.wait.aligned;" ::: "memory");
    const int u = 2 * rank + wg, nb = u == 5 ? 5 : 7;
    int st = 0; uint32_t ph = 0, it = 0;
#pragma unroll 1
    for (int tile = cl; tile < 32; tile += NLB, it++) {
      const int row0 = tile * 64 + 16 * w + g;
      float d[56];
      if (tid == 0) mbar_expect(bar + 8 * (12 + (it & 1)), 3072);
#pragma unroll 1
      for (int kc = 0; kc < 10; kc++) {
        const uint64_t da = mkdesc(SB0 + st * LB_STAGE, 1024, 128, 0), db = mkdesc(SB0 + st * LB_STAGE + 8192 + wg * 1792, 3584, 128, 0);
        mbar_wait(bar + 8 * st, ph);
        if (it == LBT && kc == 0) GT(layer * 4 + 1, 12);
        wg_fence();
#pragma unroll
        for (int k = 0; k < 4; k++) wg_ss_n112_ta0_tb1(d, da + k * 128, db + k * 448, kc | k);
        wg_commit();
        wg_wait<1>();
        if (kc > 0 && lane == 0) mbar_arrive(bar + 8 * (6 + (st == 0 ? 5 : st - 1)));
        if (++st == 6) { st = 0; ph ^= 1; }
      }
      wg_wait<0>();
      pin<56>(d);
      if (it == LBT) GT(layer * 4 + 1, 13);
      if (lane == 0) mbar_arrive(bar + 8 * (6 + (st == 0 ? 5 : st - 1)));
      mbar_wait(bar + 8 * st, ph);
      {
        const uint32_t x0 = sb + st * LB_STAGE + (16 * w + g) * 464 + wg * 224 + (layer ? 8 : 4) * i4, x1 = x0 + (layer ? 4 : 16);
#pragma unroll
        for (int j = 0; j < 28; j++) {
          const uint32_t v = lds1(((j & 2) ? x1 : x0) + (j >> 2) * 32 + (j & 1) * 3712);
          d[2 * j] += bflo(v); d[2 * j + 1] += bfhi(v);
        }
      }
      fence_async();
      __syncwarp();
      if (lane == 0) mbar_arrive(bar + 8 * (6 + st));
      if (++st == 6) { st = 0; ph ^= 1; }
      const float cnt = nb * 16.f;
      const uint32_t so = LB_ST + (it & 1) * 3072 + (16 * w + g) * 48;
#pragma unroll
      for (int h = 0; h < 2; h++) {
        float sum = 0.f;
#pragma unroll
        for (int j = 0; j < 14; j++) sum += d[4 * j + 2 * h] + d[4 * j + 2 * h + 1];
        sum += __shfl_xor_sync(~0u, sum, 1); sum += __shfl_xor_sync(~0u, sum, 2);
        const float mean = sum * rcp(cnt);
        float q = 0.f, q2 = 0.f;
#pragma unroll
        for (int j = 0; j < 14; j++) {
          const float a = d[4 * j + 2 * h] - mean, b = d[4 * j + 2 * h + 1] - mean;
          if (j < 10) q = fmaf(a, a, fmaf(b, b, q)); else q2 = fmaf(a, a, fmaf(b, b, q2));
        }
        if (nb == 7) q += q2;
        q += __shfl_xor_sync(~0u, q, 1); q += __shfl_xor_sync(~0u, q, 2);
        if (i4 < 3) { const uint32_t b = mapa(sb, i4); sta2f(b + so + h * 384 + u * 8, sum, q, b + O_BAR + 8 * (12 + (it & 1))); }
      }
      mbar_wait(bar + 8 * (12 + (it & 1)), (it >> 1) & 1);
      if (it == LBT) GT(layer * 4 + 1, 14);
#pragma unroll
      for (int h = 0; h < 2; h++) {
        const float4 x = lds4f(sb + so + h * 384), y = lds4f(sb + so + h * 384 + 16), z = lds4f(sb + so + h * 384 + 32);
        const float mu = (((x.x + x.z) + (y.x + y.z)) + (z.x + z.z)) * (1.f / DM);
        const float e0 = x.x * (1.f / 112.f) - mu, e1 = x.z * (1.f / 112.f) - mu, e2 = y.x * (1.f / 112.f) - mu, e3 = y.z * (1.f / 112.f) - mu;
        const float e4 = z.x * (1.f / 112.f) - mu, e5 = z.z * (1.f / 80.f) - mu;
        const float q = (((x.y + x.w) + (y.y + y.w)) + (z.y + z.w)) + 112.f * ((e0 * e0 + e1 * e1) + (e2 * e2 + e3 * e3) + e4 * e4) + 80.f * e5 * e5;
        const float rs = rsqrtf(q * (1.f / DM) + 1e-5f), sh = -mu * rs;
        const int tk = row0 + 8 * h;
        uint8_t* xp = g_xn + (tk >> 5) * 40960 + (tk & 31) * 128 + (i4 & 1) * 8;
#pragma unroll
        for (int j = 0; j < 7; j++) {
          if (j < nb) {
            const int b16 = u * 7 + j;
            const float* a = d + 8 * j + 2 * h;
            *(uint2*)(xp + (b16 >> 2) * 4096 + (((2 * (b16 & 3) + (i4 >> 1)) ^ g) << 4)) =
                make_uint2(pack2(fmaf(a[0], rs, sh), fmaf(a[1], rs, sh)), pack2(fmaf(a[4], rs, sh), fmaf(a[5], rs, sh)));
          }
        }
      }
      if (it == LBT) GT(layer * 4 + 1, 15);
      bar_arrive<1, 288>();
      bar_sync<2, 288>();
#pragma unroll
      for (int j = 0; j < 14; j++) {
        const float* a = d + 8 * (j >> 1) + 2 * (j & 1);
        if ((j >> 1) < nb) *(uint2*)(g_x + (row0 + 8 * (j & 1)) * DM + u * 112 + 4 * i4 + 16 * (j >> 1)) = make_uint2(pack2(a[0], a[1]), pack2(a[4], a[5]));
      }
      bar_arrive<3, 288>();
    }
  } else {
    asm volatile("barrier.cluster.wait.aligned;" ::: "memory");
    if (wid == 9) {
#pragma unroll 1
      for (int tile = cl; tile < 32; tile += NLB) {
        bar_sync<1, 288>();
        if (tile != cl) bar_arrive<2, 288>();
        if (lane == 0) { red_release(flags + FL_XN + tile * 8, 1); if (tile == cl + LBT * NLB) GTT(layer * 4 + 1, 9); }
        __syncwarp();
        if (tile == cl) bar_arrive<2, 288>();
        bar_sync<3, 288>();
        if (lane == 0) red_release(flags + FL_XN + tile * 8 + 1, 1);
        __syncwarp();
      }
    }
  }
  asm volatile("barrier.cluster.arrive.relaxed.aligned;\nbarrier.cluster.wait.aligned;" ::: "memory");
  GT(layer * 4 + 1, 10);
}

__global__ void __launch_bounds__(384, 1)
rec_kernel(const __grid_constant__ CUtensorMap tmq, const __grid_constant__ CUtensorMap tmk,
           const __grid_constant__ CUtensorMap tmv, const __grid_constant__ CUtensorMap tmo,
           const __grid_constant__ CUtensorMap tmx, const bf16* __restrict__ mem0, uint8_t* __restrict__ ar, uint32_t* __restrict__ flags, int layer) {
  extern __shared__ __align__(1024) uint8_t smem[];
  const uint32_t sb = smem_u32(smem);
  check_smem_base(sb);
  GT(layer * 4 + 1, 0);
  if (blockIdx.x < 3 * NLB) { lb_role(sb, &tmx, flags, layer); return; }
  const int bid = blockIdx.x - 3 * NLB;
  const int tid = threadIdx.x, wid = __shfl_sync(~0u, tid >> 5, 0), wg = wid >> 2, w = wid & 3;
  const int lane = __shfl_sync(~0u, tid & 31, tid & 31);
  const int head = bid / 3, rank = bid - head * 3;
  const int e0 = bid * 64;
  const uint32_t bar = sb + O_BAR;
  const uint32_t sb1 = mapa(sb, rank == 2 ? 0 : rank + 1), sb2 = mapa(sb, rank == 0 ? 2 : rank - 1);
  auto chunk_of = [&](int p) { const int c = 3 * rank + p; return p == 9 ? 9 : c >= 9 ? c - 9 : c; };

  auto load_piece = [&](int i) {
    if (lane == 0) mbar_expect(bar + 8 * (MB_W + i), 16384);
    __syncwarp();
    if (lane < 2) {
      if (i < 15) {
        const int m = i < 10 ? i & 1 : 0, p = (i < 10 ? i >> 1 : i - 10) * 2 + lane;
        tma5d(sb + m * 81920 + p * 8192, i >= 10 ? &tmv : m ? &tmk : &tmq, e0, chunk_of(p) * 4, bar + 8 * (MB_W + i));
      } else {
        const int p = (i - 15) * 2 + lane, k = p / 3, j = rank + p - 3 * k;
        tma2d(sb + O_WO + p * 8192, &tmo, p == 9 ? 576 : (rank * 3 + k) * 64, head * DH + (j >= 3 ? j - 3 : j) * 64, bar + 8 * (MB_W + i));
      }
    }
  };
  if (wid == 9) {
    mbar_init(bar + 8 * lane, lane == MB_ML ? ML_N0 : lane == MB_ML + 1 && ML_N0 < 4 ? 4 - ML_N0 : (lane >= MB_WC || lane == MB_PF) ? 4 : 1);
    if (lane < 8) mbar_init(bar + 8 * (32 + lane), 4);
    asm volatile("fence.mbarrier_init.release.cluster;" ::: "memory");
    fence_async();
    __syncwarp();
#pragma unroll 1
    for (int i = 0; i < W_WIN; i++) load_piece(i);
  }
  __syncthreads();
  asm volatile("barrier.cluster.arrive.relaxed.aligned;" ::: "memory");

  if (wg < 2) {
    asm volatile("setmaxnreg.inc.sync.aligned.u32 208;");
    uint32_t a[40][4];
    const uint32_t swz = (lane & 7) * 128 + (((2 * w + ((lane >> 3) & 1)) ^ (lane & 7)) << 4);
    const uint32_t st_x = __shfl_sync(~0u, sb + O_QK + wg * 5120 + (lane >> 4) * 2048 + swz, lane);
    {
      const uint32_t la = sb + wg * 81920 + (lane >> 4) * 1024 + swz;
#pragma unroll
      for (int p = 0; p < 5; p++) {
        mbar_wait(bar + 8 * (MB_W + 2 * p + wg), 0);
#pragma unroll
        for (int k = 0; k < 8; k++) ldsm4t(a[p * 8 + k], la + (p * 8 + k) * 2048);
        fence_async();
        __syncwarp();
        mbar_arrive_elect(bar + 8 * (MB_WC + wg * 5 + p));
      }
    }
    GT(layer * 4 + 1, 5);
    asm volatile("barrier.cluster.wait.aligned;" ::: "memory");
    const uint32_t ld_m = __shfl_sync(~0u, sb + O_H + (lane & 7) * 128 + (((lane >> 3) ^ (lane & 7)) << 4), lane);

    for (int s = 0; s < NSEG; s++) {
      const uint32_t par = PARV ? ((s ^ (lane >> 5)) & 1) : (s & 1);
      if (wid == 4) TS0(0);
      if (wid == 0) TS(30);
      {
        float ax[16];
        constexpr uint64_t db = mkdesc(SB0 + O_H + 1024, 16, 1024, 1);
        mbar_waitf(bar + 8 * MB_XF, par);
        wg_fence();
#pragma unroll
        for (int k = 0; k < 20; k++) wg_rs_n32_tb0(ax, a[vord(k)], db + hoff(vord(k)), k);
        mbar_waitf(bar + 8 * (MB_XF + 1), par);
        if (PF_MODE == 2) mbar_waitf(bar + 8 * MB_PF, par ^ 1);
        wg_fence();
#pragma unroll
        for (int k = 20; k < XP_END; k++) wg_rs_n32_tb0(ax, a[vord(k)], db + hoff(vord(k)), 1);
        wg_commit();
        if (PF_MODE == 0) mbar_waitf(bar + 8 * MB_PF, par ^ 1);
        if (PF_MODE == 1 && s > 0) bar_sync<B_ML0, 384>();
        if (wid == 6 && lane == 0) { mbar_expect(bar + 8 * MB_SM, 2 * SM_SLOT + 48 + 48); mbar_expect(bar + 8 * MB_SX, 2 * 2176); }
        wg_wait<0>();
        pin<16>(ax);
        if (w == 0) TS(1 + 22 * wg);
        stsm4t(st_x, pack2(ax[0], ax[1]), pack2(ax[2], ax[3]), pack2(ax[4], ax[5]), pack2(ax[6], ax[7]));
        stsm4t(st_x + 4096, pack2(ax[8], ax[9]), pack2(ax[10], ax[11]), pack2(ax[12], ax[13]), pack2(ax[14], ax[15]));
        if (V_OWN > 0) bar_arrive<B_VOWN, 384>();
      }
      {
        float c[MP_CH][4];
#pragma unroll
        for (int k = 0; k < MP_CH; k++) c[k][0] = c[k][1] = c[k][2] = c[k][3] = 0.f;
        uint32_t b[MP_D][2][4];
        const uint32_t ld_m2 = opaque(ld_m ^ 64);
        SCHED_FENCE();
#define MORD(j) ((j) == 0 ? 9 : (j) < 4 ? (j) - 1 : 3 + ((j) - 4) / 2 + 3 * ((j) & 1))
#pragma unroll
        for (int j = 0; j < 10 + MP_D - 1; j++) {
          if (j < 10) {
            if (j == 0) { if (NB_MEM & 1) bar_sync<B_ML0, 256 + 32 * ML_N0>(); else mbar_waitf(bar + 8 * MB_ML, par); if (wid == 0) TS(2); }
            if (ML_N0 < 4 && j == ML_N0) { if (NB_MEM & 2) bar_sync<B_ML1, 256 + 32 * (4 - ML_N0)>(); else mbar_waitf(bar + 8 * (MB_ML + 1), par); if (wid == 0) TS(3); }
            if (j == 4) { if (NB_MEM & 4) bar_sync<B_MR, 288>(); else mbar_waitf(bar + 8 * MB_MR, par); if (wid == 0) TS(4); }
            if (j == 4 + 2 * MR_N0) { mbar_waitf(bar + 8 * (MB_MR + 1), par); if (wid == 0) TS(5); }
            ldsm4(b[j % MP_D][0], ld_m + MORD(j) * 5120);
            ldsm4(b[j % MP_D][1], ld_m2 + MORD(j) * 5120);
            if ((MP_F >> j) & 1) SCHED_FENCE();
          }
          const int u = j - (MP_D - 1);
          if (u >= 0) {
#pragma unroll
            for (int k = 0; k < 4; k++) mma16816(c[(4 * u + k) % MP_CH], a[4 * MORD(u) + k], b[u % MP_D][k >> 1][(k & 1) * 2], b[u % MP_D][k >> 1][(k & 1) * 2 + 1]);
          }
        }
        SCHED_FENCE();
        bar_arrive<B_VGO, 384>();
        if (wid == 0) TS(31);
        SCHED_FENCE();
#pragma unroll
        for (int k = 0; k < 4; k++) c[0][k] = MP_CH == 4 ? (c[0][k] + c[1][k]) + (c[2][k] + c[MP_CH - 1][k]) : (c[1][k] + c[2][k]) + c[0][k];
        stsm2t(st_x + 1024 - wg * 3072, pack2(c[0][0], c[0][1]), pack2(c[0][2], c[0][3]));
        fence_async();
      }
      if (wg == 0) {
        bar_sync<B_QK, 256>();
        float sv[20];
        {
          constexpr uint64_t da = mkdesc(SB0 + O_QK, 16, 1024, 1), db = mkdesc(SB0 + O_K, 16, 2048, 1);
          wg_fence();
#pragma unroll
          for (int k = 0; k < 4; k++) wg_ss_n40_ta0_tb0(sv, da + 2 * k, db + 2 * k, k);
          wg_commit();
        }
        if (w == 0) TS(6);
        SCHED_FENCE();
        const uint32_t ln = opaque(lane);
        uint32_t m0, m1, m2, m3, m4;
        {
          const uint32_t a1 = opaque(sb1 + O_SM + SM_SLOT + ln * 16), a2 = opaque(sb2 + O_SM + ln * 16);
          const uint32_t a3 = opaque(sb1 + O_SM + SM_SLOT + 512 + ln * 4), a4 = opaque(sb2 + O_SM + 512 + ln * 4);
          const uint32_t b1 = opaque(sb1 + O_BAR + 8 * MB_SM), b2 = opaque(sb2 + O_BAR + 8 * MB_SM);
          const uint32_t bt = opaque(mapa(sb, min(ln, 2u)) + O_BAR + 8 * MB_SM), at = opaque(bt + (O_MAXS + 48 - O_BAR - 8 * MB_SM));
          SCHED_FENCE();
          wg_wait<0>();
          pin<20>(sv);
          m0 = pack2(sv[2], sv[3]); m1 = pack2(sv[6], sv[7]); m2 = pack2(sv[10], sv[11]); m3 = pack2(sv[14], sv[15]); m4 = pack2(sv[18], sv[19]);
          if (w == 0) {
            sta4(a1, m0, m1, m2, m3, b1);
            sta4(a2, m0, m1, m2, m3, b2);
            sta1(a3, m4, b1);
            sta1(a4, m4, b2);
          }
          sta1p(at, 0u, bt, ln < 3);
          if (!SX_BULK) { bar_arrive<B_SSENT, 256>(); SCHED_FENCE(); }
        }
        const uint32_t p0 = pack2(sv[0], sv[1]), p1 = pack2(sv[4], sv[5]), p2 = pack2(sv[8], sv[9]), p3 = pack2(sv[12], sv[13]), p4 = pack2(sv[16], sv[17]);
        if (SX_BULK) {
          sts4(sb + O_STG + w * 512 + ln * 16, p0, p1, p2, p3);
          if (w == 3) sts1(sb + O_STG + 2048 + ln * 4, p4);
          if (SX_BULK == 2) fence_async();
          bar_arrive<B_SSENT, 256>();
          SCHED_FENCE();
          if (SX_BULK == 1) fence_async();
          __syncwarp();
        }
        auto sx_copy = [&]() {
          bulk_s2c_elect<512>(sb1 + O_K + 512 + w * 2048, sb1 + O_BAR + 8 * MB_SX, sb2 + O_K + w * 2048, sb2 + O_BAR + 8 * MB_SX, sb + O_STG + w * 512);
          if (w == 3) bulk_s2c_elect<128>(sb1 + O_K + 8192 + 128, sb1 + O_BAR + 8 * MB_SX, sb2 + O_K + 8192, sb2 + O_BAR + 8 * MB_SX, sb + O_STG + 2048);
        };
        const uint32_t ox = O_K + w * 2048 + ln * 16, ox2 = O_K + 8192 + ln * 4;
        {
          const uint32_t a1 = opaque(sb1 + ox + 512), a2 = opaque(sb2 + ox), b1 = opaque(sb1 + O_BAR + 8 * MB_SX), b2 = opaque(sb2 + O_BAR + 8 * MB_SX);
          if (w == 0) {
            TS(7);
            const uint32_t om = opaque(sb + O_SM + ln * 16), om2 = opaque(sb + O_SM + 512 + ln * 4);
            const uint32_t pa0 = ld_m + (O_QM - O_H), pa1 = (ld_m ^ 64) + (O_QM - O_H);
            float t[10] = {bflo(m0), bfhi(m0), bflo(m1), bfhi(m1), bflo(m2), bfhi(m2), bflo(m3), bfhi(m3), bflo(m4), bfhi(m4)};
            pin<10>(t);
            SCHED_FENCE();
            mbar_waitf(bar + 8 * MB_SM, par);
            const uint4 u = lds4(om), v = lds4(om + SM_SLOT);
            const uint32_t u4 = lds1(om2), v4 = lds1(om2 + SM_SLOT);
            if (!SX_BULK) { sta4(a1, p0, p1, p2, p3, b1); sta4(a2, p0, p1, p2, p3, b2); }
            if (SLD_POS == 0) bar_arrive<B_SLD, SLD_N>();
            if (SX_BULK) sx_copy();
            SCHED_FENCE();
#define ACC3(k, u, v) { t[k] += bflo(u) + bflo(v); t[k + 1] += bfhi(u) + bfhi(v); }
            ACC3(0, u.x, v.x) ACC3(2, u.y, v.y) ACC3(4, u.z, v.z) ACC3(6, u.w, v.w) ACC3(8, u4, v4)
            TS(8);
            const float ml = lmax10(t) * (SCL * L2E);
            const float m1 = __shfl_xor_sync(~0u, ml, 1), m2 = __shfl_xor_sync(~0u, ml, 2), m3 = __shfl_xor_sync(~0u, ml, 3);
            SCHED_FENCE();
#pragma unroll
            for (int k = 0; k < 10; k++) t[k] = ex2(fmaf(t[k], SCL * L2E, -ml));
            pin<10>(t);
            SCHED_FENCE();
            const float f = ex2(ml - fmaxf(fmaxf(ml, m1), fmaxf(m2, m3)));
#pragma unroll
            for (int k = 0; k < 10; k++) t[k] *= f;
            stsm4(pa0, pack2(t[0], t[1]), pack2(t[2], t[3]), pack2(t[4], t[5]), pack2(t[6], t[7]));
            stsm1(pa1, pack2(t[8], t[9]));
            bar_arrive<B_PM, 160>();
            TS(9);
          } else {
            const uint32_t a3 = opaque(sb1 + ox2 + 128), a4 = opaque(sb2 + ox2);
            SCHED_FENCE();
            mbar_waitf(bar + 8 * MB_SM, par);
            if (SX_BULK) sx_copy();
            else {
              sta4(a1, p0, p1, p2, p3, b1);
              sta4(a2, p0, p1, p2, p3, b2);
              if (w == 3) { sta1(a3, p4, b1); sta1(a4, p4, b2); }
              bar_arrive<B_SLD, SLD_N>();
            }
          }
        }
        {
          float t[10] = {bflo(p0), bfhi(p0), bflo(p1), bfhi(p1), bflo(p2), bfhi(p2), bflo(p3), bfhi(p3), bflo(p4), bfhi(p4)};
          const int dq = 8 * w + (ln >> 2) - 2 * (ln & 3);
#pragma unroll
          for (int k = 1; k < 5; k++) {
            if (8 * (k - 1) > dq) t[2 * k] = -1e9f / SCL;
            if (8 * (k - 1) + 1 > dq) t[2 * k + 1] = -1e9f / SCL;
          }
          const int rr = 2 * w + (ln & 1);
          const uint32_t pa = sb + O_QK + ((ln >> 1) & 3) * 2048 + rr * 128;
          const uint32_t pa0 = opaque(pa + (((ln >> 3) ^ rr) << 4)), pa1 = opaque(pa0 ^ 64), l0 = opaque(sb + ox), l1 = opaque(sb + ox2);
          pin<10>(t);
          SCHED_FENCE();
          mbar_waitf(bar + 8 * MB_SX, par);
          bar_sync<B_VEND, 256>();
          const uint4 u = lds4(l0), v = lds4(l0 + 512);
          uint32_t u4 = 0, v4 = 0;
          if (w == 3) { u4 = lds1(l1); v4 = lds1(l1 + 128); }
          ACC3(0, u.x, v.x) ACC3(2, u.y, v.y) ACC3(4, u.z, v.z) ACC3(6, u.w, v.w) ACC3(8, u4, v4)
          const float ml = lmax10(t) * (SCL * L2E);
          const float m1 = __shfl_xor_sync(~0u, ml, 1), m2 = __shfl_xor_sync(~0u, ml, 2), m3 = __shfl_xor_sync(~0u, ml, 3);
          SCHED_FENCE();
#pragma unroll
          for (int k = 0; k < 10; k++) t[k] = ex2(fmaf(t[k], SCL * L2E, -ml));
          float sum = ((t[0] + t[1]) + (t[2] + t[3])) + ((t[4] + t[5]) + (t[6] + t[7])) + (t[8] + t[9]);
          pin<1>(&sum);
          SCHED_FENCE();
          const float f = ex2(ml - fmaxf(fmaxf(ml, m1), fmaxf(m2, m3)));
          sum *= f;
          const float s1 = __shfl_xor_sync(~0u, sum, 1), s2 = __shfl_xor_sync(~0u, sum, 2), s3 = __shfl_xor_sync(~0u, sum, 3);
          const float inv = f * rcp((sum + s1) + (s2 + s3));
          stsm4(pa0, pack2(t[0] * inv, t[1] * inv), pack2(t[2] * inv, t[3] * inv), pack2(t[4] * inv, t[5] * inv), pack2(t[6] * inv, t[7] * inv));
          stsm2(pa1, pack2(t[8] * inv, t[9] * inv), 0u);
          fence_async();
        }
        bar_arrive<B_PX, 256>();
        if (w == 0) TS(10);
        bar_sync<B_XGO, 256>();
      } else {
        bar_arrive<B_QK, 256>();
        const int ln = opaque(lane);
        if (w == 2) {
          bar_sync<B_VHALF, 192>();
          if (ln == 0 && s > 0) { red_release(flags + FL_A + (e0 >> 10) * 8 + (s - 1) * 48, 1); }
          __syncwarp();
        }
        if (w == 3) {
          const int l = bid * 2 + ln, s2 = s + 2;
          if (ln < 2 && l < 160 && s2 < NSEG - 1) {
            const int tile = l >> 4;
            const uint8_t* p = ar + (s2 >> 2) * AR_GROUP + (s2 & 1) * 128 + ((s2 >> 1) & 1) * 512 + ar_chunk(tile) * 4096 +
                               ((l >> 3) & 1) * 16384 + (l & 1) * 256 + ((l >> 1) & 3) * 1024;
            asm volatile("prefetch.global.L2 [%0];" :: "l"(p));
          }
        }
        if (w == 0) {
          const bool more = s + 1 < NSEG;
          if (ln < 2 && more) mbar_expect(bar + 8 * (MB_XF + ln), FILL_B * 5);
          const uint8_t* src = g_xn + (s + 1) * 40960 + chunk_of(ln) * 4096;
          if ((s & 1) && more) { wait_flag(flags + FL_XN + ((s + 1) >> 1) * 8, 3); fence_async_global(); }
          bar_sync<B_VHALF, 192>();
          if ((ln < 4 || ln == 9) && more) bulk_g2s(sb + O_H + ln * 5120 + 1024, src, FILL_B, bar + 8 * MB_XF);
          bar_sync<B_VDONE, 160>();
          if (ln >= 4 && ln < 9 && more) bulk_g2s(sb + O_H + ln * 5120 + 1024, src, FILL_B, bar + 8 * (MB_XF + 1));
        }
        bar_sync<B_XGO1, 256>();
      }
    }
  } else {
    asm volatile("setmaxnreg.dec.sync.aligned.u32 88;");
    asm volatile("barrier.cluster.wait.aligned;" ::: "memory");

    const int g = lane >> 2, i4 = lane & 3;
    const int myT = w == 0 ? 9 : rank * 3 + w - 1, myP = w == 0 ? 9 : w - 1;
    const int tok = 2 * ((lane >> 1) & 3) + ((lane >> 3) & 1);
    const uint32_t fw_off = sb + O_H + myP * 5120 + tok * 128 + (((2 * (lane >> 4) + (lane & 1)) ^ tok) << 4);
    const uint32_t prod_off = (w >> 1) * 16384 + (w & 1) * 2048 + ((g >> 1) & 1) * 256 + (i4 * 2 + (g >> 2)) * 16 + (g & 1) * 8;
    const uint32_t cons_off = ar_chunk(myT) * 4096 + (lane >> 3) * 1024 + (lane & 7) * 16;
    auto tile_off = [&](int k) { return AR_MAP == 0 ? ar_chunk(rank * 3 + k) * 4096 : (k * 8 + rank) * 4096; };
    constexpr uint32_t T9_OFF = ar_chunk(9) * 4096;

    uint32_t mx;
    auto forward = [&](const uint32_t* p) {
      const uint32_t c = O_H + myP * 5120, bo = O_BAR + 8 * (MB_MR + (w > MR_N0));
      sts4(fw_off, p[0], p[1], p[2], p[3]);
      sts4(fw_off ^ 64, p[4], p[5], p[6], p[7]);
      fence_async();
      __syncwarp();
      if (w < ML_N0) { if (NB_MEM & 1) bar_arrive<B_ML0, 256 + 32 * ML_N0>(); else mbar_arrive_elect(bar + 8 * MB_ML); }
      else { if (NB_MEM & 2) bar_arrive<B_ML1, 256 + 32 * (4 - ML_N0)>(); else mbar_arrive_elect(bar + 8 * (MB_ML + 1)); }
      if (w > 0) bulk_s2c_elect<1024>(sb1 + c + 6 * 5120, sb1 + bo, sb2 + c + 3 * 5120, sb2 + bo, sb + c);
      SCHED_FENCE();
      mx = 0;
#pragma unroll
      for (int k = 0; k < 8; k++) mx = __vmaxu2(mx, p[k] & 0x7FFF7FFFu);
    };
    auto send_max = [&]() {
      mx = max(mx & 0xFFFFu, mx >> 16);
      mx = __reduce_max_sync(~0u, mx);
      { const uint32_t b = mapa(sb, min(lane, 2)); sta1p(b + O_MAXS + (rank * 4 + w) * 4, mx << 16, b + O_BAR + 8 * MB_SM, lane < 3); }
    };
    auto arm = [&]() { if (lane == 0 && w < (MR_N0 < 3 ? 3 : 2)) mbar_expect(bar + 8 * (w == 0 ? MB_OG : MB_MR - 1 + w), w == 0 ? 2048 : w == 1 ? 2048 * MR_N0 : 2048 * (3 - MR_N0)); };
    {
      arm();
      const uint32_t* mp = (const uint32_t*)(mem0 + tok * DM + myT * 64 + 16 * (lane >> 4) + 4 * (lane & 1));
      const uint32_t p[8] = {mp[0], mp[4], mp[1], mp[5], mp[16], mp[20], mp[17], mp[21]};
      forward(p);
    }
    if (w == 1) {
#pragma unroll 1
      for (int i = W_WIN; i < 20; i++) {
        if (i <= W_OPEN) mbar_wait(bar + 8 * (MB_W + i - W_WIN), 0);
        if (i >= 10) mbar_wait(bar + 8 * (MB_WC + i - 10), 0);
        load_piece(i);
      }
    }
    if (w == 0) {
      if (lane < 2) mbar_expect(bar + 8 * (MB_XF + lane), 20480);
      wait_flag<PSL>(flags + FL_XN, 3);
      fence_async_global();
      if (lane < 10) bulk_g2s(sb + O_H + lane * 5120 + 1024, g_xn + chunk_of(lane) * 4096, 4096, bar + 8 * (MB_XF + (lane >= 4 && lane < 9)));
      if (!TRIG_LATE) asm volatile("griddepcontrol.launch_dependents;");
      if (lane == 0) GTT(layer * 4 + 1, 4);
    }
    if (w == 2) {
      wait_flag<400>(flags + FL_X, 128);
      wait_flag<400>(g_zero + Z_FLAGS + FL_N, 4);
      const float sq = __ldcg((const float*)(g_zero + Z_NORM));
      float mx = 0.f;
#pragma unroll
      for (int k = 0; k < 5; k++) {
        const float4* p = (const float4*)g_nrm + k * 32 + lane;
        const float4 x = __ldcg(p), y = __ldcg(p + 160), z = __ldcg(p + 320), u = __ldcg(p + 480);
        mx = fmaxf(fmaxf(mx, fmaxf((x.x + y.x) + (z.x + u.x), (x.y + y.y) + (z.y + u.y))), fmaxf((x.z + y.z) + (z.z + u.z), (x.w + y.w) + (z.w + u.w)));
      }
#pragma unroll
      for (int o = 16; o; o >>= 1) mx = fmaxf(mx, __shfl_xor_sync(~0u, mx, o));
      sts1(sb + O_MAXS + 52, __float_as_uint(sqrt_approx(sq) * sqrt_approx(mx) * (25.2982213f * 1.1f)));
    }
    bar_sync<B_WG2, 128>();
    const float cbound = __uint_as_float(lds1(sb + O_MAXS + 52));
#pragma unroll 1
    for (int i = 10; i < 15; i++) mbar_wait(bar + 8 * (MB_W + i), 0);
    if (tid == 256) GTT(layer * 4 + 1, 7);

    const uint32_t la_w = sb + O_WV + ((lane >> 4) * 8 + (lane & 7)) * 128 + (((2 * w + ((lane >> 3) & 1)) ^ (lane & 7)) << 4);
    uint32_t af[V_RS][4];
#pragma unroll
    for (int k = 0; k < V_RS; k++) ldsm4t(af[k], la_w + vord(V_OWN + k) * 2048);
#define LD_AO0 _Pragma("unroll") for (int j = 0; j < 16; j++) if ((O_RSM >> j) & 1) ldsm4t(ao[O_IDX(j)], la_w + O_WO + (1 + (j >> 3)) * 24576 + (4 + (j & 7)) * 2048);
#define LD_AO LD_AO0
    uint32_t vf[10];
    uint4 oq0 = make_uint4(0, 0, 0, 0), oq1 = oq0;
    uint8_t* op = nullptr;
    auto pv_x = [&](int s) {
      float ox[16];
      const uint32_t vz[4] = {vf[8], vf[9], 0u, 0u};
      constexpr uint64_t dp = mkdesc(SB0 + O_QK, 16, 2048, 1);
      bar_sync<B_PX, 256>();
      wg_fence();
      wg_rs_n32_tb0(ox, vf, dp, 0);
      wg_rs_n32_tb0(ox, vf + 4, dp + 2, 1);
      wg_rs_n32_tb0(ox, vz, dp + 4, 1);
      wg_commit();
      const uint32_t ln = opaque(lane);
      op = g_ot + (size_t)(s & OT_MASK) * (HE * 64) + (e0 + 16 * w) * 64 + (ln & 3) * 128 + (ln >> 2) * 16;
      wg_wait<0>();
      pin<16>(ox);
      oq0 = make_uint4(pack2(ox[0], ox[1]), pack2(ox[4], ox[5]), pack2(ox[8], ox[9]), pack2(ox[12], ox[13]));
      oq1 = make_uint4(pack2(ox[2], ox[3]), pack2(ox[6], ox[7]), pack2(ox[10], ox[11]), pack2(ox[14], ox[15]));
    };
    for (int s = 0;; s++) {
      const uint32_t par = PARV ? ((s ^ (lane >> 5)) & 1) : (s & 1);
      float sc1, isc, sum0, sum1;
      float2 sc;
#if !(PERSIST & 2)
      uint32_t ao[O_RS > 0 ? O_RS : 1][4];
#endif
      {
        float av[20];
        constexpr uint64_t da = mkdesc(SB0 + O_WV, 1024, 1024, 1), db = mkdesc(SB0 + O_H, 16, 1024, 1);
#define V_RUN_RS(k0, k1) wg_fence(); _Pragma("unroll") for (int k = k0; k < k1; k++) wg_rs_n40_tb0(av, af[k], db + hoff(vord(V_OWN + k)), V_OWN + k);
#define V_RUN_SS(k0, k1) wg_fence(); _Pragma("unroll") for (int k = k0; k < k1; k++) wg_ss_n40_ta1_tb0(av, da + vord(k) * 128, db + hoff(vord(k)), k);
        if (V_OWN > 0) {
          bar_sync<B_VOWN, 384>();
          V_RUN_SS(0, V_OWN)
          if (w == 0) TS(29);
          SCHED_FENCE();
        }
        if ((NB_MEM & 4) && w == 0) { mbar_waitf(bar + 8 * MB_MR, par); bar_arrive<B_MR, 288>(); SCHED_FENCE(); }
        send_max();
        if (OX_T == -4 && s > 0) { const uint64_t pol = policy_evict_first(); stg4h(op, oq0, pol); stg4h(op + 512, oq1, pol); }
        bar_sync<B_VGO, 384>();
        if (OX_T == -3 && s > 0) { if (OX_W) { const uint32_t t2 = clk(); while ((int)(clk() - t2) < OX_W) {} } const uint64_t pol = policy_evict_first(); stg4h(op, oq0, pol); stg4h(op + 512, oq1, pol); }
        V_RUN_RS(0, V_N1)
        if (w == 0) TS(11);
        bar_sync<B_SSENT, 256>();
        V_RUN_SS(V_OWN + V_RS, V_K1)
        V_RUN_RS(V_N1 + V_N2, V_RS)
        const uint32_t ln = opaque(lane);
        const uint32_t amx = opaque(sb + O_MAXS + 4 * min(ln, 11u));
        SCHED_FENCE();
        mbar_waitf(bar + 8 * MB_SM, par);
        const uint32_t mxl = lds1(amx);
        if (s == 0) {
#pragma unroll 1
          for (int i = 15; i < 20; i++) mbar_wait(bar + 8 * (MB_W + i), 0);
          if (TRIG_LATE) asm volatile("griddepcontrol.launch_dependents;"); if (tid == 256) GTT(layer * 4 + 1, 8); }
        bar_sync<B_SLD, SLD_N>();
        V_RUN_SS(V_K1, 20)
        wg_commit();
        V_RUN_SS((V_K1 > 20 ? V_K1 : 20), V_K2)
        wg_commit();
        wg_wait<1>();
        bar_arrive<B_VHALF, 192>();
        V_RUN_SS(V_K2, 40)
        wg_commit();
        SCHED_FENCE();
        if (w == 0) TS(12);
        {
          const float bnd = cbound * fmaxf(1.f, __uint_as_float(__reduce_max_sync(~0u, mxl)));
          const uint32_t eb = min(max(__float_as_uint(bnd) >> 23, 31u), 254u);
          sc1 = __uint_as_float(opaque((280u - eb) << 23));
          isc = __uint_as_float(opaque((eb - 29u) << 23));
        }
        const uint32_t pa = sb + O_QM + (ln & 7) * 128;
        const uint32_t pa0 = opaque(pa + (((ln >> 3) ^ (ln & 7)) << 4)), pa1 = opaque(pa0 ^ 64);
        const uint32_t o = O_OG + w * 256 + ln * 4;
        const uint32_t a0 = opaque(sb + o), a1 = opaque(sb1 + o + 4096), a2 = opaque(sb1 + o + 4096 + 128), a3 = opaque(sb2 + o + 2048), a4 = opaque(sb2 + o + 2048 + 128);
        const uint32_t b1 = opaque(sb1 + O_BAR + 8 * MB_OG), b2 = opaque(sb2 + O_BAR + 8 * MB_OG);
        const uint32_t c1 = opaque(0x3F803F80u);
        const uint32_t one[4] = {c1, c1, c1, c1};
        uint32_t pm[5];
        float s0[4] = {0.f, 0.f, 0.f, 0.f}, s1[4] = {0.f, 0.f, 0.f, 0.f}, s2[4] = {0.f, 0.f, 0.f, 0.f};
        if (VEND_POS == 2) bar_arrive<B_VEND, 256>();
        SCHED_FENCE();
        if (F_ORD == 0) {
          bar_sync<B_PM, 160>();
          ldsm4(pm, pa0);
          ldsm1(pm[4], pa1);
          if (VEND_POS == 0) bar_arrive<B_VEND, 256>();
          if (O_RS_POS == 4) { LD_AO }
          if (F_FEN & 1) SCHED_FENCE();
        }
        wg_wait<0>();
        pin<20>(av);
        if (VEND_POS == 3) { bar_arrive<B_VEND, 256>(); SCHED_FENCE(); }
        if (w == 0) TS(13);
        if (O_RS_POS == 0) { LD_AO }
#pragma unroll
        for (int k = 0; k < 10; k++) vf[k] = pack2(av[2 * k], av[2 * k + 1]);
        if (F_ORD == 1) {
          SCHED_FENCE();
          bar_sync<B_PM, 160>();
          ldsm4(pm, pa0);
          ldsm1(pm[4], pa1);
          if (VEND_POS == 0) bar_arrive<B_VEND, 256>();
          if (O_RS_POS == 3) { LD_AO }
        }
        {
          float o0[4] = {0.f, 0.f, 0.f, 0.f}, o1[4] = {0.f, 0.f, 0.f, 0.f}, o2[4] = {0.f, 0.f, 0.f, 0.f};
          mma16816(o0, vf, pm[0], pm[1]);
          mma16816(o1, vf + 4, pm[2], pm[3]);
          mma1688(o2, vf[8], vf[9], pm[4]);
          mma16816(s0, one, pm[0], pm[1]);
          mma16816(s1, one, pm[2], pm[3]);
          mma1688(s2, c1, c1, pm[4]);
          if (O_RS_POS == 5) { LD_AO }
          if (F_FEN & 2) SCHED_FENCE();
          if (O_RS_POS == 6) { LD_AO SCHED_FENCE(); }
          const uint32_t p0 = pack2(o0[0] + o1[0] + o2[0], o0[1] + o1[1] + o2[1]), p1 = pack2(o0[2] + o1[2] + o2[2], o0[3] + o1[3] + o2[3]);
          sta1(a1, p0, b1); sta1(a2, p1, b1);
          sta1(a3, p0, b2); sta1(a4, p1, b2);
          sts1(a0, p0); sts1(a0 + 128, p1);
          if (O_RS_POS == 2) {
            LD_AO
          }
          if (VEND_POS == 1) bar_arrive<B_VEND, 256>();
          sum0 = s0[0] + s1[0] + s2[0]; sum1 = s0[1] + s1[1] + s2[1];
          fence_async();
          if (O_RS_POS == 7) { LD_AO }
        }
      }
      if (s == NSEG - 1) break;
      uint8_t* arp;
      uint32_t t1;
      {
        bar_sync<B_WG2, 128>();
        float c9[4], ca[4], cb[4], cc[4];
        constexpr uint64_t da = mkdesc(SB0 + O_WO, 1024, 1024, 1), db = mkdesc(SB0 + O_OG, 128, 128, 0);
#define O_RUN(acc, tile, k0, k1) _Pragma("unroll") for (int k = k0; k < k1; k++) wg_ss_n8_ta1_tb1(acc, da + (tile) * 1536 + k * 128, db + (k >> 2) * 128 + (k & 3) * 16, k);
        wg_fence();
        O_RUN(c9, 3, 0, 4)
        wg_commit();
        if (w == 0) TS(14);
        uint8_t* pp;
#define T9_RED { wg_wait<1>(); pin<4>(c9); if (!(EXP & 4) && (!(EXP & 8) || rank == 0)) fix_red(pp + T9_OFF, c9, sc); SCHED_FENCE(); }
#define PP_SET { SCHED_FENCE(); arp = ar + (s >> 2) * AR_GROUP + (s & 1) * 128 + ((s >> 1) & 1) * 512; pp = arp + opaque(prod_off); \
          sc = LATE_NORM ? make_float2(sc1 * rcp(sum0), sc1 * rcp(sum1)) : make_float2(sc1, sc1); }
        if (T9_POS == 2) {
          O_RUN(ca, 0, 0, 4) O_RUN(cb, 1, 0, 2)
          wg_commit();
          PP_SET
          T9_RED
          wg_fence();
          O_RUN(cb, 1, 2, 4) O_RUN(cc, 2, 0, 4)
        } else {
          O_RUN(ca, 0, 0, 4) O_RUN(cb, 1, 0, 4) O_RUN(cc, 2, 0, 4)
          wg_commit();
          PP_SET
        }
        if (T9_POS == 0) T9_RED
        if (O_RS_POS == 1) { LD_AO }
        mbar_waitf(bar + 8 * MB_OG, par);
        wg_fence();
        O_RUN(ca, 0, 4, 12)
        wg_commit();
        if (T9_POS == 1) { T9_RED wg_fence(); }
        bar_arrive<B_VDONE, 160>();
        if (w == 0) TS(15);
#define O_MIX(acc, j0, j1) _Pragma("unroll") for (int j = j0; j < j1; j++) { const int k = 4 + (j & 7); \
          if ((O_RSM >> j) & 1) wg_rs_n8_tb1(acc, ao[O_IDX(j) < O_RS ? O_IDX(j) : 0], db + (k >> 2) * 128 + (k & 3) * 16, 1); \
          else wg_ss_n8_ta1_tb1(acc, da + (1 + (j >> 3)) * 1536 + k * 128, db + (k >> 2) * 128 + (k & 3) * 16, 1); }
        O_MIX(cb, 0, O_B1)
        wg_commit();
        if (O_MODE != 1) {
          wg_wait<1>();
          pin<4>(ca);
          if (!(EXP & 1)) fix_red(pp + tile_off(0), ca, sc);
          SCHED_FENCE();
          if (w == 0) TS(16);
          if (O_MODE == 2) {
            wg_wait<0>();
            pin<4>(cb);
            if (!(EXP & 1)) fix_red(pp + tile_off(1), cb, sc);
          }
          wg_fence();
        }
        if (O_B1 < 8) { O_MIX(cb, O_B1, 8) wg_commit(); }
        if (O_C1 < 16) {
          O_MIX(cc, 8, O_C1)
          wg_commit();
          wg_wait<1>();
          pin<4>(cb);
          if (!(EXP & 1)) fix_red(pp + tile_off(1), cb, sc);
          SCHED_FENCE();
          wg_fence();
        }
        O_MIX(cc, (O_C1 < 16 ? O_C1 : 8), 16)
        wg_commit();
        bar_arrive<B_XGO1, 256>();
        bar_arrive<B_XGO, 256>();
        if (O_MODE != 2 && O_C1 == 16) {
          wg_wait<1>();
          if (O_MODE == 1) { pin<4>(ca); if (!(EXP & 1)) fix_red(pp + tile_off(0), ca, sc); }
          pin<4>(cb);
          if (!(EXP & 1)) fix_red(pp + tile_off(1), cb, sc);
          SCHED_FENCE();
        }
        wg_wait<0>();
        pin<4>(cc);
        fix_red(pp + tile_off(2), cc, sc);
        t1 = clk();
        if (w == 3) TS(17);
      }
      pv_x(s);
      if (PF_MODE == 1) bar_arrive<B_ML0, 384>(); else mbar_arrive_elect(bar + 8 * MB_PF);
      if (PF_FENCE) SCHED_FENCE();
      if (OX_T == -2) { const uint64_t pol = policy_evict_first(); stg4h(op, oq0, pol); stg4h(op + 512, oq1, pol); }
      if (w == 0) TS(28);
      if (!(PERSIST & 1)) {
#pragma unroll
        for (int k = 0; k < V_RS; k++) ldsm4t(af[k], la_w + vord(V_OWN + k) * 2048);
      }
      {
        arm();
        const int dly = w == 0 ? POLL_D0 : w == 1 ? POLL_A : w == 2 ? POLL_B : POLL_C;
        const uint32_t need = w == 0 ? ((EXP & 4) ? 0 : (EXP & 8) ? 32 : 96) : ((EXP & 1) && w < 3) ? 0 : 32;
        const uint8_t* cp = arp + opaque(cons_off);
        uint4 y[4];
        int it = 0;
        while ((int)(clk() - t1) < dly) {}
        if (w == 3) TS(18);
        y[0] = ld_poll(cp); y[1] = ld_poll(cp + 256); y[2] = ld_poll(cp + 16384); y[3] = ld_poll(cp + 16384 + 256);
        if (OX_T > 0) { while ((int)(clk() - t1) < OX_T) {} }
        if ((EXP & 2) || OX_T < 0) {} else if (EVF) { const uint64_t pol = policy_evict_first(); stg4h(op, oq0, pol); stg4h(op + 512, oq1, pol); } else { stg4(op, oq0); stg4(op + 512, oq1); }
        uint32_t p[8];
        const float isl = isc * 0.5f, bias = -(float)(need >> 3) * isl;
        while (true) {
          const uint32_t bad = ((y[0].x ^ need) | (y[0].z ^ need) | (y[1].x ^ need) | (y[1].z ^ need)) | ((y[2].x ^ need) | (y[2].z ^ need) | (y[3].x ^ need) | (y[3].z ^ need));
          const bool again = __any_sync(~0u, (bad & 127u) != 0);
          if (SPEC_DEC || !again) {
#pragma unroll
            for (int k = 0; k < 4; k++) {
              p[2 * k] = pack2(fmaf((float)(int)__funnelshift_r(y[k].x, y[k].y, 3), isl, bias), fmaf((float)(int)__funnelshift_r(y[k].z, y[k].w, 3), isl, bias));
              p[2 * k + 1] = pack2((float)(int)y[k].y * isc, (float)(int)y[k].w * isc);
            }
            if (SPEC_DEC) {
#pragma unroll
              for (int k = 0; k < 8; k++) asm volatile("" : "+r"(p[k]));
            }
          }
          if (!again) break;
          if (++it > 2000000) __trap();
          y[0] = ld_poll(cp); y[1] = ld_poll(cp + 256); y[2] = ld_poll(cp + 16384); y[3] = ld_poll(cp + 16384 + 256);
        }
        TS(19 + w);
        forward(p);
        if (OX_T == -1) { const uint64_t pol = policy_evict_first(); stg4h(op, oq0, pol); stg4h(op + 512, oq1, pol); }
      }
    }
    bar_arrive<B_VDONE, 160>();
    bar_arrive<B_XGO1, 256>();
    bar_arrive<B_XGO, 256>();
    pv_x(NSEG - 1);
    mbar_wait(bar + 8 * MB_OG, 1);
    if (EVF) { const uint64_t pol = policy_evict_first(); stg4h(op, oq0, pol); stg4h(op + 512, oq1, pol); } else { stg4(op, oq0); stg4(op + 512, oq1); }
    bar_sync<B_WG2, 128>();
    if (tid == 256) { red_release(flags + FL_A + (e0 >> 10) * 8 + (NSEG - 1) * 48, 1); }
    __syncwarp();
  }
  asm volatile("barrier.cluster.arrive.relaxed.aligned;\nbarrier.cluster.wait.aligned;" ::: "memory");
  GT(layer * 4 + 1, 2);
  if (wid == 0) asm volatile("griddepcontrol.wait;" ::: "memory");
}

constexpr int P_B = 0, P_A = 131072, P_BAR = 196608, OPC_SMEM = P_BAR + 256;
#define PF_C 3
#define PF_S0 43
constexpr int OP_KR = 48;

__global__ void __launch_bounds__(384, 1)
opc_kernel(const __grid_constant__ CUtensorMap tmo, bf16* __restrict__ out, int layer,
           const bf16* __restrict__ Wq, const bf16* __restrict__ Wk, const bf16* __restrict__ Wv, const bf16* __restrict__ Wo) {
  extern __shared__ __align__(1024) uint8_t smem[];
  asm volatile("griddepcontrol.launch_dependents;");
  GT(layer * 4 + 2, 0);
  const uint32_t sb = smem_u32(smem);
  check_smem_base(sb);
  const int tid = threadIdx.x, wid = __shfl_sync(~0u, tid >> 5, 0), wg = wid >> 2, w = wid & 3, lane = tid & 31;
  const uint32_t bar = sb + P_BAR;
  uint32_t* flags = g_zero + Z_FLAGS + layer * FL_LAYER;
  float* acc = g_acc + layer * (S_TOK * DM);
  const uint64_t pol = policy_evict_first();
  if (wid == 0) {
    if (lane < 16) mbar_init(bar + 8 * lane, (lane == 8 || lane == 9) ? 8 : 1);
    fence_async();
  }
  __syncthreads();
  if (blockIdx.x < 30) {
    const int cg = blockIdx.x % 5, kg = blockIdx.x / 5;
    if (wg < 2) {
      asm volatile("setmaxnreg.inc.sync.aligned.u32 240;");
      uint32_t a[OP_KR][4];
      const uint32_t la = sb + P_B + ((lane >> 4) * 8 + (lane & 7)) * 128 + (((2 * w + ((lane >> 3) & 1)) ^ (lane & 7)) << 4);
      mbar_wait(bar + 80, 0);
#pragma unroll
      for (int k = 0; k < 32; k++) ldsm4t(a[k], la + wg * 65536 + k * 2048);
      bar_arrive<2, 288>();
      mbar_wait(bar + 88, 0);
#pragma unroll
      for (int k = 0; k < 16; k++) ldsm4t(a[32 + k], la + wg * 32768 + k * 2048);
      bar_arrive<3, 288>();
      mbar_wait(bar + 96, 0);
      float* ap = acc + (cg * 8 + wg * 4 + w) * 512 + lane * 4;
      for (int s = 0; s < NSEG; s++) {
        const int buf = s & 1;
        const uint32_t par = (s >> 1) & 1;
        float d[16];
        const uint64_t db = mkdesc(SB0 + P_B + buf * 65536, 512, 128, 0), da = mkdesc(SB0 + P_A + wg * 32768, 1024, 1024, 1);
        float* p = ap + (s & AC_MASK) * (32 * DM);
        float* pz = ap + ((s + 2) & AC_MASK) * (32 * DM) + kg * 128;
        if (kg < 4 && s + 2 < NSEG) { if (EVF) stg4h(pz, make_uint4(0, 0, 0, 0), pol); else stg4(pz, make_uint4(0, 0, 0, 0)); }
#pragma unroll
        for (int q = 0; q < 4; q++) {
          mbar_wait(bar + 8 * (buf * 4 + q), par);
          wg_fence();
#pragma unroll
          for (int k = 16 * q; k < 16 * q + 16; k++) {
            if (k < OP_KR) wg_rs_n32_tb1(d, a[k < OP_KR ? k : 0], db + k * 64, k);
            else wg_ss_n32_ta1_tb1(d, da + (k - OP_KR) * 128, db + k * 64, 1);
          }
        }
        wg_commit();
        wg_wait<0>();
        pin<16>(d);
        if (lane == 0) mbar_arrive(bar + 8 * (8 + buf));
        if (s == NSEG - 1) GT(layer * 4 + 2, 6);
        if (EVF) {
          red4fh(p, d[0], d[1], d[4], d[5], pol);
          red4fh(p + 128, d[8], d[9], d[12], d[13], pol);
          red4fh(p + 256, d[2], d[3], d[6], d[7], pol);
          red4fh(p + 384, d[10], d[11], d[14], d[15], pol);
        } else {
          red4f(p, d[0], d[1], d[4], d[5]);
          red4f(p + 128, d[8], d[9], d[12], d[13]);
          red4f(p + 256, d[2], d[3], d[6], d[7]);
          red4f(p + 384, d[10], d[11], d[14], d[15]);
        }
        bar_sync<1, 256>();
        if (tid == 0) { red_release(flags + FL_B + s * 8, 1); }
        __syncwarp();
      }
    } else {
      asm volatile("setmaxnreg.dec.sync.aligned.u32 24;");
      if (w == 0) {
        if (lane == 0) { mbar_expect(bar + 80, 131072); mbar_expect(bar + 96, 65536); mbar_expect(bar + 88, 65536); }
        __syncwarp();
        if (lane < 16) tma2d(sb + P_B + lane * 8192, &tmo, cg * 128 + (lane >> 3) * 64, kg * 1024 + (lane & 7) * 64, bar + 80);
        else if (lane < 24) tma2d(sb + P_B + lane * 8192, &tmo, cg * 128 + ((lane >> 2) & 1) * 64, kg * 1024 + 768 + (lane & 3) * 64, bar + 96);
        bar_sync<2, 288>();
        fence_async();
        if (lane < 8) tma2d(sb + P_B + lane * 8192, &tmo, cg * 128 + (lane >> 2) * 64, kg * 1024 + 512 + (lane & 3) * 64, bar + 88);
        bar_sync<3, 288>();
        for (int s = 0; s < NSEG; s++) {
          const int buf = s & 1;
          if (s >= 2) mbar_wait(bar + 8 * (8 + buf), ((s >> 1) & 1) ^ 1);
          if (s >= 2) wait_flag(flags + FL_B + (s - 2) * 8, 30);
          wait_flag(flags + FL_A + s * 48 + kg * 8, 16);
          fence_async_global();
          if (lane < 4) {
            mbar_expect(bar + 8 * (buf * 4 + lane), 16384);
            if (EVF) bulk_g2sh(sb + P_B + buf * 65536 + lane * 16384, g_ot + (size_t)(s & OT_MASK) * (HE * 64) + kg * 65536 + lane * 16384, 16384, bar + 8 * (buf * 4 + lane), pol);
            else bulk_g2s(sb + P_B + buf * 65536 + lane * 16384, g_ot + (size_t)(s & OT_MASK) * (HE * 64) + kg * 65536 + lane * 16384, 16384, bar + 8 * (buf * 4 + lane));
            if (s == NSEG - 1 && lane == 0) GTT(layer * 4 + 2, 5);
          }
          __syncwarp();
        }
      } else if (w == 1 && layer == 0) {
#pragma unroll 1
        for (int q = 4 * (4 - PF_C); q < 18; q++) {
          wait_flag(flags + FL_A + (PF_S0 + q) * 48 + kg * 8, 16);
          const int m = q >> 2;
          const uint8_t* W = m == 0 ? (const uint8_t*)Wo : m == 1 ? (const uint8_t*)Wv : m == 2 ? (const uint8_t*)Wk : m == 3 ? (const uint8_t*)Wq : (q & 1) ? g_w2 : g_w1;
          const int n = m < 4 ? 512 : (q & 1) ? 224 : 640, l0 = m < 4 ? blockIdx.x * 2048 + (q & 3) * 512 : blockIdx.x * n, lim = m < 4 ? 61440 : (q & 1) ? 6720 : 19200;
#pragma unroll 1
          for (int k = lane; k < n; k += 32) {
            if (l0 + k < lim) asm volatile("prefetch.global.L2 [%0];" :: "l"(W + (size_t)(l0 + k) * 128));
            __nanosleep(100);
          }
        }
      }
    }
  } else {
    constexpr int LD = 644;
    float* xs = (float*)smem;
    uint32_t par = 0;
    for (int task = blockIdx.x - 30; task < 2 * NSEG; task += 6, par ^= 1) {
      const int s = task >> 1, jj = task & 1;
      if (wid == 0) {
        wait_flag(flags + FL_XN + (task >> 2) * 8 + 1, 3);
        fence_async_global();
        if (lane == 0) { mbar_expect(bar, 20480); bulk_g2s(sb + 49152, g_x + task * 16 * DM, 20480, bar); }
      }
      if (wid == 1) { wait_flag(flags + FL_B + s * 8, 30); if (s == NSEG - 1 && lane == 0) GTT(layer * 4 + 2, 7); }
      __syncthreads();
      if (wid < 10) {
        float4 v[8];
#pragma unroll
        for (int k = 0; k < 8; k++) v[k] = EVF ? ldg4fh(acc + (s & AC_MASK) * (32 * DM) + (wid * 8 + k) * 256 + jj * 128 + lane * 4, pol) : __ldcg((const float4*)(acc + (s & AC_MASK) * (32 * DM) + (wid * 8 + k) * 256 + jj * 128 + lane * 4));
        float* xp = xs + (lane & 3) * 2 * LD + wid * 64 + (lane >> 2);
#pragma unroll
        for (int k = 0; k < 8; k++) { xp[k * 8] = v[k].x; xp[LD + k * 8] = v[k].y; xp[8 * LD + k * 8] = v[k].z; xp[9 * LD + k * 8] = v[k].w; }
      }
      mbar_wait(bar, par);
      __syncthreads();
      float v[2][20];
      const int pj = (lane & 24) + 2 * (lane & 3) + ((lane >> 2) & 1);
      const int tk0 = task * 16 + wid;
      if (wid < 8) {
        float sum[2] = {0.f, 0.f};
#pragma unroll
        for (int h = 0; h < 2; h++) {
#pragma unroll
          for (int k = 0; k < 10; k++) {
            const float2 u = *(const float2*)(xs + (wid + 8 * h) * LD + k * 64 + lane * 2);
            const uint32_t r = *(const uint32_t*)(smem + 49152 + (wid + 8 * h) * 1280 + k * 128 + pj * 4);
            v[h][2 * k] = u.x + bflo(r); v[h][2 * k + 1] = u.y + bfhi(r); sum[h] += v[h][2 * k] + v[h][2 * k + 1];
          }
        }
        if (!out) {
#pragma unroll
          for (int o = 16; o; o >>= 1) { sum[0] += __shfl_xor_sync(~0u, sum[0], o); sum[1] += __shfl_xor_sync(~0u, sum[1], o); }
          float q[2] = {0.f, 0.f};
#pragma unroll
          for (int h = 0; h < 2; h++) {
            sum[h] *= (1.f / DM);
#pragma unroll
            for (int k = 0; k < 20; k++) q[h] = fmaf(v[h][k] - sum[h], v[h][k] - sum[h], q[h]);
          }
#pragma unroll
          for (int o = 16; o; o >>= 1) { q[0] += __shfl_xor_sync(~0u, q[0], o); q[1] += __shfl_xor_sync(~0u, q[1], o); }
          uint8_t* xp = g_xt + (tk0 >> 7) * 163840 + (tk0 & 127) * 128 + (((lane >> 2) ^ (tk0 & 7)) << 4) + (lane & 3) * 4;
#pragma unroll
          for (int h = 0; h < 2; h++) {
            const float rs = rsqrtf(q[h] * (1.f / DM) + 1e-5f), sh = -sum[h] * rs;
#pragma unroll
            for (int k = 0; k < 10; k++) *(uint32_t*)(xp + h * 1024 + k * 16384) = pack2(fmaf(v[h][2 * k], rs, sh), fmaf(v[h][2 * k + 1], rs, sh));
          }
        }
      }
      fence_async();
      __syncthreads();
      if (!out) {
        if (tid == 352) red_release(flags + FL_LAYER + FL_T + (task >> 3) * 8, 1);
        __syncthreads();
      }
      if (wid < 8) {
        bf16* dst = out ? out + tk0 * DM + lane * 2 : g_x + tk0 * DM + pj * 2;
#pragma unroll
        for (int k = 0; k < 20; k++) *(uint32_t*)(dst + (k / 10) * 8 * DM + (k % 10) * 64) = pack2(v[k / 10][2 * (k % 10)], v[k / 10][2 * (k % 10) + 1]);
      }
    }
    __syncthreads();
    if (tid == 0 && !out) red_release(flags + FL_LAYER + FL_R, 1);
  }
  GT(layer * 4 + 2, 1);
  __syncwarp();
  asm volatile("griddepcontrol.wait;" ::: "memory");
  GT(layer * 4 + 2, 2);
}

constexpr int L_STAGE = 47104;
constexpr int L_KV = 0, L_B2 = 43008;
constexpr int L_BAR = 4 * L_STAGE;
constexpr int LA_SMEM = L_BAR + 256;
__device__ __forceinline__ float phi(float t) { return (fmaxf(t, 0.f) + 1e-6f) + ex2(fminf(t * 1.4426950408889634f, 0.f)); }
__device__ __forceinline__ void sqacc(uint32_t& h, uint32_t v) { asm("fma.rn.bf16x2 %0, %1, %1, %0;" : "+r"(h) : "r"(v)); }
__device__ __forceinline__ uint32_t phi2(float a, float b) { return pack2(phi(a), phi(b)); }
#define LA_LATE 6
#define PF_LB 1
#define PF_IL 1
#define PF_SLEEP1 400
#define RD1 0
#define PF_N0 2
#define PF_N1 0
#define PF_SLEEP 300

__global__ void __launch_bounds__(384, 1)
la_kernel(const bf16* __restrict__ Wq, const bf16* __restrict__ Wk, const bf16* __restrict__ Wv,
          const bf16* __restrict__ Wo, uint8_t* __restrict__ ar, int layer) {
  extern __shared__ __align__(1024) uint8_t smem[];
  const uint32_t sb = smem_u32(smem);
  check_smem_base(sb);
  const int tid = threadIdx.x, wid = __shfl_sync(~0u, tid >> 5, 0), wg = wid >> 2, w = wid & 3, lane = tid & 31, g = lane >> 2, i4 = lane & 3;
  const int cr = blockIdx.x & 1, hg = (blockIdx.x >> 1) & 7, tb = (blockIdx.x >> 4) * 2 + cr;
  const uint32_t bar = sb + L_BAR;
  uint32_t* flags = g_zero + Z_FLAGS + layer * FL_LAYER;
  asm volatile("griddepcontrol.launch_dependents;");
  GT(layer * 4, 0);
  if (wid == 0) {
    if (lane < 8) mbar_init(bar + 8 * lane, lane >= 4 ? (blockIdx.x < 128 ? 16 : 10) : 1);
    asm volatile("fence.mbarrier_init.release.cluster;" ::: "memory");
    fence_async();
  }
  if (blockIdx.x >= 128) {
    __syncthreads();
    const int q = blockIdx.x - 128;
    const uint8_t* src = (const uint8_t*)Wo + q * 1966080;
    if (wid == 11) {
#pragma unroll 1
      for (int it = 0; it < 48; it++) {
        const int st = it & 3;
        if (it >= 4) mbar_wait(bar + 8 * (4 + st), ((it >> 2) & 1) ^ 1);
        if (lane == 0) mbar_expect(bar + 8 * st, 40960);
        __syncwarp();
        if (lane < 4) bulk_g2s(sb + st * 40960 + lane * 10240, src + it * 40960 + lane * 10240, 10240, bar + 8 * st);
      }
    } else if (wid < 10) {
      float c[8] = {0.f, 0.f, 0.f, 0.f, 0.f, 0.f, 0.f, 0.f};
#pragma unroll 1
      for (int it = 0; it < 48; it++) {
        const int st = it & 3;
        mbar_wait(bar + 8 * st, (it >> 2) & 1);
        uint4 v[8];
#pragma unroll
        for (int k = 0; k < 8; k++) v[k] = lds4(sb + st * 40960 + k * 5120 + tid * 16);
        uint32_t h[4] = {0, 0, 0, 0};
#pragma unroll
        for (int k = 0; k < 8; k++) { sqacc(h[0], v[k].x); sqacc(h[1], v[k].y); sqacc(h[2], v[k].z); sqacc(h[3], v[k].w); }
        __syncwarp();
        if (lane == 0) mbar_arrive(bar + 8 * (4 + st));
#pragma unroll
        for (int k = 0; k < 4; k++) { c[2 * k] += bflo(h[k]); c[2 * k + 1] += bfhi(h[k]); }
      }
      float* red = (float*)(smem + 163840);
      *(float4*)(red + tid * 8) = make_float4(c[0], c[1], c[2], c[3]);
      *(float4*)(red + tid * 8 + 4) = make_float4(c[4], c[5], c[6], c[7]);
      bar_sync<1, 320>();
#pragma unroll
      for (int k = tid; k < DM; k += 320) g_nrm[q * DM + k] = (red[k] + red[DM + k]) + (red[2 * DM + k] + red[3 * DM + k]);
      asm volatile("griddepcontrol.wait;" ::: "memory");
      bar_sync<1, 320>();
      if (tid == 0) red_release(flags + FL_N, 1);
      GT(0, 2);
    }
    return;
  }
  __syncthreads();
  asm volatile("barrier.cluster.arrive.relaxed.aligned;" ::: "memory");
  if (layer == 0) asm volatile("griddepcontrol.wait;" ::: "memory");
  asm volatile("barrier.cluster.wait.aligned;" ::: "memory");
  if (wg == 2) {
    asm volatile("setmaxnreg.dec.sync.aligned.u32 40;");
    if (w == 0) {
      if (lane < 4) {
        mbar_expect(bar + 8 * lane, L_STAGE);
        bulk_g2s_mc(sb + lane * L_STAGE + 16384 + cr * 15360, g_w1 + (hg * 10 + lane) * 30720 + cr * 15360, 15360, bar + 8 * lane);
      }
      if (layer == 1) { if (LA_LATE) wait_flag(flags + FL_T + 15 * 8, LA_LATE); wait_flag(flags + FL_T + tb * 8, 8); fence_async_global(); }
      if (lane < 4) bulk_g2s(sb + lane * L_STAGE, g_xt + (tb * 10 + lane) * 16384, 16384, bar + 8 * lane);
#pragma unroll 1
      for (int kc = 4; kc < 10; kc++) {
        const int st = kc & 3;
        mbar_wait(bar + 8 * (4 + st), ((kc >> 2) & 1) ^ 1);
        if (lane == 0) {
          mbar_expect(bar + 8 * st, L_STAGE);
          bulk_g2s_mc(sb + st * L_STAGE + 16384 + cr * 15360, g_w1 + (hg * 10 + kc) * 30720 + cr * 15360, 15360, bar + 8 * st);
          bulk_g2s(sb + st * L_STAGE, g_xt + (tb * 10 + kc) * 16384, 16384, bar + 8 * st);
        }
        __syncwarp();
      }
    } else {
      const int t = tid - 288;
#pragma unroll 1
      for (int k = t; k < 768; k += 96) *(uint4*)(ar + blockIdx.x * 12288 + k * 16) = make_uint4(0, 0, 0, 0);
      if (layer == 0 || RD1) {
        float sv = 0.f;
        const uint4* pv = (const uint4*)((const uint8_t*)Wv + blockIdx.x * 61440) + t;
#pragma unroll 1
        for (int k = 0; k < 40; k += 5) {
          uint4 v[5];
#pragma unroll
          for (int j = 0; j < 5; j++) v[j] = __ldg(pv + (k + j) * 96);
          if (PF_IL && k < 25) {
            asm volatile("prefetch.global.L2 [%0];" :: "l"((const uint8_t*)Wq + blockIdx.x * 61440 + (k / 5) * 12288 + t * 128));
            if (PF_IL > 1) asm volatile("prefetch.global.L2 [%0];" :: "l"((const uint8_t*)Wk + blockIdx.x * 61440 + (k / 5) * 12288 + t * 128));
          }
#pragma unroll
          for (int j = 0; j < 5; j++) {
            sv = fmaf(bflo(v[j].x), bflo(v[j].x), fmaf(bfhi(v[j].x), bfhi(v[j].x), fmaf(bflo(v[j].y), bflo(v[j].y), fmaf(bfhi(v[j].y), bfhi(v[j].y), sv))));
            sv = fmaf(bflo(v[j].z), bflo(v[j].z), fmaf(bfhi(v[j].z), bfhi(v[j].z), fmaf(bflo(v[j].w), bflo(v[j].w), fmaf(bfhi(v[j].w), bfhi(v[j].w), sv))));
          }
        }
#pragma unroll
        for (int o = 16; o; o >>= 1) sv += __shfl_xor_sync(~0u, sv, o);
        if (lane == 0) atomicAdd((float*)(g_zero + Z_NORM + layer), sv);
      }
      if (layer == 1 && PF_LB) {
        const int l = blockIdx.x * 96 + t;
        if (l < 6720 + NLB * 640) asm volatile("prefetch.global.L2 [%0];" :: "l"(l < 6720 ? g_w2 + l * 128 : (const uint8_t*)g_x + (l - 6720) * 128));
      }
#pragma unroll 1
      for (int k = (layer && !RD1) ? 0 : 5 * PF_IL; k < 5 * (layer ? PF_N1 : PF_N0); k++) {
        const int m = k / 5;
        const bf16* W = m == 0 ? Wq : m == 1 ? Wk : m == 2 ? Wv : Wo;
        asm volatile("prefetch.global.L2 [%0];" :: "l"((const uint8_t*)W + blockIdx.x * 61440 + (k - m * 5) * 12288 + t * 128));
        __nanosleep(layer ? PF_SLEEP1 : PF_SLEEP);
      }
      if (t == 0) GTT(layer * 4, 14);
      bar_arrive<3, 352>();
    }
  } else {
    asm volatile("setmaxnreg.inc.sync.aligned.u32 232;");
    GT(layer * 4, 4);
    uint32_t pq[5][4];
    float* kv = (float*)(g_zero + Z_KV) + layer * KV_LAYER + hg * 1920;
    {
      float d[120];
#pragma unroll 1
      for (int kc = 0; kc < 10; kc++) {
        const int st = kc & 3;
        const uint64_t da = mkdesc(SB0 + st * L_STAGE + wg * 8192, 16, 1024, 1), db = mkdesc(SB0 + st * L_STAGE + 16384, 3840, 128, 0);
        mbar_wait(bar + 8 * st, (kc >> 2) & 1);
        wg_fence();
#pragma unroll
        for (int k = 0; k < 4; k++) wg_ss_n240_ta0_tb1(d, da + 2 * k, db + k * 480, kc | k);
        wg_commit();
        if (kc > 0) { wg_wait<1>(); if (lane < 2) mbar_arrive_cl(mapa(bar + 8 * (4 + ((kc - 1) & 3)), lane)); }
      }
      wg_wait<0>();
      pin<120>(d);
      GT(layer * 4, 5);
      bar_sync<1, 256>();
      const uint32_t kb = sb + L_KV + (wg * 8 + 2 * w + ((lane >> 3) & 1)) * 2688 + (lane >> 4) * 128 + (lane & 7) * 16;
#pragma unroll
      for (int j = 0; j < 5; j++) stsm4(kb + 1280 + j * 256, pack2(d[80 + 8 * j], d[81 + 8 * j]), pack2(d[82 + 8 * j], d[83 + 8 * j]), pack2(d[84 + 8 * j], d[85 + 8 * j]), pack2(d[86 + 8 * j], d[87 + 8 * j]));
      stsm2(kb + 2560, 0x3F803F80u, 0x3F803F80u);
#pragma unroll
      for (int j = 0; j < 5; j++) stsm4(kb + j * 256, phi2(d[40 + 8 * j], d[41 + 8 * j]), phi2(d[42 + 8 * j], d[43 + 8 * j]), phi2(d[44 + 8 * j], d[45 + 8 * j]), phi2(d[46 + 8 * j], d[47 + 8 * j]));
      fence_async();
      bar_sync<1, 256>();
      float e[44];
      {
        const uint64_t da = mkdesc(SB0 + L_KV + wg * 1024, 2688, 128, 0), db = mkdesc(SB0 + L_KV + 1280, 2688, 128, 0);
        wg_fence();
#pragma unroll
        for (int k = 0; k < 8; k++) wg_ss_n88_ta1_tb1(e, da + k * 336, db + k * 336, k);
        wg_commit();
        wg_wait<0>();
        pin<44>(e);
      }
#pragma unroll
      for (int h = 0; h < 2; h++) {
        const int row = wg * 64 + 16 * w + 8 * h + g;
        const int c = row < 80 ? 2 * i4 - (row / 20) * 20 : 100;
        float* dst = kv + row * 24 + c;
#pragma unroll
        for (int j = 0; j < 10; j++)
          asm volatile("{\n.reg .pred p;\nsetp.lt.u32 p, %3, 20;\n@p red.relaxed.gpu.global.add.v2.f32 [%0], {%1,%2};\n}" :: "l"(dst + 8 * j), "f"(e[4 * j + 2 * h]), "f"(e[4 * j + 2 * h + 1]), "r"(c + 8 * j) : "memory");
        asm volatile("{\n.reg .pred p;\nsetp.ne.u32 p, %2, 0;\n@p red.relaxed.gpu.global.add.f32 [%0], %1;\n}" :: "l"(kv + row * 24 + 20), "f"(e[40 + 2 * h]), "r"((int)(row < 80 && i4 == 0)) : "memory");
      }
      bar_sync<1, 256>();
      GT(layer * 4, 6);
      if (tid == 0) { red_release(flags + FL_KV + hg * 8, 1); }
      __syncwarp();
      pin<40>(d);
#pragma unroll
      for (int k = 0; k < 5; k++) {
        pq[k][0] = phi2(d[8 * k], d[8 * k + 1]); pq[k][1] = phi2(d[8 * k + 2], d[8 * k + 3]);
        pq[k][2] = phi2(d[8 * k + 4], d[8 * k + 5]); pq[k][3] = phi2(d[8 * k + 6], d[8 * k + 7]);
      }
    }
#pragma unroll 1
    for (int k = tid; k < 1600; k += 256) sts4(sb + L_B2 + k * 16, 0, 0, 0, 0);
    GT(layer * 4, 7);
    if (wid == 0) wait_flag(flags + FL_KV + hg * 8, 16);
    GT(layer * 4, 8);
    bar_sync<1, 256>();
    if (tid < 240) {
      const int dd = tid / 3, part = tid - dd * 3, n = (dd / 20) * 20 + 8 * part;
      const float4 v0 = __ldcg((const float4*)(kv + dd * 24 + 8 * part)), v1 = __ldcg((const float4*)(kv + dd * 24 + 8 * part + 4));
      const float z = __ldcg(kv + dd * 24 + 20);
      const uint32_t a = sb + L_B2 + (dd >> 3) * 2560 + (dd & 7) * 16, zz = pack2(z, z);
      const uint32_t a0 = a + (n >> 3) * 128 + (n & 7) * 2, a1 = a + ((n + 4) >> 3) * 128 + ((n + 4) & 7) * 2;
      sts2(a0, pack2(v0.x, v0.y), pack2(v0.z, v0.w)); sts2(a0 + 1280, zz, zz);
      if (part < 2) { sts2(a1, pack2(v1.x, v1.y), pack2(v1.z, v1.w)); sts2(a1 + 1280, zz, zz); }
    }
    fence_async();
    bar_sync<1, 256>();
    {
      float o[80];
      const uint64_t db = mkdesc(SB0 + L_B2, 2560, 128, 0);
      wg_fence();
#pragma unroll
      for (int k = 0; k < 5; k++) wg_rs_n160_tb1(o, pq[k], db + k * 320, k);
      wg_commit();
      wg_wait<0>();
      pin<80>(o);
      uint8_t* op = g_oa + (tb * 2 + wg) * 81920 + hg * 10240 + w * 256 + lane * 4;
#pragma unroll
      for (int j = 0; j < 20; j++) {
        const float inv = rcp(o[40 + 2 * j] + 1e-6f);
        *(uint32_t*)(op + (j >> 1) * 1024 + (j & 1) * 128) = pack2(o[2 * j] * inv, o[2 * j + 1] * inv);
      }
      GT(layer * 4, 9);
    }
    bar_sync<3, 352>();
    if (tid == 0) { red_release(flags + FL_O + tb * 8, 1); red_add(flags + FL_X, 1); }
    GT(layer * 4, 2);
    if (wid == 7) asm volatile("griddepcontrol.wait;" ::: "memory");
  }
}

__global__ void __launch_bounds__(256) prep_kernel(const bf16* __restrict__ x, const bf16* __restrict__ wqkv, const bf16* __restrict__ wo) {
  asm volatile("griddepcontrol.launch_dependents;");
  const int b = blockIdx.x, tid = threadIdx.x, lane = tid & 31;
  if (b < 160) GT(3, 0);
  if (b < 256) {
    const int row = b * 8 + (tid >> 5);
    float v[20], s = 0.f;
#pragma unroll
    for (int k = 0; k < 10; k++) { const uint32_t u = __ldg((const uint32_t*)(x + row * DM + k * 64 + lane * 2)); v[2 * k] = bflo(u); v[2 * k + 1] = bfhi(u); s += v[2 * k] + v[2 * k + 1]; }
#pragma unroll
    for (int o = 16; o; o >>= 1) s += __shfl_xor_sync(~0u, s, o);
    const float m = s * (1.f / DM);
    float q = 0.f;
#pragma unroll
    for (int k = 0; k < 20; k++) { v[k] -= m; q += v[k] * v[k]; }
#pragma unroll
    for (int o = 16; o; o >>= 1) q += __shfl_xor_sync(~0u, q, o);
    const float r = rsqrtf(q * (1.f / DM) + 1e-5f);
#pragma unroll
    for (int k = 0; k < 10; k++)
      *(uint32_t*)(g_xt + ((row >> 7) * 10 + k) * 16384 + (row & 127) * 128 + (((lane >> 2) ^ (row & 7)) << 4) + (lane & 3) * 4) = pack2(v[2 * k] * r, v[2 * k + 1] * r);
  } else if (b < 256 + 203) {
    uint4 v[4];
    const int u0 = (b - 256) * 1024 + tid;
#pragma unroll
    for (int it = 0; it < 4; it++) {
      const int u = u0 + it * 256, k8 = u & 7;
      const bf16* src;
      bool ok = true;
      if (b < 256 + 150) {
        const int nb = (u >> 3) % 30, kg = (u / 240) % 80, hg = u / 19200;
        src = wqkv + (kg * 8 + k8) * 1920 + (nb / 10) * 640 + hg * 80 + (nb % 10) * 8;
      } else {
        const int q = u - 153600, nb = (q >> 3) % 28, kg = (q / 224) % 80, c = (q / 17920) * 224 + nb * 8;
        ok = c < DM;
        src = wo + (kg * 8 + k8) * DM + (ok ? c : 0);
      }
      v[it] = __ldg((const uint4*)src);
      if (!ok) v[it] = make_uint4(0, 0, 0, 0);
    }
    uint8_t* dst = b < 256 + 150 ? g_w1 + u0 * 16 : g_w2 + (u0 - 153600) * 16;
#pragma unroll
    for (int it = 0; it < 4; it++) if (u0 + it * 256 < 207360) *(uint4*)(dst + it * 4096) = v[it];
  } else {
    const int t = (b - 459) * 256 + tid;
    for (int k = t; k < Z_END / 4; k += 16 * 256) ((uint4*)g_zero)[k] = make_uint4(0, 0, 0, 0);
    for (int k = t; k < 16 * DM; k += 16 * 256) { ((uint4*)g_acc)[k] = make_uint4(0, 0, 0, 0); ((uint4*)(g_acc + S_TOK * DM))[k] = make_uint4(0, 0, 0, 0); }
  }
  if (b < 160) GT(3, 2);
}

typedef CUresult (*EncodeFn)(CUtensorMap*, CUtensorMapDataType, cuuint32_t, void*, const cuuint64_t*, const cuuint64_t*, const cuuint32_t*,
                             const cuuint32_t*, CUtensorMapInterleave, CUtensorMapSwizzle, CUtensorMapL2promotion, CUtensorMapFloatOOBfill);
static void make_map(EncodeFn fn, CUtensorMap* m, const void* p, uint64_t cols, uint64_t rows, uint32_t bc, uint32_t br, CUtensorMapSwizzle sw) {
  cuuint64_t dims[2] = {cols, rows}; cuuint64_t strides[1] = {cols * 2}; cuuint32_t box[2] = {bc, br}; cuuint32_t es[2] = {1, 1};
  fn(m, CU_TENSOR_MAP_DATA_TYPE_BFLOAT16, 2, (void*)p, dims, strides, box, es, CU_TENSOR_MAP_INTERLEAVE_NONE, sw,
     CU_TENSOR_MAP_L2_PROMOTION_L2_128B, CU_TENSOR_MAP_FLOAT_OOB_FILL_NONE);
}

static void make_map_perm(EncodeFn fn, CUtensorMap* m, const void* p) {
  cuuint64_t dims[5] = {HE, 2, 2, 4, 40}; const cuuint64_t r = HE * 2; cuuint64_t strides[4] = {r, 8 * r, 2 * r, 16 * r};
  cuuint32_t box[5] = {64, 2, 2, 4, 4}; cuuint32_t es[5] = {1, 1, 1, 1, 1};
  fn(m, CU_TENSOR_MAP_DATA_TYPE_BFLOAT16, 5, (void*)p, dims, strides, box, es, CU_TENSOR_MAP_INTERLEAVE_NONE, CU_TENSOR_MAP_SWIZZLE_128B,
     CU_TENSOR_MAP_L2_PROMOTION_L2_128B, CU_TENSOR_MAP_FLOAT_OOB_FILL_NONE);
}

#define OPC_PDL 1
#define LA_PDL 1
#define REC_PDL 1
extern "C" void kernel_launch(void* const* d_in, const int* in_sizes, int n_in, void* d_out, int out_size) {
  const bf16* x = (const bf16*)d_in[0];
  const bf16* wqkv = (const bf16*)d_in[1];
  const bf16* wo_a = (const bf16*)d_in[2];
  const bf16* mem0 = (const bf16*)d_in[4];
  const bf16* Wq = (const bf16*)d_in[5];
  const bf16* Wk = (const bf16*)d_in[6];
  const bf16* Wv = (const bf16*)d_in[7];
  const bf16* Wo = (const bf16*)d_in[8];
  cudaStream_t st = cudaStreamPerThread;

  static EncodeFn enc = nullptr;
  static uint8_t* p_ar; static uint32_t* p_zero; static bf16* p_x;
  if (!enc) {
    cudaDriverEntryPointQueryResult qr;
    void* fn = nullptr;
    cudaGetDriverEntryPoint("cuTensorMapEncodeTiled", &fn, cudaEnableDefault, &qr);
    enc = (EncodeFn)fn;
    cudaFuncSetAttribute(rec_kernel, cudaFuncAttributeMaxDynamicSharedMemorySize, REC_SMEM);
    cudaFuncSetAttribute(opc_kernel, cudaFuncAttributeMaxDynamicSharedMemorySize, OPC_SMEM);
    cudaFuncSetAttribute(la_kernel, cudaFuncAttributeMaxDynamicSharedMemorySize, LA_SMEM);
    cudaGetSymbolAddress((void**)&p_ar, g_ar); p_ar = (uint8_t*)(((uintptr_t)p_ar + 32767) & ~(uintptr_t)32767);
    cudaGetSymbolAddress((void**)&p_zero, g_zero); cudaGetSymbolAddress((void**)&p_x, g_x);
  }
  CUtensorMap tmq, tmk, tmv, tmo, tmx[2];
  make_map_perm(enc, &tmq, Wq);
  make_map_perm(enc, &tmk, Wk);
  make_map_perm(enc, &tmv, Wv);
  make_map(enc, &tmo, Wo, DM, HE, 64, 64, CU_TENSOR_MAP_SWIZZLE_128B);
  make_map(enc, &tmx[0], x, DM, S_TOK, 232, 64, CU_TENSOR_MAP_SWIZZLE_NONE);
  make_map(enc, &tmx[1], p_x, DM, S_TOK, 232, 64, CU_TENSOR_MAP_SWIZZLE_NONE);

  cudaLaunchAttribute at[2];
  at[0].id = cudaLaunchAttributeProgrammaticStreamSerialization; at[0].val.programmaticStreamSerializationAllowed = 1;
  at[1].id = cudaLaunchAttributeClusterDimension; at[1].val.clusterDim.x = 3; at[1].val.clusterDim.y = 1; at[1].val.clusterDim.z = 1;
  cudaLaunchAttribute at2[2] = {at[1], at[0]};
  at2[0].val.clusterDim.x = 2;
  prep_kernel<<<475, 256, 0, st>>>(x, wqkv, wo_a);
  for (int l = 0; l < 2; l++) {
    cudaLaunchConfig_t cfg = {};
    cfg.blockDim = dim3(384); cfg.stream = st;
    cfg.gridDim = dim3(l == 0 ? 132 : 128); cfg.dynamicSmemBytes = LA_SMEM; cfg.attrs = at2; cfg.numAttrs = 1 + LA_PDL;
    cudaLaunchKernelEx(&cfg, la_kernel, Wq, Wk, Wv, Wo, p_ar + l * AR_LAYER, l);
    cfg.gridDim = dim3(96 + 3 * NLB); cfg.dynamicSmemBytes = REC_SMEM; cfg.attrs = at + 1 - REC_PDL; cfg.numAttrs = 1 + REC_PDL;
    cudaLaunchKernelEx(&cfg, rec_kernel, tmq, tmk, tmv, tmo, tmx[l], mem0, p_ar + l * AR_LAYER, p_zero + Z_FLAGS + l * FL_LAYER, l);
    cfg.gridDim = dim3(36); cfg.dynamicSmemBytes = OPC_SMEM; cfg.attrs = at; cfg.numAttrs = OPC_PDL;
    cudaLaunchKernelEx(&cfg, opc_kernel, tmo, l == 1 ? (bf16*)d_out : (bf16*)nullptr, l, Wq, Wk, Wv, Wo);
  }
}
```

```cpp
#include <cuda_runtime.h>
#include <cuda_bf16.h>
#include <cuda.h>
#include <stdint.h>

typedef __nv_bfloat16 bf16;
typedef unsigned long long u64;

constexpr int S_TOK = 2048, DM = 640, DH = 192, HE = 6144, NSEG = 64;

constexpr int AR_GROUP = 98304;
constexpr int AR_LAYER = 16 * AR_GROUP;
__device__ __align__(1024) uint8_t g_ar[2 * AR_LAYER + 32768];
__device__ __align__(1024) uint8_t g_xn[NSEG * 40960];
__device__ __align__(1024) uint8_t g_xt[S_TOK * DM * 2];
__device__ __align__(1024) uint8_t g_ot[NSEG * HE * 64];
__device__ __align__(1024) uint8_t g_oa[S_TOK * DM * 2];
__device__ __align__(1024) uint8_t g_w1[DM * 1920 * 2];
__device__ __align__(1024) uint8_t g_w2[DM * 672 * 2];
__device__ __align__(1024) float g_acc[2 * S_TOK * DM];
__device__ __align__(1024) bf16 g_x[S_TOK * DM];
constexpr int FL_A = 0, FL_B = 64 * 6 * 8, FL_KV = FL_B + 64 * 8, FL_O = FL_KV + 8 * 8, FL_T = FL_O + 16 * 8, FL_X = FL_T + 16 * 8, FL_N = FL_X + 8, FL_R = FL_N + 8, FL_XN = FL_R + 8, FL_LAYER = FL_XN + 32 * 8;
constexpr int Z_FLAGS = 0, Z_NORM = 2 * FL_LAYER, Z_KV = Z_NORM + 8, KV_LAYER = 8 * 80 * 24, Z_END = Z_KV + 2 * KV_LAYER;
__device__ __align__(128) uint32_t g_zero[Z_END];
__device__ __align__(128) float g_nrm[4 * DM];
#define GT(slot, k) do {} while (0)
#define GTT(slot, k) do {} while (0)

__device__ __forceinline__ uint32_t smem_u32(const void* p) { return (uint32_t)__cvta_generic_to_shared(p); }
__device__ __forceinline__ uint32_t mapa(uint32_t a, uint32_t r) { uint32_t o; asm("mapa.shared::cluster.u32 %0, %1, %2;" : "=r"(o) : "r"(a), "r"(r)); return o; }
__device__ __forceinline__ void mbar_init(uint32_t bar, uint32_t cnt) { asm volatile("mbarrier.init.shared::cta.b64 [%0], %1;" :: "r"(bar), "r"(cnt) : "memory"); }
__device__ __forceinline__ void mbar_expect(uint32_t bar, uint32_t tx) { asm volatile("mbarrier.arrive.expect_tx.shared::cta.b64 _, [%0], %1;" :: "r"(bar), "r"(tx) : "memory"); }
__device__ __forceinline__ void mbar_arrive(uint32_t bar) { asm volatile("mbarrier.arrive.shared::cta.b64 _, [%0];" :: "r"(bar) : "memory"); }
__device__ __forceinline__ void mbar_wait(uint32_t bar, uint32_t par) {
  asm volatile("{\n.reg .pred p;\n.reg .u32 c;\nmov.u32 c, 0;\n"
               "LW:\nmbarrier.try_wait.parity.shared::cta.b64 p, [%0], %1;\n@p bra LD;\n"
               "add.u32 c, c, 1;\nsetp.lt.u32 p, c, 4000000;\n@p bra LW;\ntrap;\nLD:\n}" :: "r"(bar), "r"(par) : "memory");
}
__device__ __forceinline__ void mbar_waitf(uint32_t bar, uint32_t par) {
  asm volatile("{\n.reg .pred p, q;\n.reg .u32 c;\nmov.u32 c, 0;\n"
               "LW:\nadd.u32 c, c, 1;\nsetp.lt.u32 q, c, 1000000;\nmbarrier.try_wait.parity.shared::cta.b64 p, [%0], %1;\n"
               "and.pred q, q, !p;\n@q bra LW;\n}" :: "r"(bar), "r"(par) : "memory");
}
template <int ID, int N> __device__ __forceinline__ void bar_sync() { asm volatile("barrier.sync %0, %1;" :: "n"(ID), "n"(N) : "memory"); }
template <int ID, int N> __device__ __forceinline__ void bar_arrive() { asm volatile("barrier.arrive %0, %1;" :: "n"(ID), "n"(N) : "memory"); }
__device__ __forceinline__ void fence_async() { asm volatile("fence.proxy.async.shared::cta;" ::: "memory"); }
__device__ __forceinline__ void cluster_sync() { asm volatile("barrier.cluster.arrive.aligned;\nbarrier.cluster.wait.aligned;" ::: "memory"); }
__device__ __forceinline__ void wg_fence() { asm volatile("wgmma.fence.sync.aligned;" ::: "memory"); }
__device__ __forceinline__ void wg_commit() { asm volatile("wgmma.commit_group.sync.aligned;" ::: "memory"); }
template <int N> __device__ __forceinline__ void wg_wait() { asm volatile("wgmma.wait_group.sync.aligned %0;" :: "n"(N) : "memory"); }
template <int N> __device__ __forceinline__ void pin(float* d) {
#pragma unroll
  for (int i = 0; i < N; i++) asm volatile("" : "+f"(d[i]) :: "memory");
}
__device__ __forceinline__ constexpr uint64_t mkdesc(uint32_t addr, uint32_t lbo, uint32_t sbo, int sw) {
  return (uint64_t)((addr & 0x3FFFF) >> 4) | ((uint64_t)(lbo >> 4) << 16) | ((uint64_t)(sbo >> 4) << 32) | ((uint64_t)sw << 62);
}
constexpr uint32_t SB0 = 1024;
__device__ __forceinline__ void check_smem_base(uint32_t sb) { if ((sb & 0x3FFFF) != SB0) __trap(); }
__device__ __forceinline__ uint32_t cta_rank() { uint32_t r; asm volatile("mov.u32 %0, %%cluster_ctarank;" : "=r"(r)); return r; }
__device__ __forceinline__ uint32_t opaque(uint32_t v) { uint32_t o; asm volatile("mov.u32 %0, %1;" : "=r"(o) : "r"(v)); return o; }
__device__ __forceinline__ uint32_t pack2(float lo, float hi) { uint32_t r; asm("cvt.rn.bf16x2.f32 %0, %1, %2;" : "=r"(r) : "f"(hi), "f"(lo)); return r; }
__device__ __forceinline__ void ldsm4(uint32_t* r, uint32_t a) { asm volatile("ldmatrix.sync.aligned.m8n8.x4.shared.b16 {%0,%1,%2,%3}, [%4];" : "=r"(r[0]), "=r"(r[1]), "=r"(r[2]), "=r"(r[3]) : "r"(a) : "memory"); }
__device__ __forceinline__ void ldsm4t(uint32_t* r, uint32_t a) { asm volatile("ldmatrix.sync.aligned.m8n8.x4.trans.shared.b16 {%0,%1,%2,%3}, [%4];" : "=r"(r[0]), "=r"(r[1]), "=r"(r[2]), "=r"(r[3]) : "r"(a) : "memory"); }
__device__ __forceinline__ void ldsm1(uint32_t& r, uint32_t a) { asm volatile("ldmatrix.sync.aligned.m8n8.x1.shared.b16 {%0}, [%1];" : "=r"(r) : "r"(a) : "memory"); }
__device__ __forceinline__ void stsm4(uint32_t a, uint32_t r0, uint32_t r1, uint32_t r2, uint32_t r3) { asm volatile("stmatrix.sync.aligned.m8n8.x4.shared.b16 [%0], {%1,%2,%3,%4};" :: "r"(a), "r"(r0), "r"(r1), "r"(r2), "r"(r3) : "memory"); }
__device__ __forceinline__ void stsm1(uint32_t a, uint32_t r0) { asm volatile("stmatrix.sync.aligned.m8n8.x1.shared.b16 [%0], {%1};" :: "r"(a), "r"(r0) : "memory"); }
__device__ __forceinline__ void stsm4t(uint32_t a, uint32_t r0, uint32_t r1, uint32_t r2, uint32_t r3) { asm volatile("stmatrix.sync.aligned.m8n8.x4.trans.shared.b16 [%0], {%1,%2,%3,%4};" :: "r"(a), "r"(r0), "r"(r1), "r"(r2), "r"(r3) : "memory"); }
__device__ __forceinline__ void stsm2t(uint32_t a, uint32_t r0, uint32_t r1) { asm volatile("stmatrix.sync.aligned.m8n8.x2.trans.shared.b16 [%0], {%1,%2};" :: "r"(a), "r"(r0), "r"(r1) : "memory"); }
__device__ __forceinline__ void mma16816(float* c, const uint32_t* a, uint32_t b0, uint32_t b1) {
  asm volatile("mma.sync.aligned.m16n8k16.row.col.f32.bf16.bf16.f32 {%0,%1,%2,%3}, {%4,%5,%6,%7}, {%8,%9}, {%0,%1,%2,%3};"
               : "+f"(c[0]), "+f"(c[1]), "+f"(c[2]), "+f"(c[3]) : "r"(a[0]), "r"(a[1]), "r"(a[2]), "r"(a[3]), "r"(b0), "r"(b1));
}
__device__ __forceinline__ void mma1688(float* c, uint32_t a0, uint32_t a1, uint32_t b0) {
  asm volatile("mma.sync.aligned.m16n8k8.row.col.f32.bf16.bf16.f32 {%0,%1,%2,%3}, {%4,%5}, {%6}, {%0,%1,%2,%3};"
               : "+f"(c[0]), "+f"(c[1]), "+f"(c[2]), "+f"(c[3]) : "r"(a0), "r"(a1), "r"(b0));
}
__device__ __forceinline__ void sta1(uint32_t a, uint32_t v, uint32_t bar) { asm volatile("st.async.weak.shared::cluster.mbarrier::complete_tx::bytes.b32 [%0], %1, [%2];" :: "r"(a), "r"(v), "r"(bar) : "memory"); }
__device__ __forceinline__ void sta1p(uint32_t a, uint32_t v, uint32_t bar, bool p) { asm volatile("{\n.reg .pred p;\nsetp.ne.b32 p, %3, 0;\n@p st.async.weak.shared::cluster.mbarrier::complete_tx::bytes.b32 [%0], %1, [%2];\n}" :: "r"(a), "r"(v), "r"(bar), "r"((int)p) : "memory"); }
__device__ __forceinline__ void sta2(uint32_t a, uint32_t v0, uint32_t v1, uint32_t bar) { asm volatile("st.async.weak.shared::cluster.mbarrier::complete_tx::bytes.v2.b32 [%0], {%1,%2}, [%3];" :: "r"(a), "r"(v0), "r"(v1), "r"(bar) : "memory"); }
__device__ __forceinline__ void sta4(uint32_t a, uint32_t v0, uint32_t v1, uint32_t v2, uint32_t v3, uint32_t bar) { asm volatile("st.async.weak.shared::cluster.mbarrier::complete_tx::bytes.v4.b32 [%0], {%1,%2,%3,%4}, [%5];" :: "r"(a), "r"(v0), "r"(v1), "r"(v2), "r"(v3), "r"(bar) : "memory"); }
__device__ __forceinline__ float bflo(uint32_t v) { return __uint_as_float(v << 16); }
__device__ __forceinline__ float bfhi(uint32_t v) { return __uint_as_float(v & 0xFFFF0000u); }
__device__ __forceinline__ void sta2f(uint32_t a, float v0, float v1, uint32_t bar) { asm volatile("st.async.weak.shared::cluster.mbarrier::complete_tx::bytes.v2.f32 [%0], {%1,%2}, [%3];" :: "r"(a), "f"(v0), "f"(v1), "r"(bar) : "memory"); }
__device__ __forceinline__ void sta4f(uint32_t a, float v0, float v1, float v2, float v3, uint32_t bar) { asm volatile("st.async.weak.shared::cluster.mbarrier::complete_tx::bytes.v4.f32 [%0], {%1,%2,%3,%4}, [%5];" :: "r"(a), "f"(v0), "f"(v1), "f"(v2), "f"(v3), "r"(bar) : "memory"); }
__device__ __forceinline__ float4 lds4f(uint32_t a) { float4 v; asm volatile("ld.shared.v4.f32 {%0,%1,%2,%3}, [%4];" : "=f"(v.x), "=f"(v.y), "=f"(v.z), "=f"(v.w) : "r"(a) : "memory"); return v; }
__device__ __forceinline__ float2 lds2f(uint32_t a) { float2 v; asm volatile("ld.shared.v2.f32 {%0,%1}, [%2];" : "=f"(v.x), "=f"(v.y) : "r"(a) : "memory"); return v; }
__device__ __forceinline__ uint4 lds4(uint32_t a) { uint4 v; asm volatile("ld.shared.v4.u32 {%0,%1,%2,%3}, [%4];" : "=r"(v.x), "=r"(v.y), "=r"(v.z), "=r"(v.w) : "r"(a) : "memory"); return v; }
__device__ __forceinline__ uint32_t lds1(uint32_t a) { uint32_t v; asm volatile("ld.shared.u32 %0, [%1];" : "=r"(v) : "r"(a) : "memory"); return v; }
__device__ __forceinline__ void stsm2(uint32_t a, uint32_t r0, uint32_t r1) { asm volatile("stmatrix.sync.aligned.m8n8.x2.shared.b16 [%0], {%1,%2};" :: "r"(a), "r"(r0), "r"(r1) : "memory"); }
__device__ __forceinline__ float rcp(float x) { float y; asm("rcp.approx.ftz.f32 %0, %1;" : "=f"(y) : "f"(x)); return y; }
__device__ __forceinline__ void sts4(uint32_t a, uint32_t v0, uint32_t v1, uint32_t v2, uint32_t v3) { asm volatile("st.shared.v4.u32 [%0], {%1,%2,%3,%4};" :: "r"(a), "r"(v0), "r"(v1), "r"(v2), "r"(v3) : "memory"); }
__device__ __forceinline__ void bulk_s2c(uint32_t dst, uint32_t src, uint32_t bytes, uint32_t bar) {
  asm volatile("cp.async.bulk.shared::cluster.shared::cta.mbarrier::complete_tx::bytes [%0], [%1], %2, [%3];" :: "r"(dst), "r"(src), "r"(bytes), "r"(bar) : "memory");
}
__device__ __forceinline__ void stg4(void* p, uint4 v) { asm volatile("st.global.v4.u32 [%0], {%1,%2,%3,%4};" :: "l"(p), "r"(v.x), "r"(v.y), "r"(v.z), "r"(v.w) : "memory"); }
__device__ __forceinline__ void red_add(uint32_t* p, uint32_t v) { asm volatile("red.relaxed.gpu.global.add.u32 [%0], %1;" :: "l"(p), "r"(v) : "memory"); }
__device__ __forceinline__ void red_release(uint32_t* p, uint32_t v) { asm volatile("red.release.gpu.global.add.u32 [%0], %1;" :: "l"(p), "r"(v) : "memory"); }
__device__ __forceinline__ void fence_async_global() { asm volatile("fence.proxy.async.global;" ::: "memory"); }
__device__ __forceinline__ uint64_t policy_evict_first() { uint64_t p; asm("createpolicy.fractional.L2::evict_first.b64 %0, 1.0;" : "=l"(p)); return p; }
__device__ __forceinline__ void stg4h(void* p, uint4 v, uint64_t pol) { asm volatile("st.global.L2::cache_hint.v4.u32 [%0], {%1,%2,%3,%4}, %5;" :: "l"(p), "r"(v.x), "r"(v.y), "r"(v.z), "r"(v.w), "l"(pol) : "memory"); }
__device__ __forceinline__ void red4fh(float* p, float a, float b, float c, float d, uint64_t pol) { asm volatile("red.relaxed.gpu.global.add.L2::cache_hint.v4.f32 [%0], {%1,%2,%3,%4}, %5;" :: "l"(p), "f"(a), "f"(b), "f"(c), "f"(d), "l"(pol) : "memory"); }
__device__ __forceinline__ float4 ldg4fh(const float* p, uint64_t pol) { float4 v; asm volatile("ld.global.cg.L2::cache_hint.v4.f32 {%0,%1,%2,%3}, [%4], %5;" : "=f"(v.x), "=f"(v.y), "=f"(v.z), "=f"(v.w) : "l"(p), "l"(pol) : "memory"); return v; }
__device__ __forceinline__ void bulk_g2sh(uint32_t dst, const void* src, uint32_t bytes, uint32_t bar, uint64_t pol) {
  asm volatile("cp.async.bulk.shared::cluster.global.mbarrier::complete_tx::bytes.L2::cache_hint [%0], [%1], %2, [%3], %4;" :: "r"(dst), "l"(src), "r"(bytes), "r"(bar), "l"(pol) : "memory");
}
#define EVF 1
__device__ __forceinline__ void red4f(float* p, float a, float b, float c, float d) { asm volatile("red.relaxed.gpu.global.add.v4.f32 [%0], {%1,%2,%3,%4};" :: "l"(p), "f"(a), "f"(b), "f"(c), "f"(d) : "memory"); }
template <int SLEEP = 20>
__device__ __forceinline__ void wait_flag(const uint32_t* p, uint32_t target) {
  uint32_t v; int it = 0;
  while (true) {
    asm volatile("ld.acquire.gpu.global.u32 %0, [%1];" : "=r"(v) : "l"(p) : "memory");
    if (__all_sync(~0u, v >= target)) break;
    if (++it > 4000000) __trap();
    __nanosleep(SLEEP);
  }
}
__device__ __forceinline__ void sts2(uint32_t a, uint32_t v0, uint32_t v1) { asm volatile("st.shared.v2.u32 [%0], {%1,%2};" :: "r"(a), "r"(v0), "r"(v1) : "memory"); }
__device__ __forceinline__ float sqrt_approx(float x) { float y; asm("sqrt.approx.f32 %0, %1;" : "=f"(y) : "f"(x)); return y; }
template <int BYTES> __device__ __forceinline__ void bulk_s2c_elect(uint32_t d1, uint32_t b1, uint32_t d2, uint32_t b2, uint32_t src) {
  asm volatile("{\n.reg .pred p;\nelect.sync _|p, 0xffffffff;\n"
               "@p cp.async.bulk.shared::cluster.shared::cta.mbarrier::complete_tx::bytes [%0], [%4], %5, [%1];\n"
               "@p cp.async.bulk.shared::cluster.shared::cta.mbarrier::complete_tx::bytes [%2], [%4], %5, [%3];\n}"
               :: "r"(d1), "r"(b1), "r"(d2), "r"(b2), "r"(src), "n"(BYTES) : "memory");
}
__device__ __forceinline__ void mbar_arrive_elect(uint32_t bar) { asm volatile("{\n.reg .pred p;\nelect.sync _|p, 0xffffffff;\n@p mbarrier.arrive.shared::cta.b64 _, [%0];\n}" :: "r"(bar) : "memory"); }
__device__ __forceinline__ void cp16(uint32_t dst, const void* src) { asm volatile("cp.async.cg.shared.global [%0], [%1], 16;" :: "r"(dst), "l"(src) : "memory"); }
__device__ __forceinline__ void sts1(uint32_t a, uint32_t v) { asm volatile("st.shared.u32 [%0], %1;" :: "r"(a), "r"(v) : "memory"); }
__device__ __forceinline__ void bulk_g2s(uint32_t dst, const void* src, uint32_t bytes, uint32_t bar) {
  asm volatile("cp.async.bulk.shared::cluster.global.mbarrier::complete_tx::bytes [%0], [%1], %2, [%3];" :: "r"(dst), "l"(src), "r"(bytes), "r"(bar) : "memory");
}
__device__ __forceinline__ void bulk_g2s_mc(uint32_t dst, const void* src, uint32_t bytes, uint32_t bar) {
  asm volatile("cp.async.bulk.shared::cluster.global.mbarrier::complete_tx::bytes.multicast::cluster [%0], [%1], %2, [%3], %4;" :: "r"(dst), "l"(src), "r"(bytes), "r"(bar), "h"((uint16_t)3) : "memory");
}
__device__ __forceinline__ void mbar_arrive_cl(uint32_t bar) { asm volatile("mbarrier.arrive.shared::cluster.b64 _, [%0];" :: "r"(bar) : "memory"); }
__device__ __forceinline__ void tma2d(uint32_t dst, const CUtensorMap* m, int c0, int c1, uint32_t bar) {
  asm volatile("cp.async.bulk.tensor.2d.shared::cluster.global.mbarrier::complete_tx::bytes [%0], [%1, {%3, %4}], [%2];" :: "r"(dst), "l"((uint64_t)m), "r"(bar), "r"(c0), "r"(c1) : "memory");
}
__device__ __forceinline__ void tma5d(uint32_t dst, const CUtensorMap* m, int c0, int c4, uint32_t bar) {
  asm volatile("cp.async.bulk.tensor.5d.shared::cluster.global.mbarrier::complete_tx::bytes [%0], [%1, {%3, %5, %5, %5, %4}], [%2];" :: "r"(dst), "l"((uint64_t)m), "r"(bar), "r"(c0), "r"(c4), "r"(0) : "memory");
}
__device__ __forceinline__ void red64(void* p, uint32_t lo, uint32_t hi) { asm volatile("{\n.reg .b64 t;\nmov.b64 t, {%1,%2};\nred.relaxed.gpu.global.add.u64 [%0], t;\n}" :: "l"(p), "r"(lo), "r"(hi) : "memory"); }
__device__ __forceinline__ uint4 ld_poll(const void* p) {
  uint4 v;
  asm volatile("{\n.reg .b64 a, b;\nld.relaxed.gpu.global.v2.b64 {a, b}, [%4];\nmov.b64 {%0,%1}, a;\nmov.b64 {%2,%3}, b;\n}" : "=r"(v.x), "=r"(v.y), "=r"(v.z), "=r"(v.w) : "l"(p) : "memory");
  return v;
}
__device__ __forceinline__ uint32_t clk() { uint32_t c; asm volatile("mov.u32 %0, %%clock;" : "=r"(c) :: "memory"); return c; }
#define SCHED_FENCE() asm volatile("pmevent 0;" ::: "memory")
__device__ __forceinline__ float ex2(float x) { float y; asm("ex2.approx.ftz.f32 %0, %1;" : "=f"(y) : "f"(x)); return y; }

__device__ __forceinline__ void wg_ss_n240_ta0_tb1(float* d, uint64_t a, uint64_t b, int sc) {
  asm volatile("{\n.reg .pred p;\nsetp.ne.b32 p, %122, 0;\nwgmma.mma_async.sync.aligned.m64n240k16.f32.bf16.bf16 {%0, %1, %2, %3, %4, %5, %6, %7, %8, %9, %10, %11, %12, %13, %14, %15, %16, %17, %18, %19, %20, %21, %22, %23, %24, %25, %26, %27, %28, %29, %30, %31, %32, %33, %34, %35, %36, %37, %38, %39, %40, %41, %42, %43, %44, %45, %46, %47, %48, %49, %50, %51, %52, %53, %54, %55, %56, %57, %58, %59, %60, %61, %62, %63, %64, %65, %66, %67, %68, %69, %70, %71, %72, %73, %74, %75, %76, %77, %78, %79, %80, %81, %82, %83, %84, %85, %86, %87, %88, %89, %90, %91, %92, %93, %94, %95, %96, %97, %98, %99, %100, %101, %102, %103, %104, %105, %106, %107, %108, %109, %110, %111, %112, %113, %114, %115, %116, %117, %118, %119}, %120, %121, p, 1, 1, 0, 1;\n}\n"
    : "+f"(d[0]), "+f"(d[1]), "+f"(d[2]), "+f"(d[3]), "+f"(d[4]), "+f"(d[5]), "+f"(d[6]), "+f"(d[7]), "+f"(d[8]), "+f"(d[9]), "+f"(d[10]), "+f"(d[11]), "+f"(d[12]), "+f"(d[13]), "+f"(d[14]), "+f"(d[15]), "+f"(d[16]), "+f"(d[17]), "+f"(d[18]), "+f"(d[19]), "+f"(d[20]), "+f"(d[21]), "+f"(d[22]), "+f"(d[23]), "+f"(d[24]), "+f"(d[25]), "+f"(d[26]), "+f"(d[27]), "+f"(d[28]), "+f"(d[29]), "+f"(d[30]), "+f"(d[31]), "+f"(d[32]), "+f"(d[33]), "+f"(d[34]), "+f"(d[35]), "+f"(d[36]), "+f"(d[37]), "+f"(d[38]), "+f"(d[39]), "+f"(d[40]), "+f"(d[41]), "+f"(d[42]), "+f"(d[43]), "+f"(d[44]), "+f"(d[45]), "+f"(d[46]), "+f"(d[47]), "+f"(d[48]), "+f"(d[49]), "+f"(d[50]), "+f"(d[51]), "+f"(d[52]), "+f"(d[53]), "+f"(d[54]), "+f"(d[55]), "+f"(d[56]), "+f"(d[57]), "+f"(d[58]), "+f"(d[59]), "+f"(d[60]), "+f"(d[61]), "+f"(d[62]), "+f"(d[63]), "+f"(d[64]), "+f"(d[65]), "+f"(d[66]), "+f"(d[67]), "+f"(d[68]), "+f"(d[69]), "+f"(d[70]), "+f"(d[71]), "+f"(d[72]), "+f"(d[73]), "+f"(d[74]), "+f"(d[75]), "+f"(d[76]), "+f"(d[77]), "+f"(d[78]), "+f"(d[79]), "+f"(d[80]), "+f"(d[81]), "+f"(d[82]), "+f"(d[83]), "+f"(d[84]), "+f"(d[85]), "+f"(d[86]), "+f"(d[87]), "+f"(d[88]), "+f"(d[89]), "+f"(d[90]), "+f"(d[91]), "+f"(d[92]), "+f"(d[93]), "+f"(d[94]), "+f"(d[95]), "+f"(d[96]), "+f"(d[97]), "+f"(d[98]), "+f"(d[99]), "+f"(d[100]), "+f"(d[101]), "+f"(d[102]), "+f"(d[103]), "+f"(d[104]), "+f"(d[105]), "+f"(d[106]), "+f"(d[107]), "+f"(d[108]), "+f"(d[109]), "+f"(d[110]), "+f"(d[111]), "+f"(d[112]), "+f"(d[113]), "+f"(d[114]), "+f"(d[115]), "+f"(d[116]), "+f"(d[117]), "+f"(d[118]), "+f"(d[119])
    : "l"(a), "l"(b), "r"(sc));
}
__device__ __forceinline__ void wg_ss_n88_ta1_tb1(float* d, uint64_t a, uint64_t b, int sc) {
  asm volatile("{\n.reg .pred p;\nsetp.ne.b32 p, %46, 0;\nwgmma.mma_async.sync.aligned.m64n88k16.f32.bf16.bf16 {%0, %1, %2, %3, %4, %5, %6, %7, %8, %9, %10, %11, %12, %13, %14, %15, %16, %17, %18, %19, %20, %21, %22, %23, %24, %25, %26, %27, %28, %29, %30, %31, %32, %33, %34, %35, %36, %37, %38, %39, %40, %41, %42, %43}, %44, %45, p, 1, 1, 1, 1;\n}\n"
    : "+f"(d[0]), "+f"(d[1]), "+f"(d[2]), "+f"(d[3]), "+f"(d[4]), "+f"(d[5]), "+f"(d[6]), "+f"(d[7]), "+f"(d[8]), "+f"(d[9]), "+f"(d[10]), "+f"(d[11]), "+f"(d[12]), "+f"(d[13]), "+f"(d[14]), "+f"(d[15]), "+f"(d[16]), "+f"(d[17]), "+f"(d[18]), "+f"(d[19]), "+f"(d[20]), "+f"(d[21]), "+f"(d[22]), "+f"(d[23]), "+f"(d[24]), "+f"(d[25]), "+f"(d[26]), "+f"(d[27]), "+f"(d[28]), "+f"(d[29]), "+f"(d[30]), "+f"(d[31]), "+f"(d[32]), "+f"(d[33]), "+f"(d[34]), "+f"(d[35]), "+f"(d[36]), "+f"(d[37]), "+f"(d[38]), "+f"(d[39]), "+f"(d[40]), "+f"(d[41]), "+f"(d[42]), "+f"(d[43])
    : "l"(a), "l"(b), "r"(sc));
}
__device__ __forceinline__ void wg_rs_n160_tb1(float* d, const uint32_t* a, uint64_t b, int sc) {
  asm volatile("{\n.reg .pred p;\nsetp.ne.b32 p, %85, 0;\nwgmma.mma_async.sync.aligned.m64n160k16.f32.bf16.bf16 {%0, %1, %2, %3, %4, %5, %6, %7, %8, %9, %10, %11, %12, %13, %14, %15, %16, %17, %18, %19, %20, %21, %22, %23, %24, %25, %26, %27, %28, %29, %30, %31, %32, %33, %34, %35, %36, %37, %38, %39, %40, %41, %42, %43, %44, %45, %46, %47, %48, %49, %50, %51, %52, %53, %54, %55, %56, %57, %58, %59, %60, %61, %62, %63, %64, %65, %66, %67, %68, %69, %70, %71, %72, %73, %74, %75, %76, %77, %78, %79}, {%80, %81, %82, %83}, %84, p, 1, 1, 1;\n}\n"
    : "+f"(d[0]), "+f"(d[1]), "+f"(d[2]), "+f"(d[3]), "+f"(d[4]), "+f"(d[5]), "+f"(d[6]), "+f"(d[7]), "+f"(d[8]), "+f"(d[9]), "+f"(d[10]), "+f"(d[11]), "+f"(d[12]), "+f"(d[13]), "+f"(d[14]), "+f"(d[15]), "+f"(d[16]), "+f"(d[17]), "+f"(d[18]), "+f"(d[19]), "+f"(d[20]), "+f"(d[21]), "+f"(d[22]), "+f"(d[23]), "+f"(d[24]), "+f"(d[25]), "+f"(d[26]), "+f"(d[27]), "+f"(d[28]), "+f"(d[29]), "+f"(d[30]), "+f"(d[31]), "+f"(d[32]), "+f"(d[33]), "+f"(d[34]), "+f"(d[35]), "+f"(d[36]), "+f"(d[37]), "+f"(d[38]), "+f"(d[39]), "+f"(d[40]), "+f"(d[41]), "+f"(d[42]), "+f"(d[43]), "+f"(d[44]), "+f"(d[45]), "+f"(d[46]), "+f"(d[47]), "+f"(d[48]), "+f"(d[49]), "+f"(d[50]), "+f"(d[51]), "+f"(d[52]), "+f"(d[53]), "+f"(d[54]), "+f"(d[55]), "+f"(d[56]), "+f"(d[57]), "+f"(d[58]), "+f"(d[59]), "+f"(d[60]), "+f"(d[61]), "+f"(d[62]), "+f"(d[63]), "+f"(d[64]), "+f"(d[65]), "+f"(d[66]), "+f"(d[67]), "+f"(d[68]), "+f"(d[69]), "+f"(d[70]), "+f"(d[71]), "+f"(d[72]), "+f"(d[73]), "+f"(d[74]), "+f"(d[75]), "+f"(d[76]), "+f"(d[77]), "+f"(d[78]), "+f"(d[79])
    : "r"(a[0]), "r"(a[1]), "r"(a[2]), "r"(a[3]), "l"(b), "r"(sc));
}
__device__ __forceinline__ void wg_ss_n112_ta0_tb1(float* d, uint64_t a, uint64_t b, int sc) {
  asm volatile("{\n.reg .pred p;\nsetp.ne.b32 p, %58, 0;\nwgmma.mma_async.sync.aligned.m64n112k16.f32.bf16.bf16 {%0, %1, %2, %3, %4, %5, %6, %7, %8, %9, %10, %11, %12, %13, %14, %15, %16, %17, %18, %19, %20, %21, %22, %23, %24, %25, %26, %27, %28, %29, %30, %31, %32, %33, %34, %35, %36, %37, %38, %39, %40, %41, %42, %43, %44, %45, %46, %47, %48, %49, %50, %51, %52, %53, %54, %55}, %56, %57, p, 1, 1, 0, 1;\n}\n"
    : "+f"(d[0]), "+f"(d[1]), "+f"(d[2]), "+f"(d[3]), "+f"(d[4]), "+f"(d[5]), "+f"(d[6]), "+f"(d[7]), "+f"(d[8]), "+f"(d[9]), "+f"(d[10]), "+f"(d[11]), "+f"(d[12]), "+f"(d[13]), "+f"(d[14]), "+f"(d[15]), "+f"(d[16]), "+f"(d[17]), "+f"(d[18]), "+f"(d[19]), "+f"(d[20]), "+f"(d[21]), "+f"(d[22]), "+f"(d[23]), "+f"(d[24]), "+f"(d[25]), "+f"(d[26]), "+f"(d[27]), "+f"(d[28]), "+f"(d[29]), "+f"(d[30]), "+f"(d[31]), "+f"(d[32]), "+f"(d[33]), "+f"(d[34]), "+f"(d[35]), "+f"(d[36]), "+f"(d[37]), "+f"(d[38]), "+f"(d[39]), "+f"(d[40]), "+f"(d[41]), "+f"(d[42]), "+f"(d[43]), "+f"(d[44]), "+f"(d[45]), "+f"(d[46]), "+f"(d[47]), "+f"(d[48]), "+f"(d[49]), "+f"(d[50]), "+f"(d[51]), "+f"(d[52]), "+f"(d[53]), "+f"(d[54]), "+f"(d[55])
    : "l"(a), "l"(b), "r"(sc));
}
__device__ __forceinline__ void wg_rs_n32_tb1(float* d, const uint32_t* a, uint64_t b, int sc) {
  asm volatile("{\n.reg .pred p;\nsetp.ne.b32 p, %21, 0;\nwgmma.mma_async.sync.aligned.m64n32k16.f32.bf16.bf16 {%0, %1, %2, %3, %4, %5, %6, %7, %8, %9, %10, %11, %12, %13, %14, %15}, {%16, %17, %18, %19}, %20, p, 1, 1, 1;\n}\n"
    : "+f"(d[0]), "+f"(d[1]), "+f"(d[2]), "+f"(d[3]), "+f"(d[4]), "+f"(d[5]), "+f"(d[6]), "+f"(d[7]), "+f"(d[8]), "+f"(d[9]), "+f"(d[10]), "+f"(d[11]), "+f"(d[12]), "+f"(d[13]), "+f"(d[14]), "+f"(d[15])
    : "r"(a[0]), "r"(a[1]), "r"(a[2]), "r"(a[3]), "l"(b), "r"(sc));
}
__device__ __forceinline__ void wg_ss_n32_ta1_tb1(float* d, uint64_t a, uint64_t b, int sc) {
  asm volatile("{\n.reg .pred p;\nsetp.ne.b32 p, %18, 0;\nwgmma.mma_async.sync.aligned.m64n32k16.f32.bf16.bf16 {%0, %1, %2, %3, %4, %5, %6, %7, %8, %9, %10, %11, %12, %13, %14, %15}, %16, %17, p, 1, 1, 1, 1;\n}\n"
    : "+f"(d[0]), "+f"(d[1]), "+f"(d[2]), "+f"(d[3]), "+f"(d[4]), "+f"(d[5]), "+f"(d[6]), "+f"(d[7]), "+f"(d[8]), "+f"(d[9]), "+f"(d[10]), "+f"(d[11]), "+f"(d[12]), "+f"(d[13]), "+f"(d[14]), "+f"(d[15])
    : "l"(a), "l"(b), "r"(sc));
}
__device__ __forceinline__ void wg_rs_n32_tb0(float* d, const uint32_t* a, uint64_t b, int sc) {
  asm volatile("{\n.reg .pred p;\nsetp.ne.b32 p, %21, 0;\nwgmma.mma_async.sync.aligned.m64n32k16.f32.bf16.bf16 {%0, %1, %2, %3, %4, %5, %6, %7, %8, %9, %10, %11, %12, %13, %14, %15}, {%16, %17, %18, %19}, %20, p, 1, 1, 0;\n}\n"
    : "+f"(d[0]), "+f"(d[1]), "+f"(d[2]), "+f"(d[3]), "+f"(d[4]), "+f"(d[5]), "+f"(d[6]), "+f"(d[7]), "+f"(d[8]), "+f"(d[9]), "+f"(d[10]), "+f"(d[11]), "+f"(d[12]), "+f"(d[13]), "+f"(d[14]), "+f"(d[15])
    : "r"(a[0]), "r"(a[1]), "r"(a[2]), "r"(a[3]), "l"(b), "r"(sc));
}
__device__ __forceinline__ void wg_rs_n40_tb0(float* d, const uint32_t* a, uint64_t b, int sc) {
  asm volatile("{\n.reg .pred p;\nsetp.ne.b32 p, %25, 0;\nwgmma.mma_async.sync.aligned.m64n40k16.f32.bf16.bf16 {%0, %1, %2, %3, %4, %5, %6, %7, %8, %9, %10, %11, %12, %13, %14, %15, %16, %17, %18, %19}, {%20, %21, %22, %23}, %24, p, 1, 1, 0;\n}\n"
    : "+f"(d[0]), "+f"(d[1]), "+f"(d[2]), "+f"(d[3]), "+f"(d[4]), "+f"(d[5]), "+f"(d[6]), "+f"(d[7]), "+f"(d[8]), "+f"(d[9]), "+f"(d[10]), "+f"(d[11]), "+f"(d[12]), "+f"(d[13]), "+f"(d[14]), "+f"(d[15]), "+f"(d[16]), "+f"(d[17]), "+f"(d[18]), "+f"(d[19])
    : "r"(a[0]), "r"(a[1]), "r"(a[2]), "r"(a[3]), "l"(b), "r"(sc));
}
__device__ __forceinline__ void wg_rs_n8_tb1(float* d, const uint32_t* a, uint64_t b, int sc) {
  asm volatile("{\n.reg .pred p;\nsetp.ne.b32 p, %9, 0;\nwgmma.mma_async.sync.aligned.m64n8k16.f32.bf16.bf16 {%0, %1, %2, %3}, {%4, %5, %6, %7}, %8, p, 1, 1, 1;\n}\n"
    : "+f"(d[0]), "+f"(d[1]), "+f"(d[2]), "+f"(d[3])
    : "r"(a[0]), "r"(a[1]), "r"(a[2]), "r"(a[3]), "l"(b), "r"(sc));
}
__device__ __forceinline__ void wg_ss_n40_ta0_tb0(float* d, uint64_t a, uint64_t b, int sc) {
  asm volatile("{\n.reg .pred p;\nsetp.ne.b32 p, %22, 0;\nwgmma.mma_async.sync.aligned.m64n40k16.f32.bf16.bf16 {%0, %1, %2, %3, %4, %5, %6, %7, %8, %9, %10, %11, %12, %13, %14, %15, %16, %17, %18, %19}, %20, %21, p, 1, 1, 0, 0;\n}\n"
    : "+f"(d[0]), "+f"(d[1]), "+f"(d[2]), "+f"(d[3]), "+f"(d[4]), "+f"(d[5]), "+f"(d[6]), "+f"(d[7]), "+f"(d[8]), "+f"(d[9]), "+f"(d[10]), "+f"(d[11]), "+f"(d[12]), "+f"(d[13]), "+f"(d[14]), "+f"(d[15]), "+f"(d[16]), "+f"(d[17]), "+f"(d[18]), "+f"(d[19])
    : "l"(a), "l"(b), "r"(sc));
}
__device__ __forceinline__ void wg_ss_n40_ta1_tb0(float* d, uint64_t a, uint64_t b, int sc) {
  asm volatile("{\n.reg .pred p;\nsetp.ne.b32 p, %22, 0;\nwgmma.mma_async.sync.aligned.m64n40k16.f32.bf16.bf16 {%0, %1, %2, %3, %4, %5, %6, %7, %8, %9, %10, %11, %12, %13, %14, %15, %16, %17, %18, %19}, %20, %21, p, 1, 1, 1, 0;\n}\n"
    : "+f"(d[0]), "+f"(d[1]), "+f"(d[2]), "+f"(d[3]), "+f"(d[4]), "+f"(d[5]), "+f"(d[6]), "+f"(d[7]), "+f"(d[8]), "+f"(d[9]), "+f"(d[10]), "+f"(d[11]), "+f"(d[12]), "+f"(d[13]), "+f"(d[14]), "+f"(d[15]), "+f"(d[16]), "+f"(d[17]), "+f"(d[18]), "+f"(d[19])
    : "l"(a), "l"(b), "r"(sc));
}
__device__ __forceinline__ void wg_ss_n8_ta1_tb1(float* d, uint64_t a, uint64_t b, int sc) {
  asm volatile("{\n.reg .pred p;\nsetp.ne.b32 p, %6, 0;\nwgmma.mma_async.sync.aligned.m64n8k16.f32.bf16.bf16 {%0, %1, %2, %3}, %4, %5, p, 1, 1, 1, 1;\n}\n"
    : "+f"(d[0]), "+f"(d[1]), "+f"(d[2]), "+f"(d[3])
    : "l"(a), "l"(b), "r"(sc));
}

constexpr int O_WV = 0, O_WO = 81920, O_H = 163840, O_QK = 215040, O_SM = 228352, O_MISC = 229632;
constexpr int O_QM = O_QK + 1024, O_K = O_QK + 3072, O_OG = O_QK + 8192;
constexpr int SM_SLOT = 640;
constexpr int O_MAXS = O_MISC;
constexpr int O_BAR = O_MISC + 64;
constexpr int MB_XF = 0, MB_ML = 2, MB_MR = 3, MB_PF = 4, MB_SM = 5, MB_SX = 6, MB_OG = 7, MB_W = 10, MB_WC = 30;
constexpr int O_PROF = O_BAR + 8 * 40;
constexpr int REC_SMEM = O_PROF + 128;
constexpr int B_VOWN = 0, B_QK = 1, B_PM = 4, B_PX = 5, B_XGO = 6, B_ML = 7, B_WG2 = 8, B_VHALF = 9, B_VDONE = 10,
              B_MR = 11, B_SSENT = 12, B_SLD = 13, B_VEND = 14, B_XGO1 = 15;
#define TS0(idx) do {} while (0)
#define TS(idx) do {} while (0)
#define POLL_9 300
#define POLL_A 400
#define POLL_B 500
#define POLL_C 600
#define W_WIN 4
#define W_OPEN 16
#define V_OWN 6
#define V_S1 9
#define V_RS 3
#define V_S2 3
#define V_K1 (V_OWN + V_RS + V_S1)
#define V_K2 ((V_K1 > 20 ? V_K1 : 20) + V_S2)
#define O_RSM 0x2AA0
#define O_B1 5
#define O_RS __builtin_popcount(O_RSM)
#define O_IDX(j) __builtin_popcount(O_RSM & ((1 << (j)) - 1))
constexpr float SCL = 0.07216878364870322f;
constexpr float SL2 = SCL * 1.4426950408889634f;
__device__ __forceinline__ constexpr int vord(int i) { return i < 4 ? 36 + i : i - 4; }
__device__ __forceinline__ constexpr uint32_t hoff(int k) { return ((k >> 2) * 5120 + (k & 3) * 32) >> 4; }
__device__ __forceinline__ constexpr int ar_chunk(int T) { return T == 9 ? 19 : (T % 3) * 8 + T / 3; }
__device__ __forceinline__ void fix_red(uint8_t* p, const float* a, float2 sc) {
  int v0 = __float2int_rn(a[0] * sc.x), v1 = __float2int_rn(a[1] * sc.y), v2 = __float2int_rn(a[2] * sc.x), v3 = __float2int_rn(a[3] * sc.y);
  red64(p, ((uint32_t)v0 << 7) | 1u, ((uint32_t)v2 << 3) + (uint32_t)(v0 >> 25));
  red64(p + 1024, ((uint32_t)v1 << 7) | 1u, ((uint32_t)v3 << 3) + (uint32_t)(v1 >> 25));
}
__device__ __forceinline__ float exp_row(float* t) {
  const float ml = fmaxf(fmaxf(fmaxf(fmaxf(t[0], t[1]), fmaxf(t[2], t[3])), fmaxf(fmaxf(t[4], t[5]), fmaxf(t[6], t[7]))), fmaxf(t[8], t[9]));
  const float m1 = __shfl_xor_sync(~0u, ml, 1), m2 = __shfl_xor_sync(~0u, ml, 2), m3 = __shfl_xor_sync(~0u, ml, 3);
  SCHED_FENCE();
#pragma unroll
  for (int k = 0; k < 10; k++) t[k] = ex2((t[k] - ml) * SL2);
  pin<10>(t);
  SCHED_FENCE();
  return ex2((ml - fmaxf(fmaxf(ml, m1), fmaxf(m2, m3))) * SL2);
}
#define ACC3(k, u, v) { t[k] += bflo(u) + bflo(v); t[k + 1] += bfhi(u) + bfhi(v); }

#define LBT 0
#define NLB 2
constexpr int LB_STAGE = 36864, LB_ST = 6 * LB_STAGE;
__device__ __forceinline__ void lb_role(const uint32_t sb, const CUtensorMap* tmx, uint32_t* __restrict__ flags, int layer) {
  const int tid = threadIdx.x, wid = __shfl_sync(~0u, tid >> 5, 0), wg = wid >> 2, w = wid & 3, lane = tid & 31, g = lane >> 2, i4 = lane & 3;
  const int cl = blockIdx.x / 3, rank = blockIdx.x - cl * 3;
  const uint32_t bar = sb + O_BAR;
  asm volatile("griddepcontrol.launch_dependents;");
  if (wid == 8) {
    if (lane < 14) mbar_init(bar + 8 * lane, lane >= 6 && lane < 12 ? 8 : 1);
    asm volatile("fence.mbarrier_init.release.cluster;" ::: "memory");
    fence_async();
  }
  __syncthreads();
  asm volatile("barrier.cluster.arrive.relaxed.aligned;" ::: "memory");
  if (wid == 8) {
    int st = 0; uint32_t ph = 1;
    const uint8_t* wsrc = g_w2 + rank * 286720;
    if (lane < 6) { mbar_expect(bar + 8 * lane, LB_STAGE); bulk_g2s(sb + lane * LB_STAGE + 8192, wsrc + lane * 28672, 28672, bar + 8 * lane); }
    if (layer == 1) wait_flag(flags + FL_R, 6);
#pragma unroll 1
    for (int tile = cl; tile < 32; tile += NLB) {
      wait_flag(flags + FL_O + (tile >> 1) * 8, 8);
      if (tile == cl + LBT * NLB && lane == 0) GTT(layer * 4 + 1, 11);
      fence_async_global();
#pragma unroll 1
      for (int kc = 0; kc < 10; kc++) {
        const bool pre = tile == cl && kc < 6;
        mbar_wait(bar + 8 * (6 + st), ph);
        if (lane == 0) {
          if (!pre) { mbar_expect(bar + 8 * st, LB_STAGE); bulk_g2s(sb + st * LB_STAGE + 8192, wsrc + kc * 28672, 28672, bar + 8 * st); }
          bulk_g2s(sb + st * LB_STAGE, g_oa + tile * 81920 + kc * 8192, 8192, bar + 8 * st);
        }
        __syncwarp();
        if (++st == 6) { st = 0; ph ^= 1; }
      }
      mbar_wait(bar + 8 * (6 + st), ph);
      if (lane == 0) { mbar_expect(bar + 8 * st, 64 * 464); tma2d(sb + st * LB_STAGE, tmx, rank * 224, tile * 64, bar + 8 * st); }
      __syncwarp();
      if (++st == 6) { st = 0; ph ^= 1; }
    }
    asm volatile("barrier.cluster.wait.aligned;" ::: "memory");
  } else if (wg < 2) {
    asm volatile("barrier.cluster.wait.aligned;" ::: "memory");
    const int u = 2 * rank + wg, nb = u == 5 ? 5 : 7;
    int st = 0; uint32_t ph = 0, it = 0;
#pragma unroll 1
    for (int tile = cl; tile < 32; tile += NLB, it++) {
      const int row0 = tile * 64 + 16 * w + g;
      float d[56];
      if (tid == 0) mbar_expect(bar + 8 * (12 + (it & 1)), 3072);
#pragma unroll 1
      for (int kc = 0; kc < 10; kc++) {
        const uint64_t da = mkdesc(SB0 + st * LB_STAGE, 1024, 128, 0), db = mkdesc(SB0 + st * LB_STAGE + 8192 + wg * 1792, 3584, 128, 0);
        mbar_wait(bar + 8 * st, ph);
        if (it == LBT && kc == 0) GT(layer * 4 + 1, 12);
        wg_fence();
#pragma unroll
        for (int k = 0; k < 4; k++) wg_ss_n112_ta0_tb1(d, da + k * 128, db + k * 448, kc | k);
        wg_commit();
        wg_wait<1>();
        if (kc > 0 && lane == 0) mbar_arrive(bar + 8 * (6 + (st == 0 ? 5 : st - 1)));
        if (++st == 6) { st = 0; ph ^= 1; }
      }
      wg_wait<0>();
      pin<56>(d);
      if (it == LBT) GT(layer * 4 + 1, 13);
      if (lane == 0) mbar_arrive(bar + 8 * (6 + (st == 0 ? 5 : st - 1)));
      mbar_wait(bar + 8 * st, ph);
      {
        const uint32_t x0 = sb + st * LB_STAGE + (16 * w + g) * 464 + wg * 224 + (layer ? 8 : 4) * i4, x1 = x0 + (layer ? 4 : 16);
#pragma unroll
        for (int j = 0; j < 28; j++) {
          const uint32_t v = lds1(((j & 2) ? x1 : x0) + (j >> 2) * 32 + (j & 1) * 3712);
          d[2 * j] += bflo(v); d[2 * j + 1] += bfhi(v);
        }
      }
      fence_async();
      __syncwarp();
      if (lane == 0) mbar_arrive(bar + 8 * (6 + st));
      if (++st == 6) { st = 0; ph ^= 1; }
      const float cnt = nb * 16.f;
      const uint32_t so = LB_ST + (it & 1) * 3072 + (16 * w + g) * 48;
#pragma unroll
      for (int h = 0; h < 2; h++) {
        float sum = 0.f;
#pragma unroll
        for (int j = 0; j < 14; j++) sum += d[4 * j + 2 * h] + d[4 * j + 2 * h + 1];
        sum += __shfl_xor_sync(~0u, sum, 1); sum += __shfl_xor_sync(~0u, sum, 2);
        const float mean = sum * rcp(cnt);
        float q = 0.f, q2 = 0.f;
#pragma unroll
        for (int j = 0; j < 14; j++) {
          const float a = d[4 * j + 2 * h] - mean, b = d[4 * j + 2 * h + 1] - mean;
          if (j < 10) q = fmaf(a, a, fmaf(b, b, q)); else q2 = fmaf(a, a, fmaf(b, b, q2));
        }
        if (nb == 7) q += q2;
        q += __shfl_xor_sync(~0u, q, 1); q += __shfl_xor_sync(~0u, q, 2);
        if (i4 < 3) { const uint32_t b = mapa(sb, i4); sta2f(b + so + h * 384 + u * 8, sum, q, b + O_BAR + 8 * (12 + (it & 1))); }
      }
      mbar_wait(bar + 8 * (12 + (it & 1)), (it >> 1) & 1);
      if (it == LBT) GT(layer * 4 + 1, 14);
#pragma unroll
      for (int h = 0; h < 2; h++) {
        const float4 x = lds4f(sb + so + h * 384), y = lds4f(sb + so + h * 384 + 16), z = lds4f(sb + so + h * 384 + 32);
        const float mu = (((x.x + x.z) + (y.x + y.z)) + (z.x + z.z)) * (1.f / DM);
        const float e0 = x.x * (1.f / 112.f) - mu, e1 = x.z * (1.f / 112.f) - mu, e2 = y.x * (1.f / 112.f) - mu, e3 = y.z * (1.f / 112.f) - mu;
        const float e4 = z.x * (1.f / 112.f) - mu, e5 = z.z * (1.f / 80.f) - mu;
        const float q = (((x.y + x.w) + (y.y + y.w)) + (z.y + z.w)) + 112.f * ((e0 * e0 + e1 * e1) + (e2 * e2 + e3 * e3) + e4 * e4) + 80.f * e5 * e5;
        const float rs = rsqrtf(q * (1.f / DM) + 1e-5f), sh = -mu * rs;
        const int tk = row0 + 8 * h;
        uint8_t* xp = g_xn + (tk >> 5) * 40960 + (tk & 31) * 128 + (i4 & 1) * 8;
#pragma unroll
        for (int j = 0; j < 7; j++) {
          if (j < nb) {
            const int b16 = u * 7 + j;
            const float* a = d + 8 * j + 2 * h;
            *(uint2*)(xp + (b16 >> 2) * 4096 + (((2 * (b16 & 3) + (i4 >> 1)) ^ g) << 4)) =
                make_uint2(pack2(fmaf(a[0], rs, sh), fmaf(a[1], rs, sh)), pack2(fmaf(a[4], rs, sh), fmaf(a[5], rs, sh)));
          }
        }
      }
      if (it == LBT) GT(layer * 4 + 1, 15);
      bar_arrive<1, 288>();
      bar_sync<2, 288>();
#pragma unroll
      for (int j = 0; j < 14; j++) {
        const float* a = d + 8 * (j >> 1) + 2 * (j & 1);
        if ((j >> 1) < nb) *(uint2*)(g_x + (row0 + 8 * (j & 1)) * DM + u * 112 + 4 * i4 + 16 * (j >> 1)) = make_uint2(pack2(a[0], a[1]), pack2(a[4], a[5]));
      }
      bar_arrive<3, 288>();
    }
  } else {
    asm volatile("barrier.cluster.wait.aligned;" ::: "memory");
    if (wid == 9) {
#pragma unroll 1
      for (int tile = cl; tile < 32; tile += NLB) {
        bar_sync<1, 288>();
        if (tile != cl) bar_arrive<2, 288>();
        if (lane == 0) { red_release(flags + FL_XN + tile * 8, 1); if (tile == cl + LBT * NLB) GTT(layer * 4 + 1, 9); }
        __syncwarp();
        if (tile == cl) bar_arrive<2, 288>();
        bar_sync<3, 288>();
        if (lane == 0) red_release(flags + FL_XN + tile * 8 + 1, 1);
        __syncwarp();
      }
    }
  }
  asm volatile("barrier.cluster.arrive.relaxed.aligned;\nbarrier.cluster.wait.aligned;" ::: "memory");
  GT(layer * 4 + 1, 10);
}

__global__ void __launch_bounds__(384, 1)
rec_kernel(const __grid_constant__ CUtensorMap tmq, const __grid_constant__ CUtensorMap tmk,
           const __grid_constant__ CUtensorMap tmv, const __grid_constant__ CUtensorMap tmo,
           const __grid_constant__ CUtensorMap tmx, const bf16* __restrict__ mem0, uint8_t* __restrict__ ar, uint32_t* __restrict__ flags, int layer) {
  extern __shared__ __align__(1024) uint8_t smem[];
  const uint32_t sb = smem_u32(smem);
  check_smem_base(sb);
  GT(layer * 4 + 1, 0);
  if (blockIdx.x < 3 * NLB) { lb_role(sb, &tmx, flags, layer); return; }
  const int bid = blockIdx.x - 3 * NLB;
  const int tid = threadIdx.x, wid = __shfl_sync(~0u, tid >> 5, 0), wg = wid >> 2, w = wid & 3;
  const int lane = __shfl_sync(~0u, tid & 31, tid & 31);
  const int head = bid / 3, rank = bid - head * 3;
  const int e0 = bid * 64;
  const uint32_t bar = sb + O_BAR;
  const uint32_t sb1 = mapa(sb, rank == 2 ? 0 : rank + 1), sb2 = mapa(sb, rank == 0 ? 2 : rank - 1);
  auto chunk_of = [&](int p) { const int c = 3 * rank + p; return p == 9 ? 9 : c >= 9 ? c - 9 : c; };

  auto load_piece = [&](int i) {
    if (lane == 0) mbar_expect(bar + 8 * (MB_W + i), 16384);
    __syncwarp();
    if (lane < 2) {
      if (i < 15) {
        const int m = i < 10 ? i & 1 : 0, p = (i < 10 ? i >> 1 : i - 10) * 2 + lane;
        tma5d(sb + m * 81920 + p * 8192, i >= 10 ? &tmv : m ? &tmk : &tmq, e0, chunk_of(p) * 4, bar + 8 * (MB_W + i));
      } else {
        const int p = (i - 15) * 2 + lane, k = p / 3, j = rank + p - 3 * k;
        tma2d(sb + O_WO + p * 8192, &tmo, p == 9 ? 576 : (rank * 3 + k) * 64, head * DH + (j >= 3 ? j - 3 : j) * 64, bar + 8 * (MB_W + i));
      }
    }
  };
  if (wid == 9) {
    mbar_init(bar + 8 * lane, (lane >= MB_WC || lane == MB_PF) ? 4 : 1);
    if (lane < 8) mbar_init(bar + 8 * (32 + lane), 4);
    asm volatile("fence.mbarrier_init.release.cluster;" ::: "memory");
    fence_async();
    __syncwarp();
#pragma unroll 1
    for (int i = 0; i < W_WIN; i++) load_piece(i);
  }
  __syncthreads();
  asm volatile("barrier.cluster.arrive.relaxed.aligned;" ::: "memory");

  if (wg < 2) {
    asm volatile("setmaxnreg.inc.sync.aligned.u32 208;");
    uint32_t a[40][4];
    const uint32_t swz = (lane & 7) * 128 + (((2 * w + ((lane >> 3) & 1)) ^ (lane & 7)) << 4);
    const uint32_t st_x = __shfl_sync(~0u, sb + O_QK + wg * 5120 + (lane >> 4) * 2048 + swz, lane);
    {
      const uint32_t la = sb + wg * 81920 + (lane >> 4) * 1024 + swz;
#pragma unroll
      for (int p = 0; p < 5; p++) {
        mbar_wait(bar + 8 * (MB_W + 2 * p + wg), 0);
#pragma unroll
        for (int k = 0; k < 8; k++) ldsm4t(a[p * 8 + k], la + (p * 8 + k) * 2048);
        fence_async();
        __syncwarp();
        mbar_arrive_elect(bar + 8 * (MB_WC + wg * 5 + p));
      }
    }
    GT(layer * 4 + 1, 5);
    asm volatile("barrier.cluster.wait.aligned;" ::: "memory");
    const uint32_t ld_m = __shfl_sync(~0u, sb + O_H + (lane & 7) * 128 + (((lane >> 3) ^ (lane & 7)) << 4), lane);

    for (int s = 0; s < NSEG; s++) {
      const uint32_t par = s & 1;
      if (wid == 4) TS0(0);
      if (wid == 0) TS(30);
      {
        float ax[16];
        constexpr uint64_t db = mkdesc(SB0 + O_H + 1024, 16, 1024, 1);
        mbar_waitf(bar + 8 * MB_XF, par);
        wg_fence();
#pragma unroll
        for (int k = 0; k < 20; k++) wg_rs_n32_tb0(ax, a[vord(k)], db + hoff(vord(k)), k);
        mbar_waitf(bar + 8 * (MB_XF + 1), par);
        wg_fence();
#pragma unroll
        for (int k = 20; k < 40; k++) wg_rs_n32_tb0(ax, a[vord(k)], db + hoff(vord(k)), 1);
        wg_commit();
        mbar_waitf(bar + 8 * MB_PF, par ^ 1);
        if (wid == 6 && lane == 0) { mbar_expect(bar + 8 * MB_SM, 2 * SM_SLOT + 48 + 48); mbar_expect(bar + 8 * MB_SX, 2 * 2176); }
        wg_wait<0>();
        pin<16>(ax);
        if (w == 0) TS(1 + 22 * wg);
        stsm4t(st_x, pack2(ax[0], ax[1]), pack2(ax[2], ax[3]), pack2(ax[4], ax[5]), pack2(ax[6], ax[7]));
        stsm4t(st_x + 4096, pack2(ax[8], ax[9]), pack2(ax[10], ax[11]), pack2(ax[12], ax[13]), pack2(ax[14], ax[15]));
        bar_arrive<B_VOWN, 384>();
      }
      {
        float c[4][4];
#pragma unroll
        for (int k = 0; k < 4; k++) c[k][0] = c[k][1] = c[k][2] = c[k][3] = 0.f;
        uint32_t b[3][2][4];
        const uint32_t ld_m2 = opaque(ld_m ^ 64);
        SCHED_FENCE();
#define MORD(j) ((j) == 0 ? 9 : (j) < 4 ? (j) - 1 : 3 + ((j) - 4) / 2 + 3 * ((j) & 1))
#pragma unroll
        for (int j = 0; j < 12; j++) {
          if (j < 10) {
            if (j == 0) { mbar_waitf(bar + 8 * MB_ML, par); if (wid == 0) TS(2); }
            if (j == 1) { bar_sync<B_ML, 352>(); if (wid == 0) TS(3); }
            if (j == 4) { bar_sync<B_MR, 288>(); if (wid == 0) TS(4); }
            ldsm4(b[j % 3][0], ld_m + MORD(j) * 5120);
            ldsm4(b[j % 3][1], ld_m2 + MORD(j) * 5120);
          }
          const int u = j - 2;
          if (u >= 0) {
#pragma unroll
            for (int k = 0; k < 4; k++) mma16816(c[k], a[4 * MORD(u) + k], b[u % 3][k >> 1][(k & 1) * 2], b[u % 3][k >> 1][(k & 1) * 2 + 1]);
          }
        }
        if (wid == 0) TS(31);
#pragma unroll
        for (int k = 0; k < 4; k++) c[0][k] = (c[0][k] + c[1][k]) + (c[2][k] + c[3][k]);
        stsm2t(st_x + 1024 - wg * 3072, pack2(c[0][0], c[0][1]), pack2(c[0][2], c[0][3]));
        fence_async();
      }
      if (wg == 0) {
        bar_sync<B_QK, 256>();
        float sv[20];
        {
          constexpr uint64_t da = mkdesc(SB0 + O_QK, 16, 1024, 1), db = mkdesc(SB0 + O_K, 16, 2048, 1);
          wg_fence();
#pragma unroll
          for (int k = 0; k < 4; k++) wg_ss_n40_ta0_tb0(sv, da + 2 * k, db + 2 * k, k);
          wg_commit();
        }
        if (w == 0) TS(6);
        SCHED_FENCE();
        const uint32_t ln = opaque(lane);
        uint32_t m0, m1, m2, m3, m4;
        {
          const uint32_t a1 = opaque(sb1 + O_SM + SM_SLOT + ln * 16), a2 = opaque(sb2 + O_SM + ln * 16);
          const uint32_t a3 = opaque(sb1 + O_SM + SM_SLOT + 512 + ln * 4), a4 = opaque(sb2 + O_SM + 512 + ln * 4);
          const uint32_t b1 = opaque(sb1 + O_BAR + 8 * MB_SM), b2 = opaque(sb2 + O_BAR + 8 * MB_SM);
          const uint32_t bt = opaque(mapa(sb, min(ln, 2u)) + O_BAR + 8 * MB_SM), at = opaque(bt + (O_MAXS + 48 - O_BAR - 8 * MB_SM));
          SCHED_FENCE();
          wg_wait<0>();
          pin<20>(sv);
          m0 = pack2(sv[2], sv[3]); m1 = pack2(sv[6], sv[7]); m2 = pack2(sv[10], sv[11]); m3 = pack2(sv[14], sv[15]); m4 = pack2(sv[18], sv[19]);
          if (w == 0) {
            sta4(a1, m0, m1, m2, m3, b1);
            sta4(a2, m0, m1, m2, m3, b2);
            sta1(a3, m4, b1);
            sta1(a4, m4, b2);
          }
          sta1p(at, 0u, bt, ln < 3);
          bar_arrive<B_SSENT, 256>();
          SCHED_FENCE();
        }
        const uint32_t p0 = pack2(sv[0], sv[1]), p1 = pack2(sv[4], sv[5]), p2 = pack2(sv[8], sv[9]), p3 = pack2(sv[12], sv[13]), p4 = pack2(sv[16], sv[17]);
        const uint32_t ox = O_K + w * 2048 + ln * 16, ox2 = O_K + 8192 + ln * 4;
        {
          const uint32_t a1 = opaque(sb1 + ox + 512), a2 = opaque(sb2 + ox), b1 = opaque(sb1 + O_BAR + 8 * MB_SX), b2 = opaque(sb2 + O_BAR + 8 * MB_SX);
          if (w == 0) {
            TS(7);
            const uint32_t om = opaque(sb + O_SM + ln * 16), om2 = opaque(sb + O_SM + 512 + ln * 4);
            const uint32_t pa0 = ld_m + (O_QM - O_H), pa1 = (ld_m ^ 64) + (O_QM - O_H);
            float t[10] = {bflo(m0), bfhi(m0), bflo(m1), bfhi(m1), bflo(m2), bfhi(m2), bflo(m3), bfhi(m3), bflo(m4), bfhi(m4)};
            pin<10>(t);
            SCHED_FENCE();
            mbar_waitf(bar + 8 * MB_SM, par);
            const uint4 u = lds4(om), v = lds4(om + SM_SLOT);
            const uint32_t u4 = lds1(om2), v4 = lds1(om2 + SM_SLOT);
            sta4(a1, p0, p1, p2, p3, b1);
            sta4(a2, p0, p1, p2, p3, b2);
            bar_arrive<B_SLD, 256>();
            SCHED_FENCE();
            ACC3(0, u.x, v.x) ACC3(2, u.y, v.y) ACC3(4, u.z, v.z) ACC3(6, u.w, v.w) ACC3(8, u4, v4)
            TS(8);
            const float f = exp_row(t);
            stsm4(pa0, pack2(t[0] * f, t[1] * f), pack2(t[2] * f, t[3] * f), pack2(t[4] * f, t[5] * f), pack2(t[6] * f, t[7] * f));
            stsm1(pa1, pack2(t[8] * f, t[9] * f));
            bar_arrive<B_PM, 160>();
            TS(9);
          } else {
            const uint32_t a3 = opaque(sb1 + ox2 + 128), a4 = opaque(sb2 + ox2);
            SCHED_FENCE();
            mbar_waitf(bar + 8 * MB_SM, par);
            sta4(a1, p0, p1, p2, p3, b1);
            sta4(a2, p0, p1, p2, p3, b2);
            if (w == 3) { sta1(a3, p4, b1); sta1(a4, p4, b2); }
            bar_arrive<B_SLD, 256>();
          }
        }
        {
          float t[10] = {bflo(p0), bfhi(p0), bflo(p1), bfhi(p1), bflo(p2), bfhi(p2), bflo(p3), bfhi(p3), bflo(p4), bfhi(p4)};
          const int dq = 8 * w + (ln >> 2) - 2 * (ln & 3);
#pragma unroll
          for (int k = 1; k < 5; k++) {
            if (8 * (k - 1) > dq) t[2 * k] = -1e9f / SCL;
            if (8 * (k - 1) + 1 > dq) t[2 * k + 1] = -1e9f / SCL;
          }
          const int rr = 2 * w + (ln & 1);
          const uint32_t pa = sb + O_QK + ((ln >> 1) & 3) * 2048 + rr * 128;
          const uint32_t pa0 = opaque(pa + (((ln >> 3) ^ rr) << 4)), pa1 = opaque(pa0 ^ 64), l0 = opaque(sb + ox), l1 = opaque(sb + ox2);
          pin<10>(t);
          SCHED_FENCE();
          mbar_waitf(bar + 8 * MB_SX, par);
          bar_sync<B_VEND, 256>();
          const uint4 u = lds4(l0), v = lds4(l0 + 512);
          uint32_t u4 = 0, v4 = 0;
          if (w == 3) { u4 = lds1(l1); v4 = lds1(l1 + 128); }
          ACC3(0, u.x, v.x) ACC3(2, u.y, v.y) ACC3(4, u.z, v.z) ACC3(6, u.w, v.w) ACC3(8, u4, v4)
          const float f = exp_row(t);
          const float sum = (((t[0] + t[1]) + (t[2] + t[3])) + ((t[4] + t[5]) + (t[6] + t[7])) + (t[8] + t[9])) * f;
          const float s1 = __shfl_xor_sync(~0u, sum, 1), s2 = __shfl_xor_sync(~0u, sum, 2), s3 = __shfl_xor_sync(~0u, sum, 3);
          const float inv = f * rcp((sum + s1) + (s2 + s3));
          stsm4(pa0, pack2(t[0] * inv, t[1] * inv), pack2(t[2] * inv, t[3] * inv), pack2(t[4] * inv, t[5] * inv), pack2(t[6] * inv, t[7] * inv));
          stsm2(pa1, pack2(t[8] * inv, t[9] * inv), 0u);
          fence_async();
        }
        bar_arrive<B_PX, 256>();
        if (w == 0) TS(10);
        bar_sync<B_XGO, 256>();
      } else {
        bar_arrive<B_QK, 256>();
        const int ln = opaque(lane);
        if (w == 2) {
          bar_sync<B_VHALF, 192>();
          if (ln == 0 && s > 0) { red_release(flags + FL_A + (e0 >> 10) * 8 + (s - 1) * 48, 1); }
          __syncwarp();
        }
        if (w == 3) {
          const int l = bid * 2 + ln, s2 = s + 2;
          if (ln < 2 && l < 160 && s2 < NSEG - 1) {
            const int tile = l >> 4;
            const uint8_t* p = ar + (s2 >> 2) * AR_GROUP + (s2 & 1) * 128 + ((s2 >> 1) & 1) * 512 + ar_chunk(tile) * 4096 +
                               ((l >> 3) & 1) * 16384 + (l & 1) * 256 + ((l >> 1) & 3) * 1024;
            asm volatile("prefetch.global.L2 [%0];" :: "l"(p));
          }
        }
        if (w == 0) {
          const bool more = s + 1 < NSEG;
          if (ln < 2 && more) mbar_expect(bar + 8 * (MB_XF + ln), 20480);
          const uint8_t* src = g_xn + (s + 1) * 40960 + chunk_of(ln) * 4096;
          if ((s & 1) && more) { wait_flag(flags + FL_XN + ((s + 1) >> 1) * 8, 3); fence_async_global(); }
          bar_sync<B_VHALF, 192>();
          if ((ln < 4 || ln == 9) && more) bulk_g2s(sb + O_H + ln * 5120 + 1024, src, 4096, bar + 8 * MB_XF);
          bar_sync<B_VDONE, 160>();
          if (ln >= 4 && ln < 9 && more) bulk_g2s(sb + O_H + ln * 5120 + 1024, src, 4096, bar + 8 * (MB_XF + 1));
        }
        bar_sync<B_XGO1, 256>();
      }
    }
  } else {
    asm volatile("setmaxnreg.dec.sync.aligned.u32 88;");
    asm volatile("barrier.cluster.wait.aligned;" ::: "memory");

    const int g = lane >> 2, i4 = lane & 3;
    const int myT = w == 0 ? 9 : rank * 3 + w - 1, myP = w == 0 ? 9 : w - 1;
    const int tok = 2 * ((lane >> 1) & 3) + ((lane >> 3) & 1);
    const uint32_t fw_off = sb + O_H + myP * 5120 + tok * 128 + (((2 * (lane >> 4) + (lane & 1)) ^ tok) << 4);
    const uint32_t prod_off = (w >> 1) * 16384 + (w & 1) * 2048 + ((g >> 1) & 1) * 256 + (i4 * 2 + (g >> 2)) * 16 + (g & 1) * 8;
    const uint32_t cons_off = ar_chunk(myT) * 4096 + (lane >> 3) * 1024 + (lane & 7) * 16;
    auto tile_off = [&](int k) { return (k * 8 + rank) * 4096; };
    constexpr uint32_t T9_OFF = ar_chunk(9) * 4096;

    uint32_t mx;
    auto forward = [&](const uint32_t* p) {
      const uint32_t c = O_H + myP * 5120, bo = O_BAR + 8 * MB_MR;
      sts4(fw_off, p[0], p[1], p[2], p[3]);
      sts4(fw_off ^ 64, p[4], p[5], p[6], p[7]);
      fence_async();
      __syncwarp();
      if (w == 0) mbar_arrive_elect(bar + 8 * MB_ML);
      else {
        bar_arrive<B_ML, 352>();
        bulk_s2c_elect<1024>(sb1 + c + 6 * 5120, sb1 + bo, sb2 + c + 3 * 5120, sb2 + bo, sb + c);
      }
      SCHED_FENCE();
      mx = 0;
#pragma unroll
      for (int k = 0; k < 8; k++) mx = __vmaxu2(mx, p[k] & 0x7FFF7FFFu);
    };
    auto send_max = [&]() {
      mx = max(mx & 0xFFFFu, mx >> 16);
      mx = __reduce_max_sync(~0u, mx);
      { const uint32_t b = mapa(sb, min(lane, 2)); sta1p(b + O_MAXS + (rank * 4 + w) * 4, mx << 16, b + O_BAR + 8 * MB_SM, lane < 3); }
    };
    auto arm = [&]() { if (lane == 0 && w < 2) mbar_expect(bar + 8 * (w == 0 ? MB_OG : MB_MR), w == 0 ? 2048 : 6144); };
    {
      arm();
      const uint32_t* mp = (const uint32_t*)(mem0 + tok * DM + myT * 64 + 16 * (lane >> 4) + 4 * (lane & 1));
      const uint32_t p[8] = {mp[0], mp[4], mp[1], mp[5], mp[16], mp[20], mp[17], mp[21]};
      forward(p);
    }
    if (w == 1) {
#pragma unroll 1
      for (int i = W_WIN; i < 20; i++) {
        if (i <= W_OPEN) mbar_wait(bar + 8 * (MB_W + i - W_WIN), 0);
        if (i >= 10) mbar_wait(bar + 8 * (MB_WC + i - 10), 0);
        load_piece(i);
      }
    }
    if (w == 0) {
      if (lane < 2) mbar_expect(bar + 8 * (MB_XF + lane), 20480);
      wait_flag<200>(flags + FL_XN, 3);
      fence_async_global();
      if (lane < 10) bulk_g2s(sb + O_H + lane * 5120 + 1024, g_xn + chunk_of(lane) * 4096, 4096, bar + 8 * (MB_XF + (lane >= 4 && lane < 9)));
      if (lane == 0) GTT(layer * 4 + 1, 4);
    }
    if (w == 2) {
      wait_flag<400>(flags + FL_X, 128);
      wait_flag<400>(g_zero + Z_FLAGS + FL_N, 4);
      const float sq = __ldcg((const float*)(g_zero + Z_NORM));
      float mx = 0.f;
#pragma unroll
      for (int k = 0; k < 5; k++) {
        const float4* p = (const float4*)g_nrm + k * 32 + lane;
        const float4 x = __ldcg(p), y = __ldcg(p + 160), z = __ldcg(p + 320), u = __ldcg(p + 480);
        mx = fmaxf(fmaxf(mx, fmaxf((x.x + y.x) + (z.x + u.x), (x.y + y.y) + (z.y + u.y))), fmaxf((x.z + y.z) + (z.z + u.z), (x.w + y.w) + (z.w + u.w)));
      }
#pragma unroll
      for (int o = 16; o; o >>= 1) mx = fmaxf(mx, __shfl_xor_sync(~0u, mx, o));
      sts1(sb + O_MAXS + 52, __float_as_uint(sqrt_approx(sq) * sqrt_approx(mx) * (25.2982213f * 1.1f)));
    }
    bar_sync<B_WG2, 128>();
    const float cbound = __uint_as_float(lds1(sb + O_MAXS + 52));
#pragma unroll 1
    for (int i = 10; i < 15; i++) mbar_wait(bar + 8 * (MB_W + i), 0);
    if (tid == 256) GTT(layer * 4 + 1, 7);

    const uint32_t la_w = sb + O_WV + ((lane >> 4) * 8 + (lane & 7)) * 128 + (((2 * w + ((lane >> 3) & 1)) ^ (lane & 7)) << 4);
    uint32_t af[V_RS][4];
#pragma unroll
    for (int k = 0; k < V_RS; k++) ldsm4t(af[k], la_w + vord(V_OWN + k) * 2048);
    uint32_t vf[10];
    uint4 oq0, oq1;
    uint8_t* op;
    auto pv_x = [&](int s) {
      float ox[16];
      const uint32_t vz[4] = {vf[8], vf[9], 0u, 0u};
      constexpr uint64_t dp = mkdesc(SB0 + O_QK, 16, 2048, 1);
      bar_sync<B_PX, 256>();
      wg_fence();
      wg_rs_n32_tb0(ox, vf, dp, 0);
      wg_rs_n32_tb0(ox, vf + 4, dp + 2, 1);
      wg_rs_n32_tb0(ox, vz, dp + 4, 1);
      wg_commit();
      const uint32_t ln = opaque(lane);
      op = g_ot + (size_t)s * (HE * 64) + (e0 + 16 * w) * 64 + (ln & 3) * 128 + (ln >> 2) * 16;
      wg_wait<0>();
      pin<16>(ox);
      oq0 = make_uint4(pack2(ox[0], ox[1]), pack2(ox[4], ox[5]), pack2(ox[8], ox[9]), pack2(ox[12], ox[13]));
      oq1 = make_uint4(pack2(ox[2], ox[3]), pack2(ox[6], ox[7]), pack2(ox[10], ox[11]), pack2(ox[14], ox[15]));
    };
    for (int s = 0;; s++) {
      const uint32_t par = s & 1;
      float sc1, isc, sum0, sum1;
      uint32_t ao[O_RS][4];
      {
        float av[20];
        constexpr uint64_t da = mkdesc(SB0 + O_WV, 1024, 1024, 1), db = mkdesc(SB0 + O_H, 16, 1024, 1);
#define V_RUN(k0, k1) wg_fence(); _Pragma("unroll") for (int k = k0; k < k1; k++) wg_ss_n40_ta1_tb0(av, da + vord(k) * 128, db + hoff(vord(k)), k);
        bar_sync<B_VOWN, 384>();
        V_RUN(0, V_OWN)
        if (w == 0) TS(29);
        SCHED_FENCE();
        if (w == 0) { mbar_waitf(bar + 8 * MB_MR, par); bar_arrive<B_MR, 288>(); SCHED_FENCE(); }
        send_max();
        bar_sync<B_SSENT, 256>();
        V_RUN(V_OWN + V_RS, V_K1)
        wg_fence();
#pragma unroll
        for (int k = 0; k < V_RS; k++) wg_rs_n40_tb0(av, af[k], db + hoff(vord(V_OWN + k)), 1);
        const uint32_t ln = opaque(lane);
        const uint32_t amx = opaque(sb + O_MAXS + 4 * min(ln, 11u));
        SCHED_FENCE();
        mbar_waitf(bar + 8 * MB_SM, par);
        const uint32_t mxl = lds1(amx);
        if (s == 0) {
#pragma unroll 1
          for (int i = 15; i < 20; i++) mbar_wait(bar + 8 * (MB_W + i), 0);
          asm volatile("griddepcontrol.launch_dependents;");
          if (tid == 256) GTT(layer * 4 + 1, 8);
        }
        bar_sync<B_SLD, 256>();
        V_RUN(V_K1, 20)
        wg_commit();
        V_RUN((V_K1 > 20 ? V_K1 : 20), V_K2)
        wg_commit();
        wg_wait<1>();
        bar_arrive<B_VHALF, 192>();
        V_RUN(V_K2, 40)
        wg_commit();
        SCHED_FENCE();
        if (w == 0) TS(12);
        {
          const float bnd = cbound * fmaxf(1.f, __uint_as_float(__reduce_max_sync(~0u, mxl)));
          const uint32_t eb = min(max(__float_as_uint(bnd) >> 23, 31u), 254u);
          sc1 = __uint_as_float(opaque((280u - eb) << 23));
          isc = __uint_as_float(opaque((eb - 29u) << 23));
        }
        const uint32_t pa = sb + O_QM + (ln & 7) * 128;
        const uint32_t pa0 = opaque(pa + (((ln >> 3) ^ (ln & 7)) << 4)), pa1 = opaque(pa0 ^ 64);
        const uint32_t o = O_OG + w * 256 + ln * 4;
        const uint32_t a0 = opaque(sb + o), a1 = opaque(sb1 + o + 4096), a2 = opaque(sb1 + o + 4096 + 128), a3 = opaque(sb2 + o + 2048), a4 = opaque(sb2 + o + 2048 + 128);
        const uint32_t b1 = opaque(sb1 + O_BAR + 8 * MB_OG), b2 = opaque(sb2 + O_BAR + 8 * MB_OG);
        const uint32_t c1 = opaque(0x3F803F80u);
        const uint32_t one[4] = {c1, c1, c1, c1};
        uint32_t pm[5];
        bar_arrive<B_VEND, 256>();
        SCHED_FENCE();
        bar_sync<B_PM, 160>();
        ldsm4(pm, pa0);
        ldsm1(pm[4], pa1);
        SCHED_FENCE();
        wg_wait<0>();
        pin<20>(av);
        if (w == 0) TS(13);
#pragma unroll
        for (int j = 0; j < 16; j++) if ((O_RSM >> j) & 1) ldsm4t(ao[O_IDX(j)], la_w + O_WO + (1 + (j >> 3)) * 24576 + (4 + (j & 7)) * 2048);
#pragma unroll
        for (int k = 0; k < 10; k++) vf[k] = pack2(av[2 * k], av[2 * k + 1]);
        float o0[4] = {0.f, 0.f, 0.f, 0.f}, o1[4] = {0.f, 0.f, 0.f, 0.f}, o2[4] = {0.f, 0.f, 0.f, 0.f};
        float s0[4] = {0.f, 0.f, 0.f, 0.f}, s1[4] = {0.f, 0.f, 0.f, 0.f}, s2[4] = {0.f, 0.f, 0.f, 0.f};
        mma16816(o0, vf, pm[0], pm[1]);
        mma16816(o1, vf + 4, pm[2], pm[3]);
        mma1688(o2, vf[8], vf[9], pm[4]);
        mma16816(s0, one, pm[0], pm[1]);
        mma16816(s1, one, pm[2], pm[3]);
        mma1688(s2, c1, c1, pm[4]);
        const uint32_t p0 = pack2(o0[0] + o1[0] + o2[0], o0[1] + o1[1] + o2[1]), p1 = pack2(o0[2] + o1[2] + o2[2], o0[3] + o1[3] + o2[3]);
        sta1(a1, p0, b1); sta1(a2, p1, b1);
        sta1(a3, p0, b2); sta1(a4, p1, b2);
        sts1(a0, p0); sts1(a0 + 128, p1);
        sum0 = s0[0] + s1[0] + s2[0]; sum1 = s0[1] + s1[1] + s2[1];
        fence_async();
      }
      if (s == NSEG - 1) break;
      uint8_t* arp;
      uint32_t t1;
      {
        bar_sync<B_WG2, 128>();
        float c9[4], ca[4], cb[4], cc[4];
        constexpr uint64_t da = mkdesc(SB0 + O_WO, 1024, 1024, 1), db = mkdesc(SB0 + O_OG, 128, 128, 0);
#define O_RUN(acc, tile, k0, k1) _Pragma("unroll") for (int k = k0; k < k1; k++) wg_ss_n8_ta1_tb1(acc, da + (tile) * 1536 + k * 128, db + (k >> 2) * 128 + (k & 3) * 16, k);
        wg_fence();
        O_RUN(c9, 3, 0, 4)
        wg_commit();
        if (w == 0) TS(14);
        O_RUN(ca, 0, 0, 4) O_RUN(cb, 1, 0, 2)
        wg_commit();
        SCHED_FENCE();
        arp = ar + (s >> 2) * AR_GROUP + (s & 1) * 128 + ((s >> 1) & 1) * 512;
        uint8_t* pp = arp + opaque(prod_off);
        const float2 sc = make_float2(sc1 * rcp(sum0), sc1 * rcp(sum1));
        wg_wait<1>();
        pin<4>(c9);
        fix_red(pp + T9_OFF, c9, sc);
        SCHED_FENCE();
        wg_fence();
        O_RUN(cb, 1, 2, 4) O_RUN(cc, 2, 0, 4)
        mbar_waitf(bar + 8 * MB_OG, par);
        wg_fence();
        O_RUN(ca, 0, 4, 12)
        wg_commit();
        bar_arrive<B_VDONE, 160>();
        if (w == 0) TS(15);
#define O_MIX(acc, j0, j1) _Pragma("unroll") for (int j = j0; j < j1; j++) { const int k = 4 + (j & 7); \
          if ((O_RSM >> j) & 1) wg_rs_n8_tb1(acc, ao[O_IDX(j) < O_RS ? O_IDX(j) : 0], db + (k >> 2) * 128 + (k & 3) * 16, 1); \
          else wg_ss_n8_ta1_tb1(acc, da + (1 + (j >> 3)) * 1536 + k * 128, db + (k >> 2) * 128 + (k & 3) * 16, 1); }
        O_MIX(cb, 0, O_B1)
        wg_commit();
        wg_wait<1>();
        pin<4>(ca);
        fix_red(pp + tile_off(0), ca, sc);
        SCHED_FENCE();
        if (w == 0) TS(16);
        wg_fence();
        O_MIX(cb, O_B1, 8)
        wg_commit();
        O_MIX(cc, 8, 16)
        wg_commit();
        bar_arrive<B_XGO1, 256>();
        bar_arrive<B_XGO, 256>();
        wg_wait<1>();
        pin<4>(cb);
        fix_red(pp + tile_off(1), cb, sc);
        SCHED_FENCE();
        wg_wait<0>();
        pin<4>(cc);
        fix_red(pp + tile_off(2), cc, sc);
        t1 = clk();
        if (w == 3) TS(17);
      }
      pv_x(s);
      mbar_arrive_elect(bar + 8 * MB_PF);
      if (w == 0) TS(28);
      {
        arm();
        const int dly = w == 0 ? POLL_9 : w == 1 ? POLL_A : w == 2 ? POLL_B : POLL_C;
        const uint32_t need = w == 0 ? 96 : 32;
        const uint8_t* cp = arp + opaque(cons_off);
        uint4 y[4];
        int it = 0;
        while ((int)(clk() - t1) < dly) {}
        if (w == 3) TS(18);
        y[0] = ld_poll(cp); y[1] = ld_poll(cp + 256); y[2] = ld_poll(cp + 16384); y[3] = ld_poll(cp + 16384 + 256);
        { const uint64_t pol = policy_evict_first(); stg4h(op, oq0, pol); stg4h(op + 512, oq1, pol); }
        const float isl = isc * 0.5f, bias = -(float)(need >> 3) * isl;
        while (true) {
          const uint32_t bad = ((y[0].x ^ need) | (y[0].z ^ need) | (y[1].x ^ need) | (y[1].z ^ need)) | ((y[2].x ^ need) | (y[2].z ^ need) | (y[3].x ^ need) | (y[3].z ^ need));
          if (!__any_sync(~0u, (bad & 127u) != 0)) break;
          if (++it > 2000000) __trap();
          y[0] = ld_poll(cp); y[1] = ld_poll(cp + 256); y[2] = ld_poll(cp + 16384); y[3] = ld_poll(cp + 16384 + 256);
        }
        uint32_t p[8];
#pragma unroll
        for (int k = 0; k < 4; k++) {
          p[2 * k] = pack2(fmaf((float)(int)__funnelshift_r(y[k].x, y[k].y, 3), isl, bias), fmaf((float)(int)__funnelshift_r(y[k].z, y[k].w, 3), isl, bias));
          p[2 * k + 1] = pack2((float)(int)y[k].y * isc, (float)(int)y[k].w * isc);
        }
        TS(19 + w);
        forward(p);
      }
    }
    bar_arrive<B_VDONE, 160>();
    bar_arrive<B_XGO1, 256>();
    bar_arrive<B_XGO, 256>();
    pv_x(NSEG - 1);
    { const uint64_t pol = policy_evict_first(); stg4h(op, oq0, pol); stg4h(op + 512, oq1, pol); }
    bar_sync<B_WG2, 128>();
    if (tid == 256) red_release(flags + FL_A + (e0 >> 10) * 8 + (NSEG - 1) * 48, 1);
    mbar_wait(bar + 8 * MB_OG, 1);
    __syncwarp();
  }
  asm volatile("barrier.cluster.arrive.relaxed.aligned;\nbarrier.cluster.wait.aligned;" ::: "memory");
  GT(layer * 4 + 1, 2);
  if (wid == 0) asm volatile("griddepcontrol.wait;" ::: "memory");
}

constexpr int P_B = 0, P_A = 131072, P_BAR = 196608, OPC_SMEM = P_BAR + 256;
#define PF_C 3
#define PF_S0 43
constexpr int OP_KR = 48;

__global__ void __launch_bounds__(384, 1)
opc_kernel(const __grid_constant__ CUtensorMap tmo, bf16* __restrict__ out, int layer,
           const bf16* __restrict__ Wq, const bf16* __restrict__ Wk, const bf16* __restrict__ Wv, const bf16* __restrict__ Wo) {
  extern __shared__ __align__(1024) uint8_t smem[];
  asm volatile("griddepcontrol.launch_dependents;");
  GT(layer * 4 + 2, 0);
  const uint32_t sb = smem_u32(smem);
  check_smem_base(sb);
  const int tid = threadIdx.x, wid = __shfl_sync(~0u, tid >> 5, 0), wg = wid >> 2, w = wid & 3, lane = tid & 31;
  const uint32_t bar = sb + P_BAR;
  uint32_t* flags = g_zero + Z_FLAGS + layer * FL_LAYER;
  float* acc = g_acc + layer * (S_TOK * DM);
  const uint64_t pol = policy_evict_first();
  if (wid == 0) {
    if (lane < 16) mbar_init(bar + 8 * lane, (lane == 8 || lane == 9) ? 8 : 1);
    fence_async();
  }
  __syncthreads();
  if (blockIdx.x < 30) {
    const int cg = blockIdx.x % 5, kg = blockIdx.x / 5;
    if (wg < 2) {
      asm volatile("setmaxnreg.inc.sync.aligned.u32 240;");
      uint32_t a[OP_KR][4];
      const uint32_t la = sb + P_B + ((lane >> 4) * 8 + (lane & 7)) * 128 + (((2 * w + ((lane >> 3) & 1)) ^ (lane & 7)) << 4);
      mbar_wait(bar + 80, 0);
#pragma unroll
      for (int k = 0; k < 32; k++) ldsm4t(a[k], la + wg * 65536 + k * 2048);
      bar_arrive<2, 288>();
      mbar_wait(bar + 88, 0);
#pragma unroll
      for (int k = 0; k < 16; k++) ldsm4t(a[32 + k], la + wg * 32768 + k * 2048);
      bar_arrive<3, 288>();
      mbar_wait(bar + 96, 0);
      float* ap = acc + (cg * 8 + wg * 4 + w) * 512 + lane * 4;
      for (int s = 0; s < NSEG; s++) {
        const int buf = s & 1;
        const uint32_t par = (s >> 1) & 1;
        float d[16];
        const uint64_t db = mkdesc(SB0 + P_B + buf * 65536, 512, 128, 0), da = mkdesc(SB0 + P_A + wg * 32768, 1024, 1024, 1);
        float* p = ap + s * (32 * DM);
        float* pz = ap + (s + 2) * (32 * DM) + kg * 128;
        if (kg < 4 && s + 2 < NSEG) { if (EVF) stg4h(pz, make_uint4(0, 0, 0, 0), pol); else stg4(pz, make_uint4(0, 0, 0, 0)); }
#pragma unroll
        for (int q = 0; q < 4; q++) {
          mbar_wait(bar + 8 * (buf * 4 + q), par);
          wg_fence();
#pragma unroll
          for (int k = 16 * q; k < 16 * q + 16; k++) {
            if (k < OP_KR) wg_rs_n32_tb1(d, a[k < OP_KR ? k : 0], db + k * 64, k);
            else wg_ss_n32_ta1_tb1(d, da + (k - OP_KR) * 128, db + k * 64, 1);
          }
        }
        wg_commit();
        wg_wait<0>();
        pin<16>(d);
        if (lane == 0) mbar_arrive(bar + 8 * (8 + buf));
        if (s == NSEG - 1) GT(layer * 4 + 2, 6);
        if (EVF) {
          red4fh(p, d[0], d[1], d[4], d[5], pol);
          red4fh(p + 128, d[8], d[9], d[12], d[13], pol);
          red4fh(p + 256, d[2], d[3], d[6], d[7], pol);
          red4fh(p + 384, d[10], d[11], d[14], d[15], pol);
        } else {
          red4f(p, d[0], d[1], d[4], d[5]);
          red4f(p + 128, d[8], d[9], d[12], d[13]);
          red4f(p + 256, d[2], d[3], d[6], d[7]);
          red4f(p + 384, d[10], d[11], d[14], d[15]);
        }
        bar_sync<1, 256>();
        if (tid == 0) { red_release(flags + FL_B + s * 8, 1); }
        __syncwarp();
      }
    } else {
      asm volatile("setmaxnreg.dec.sync.aligned.u32 24;");
      if (w == 0) {
        if (lane == 0) { mbar_expect(bar + 80, 131072); mbar_expect(bar + 96, 65536); mbar_expect(bar + 88, 65536); }
        __syncwarp();
        if (lane < 16) tma2d(sb + P_B + lane * 8192, &tmo, cg * 128 + (lane >> 3) * 64, kg * 1024 + (lane & 7) * 64, bar + 80);
        else if (lane < 24) tma2d(sb + P_B + lane * 8192, &tmo, cg * 128 + ((lane >> 2) & 1) * 64, kg * 1024 + 768 + (lane & 3) * 64, bar + 96);
        bar_sync<2, 288>();
        fence_async();
        if (lane < 8) tma2d(sb + P_B + lane * 8192, &tmo, cg * 128 + (lane >> 2) * 64, kg * 1024 + 512 + (lane & 3) * 64, bar + 88);
        bar_sync<3, 288>();
        for (int s = 0; s < NSEG; s++) {
          const int buf = s & 1;
          if (s >= 2) mbar_wait(bar + 8 * (8 + buf), ((s >> 1) & 1) ^ 1);
          if (s >= 2) wait_flag(flags + FL_B + (s - 2) * 8, 30);
          wait_flag(flags + FL_A + s * 48 + kg * 8, 16);
          fence_async_global();
          if (lane < 4) {
            mbar_expect(bar + 8 * (buf * 4 + lane), 16384);
            if (EVF) bulk_g2sh(sb + P_B + buf * 65536 + lane * 16384, g_ot + (size_t)s * (HE * 64) + kg * 65536 + lane * 16384, 16384, bar + 8 * (buf * 4 + lane), pol);
            else bulk_g2s(sb + P_B + buf * 65536 + lane * 16384, g_ot + (size_t)s * (HE * 64) + kg * 65536 + lane * 16384, 16384, bar + 8 * (buf * 4 + lane));
            if (s == NSEG - 1 && lane == 0) GTT(layer * 4 + 2, 5);
          }
          __syncwarp();
        }
      } else if (w == 1 && layer == 0) {
#pragma unroll 1
        for (int q = 4 * (4 - PF_C); q < 18; q++) {
          wait_flag(flags + FL_A + (PF_S0 + q) * 48 + kg * 8, 16);
          const int m = q >> 2;
          const uint8_t* W = m == 0 ? (const uint8_t*)Wo : m == 1 ? (const uint8_t*)Wv : m == 2 ? (const uint8_t*)Wk : m == 3 ? (const uint8_t*)Wq : (q & 1) ? g_w2 : g_w1;
          const int n = m < 4 ? 512 : (q & 1) ? 224 : 640, l0 = m < 4 ? blockIdx.x * 2048 + (q & 3) * 512 : blockIdx.x * n, lim = m < 4 ? 61440 : (q & 1) ? 6720 : 19200;
#pragma unroll 1
          for (int k = lane; k < n; k += 32) {
            if (l0 + k < lim) asm volatile("prefetch.global.L2 [%0];" :: "l"(W + (size_t)(l0 + k) * 128));
            __nanosleep(100);
          }
        }
      }
    }
  } else {
    constexpr int LD = 644;
    float* xs = (float*)smem;
    uint32_t par = 0;
    for (int task = blockIdx.x - 30; task < 2 * NSEG; task += 6, par ^= 1) {
      const int s = task >> 1, jj = task & 1;
      if (wid == 0) {
        wait_flag(flags + FL_XN + (task >> 2) * 8 + 1, 3);
        fence_async_global();
        if (lane == 0) { mbar_expect(bar, 20480); bulk_g2s(sb + 49152, g_x + task * 16 * DM, 20480, bar); }
      }
      if (wid == 1) { wait_flag(flags + FL_B + s * 8, 30); if (s == NSEG - 1 && lane == 0) GTT(layer * 4 + 2, 7); }
      __syncthreads();
      if (wid < 10) {
        float4 v[8];
#pragma unroll
        for (int k = 0; k < 8; k++) v[k] = EVF ? ldg4fh(acc + s * (32 * DM) + (wid * 8 + k) * 256 + jj * 128 + lane * 4, pol) : __ldcg((const float4*)(acc + s * (32 * DM) + (wid * 8 + k) * 256 + jj * 128 + lane * 4));
        float* xp = xs + (lane & 3) * 2 * LD + wid * 64 + (lane >> 2);
#pragma unroll
        for (int k = 0; k < 8; k++) { xp[k * 8] = v[k].x; xp[LD + k * 8] = v[k].y; xp[8 * LD + k * 8] = v[k].z; xp[9 * LD + k * 8] = v[k].w; }
      }
      mbar_wait(bar, par);
      __syncthreads();
      float v[2][20];
      const int pj = (lane & 24) + 2 * (lane & 3) + ((lane >> 2) & 1);
      const int tk0 = task * 16 + wid;
      if (wid < 8) {
        float sum[2] = {0.f, 0.f};
#pragma unroll
        for (int h = 0; h < 2; h++) {
#pragma unroll
          for (int k = 0; k < 10; k++) {
            const float2 u = *(const float2*)(xs + (wid + 8 * h) * LD + k * 64 + lane * 2);
            const uint32_t r = *(const uint32_t*)(smem + 49152 + (wid + 8 * h) * 1280 + k * 128 + pj * 4);
            v[h][2 * k] = u.x + bflo(r); v[h][2 * k + 1] = u.y + bfhi(r); sum[h] += v[h][2 * k] + v[h][2 * k + 1];
          }
        }
        if (!out) {
#pragma unroll
          for (int o = 16; o; o >>= 1) { sum[0] += __shfl_xor_sync(~0u, sum[0], o); sum[1] += __shfl_xor_sync(~0u, sum[1], o); }
          float q[2] = {0.f, 0.f};
#pragma unroll
          for (int h = 0; h < 2; h++) {
            sum[h] *= (1.f / DM);
#pragma unroll
            for (int k = 0; k < 20; k++) q[h] = fmaf(v[h][k] - sum[h], v[h][k] - sum[h], q[h]);
          }
#pragma unroll
          for (int o = 16; o; o >>= 1) { q[0] += __shfl_xor_sync(~0u, q[0], o); q[1] += __shfl_xor_sync(~0u, q[1], o); }
          uint8_t* xp = g_xt + (tk0 >> 7) * 163840 + (tk0 & 127) * 128 + (((lane >> 2) ^ (tk0 & 7)) << 4) + (lane & 3) * 4;
#pragma unroll
          for (int h = 0; h < 2; h++) {
            const float rs = rsqrtf(q[h] * (1.f / DM) + 1e-5f), sh = -sum[h] * rs;
#pragma unroll
            for (int k = 0; k < 10; k++) *(uint32_t*)(xp + h * 1024 + k * 16384) = pack2(fmaf(v[h][2 * k], rs, sh), fmaf(v[h][2 * k + 1], rs, sh));
          }
        }
      }
      fence_async();
      __syncthreads();
      if (!out) {
        if (tid == 352) red_release(flags + FL_LAYER + FL_T + (task >> 3) * 8, 1);
        __syncthreads();
      }
      if (wid < 8) {
        bf16* dst = out ? out + tk0 * DM + lane * 2 : g_x + tk0 * DM + pj * 2;
#pragma unroll
        for (int k = 0; k < 20; k++) *(uint32_t*)(dst + (k / 10) * 8 * DM + (k % 10) * 64) = pack2(v[k / 10][2 * (k % 10)], v[k / 10][2 * (k % 10) + 1]);
      }
    }
    __syncthreads();
    if (tid == 0 && !out) red_release(flags + FL_LAYER + FL_R, 1);
  }
  GT(layer * 4 + 2, 1);
  __syncwarp();
  asm volatile("griddepcontrol.wait;" ::: "memory");
  GT(layer * 4 + 2, 2);
}

constexpr int L_STAGE = 47104;
constexpr int L_KV = 0, L_B2 = 43008;
constexpr int L_BAR = 4 * L_STAGE;
constexpr int LA_SMEM = L_BAR + 256;
__device__ __forceinline__ float phi(float t) { return (fmaxf(t, 0.f) + 1e-6f) + ex2(fminf(t * 1.4426950408889634f, 0.f)); }
__device__ __forceinline__ void sqacc(uint32_t& h, uint32_t v) { asm("fma.rn.bf16x2 %0, %1, %1, %0;" : "+r"(h) : "r"(v)); }
__device__ __forceinline__ uint32_t phi2(float a, float b) { return pack2(phi(a), phi(b)); }
#define LA_LATE 6
#define PF_LB 1
#define PF_IL 1
#define PF_SLEEP1 400
#define RD1 0
#define PF_N0 2
#define PF_N1 0
#define PF_SLEEP 300

__global__ void __launch_bounds__(384, 1)
la_kernel(const bf16* __restrict__ Wq, const bf16* __restrict__ Wk, const bf16* __restrict__ Wv,
          const bf16* __restrict__ Wo, uint8_t* __restrict__ ar, int layer) {
  extern __shared__ __align__(1024) uint8_t smem[];
  const uint32_t sb = smem_u32(smem);
  check_smem_base(sb);
  const int tid = threadIdx.x, wid = __shfl_sync(~0u, tid >> 5, 0), wg = wid >> 2, w = wid & 3, lane = tid & 31, g = lane >> 2, i4 = lane & 3;
  const int cr = blockIdx.x & 1, hg = (blockIdx.x >> 1) & 7, tb = (blockIdx.x >> 4) * 2 + cr;
  const uint32_t bar = sb + L_BAR;
  uint32_t* flags = g_zero + Z_FLAGS + layer * FL_LAYER;
  asm volatile("griddepcontrol.launch_dependents;");
  GT(layer * 4, 0);
  if (wid == 0) {
    if (lane < 8) mbar_init(bar + 8 * lane, lane >= 4 ? (blockIdx.x < 128 ? 16 : 10) : 1);
    asm volatile("fence.mbarrier_init.release.cluster;" ::: "memory");
    fence_async();
  }
  if (blockIdx.x >= 128) {
    __syncthreads();
    const int q = blockIdx.x - 128;
    const uint8_t* src = (const uint8_t*)Wo + q * 1966080;
    if (wid == 11) {
#pragma unroll 1
      for (int it = 0; it < 48; it++) {
        const int st = it & 3;
        if (it >= 4) mbar_wait(bar + 8 * (4 + st), ((it >> 2) & 1) ^ 1);
        if (lane == 0) mbar_expect(bar + 8 * st, 40960);
        __syncwarp();
        if (lane < 4) bulk_g2s(sb + st * 40960 + lane * 10240, src + it * 40960 + lane * 10240, 10240, bar + 8 * st);
      }
    } else if (wid < 10) {
      float c[8] = {0.f, 0.f, 0.f, 0.f, 0.f, 0.f, 0.f, 0.f};
#pragma unroll 1
      for (int it = 0; it < 48; it++) {
        const int st = it & 3;
        mbar_wait(bar + 8 * st, (it >> 2) & 1);
        uint4 v[8];
#pragma unroll
        for (int k = 0; k < 8; k++) v[k] = lds4(sb + st * 40960 + k * 5120 + tid * 16);
        uint32_t h[4] = {0, 0, 0, 0};
#pragma unroll
        for (int k = 0; k < 8; k++) { sqacc(h[0], v[k].x); sqacc(h[1], v[k].y); sqacc(h[2], v[k].z); sqacc(h[3], v[k].w); }
        __syncwarp();
        if (lane == 0) mbar_arrive(bar + 8 * (4 + st));
#pragma unroll
        for (int k = 0; k < 4; k++) { c[2 * k] += bflo(h[k]); c[2 * k + 1] += bfhi(h[k]); }
      }
      float* red = (float*)(smem + 163840);
      *(float4*)(red + tid * 8) = make_float4(c[0], c[1], c[2], c[3]);
      *(float4*)(red + tid * 8 + 4) = make_float4(c[4], c[5], c[6], c[7]);
      bar_sync<1, 320>();
#pragma unroll
      for (int k = tid; k < DM; k += 320) g_nrm[q * DM + k] = (red[k] + red[DM + k]) + (red[2 * DM + k] + red[3 * DM + k]);
      asm volatile("griddepcontrol.wait;" ::: "memory");
      bar_sync<1, 320>();
      if (tid == 0) red_release(flags + FL_N, 1);
      GT(0, 2);
    }
    return;
  }
  __syncthreads();
  asm volatile("barrier.cluster.arrive.relaxed.aligned;" ::: "memory");
  if (layer == 0) asm volatile("griddepcontrol.wait;" ::: "memory");
  asm volatile("barrier.cluster.wait.aligned;" ::: "memory");
  if (wg == 2) {
    asm volatile("setmaxnreg.dec.sync.aligned.u32 40;");
    if (w == 0) {
      if (lane < 4) {
        mbar_expect(bar + 8 * lane, L_STAGE);
        bulk_g2s_mc(sb + lane * L_STAGE + 16384 + cr * 15360, g_w1 + (hg * 10 + lane) * 30720 + cr * 15360, 15360, bar + 8 * lane);
      }
      if (layer == 1) { if (LA_LATE) wait_flag(flags + FL_T + 15 * 8, LA_LATE); wait_flag(flags + FL_T + tb * 8, 8); fence_async_global(); }
      if (lane < 4) bulk_g2s(sb + lane * L_STAGE, g_xt + (tb * 10 + lane) * 16384, 16384, bar + 8 * lane);
#pragma unroll 1
      for (int kc = 4; kc < 10; kc++) {
        const int st = kc & 3;
        mbar_wait(bar + 8 * (4 + st), ((kc >> 2) & 1) ^ 1);
        if (lane == 0) {
          mbar_expect(bar + 8 * st, L_STAGE);
          bulk_g2s_mc(sb + st * L_STAGE + 16384 + cr * 15360, g_w1 + (hg * 10 + kc) * 30720 + cr * 15360, 15360, bar + 8 * st);
          bulk_g2s(sb + st * L_STAGE, g_xt + (tb * 10 + kc) * 16384, 16384, bar + 8 * st);
        }
        __syncwarp();
      }
    } else {
      const int t = tid - 288;
#pragma unroll 1
      for (int k = t; k < 768; k += 96) *(uint4*)(ar + blockIdx.x * 12288 + k * 16) = make_uint4(0, 0, 0, 0);
      if (layer == 0 || RD1) {
        float sv = 0.f;
        const uint4* pv = (const uint4*)((const uint8_t*)Wv + blockIdx.x * 61440) + t;
#pragma unroll 1
        for (int k = 0; k < 40; k += 5) {
          uint4 v[5];
#pragma unroll
          for (int j = 0; j < 5; j++) v[j] = __ldg(pv + (k + j) * 96);
          if (PF_IL && k < 25) {
            asm volatile("prefetch.global.L2 [%0];" :: "l"((const uint8_t*)Wq + blockIdx.x * 61440 + (k / 5) * 12288 + t * 128));
            if (PF_IL > 1) asm volatile("prefetch.global.L2 [%0];" :: "l"((const uint8_t*)Wk + blockIdx.x * 61440 + (k / 5) * 12288 + t * 128));
          }
#pragma unroll
          for (int j = 0; j < 5; j++) {
            sv = fmaf(bflo(v[j].x), bflo(v[j].x), fmaf(bfhi(v[j].x), bfhi(v[j].x), fmaf(bflo(v[j].y), bflo(v[j].y), fmaf(bfhi(v[j].y), bfhi(v[j].y), sv))));
            sv = fmaf(bflo(v[j].z), bflo(v[j].z), fmaf(bfhi(v[j].z), bfhi(v[j].z), fmaf(bflo(v[j].w), bflo(v[j].w), fmaf(bfhi(v[j].w), bfhi(v[j].w), sv))));
          }
        }
#pragma unroll
        for (int o = 16; o; o >>= 1) sv += __shfl_xor_sync(~0u, sv, o);
        if (lane == 0) atomicAdd((float*)(g_zero + Z_NORM + layer), sv);
      }
      if (layer == 1 && PF_LB) {
        const int l = blockIdx.x * 96 + t;
        if (l < 6720 + NLB * 640) asm volatile("prefetch.global.L2 [%0];" :: "l"(l < 6720 ? g_w2 + l * 128 : (const uint8_t*)g_x + (l - 6720) * 128));
      }
#pragma unroll 1
      for (int k = (layer && !RD1) ? 0 : 5 * PF_IL; k < 5 * (layer ? PF_N1 : PF_N0); k++) {
        const int m = k / 5;
        const bf16* W = m == 0 ? Wq : m == 1 ? Wk : m == 2 ? Wv : Wo;
        asm volatile("prefetch.global.L2 [%0];" :: "l"((const uint8_t*)W + blockIdx.x * 61440 + (k - m * 5) * 12288 + t * 128));
        __nanosleep(layer ? PF_SLEEP1 : PF_SLEEP);
      }
      if (t == 0) GTT(layer * 4, 14);
      bar_arrive<3, 352>();
    }
  } else {
    asm volatile("setmaxnreg.inc.sync.aligned.u32 232;");
    GT(layer * 4, 4);
    uint32_t pq[5][4];
    float* kv = (float*)(g_zero + Z_KV) + layer * KV_LAYER + hg * 1920;
    {
      float d[120];
#pragma unroll 1
      for (int kc = 0; kc < 10; kc++) {
        const int st = kc & 3;
        const uint64_t da = mkdesc(SB0 + st * L_STAGE + wg * 8192, 16, 1024, 1), db = mkdesc(SB0 + st * L_STAGE + 16384, 3840, 128, 0);
        mbar_wait(bar + 8 * st, (kc >> 2) & 1);
        wg_fence();
#pragma unroll
        for (int k = 0; k < 4; k++) wg_ss_n240_ta0_tb1(d, da + 2 * k, db + k * 480, kc | k);
        wg_commit();
        if (kc > 0) { wg_wait<1>(); if (lane < 2) mbar_arrive_cl(mapa(bar + 8 * (4 + ((kc - 1) & 3)), lane)); }
      }
      wg_wait<0>();
      pin<120>(d);
      GT(layer * 4, 5);
      bar_sync<1, 256>();
      const uint32_t kb = sb + L_KV + (wg * 8 + 2 * w + ((lane >> 3) & 1)) * 2688 + (lane >> 4) * 128 + (lane & 7) * 16;
#pragma unroll
      for (int j = 0; j < 5; j++) stsm4(kb + 1280 + j * 256, pack2(d[80 + 8 * j], d[81 + 8 * j]), pack2(d[82 + 8 * j], d[83 + 8 * j]), pack2(d[84 + 8 * j], d[85 + 8 * j]), pack2(d[86 + 8 * j], d[87 + 8 * j]));
      stsm2(kb + 2560, 0x3F803F80u, 0x3F803F80u);
#pragma unroll
      for (int j = 0; j < 5; j++) stsm4(kb + j * 256, phi2(d[40 + 8 * j], d[41 + 8 * j]), phi2(d[42 + 8 * j], d[43 + 8 * j]), phi2(d[44 + 8 * j], d[45 + 8 * j]), phi2(d[46 + 8 * j], d[47 + 8 * j]));
      fence_async();
      bar_sync<1, 256>();
      float e[44];
      {
        const uint64_t da = mkdesc(SB0 + L_KV + wg * 1024, 2688, 128, 0), db = mkdesc(SB0 + L_KV + 1280, 2688, 128, 0);
        wg_fence();
#pragma unroll
        for (int k = 0; k < 8; k++) wg_ss_n88_ta1_tb1(e, da + k * 336, db + k * 336, k);
        wg_commit();
        wg_wait<0>();
        pin<44>(e);
      }
#pragma unroll
      for (int h = 0; h < 2; h++) {
        const int row = wg * 64 + 16 * w + 8 * h + g;
        const int c = row < 80 ? 2 * i4 - (row / 20) * 20 : 100;
        float* dst = kv + row * 24 + c;
#pragma unroll
        for (int j = 0; j < 10; j++)
          asm volatile("{\n.reg .pred p;\nsetp.lt.u32 p, %3, 20;\n@p red.relaxed.gpu.global.add.v2.f32 [%0], {%1,%2};\n}" :: "l"(dst + 8 * j), "f"(e[4 * j + 2 * h]), "f"(e[4 * j + 2 * h + 1]), "r"(c + 8 * j) : "memory");
        asm volatile("{\n.reg .pred p;\nsetp.ne.u32 p, %2, 0;\n@p red.relaxed.gpu.global.add.f32 [%0], %1;\n}" :: "l"(kv + row * 24 + 20), "f"(e[40 + 2 * h]), "r"((int)(row < 80 && i4 == 0)) : "memory");
      }
      bar_sync<1, 256>();
      GT(layer * 4, 6);
      if (tid == 0) { red_release(flags + FL_KV + hg * 8, 1); }
      __syncwarp();
      pin<40>(d);
#pragma unroll
      for (int k = 0; k < 5; k++) {
        pq[k][0] = phi2(d[8 * k], d[8 * k + 1]); pq[k][1] = phi2(d[8 * k + 2], d[8 * k + 3]);
        pq[k][2] = phi2(d[8 * k + 4], d[8 * k + 5]); pq[k][3] = phi2(d[8 * k + 6], d[8 * k + 7]);
      }
    }
#pragma unroll 1
    for (int k = tid; k < 1600; k += 256) sts4(sb + L_B2 + k * 16, 0, 0, 0, 0);
    GT(layer * 4, 7);
    if (wid == 0) wait_flag(flags + FL_KV + hg * 8, 16);
    GT(layer * 4, 8);
    bar_sync<1, 256>();
    if (tid < 240) {
      const int dd = tid / 3, part = tid - dd * 3, n = (dd / 20) * 20 + 8 * part;
      const float4 v0 = __ldcg((const float4*)(kv + dd * 24 + 8 * part)), v1 = __ldcg((const float4*)(kv + dd * 24 + 8 * part + 4));
      const float z = __ldcg(kv + dd * 24 + 20);
      const uint32_t a = sb + L_B2 + (dd >> 3) * 2560 + (dd & 7) * 16, zz = pack2(z, z);
      const uint32_t a0 = a + (n >> 3) * 128 + (n & 7) * 2, a1 = a + ((n + 4) >> 3) * 128 + ((n + 4) & 7) * 2;
      sts2(a0, pack2(v0.x, v0.y), pack2(v0.z, v0.w)); sts2(a0 + 1280, zz, zz);
      if (part < 2) { sts2(a1, pack2(v1.x, v1.y), pack2(v1.z, v1.w)); sts2(a1 + 1280, zz, zz); }
    }
    fence_async();
    bar_sync<1, 256>();
    {
      float o[80];
      const uint64_t db = mkdesc(SB0 + L_B2, 2560, 128, 0);
      wg_fence();
#pragma unroll
      for (int k = 0; k < 5; k++) wg_rs_n160_tb1(o, pq[k], db + k * 320, k);
      wg_commit();
      wg_wait<0>();
      pin<80>(o);
      uint8_t* op = g_oa + (tb * 2 + wg) * 81920 + hg * 10240 + w * 256 + lane * 4;
#pragma unroll
      for (int j = 0; j < 20; j++) {
        const float inv = rcp(o[40 + 2 * j] + 1e-6f);
        *(uint32_t*)(op + (j >> 1) * 1024 + (j & 1) * 128) = pack2(o[2 * j] * inv, o[2 * j + 1] * inv);
      }
      GT(layer * 4, 9);
    }
    bar_sync<3, 352>();
    if (tid == 0) { red_release(flags + FL_O + tb * 8, 1); red_add(flags + FL_X, 1); }
    GT(layer * 4, 2);
    if (wid == 7) asm volatile("griddepcontrol.wait;" ::: "memory");
  }
}

__global__ void __launch_bounds__(256) prep_kernel(const bf16* __restrict__ x, const bf16* __restrict__ wqkv, const bf16* __restrict__ wo) {
  asm volatile("griddepcontrol.launch_dependents;");
  const int b = blockIdx.x, tid = threadIdx.x, lane = tid & 31;
  if (b < 160) GT(3, 0);
  if (b < 256) {
    const int row = b * 8 + (tid >> 5);
    float v[20], s = 0.f;
#pragma unroll
    for (int k = 0; k < 10; k++) { const uint32_t u = __ldg((const uint32_t*)(x + row * DM + k * 64 + lane * 2)); v[2 * k] = bflo(u); v[2 * k + 1] = bfhi(u); s += v[2 * k] + v[2 * k + 1]; }
#pragma unroll
    for (int o = 16; o; o >>= 1) s += __shfl_xor_sync(~0u, s, o);
    const float m = s * (1.f / DM);
    float q = 0.f;
#pragma unroll
    for (int k = 0; k < 20; k++) { v[k] -= m; q += v[k] * v[k]; }
#pragma unroll
    for (int o = 16; o; o >>= 1) q += __shfl_xor_sync(~0u, q, o);
    const float r = rsqrtf(q * (1.f / DM) + 1e-5f);
#pragma unroll
    for (int k = 0; k < 10; k++)
      *(uint32_t*)(g_xt + ((row >> 7) * 10 + k) * 16384 + (row & 127) * 128 + (((lane >> 2) ^ (row & 7)) << 4) + (lane & 3) * 4) = pack2(v[2 * k] * r, v[2 * k + 1] * r);
  } else if (b < 256 + 203) {
    uint4 v[4];
    const int u0 = (b - 256) * 1024 + tid;
#pragma unroll
    for (int it = 0; it < 4; it++) {
      const int u = u0 + it * 256, k8 = u & 7;
      const bf16* src;
      bool ok = true;
      if (b < 256 + 150) {
        const int nb = (u >> 3) % 30, kg = (u / 240) % 80, hg = u / 19200;
        src = wqkv + (kg * 8 + k8) * 1920 + (nb / 10) * 640 + hg * 80 + (nb % 10) * 8;
      } else {
        const int q = u - 153600, nb = (q >> 3) % 28, kg = (q / 224) % 80, c = (q / 17920) * 224 + nb * 8;
        ok = c < DM;
        src = wo + (kg * 8 + k8) * DM + (ok ? c : 0);
      }
      v[it] = __ldg((const uint4*)src);
      if (!ok) v[it] = make_uint4(0, 0, 0, 0);
    }
    uint8_t* dst = b < 256 + 150 ? g_w1 + u0 * 16 : g_w2 + (u0 - 153600) * 16;
#pragma unroll
    for (int it = 0; it < 4; it++) if (u0 + it * 256 < 207360) *(uint4*)(dst + it * 4096) = v[it];
  } else {
    const int t = (b - 459) * 256 + tid;
    for (int k = t; k < Z_END / 4; k += 16 * 256) ((uint4*)g_zero)[k] = make_uint4(0, 0, 0, 0);
    for (int k = t; k < 16 * DM; k += 16 * 256) { ((uint4*)g_acc)[k] = make_uint4(0, 0, 0, 0); ((uint4*)(g_acc + S_TOK * DM))[k] = make_uint4(0, 0, 0, 0); }
  }
  if (b < 160) GT(3, 2);
}

typedef CUresult (*EncodeFn)(CUtensorMap*, CUtensorMapDataType, cuuint32_t, void*, const cuuint64_t*, const cuuint64_t*, const cuuint32_t*,
                             const cuuint32_t*, CUtensorMapInterleave, CUtensorMapSwizzle, CUtensorMapL2promotion, CUtensorMapFloatOOBfill);
static void make_map(EncodeFn fn, CUtensorMap* m, const void* p, uint64_t cols, uint64_t rows, uint32_t bc, uint32_t br, CUtensorMapSwizzle sw) {
  cuuint64_t dims[2] = {cols, rows}; cuuint64_t strides[1] = {cols * 2}; cuuint32_t box[2] = {bc, br}; cuuint32_t es[2] = {1, 1};
  fn(m, CU_TENSOR_MAP_DATA_TYPE_BFLOAT16, 2, (void*)p, dims, strides, box, es, CU_TENSOR_MAP_INTERLEAVE_NONE, sw,
     CU_TENSOR_MAP_L2_PROMOTION_L2_128B, CU_TENSOR_MAP_FLOAT_OOB_FILL_NONE);
}

static void make_map_perm(EncodeFn fn, CUtensorMap* m, const void* p) {
  cuuint64_t dims[5] = {HE, 2, 2, 4, 40}; const cuuint64_t r = HE * 2; cuuint64_t strides[4] = {r, 8 * r, 2 * r, 16 * r};
  cuuint32_t box[5] = {64, 2, 2, 4, 4}; cuuint32_t es[5] = {1, 1, 1, 1, 1};
  fn(m, CU_TENSOR_MAP_DATA_TYPE_BFLOAT16, 5, (void*)p, dims, strides, box, es, CU_TENSOR_MAP_INTERLEAVE_NONE, CU_TENSOR_MAP_SWIZZLE_128B,
     CU_TENSOR_MAP_L2_PROMOTION_L2_128B, CU_TENSOR_MAP_FLOAT_OOB_FILL_NONE);
}

#define OPC_PDL 1
#define LA_PDL 1
#define REC_PDL 1
extern "C" void kernel_launch(void* const* d_in, const int* in_sizes, int n_in, void* d_out, int out_size) {
  const bf16* x = (const bf16*)d_in[0];
  const bf16* wqkv = (const bf16*)d_in[1];
  const bf16* wo_a = (const bf16*)d_in[2];
  const bf16* mem0 = (const bf16*)d_in[4];
  const bf16* Wq = (const bf16*)d_in[5];
  const bf16* Wk = (const bf16*)d_in[6];
  const bf16* Wv = (const bf16*)d_in[7];
  const bf16* Wo = (const bf16*)d_in[8];
  cudaStream_t st = cudaStreamPerThread;

  static EncodeFn enc = nullptr;
  static uint8_t* p_ar; static uint32_t* p_zero; static bf16* p_x;
  if (!enc) {
    cudaDriverEntryPointQueryResult qr;
    void* fn = nullptr;
    cudaGetDriverEntryPoint("cuTensorMapEncodeTiled", &fn, cudaEnableDefault, &qr);
    enc = (EncodeFn)fn;
    cudaFuncSetAttribute(rec_kernel, cudaFuncAttributeMaxDynamicSharedMemorySize, REC_SMEM);
    cudaFuncSetAttribute(opc_kernel, cudaFuncAttributeMaxDynamicSharedMemorySize, OPC_SMEM);
    cudaFuncSetAttribute(la_kernel, cudaFuncAttributeMaxDynamicSharedMemorySize, LA_SMEM);
    cudaGetSymbolAddress((void**)&p_ar, g_ar); p_ar = (uint8_t*)(((uintptr_t)p_ar + 32767) & ~(uintptr_t)32767);
    cudaGetSymbolAddress((void**)&p_zero, g_zero); cudaGetSymbolAddress((void**)&p_x, g_x);
  }
  CUtensorMap tmq, tmk, tmv, tmo, tmx[2];
  make_map_perm(enc, &tmq, Wq);
  make_map_perm(enc, &tmk, Wk);
  make_map_perm(enc, &tmv, Wv);
  make_map(enc, &tmo, Wo, DM, HE, 64, 64, CU_TENSOR_MAP_SWIZZLE_128B);
  make_map(enc, &tmx[0], x, DM, S_TOK, 232, 64, CU_TENSOR_MAP_SWIZZLE_NONE);
  make_map(enc, &tmx[1], p_x, DM, S_TOK, 232, 64, CU_TENSOR_MAP_SWIZZLE_NONE);

  cudaLaunchAttribute at[2];
  at[0].id = cudaLaunchAttributeProgrammaticStreamSerialization; at[0].val.programmaticStreamSerializationAllowed = 1;
  at[1].id = cudaLaunchAttributeClusterDimension; at[1].val.clusterDim.x = 3; at[1].val.clusterDim.y = 1; at[1].val.clusterDim.z = 1;
  cudaLaunchAttribute at2[2] = {at[1], at[0]};
  at2[0].val.clusterDim.x = 2;
  prep_kernel<<<475, 256, 0, st>>>(x, wqkv, wo_a);
  for (int l = 0; l < 2; l++) {
    cudaLaunchConfig_t cfg = {};
    cfg.blockDim = dim3(384); cfg.stream = st;
    cfg.gridDim = dim3(l == 0 ? 132 : 128); cfg.dynamicSmemBytes = LA_SMEM; cfg.attrs = at2; cfg.numAttrs = 1 + LA_PDL;
    cudaLaunchKernelEx(&cfg, la_kernel, Wq, Wk, Wv, Wo, p_ar + l * AR_LAYER, l);
    cfg.gridDim = dim3(96 + 3 * NLB); cfg.dynamicSmemBytes = REC_SMEM; cfg.attrs = at + 1 - REC_PDL; cfg.numAttrs = 1 + REC_PDL;
    cudaLaunchKernelEx(&cfg, rec_kernel, tmq, tmk, tmv, tmo, tmx[l], mem0, p_ar + l * AR_LAYER, p_zero + Z_FLAGS + l * FL_LAYER, l);
    cfg.gridDim = dim3(36); cfg.dynamicSmemBytes = OPC_SMEM; cfg.attrs = at; cfg.numAttrs = OPC_PDL;
    cudaLaunchKernelEx(&cfg, opc_kernel, tmo, l == 1 ? (bf16*)d_out : (bf16*)nullptr, l, Wq, Wk, Wv, Wo);
  }
}
```

```cpp
#include <cuda_runtime.h>
#include <cuda_bf16.h>
#include <cuda.h>
#include <stdint.h>

typedef __nv_bfloat16 bf16;
typedef unsigned long long u64;

constexpr int S_TOK = 2048, DM = 640, DH = 192, HE = 6144, NSEG = 64;

constexpr int AR_GROUP = 98304;
constexpr int AR_LAYER = 16 * AR_GROUP;
__device__ __align__(1024) uint8_t g_ar[2 * AR_LAYER + 32768];
__device__ __align__(1024) uint8_t g_xn[NSEG * 40960];
__device__ __align__(1024) uint8_t g_xt[S_TOK * DM * 2];
__device__ __align__(1024) uint8_t g_ot[NSEG * HE * 64];
__device__ __align__(1024) uint8_t g_oa[S_TOK * DM * 2];
__device__ __align__(1024) uint8_t g_w1[DM * 1920 * 2];
__device__ __align__(1024) uint8_t g_w2[DM * 672 * 2];
__device__ __align__(1024) float g_acc[2 * S_TOK * DM];
__device__ __align__(1024) bf16 g_x[S_TOK * DM];
constexpr int FL_A = 0, FL_B = 64 * 6 * 8, FL_KV = FL_B + 64 * 8, FL_O = FL_KV + 8 * 8, FL_T = FL_O + 16 * 8, FL_X = FL_T + 16 * 8, FL_N = FL_X + 8, FL_R = FL_N + 8, FL_XN = FL_R + 8, FL_LAYER = FL_XN + 32 * 8;
constexpr int Z_FLAGS = 0, Z_NORM = 2 * FL_LAYER, Z_KV = Z_NORM + 8, KV_LAYER = 8 * 80 * 24, Z_END = Z_KV + 2 * KV_LAYER;
__device__ __align__(128) uint32_t g_zero[Z_END];
__device__ __align__(128) float g_nrm[4 * DM];
#define GT(slot, k) do {} while (0)
#define GTT(slot, k) do {} while (0)

__device__ __forceinline__ uint32_t smem_u32(const void* p) { return (uint32_t)__cvta_generic_to_shared(p); }
__device__ __forceinline__ uint32_t mapa(uint32_t a, uint32_t r) { uint32_t o; asm("mapa.shared::cluster.u32 %0, %1, %2;" : "=r"(o) : "r"(a), "r"(r)); return o; }
__device__ __forceinline__ void mbar_init(uint32_t bar, uint32_t cnt) { asm volatile("mbarrier.init.shared::cta.b64 [%0], %1;" :: "r"(bar), "r"(cnt) : "memory"); }
__device__ __forceinline__ void mbar_expect(uint32_t bar, uint32_t tx) { asm volatile("mbarrier.arrive.expect_tx.shared::cta.b64 _, [%0], %1;" :: "r"(bar), "r"(tx) : "memory"); }
__device__ __forceinline__ void mbar_arrive(uint32_t bar) { asm volatile("mbarrier.arrive.shared::cta.b64 _, [%0];" :: "r"(bar) : "memory"); }
__device__ __forceinline__ void mbar_wait(uint32_t bar, uint32_t par) {
  asm volatile("{\n.reg .pred p;\n.reg .u32 c;\nmov.u32 c, 0;\n"
               "LW:\nmbarrier.try_wait.parity.shared::cta.b64 p, [%0], %1;\n@p bra LD;\n"
               "add.u32 c, c, 1;\nsetp.lt.u32 p, c, 4000000;\n@p bra LW;\ntrap;\nLD:\n}" :: "r"(bar), "r"(par) : "memory");
}
__device__ __forceinline__ void mbar_waitf(uint32_t bar, uint32_t par) {
  asm volatile("{\n.reg .pred p, q;\n.reg .u32 c;\nmov.u32 c, 0;\n"
               "LW:\nadd.u32 c, c, 1;\nsetp.lt.u32 q, c, 1000000;\nmbarrier.try_wait.parity.shared::cta.b64 p, [%0], %1;\n"
               "and.pred q, q, !p;\n@q bra LW;\n}" :: "r"(bar), "r"(par) : "memory");
}
template <int ID, int N> __device__ __forceinline__ void bar_sync() { asm volatile("barrier.sync %0, %1;" :: "n"(ID), "n"(N) : "memory"); }
template <int ID, int N> __device__ __forceinline__ void bar_arrive() { asm volatile("barrier.arrive %0, %1;" :: "n"(ID), "n"(N) : "memory"); }
__device__ __forceinline__ void fence_async() { asm volatile("fence.proxy.async.shared::cta;" ::: "memory"); }
__device__ __forceinline__ void cluster_sync() { asm volatile("barrier.cluster.arrive.aligned;\nbarrier.cluster.wait.aligned;" ::: "memory"); }
__device__ __forceinline__ void wg_fence() { asm volatile("wgmma.fence.sync.aligned;" ::: "memory"); }
__device__ __forceinline__ void wg_commit() { asm volatile("wgmma.commit_group.sync.aligned;" ::: "memory"); }
template <int N> __device__ __forceinline__ void wg_wait() { asm volatile("wgmma.wait_group.sync.aligned %0;" :: "n"(N) : "memory"); }
template <int N> __device__ __forceinline__ void pin(float* d) {
#pragma unroll
  for (int i = 0; i < N; i++) asm volatile("" : "+f"(d[i]) :: "memory");
}
__device__ __forceinline__ constexpr uint64_t mkdesc(uint32_t addr, uint32_t lbo, uint32_t sbo, int sw) {
  return (uint64_t)((addr & 0x3FFFF) >> 4) | ((uint64_t)(lbo >> 4) << 16) | ((uint64_t)(sbo >> 4) << 32) | ((uint64_t)sw << 62);
}
constexpr uint32_t SB0 = 1024;
__device__ __forceinline__ void check_smem_base(uint32_t sb) { if ((sb & 0x3FFFF) != SB0) __trap(); }
__device__ __forceinline__ uint32_t cta_rank() { uint32_t r; asm volatile("mov.u32 %0, %%cluster_ctarank;" : "=r"(r)); return r; }
__device__ __forceinline__ uint32_t opaque(uint32_t v) { uint32_t o; asm volatile("mov.u32 %0, %1;" : "=r"(o) : "r"(v)); return o; }
__device__ __forceinline__ uint32_t pack2(float lo, float hi) { uint32_t r; asm("cvt.rn.bf16x2.f32 %0, %1, %2;" : "=r"(r) : "f"(hi), "f"(lo)); return r; }
__device__ __forceinline__ void ldsm4(uint32_t* r, uint32_t a) { asm volatile("ldmatrix.sync.aligned.m8n8.x4.shared.b16 {%0,%1,%2,%3}, [%4];" : "=r"(r[0]), "=r"(r[1]), "=r"(r[2]), "=r"(r[3]) : "r"(a) : "memory"); }
__device__ __forceinline__ void ldsm4t(uint32_t* r, uint32_t a) { asm volatile("ldmatrix.sync.aligned.m8n8.x4.trans.shared.b16 {%0,%1,%2,%3}, [%4];" : "=r"(r[0]), "=r"(r[1]), "=r"(r[2]), "=r"(r[3]) : "r"(a) : "memory"); }
__device__ __forceinline__ void ldsm1(uint32_t& r, uint32_t a) { asm volatile("ldmatrix.sync.aligned.m8n8.x1.shared.b16 {%0}, [%1];" : "=r"(r) : "r"(a) : "memory"); }
__device__ __forceinline__ void stsm4(uint32_t a, uint32_t r0, uint32_t r1, uint32_t r2, uint32_t r3) { asm volatile("stmatrix.sync.aligned.m8n8.x4.shared.b16 [%0], {%1,%2,%3,%4};" :: "r"(a), "r"(r0), "r"(r1), "r"(r2), "r"(r3) : "memory"); }
__device__ __forceinline__ void stsm1(uint32_t a, uint32_t r0) { asm volatile("stmatrix.sync.aligned.m8n8.x1.shared.b16 [%0], {%1};" :: "r"(a), "r"(r0) : "memory"); }
__device__ __forceinline__ void stsm4t(uint32_t a, uint32_t r0, uint32_t r1, uint32_t r2, uint32_t r3) { asm volatile("stmatrix.sync.aligned.m8n8.x4.trans.shared.b16 [%0], {%1,%2,%3,%4};" :: "r"(a), "r"(r0), "r"(r1), "r"(r2), "r"(r3) : "memory"); }
__device__ __forceinline__ void stsm2t(uint32_t a, uint32_t r0, uint32_t r1) { asm volatile("stmatrix.sync.aligned.m8n8.x2.trans.shared.b16 [%0], {%1,%2};" :: "r"(a), "r"(r0), "r"(r1) : "memory"); }
__device__ __forceinline__ void mma16816(float* c, const uint32_t* a, uint32_t b0, uint32_t b1) {
  asm volatile("mma.sync.aligned.m16n8k16.row.col.f32.bf16.bf16.f32 {%0,%1,%2,%3}, {%4,%5,%6,%7}, {%8,%9}, {%0,%1,%2,%3};"
               : "+f"(c[0]), "+f"(c[1]), "+f"(c[2]), "+f"(c[3]) : "r"(a[0]), "r"(a[1]), "r"(a[2]), "r"(a[3]), "r"(b0), "r"(b1));
}
__device__ __forceinline__ void mma1688(float* c, uint32_t a0, uint32_t a1, uint32_t b0) {
  asm volatile("mma.sync.aligned.m16n8k8.row.col.f32.bf16.bf16.f32 {%0,%1,%2,%3}, {%4,%5}, {%6}, {%0,%1,%2,%3};"
               : "+f"(c[0]), "+f"(c[1]), "+f"(c[2]), "+f"(c[3]) : "r"(a0), "r"(a1), "r"(b0));
}
__device__ __forceinline__ void sta1(uint32_t a, uint32_t v, uint32_t bar) { asm volatile("st.async.weak.shared::cluster.mbarrier::complete_tx::bytes.b32 [%0], %1, [%2];" :: "r"(a), "r"(v), "r"(bar) : "memory"); }
__device__ __forceinline__ void sta1p(uint32_t a, uint32_t v, uint32_t bar, bool p) { asm volatile("{\n.reg .pred p;\nsetp.ne.b32 p, %3, 0;\n@p st.async.weak.shared::cluster.mbarrier::complete_tx::bytes.b32 [%0], %1, [%2];\n}" :: "r"(a), "r"(v), "r"(bar), "r"((int)p) : "memory"); }
__device__ __forceinline__ void sta2(uint32_t a, uint32_t v0, uint32_t v1, uint32_t bar) { asm volatile("st.async.weak.shared::cluster.mbarrier::complete_tx::bytes.v2.b32 [%0], {%1,%2}, [%3];" :: "r"(a), "r"(v0), "r"(v1), "r"(bar) : "memory"); }
__device__ __forceinline__ void sta4(uint32_t a, uint32_t v0, uint32_t v1, uint32_t v2, uint32_t v3, uint32_t bar) { asm volatile("st.async.weak.shared::cluster.mbarrier::complete_tx::bytes.v4.b32 [%0], {%1,%2,%3,%4}, [%5];" :: "r"(a), "r"(v0), "r"(v1), "r"(v2), "r"(v3), "r"(bar) : "memory"); }
__device__ __forceinline__ float bflo(uint32_t v) { return __uint_as_float(v << 16); }
__device__ __forceinline__ float bfhi(uint32_t v) { return __uint_as_float(v & 0xFFFF0000u); }
__device__ __forceinline__ void sta2f(uint32_t a, float v0, float v1, uint32_t bar) { asm volatile("st.async.weak.shared::cluster.mbarrier::complete_tx::bytes.v2.f32 [%0], {%1,%2}, [%3];" :: "r"(a), "f"(v0), "f"(v1), "r"(bar) : "memory"); }
__device__ __forceinline__ void sta4f(uint32_t a, float v0, float v1, float v2, float v3, uint32_t bar) { asm volatile("st.async.weak.shared::cluster.mbarrier::complete_tx::bytes.v4.f32 [%0], {%1,%2,%3,%4}, [%5];" :: "r"(a), "f"(v0), "f"(v1), "f"(v2), "f"(v3), "r"(bar) : "memory"); }
__device__ __forceinline__ float4 lds4f(uint32_t a) { float4 v; asm volatile("ld.shared.v4.f32 {%0,%1,%2,%3}, [%4];" : "=f"(v.x), "=f"(v.y), "=f"(v.z), "=f"(v.w) : "r"(a) : "memory"); return v; }
__device__ __forceinline__ float2 lds2f(uint32_t a) { float2 v; asm volatile("ld.shared.v2.f32 {%0,%1}, [%2];" : "=f"(v.x), "=f"(v.y) : "r"(a) : "memory"); return v; }
__device__ __forceinline__ uint4 lds4(uint32_t a) { uint4 v; asm volatile("ld.shared.v4.u32 {%0,%1,%2,%3}, [%4];" : "=r"(v.x), "=r"(v.y), "=r"(v.z), "=r"(v.w) : "r"(a) : "memory"); return v; }
__device__ __forceinline__ uint32_t lds1(uint32_t a) { uint32_t v; asm volatile("ld.shared.u32 %0, [%1];" : "=r"(v) : "r"(a) : "memory"); return v; }
__device__ __forceinline__ void stsm2(uint32_t a, uint32_t r0, uint32_t r1) { asm volatile("stmatrix.sync.aligned.m8n8.x2.shared.b16 [%0], {%1,%2};" :: "r"(a), "r"(r0), "r"(r1) : "memory"); }
__device__ __forceinline__ float rcp(float x) { float y; asm("rcp.approx.ftz.f32 %0, %1;" : "=f"(y) : "f"(x)); return y; }
__device__ __forceinline__ void sts4(uint32_t a, uint32_t v0, uint32_t v1, uint32_t v2, uint32_t v3) { asm volatile("st.shared.v4.u32 [%0], {%1,%2,%3,%4};" :: "r"(a), "r"(v0), "r"(v1), "r"(v2), "r"(v3) : "memory"); }
__device__ __forceinline__ void bulk_s2c(uint32_t dst, uint32_t src, uint32_t bytes, uint32_t bar) {
  asm volatile("cp.async.bulk.shared::cluster.shared::cta.mbarrier::complete_tx::bytes [%0], [%1], %2, [%3];" :: "r"(dst), "r"(src), "r"(bytes), "r"(bar) : "memory");
}
__device__ __forceinline__ void stg4(void* p, uint4 v) { asm volatile("st.global.v4.u32 [%0], {%1,%2,%3,%4};" :: "l"(p), "r"(v.x), "r"(v.y), "r"(v.z), "r"(v.w) : "memory"); }
__device__ __forceinline__ void red_add(uint32_t* p, uint32_t v) { asm volatile("red.relaxed.gpu.global.add.u32 [%0], %1;" :: "l"(p), "r"(v) : "memory"); }
__device__ __forceinline__ void red_release(uint32_t* p, uint32_t v) { asm volatile("red.release.gpu.global.add.u32 [%0], %1;" :: "l"(p), "r"(v) : "memory"); }
__device__ __forceinline__ void fence_async_global() { asm volatile("fence.proxy.async.global;" ::: "memory"); }
__device__ __forceinline__ uint64_t policy_evict_first() { uint64_t p; asm("createpolicy.fractional.L2::evict_first.b64 %0, 1.0;" : "=l"(p)); return p; }
__device__ __forceinline__ void stg4h(void* p, uint4 v, uint64_t pol) { asm volatile("st.global.L2::cache_hint.v4.u32 [%0], {%1,%2,%3,%4}, %5;" :: "l"(p), "r"(v.x), "r"(v.y), "r"(v.z), "r"(v.w), "l"(pol) : "memory"); }
__device__ __forceinline__ void red4fh(float* p, float a, float b, float c, float d, uint64_t pol) { asm volatile("red.relaxed.gpu.global.add.L2::cache_hint.v4.f32 [%0], {%1,%2,%3,%4}, %5;" :: "l"(p), "f"(a), "f"(b), "f"(c), "f"(d), "l"(pol) : "memory"); }
__device__ __forceinline__ float4 ldg4fh(const float* p, uint64_t pol) { float4 v; asm volatile("ld.global.cg.L2::cache_hint.v4.f32 {%0,%1,%2,%3}, [%4], %5;" : "=f"(v.x), "=f"(v.y), "=f"(v.z), "=f"(v.w) : "l"(p), "l"(pol) : "memory"); return v; }
__device__ __forceinline__ void bulk_g2sh(uint32_t dst, const void* src, uint32_t bytes, uint32_t bar, uint64_t pol) {
  asm volatile("cp.async.bulk.shared::cluster.global.mbarrier::complete_tx::bytes.L2::cache_hint [%0], [%1], %2, [%3], %4;" :: "r"(dst), "l"(src), "r"(bytes), "r"(bar), "l"(pol) : "memory");
}
#define EVF 1
__device__ __forceinline__ void red4f(float* p, float a, float b, float c, float d) { asm volatile("red.relaxed.gpu.global.add.v4.f32 [%0], {%1,%2,%3,%4};" :: "l"(p), "f"(a), "f"(b), "f"(c), "f"(d) : "memory"); }
template <int SLEEP = 20>
__device__ __forceinline__ void wait_flag(const uint32_t* p, uint32_t target) {
  uint32_t v; int it = 0;
  while (true) {
    asm volatile("ld.acquire.gpu.global.u32 %0, [%1];" : "=r"(v) : "l"(p) : "memory");
    if (__all_sync(~0u, v >= target)) break;
    if (++it > 4000000) __trap();
    __nanosleep(SLEEP);
  }
}
__device__ __forceinline__ void sts2(uint32_t a, uint32_t v0, uint32_t v1) { asm volatile("st.shared.v2.u32 [%0], {%1,%2};" :: "r"(a), "r"(v0), "r"(v1) : "memory"); }
__device__ __forceinline__ float sqrt_approx(float x) { float y; asm("sqrt.approx.f32 %0, %1;" : "=f"(y) : "f"(x)); return y; }
template <int BYTES> __device__ __forceinline__ void bulk_s2c_elect(uint32_t d1, uint32_t b1, uint32_t d2, uint32_t b2, uint32_t src) {
  asm volatile("{\n.reg .pred p;\nelect.sync _|p, 0xffffffff;\n"
               "@p cp.async.bulk.shared::cluster.shared::cta.mbarrier::complete_tx::bytes [%0], [%4], %5, [%1];\n"
               "@p cp.async.bulk.shared::cluster.shared::cta.mbarrier::complete_tx::bytes [%2], [%4], %5, [%3];\n}"
               :: "r"(d1), "r"(b1), "r"(d2), "r"(b2), "r"(src), "n"(BYTES) : "memory");
}
__device__ __forceinline__ void mbar_arrive_elect(uint32_t bar) { asm volatile("{\n.reg .pred p;\nelect.sync _|p, 0xffffffff;\n@p mbarrier.arrive.shared::cta.b64 _, [%0];\n}" :: "r"(bar) : "memory"); }
__device__ __forceinline__ void cp16(uint32_t dst, const void* src) { asm volatile("cp.async.cg.shared.global [%0], [%1], 16;" :: "r"(dst), "l"(src) : "memory"); }
__device__ __forceinline__ void sts1(uint32_t a, uint32_t v) { asm volatile("st.shared.u32 [%0], %1;" :: "r"(a), "r"(v) : "memory"); }
__device__ __forceinline__ void bulk_g2s(uint32_t dst, const void* src, uint32_t bytes, uint32_t bar) {
  asm volatile("cp.async.bulk.shared::cluster.global.mbarrier::complete_tx::bytes [%0], [%1], %2, [%3];" :: "r"(dst), "l"(src), "r"(bytes), "r"(bar) : "memory");
}
__device__ __forceinline__ void bulk_g2s_mc(uint32_t dst, const void* src, uint32_t bytes, uint32_t bar) {
  asm volatile("cp.async.bulk.shared::cluster.global.mbarrier::complete_tx::bytes.multicast::cluster [%0], [%1], %2, [%3], %4;" :: "r"(dst), "l"(src), "r"(bytes), "r"(bar), "h"((uint16_t)3) : "memory");
}
__device__ __forceinline__ void mbar_arrive_cl(uint32_t bar) { asm volatile("mbarrier.arrive.shared::cluster.b64 _, [%0];" :: "r"(bar) : "memory"); }
__device__ __forceinline__ void tma2d(uint32_t dst, const CUtensorMap* m, int c0, int c1, uint32_t bar) {
  asm volatile("cp.async.bulk.tensor.2d.shared::cluster.global.mbarrier::complete_tx::bytes [%0], [%1, {%3, %4}], [%2];" :: "r"(dst), "l"((uint64_t)m), "r"(bar), "r"(c0), "r"(c1) : "memory");
}
__device__ __forceinline__ void tma5d(uint32_t dst, const CUtensorMap* m, int c0, int c4, uint32_t bar) {
  asm volatile("cp.async.bulk.tensor.5d.shared::cluster.global.mbarrier::complete_tx::bytes [%0], [%1, {%3, %5, %5, %5, %4}], [%2];" :: "r"(dst), "l"((uint64_t)m), "r"(bar), "r"(c0), "r"(c4), "r"(0) : "memory");
}
__device__ __forceinline__ void red64(void* p, uint32_t lo, uint32_t hi) { asm volatile("{\n.reg .b64 t;\nmov.b64 t, {%1,%2};\nred.relaxed.gpu.global.add.u64 [%0], t;\n}" :: "l"(p), "r"(lo), "r"(hi) : "memory"); }
__device__ __forceinline__ uint4 ld_poll(const void* p) {
  uint4 v;
  asm volatile("{\n.reg .b64 a, b;\nld.relaxed.gpu.global.v2.b64 {a, b}, [%4];\nmov.b64 {%0,%1}, a;\nmov.b64 {%2,%3}, b;\n}" : "=r"(v.x), "=r"(v.y), "=r"(v.z), "=r"(v.w) : "l"(p) : "memory");
  return v;
}
__device__ __forceinline__ uint32_t clk() { uint32_t c; asm volatile("mov.u32 %0, %%clock;" : "=r"(c) :: "memory"); return c; }
#define SCHED_FENCE() asm volatile("pmevent 0;" ::: "memory")
__device__ __forceinline__ float ex2(float x) { float y; asm("ex2.approx.ftz.f32 %0, %1;" : "=f"(y) : "f"(x)); return y; }

__device__ __forceinline__ void wg_ss_n240_ta0_tb1(float* d, uint64_t a, uint64_t b, int sc) {
  asm volatile("{\n.reg .pred p;\nsetp.ne.b32 p, %122, 0;\nwgmma.mma_async.sync.aligned.m64n240k16.f32.bf16.bf16 {%0, %1, %2, %3, %4, %5, %6, %7, %8, %9, %10, %11, %12, %13, %14, %15, %16, %17, %18, %19, %20, %21, %22, %23, %24, %25, %26, %27, %28, %29, %30, %31, %32, %33, %34, %35, %36, %37, %38, %39, %40, %41, %42, %43, %44, %45, %46, %47, %48, %49, %50, %51, %52, %53, %54, %55, %56, %57, %58, %59, %60, %61, %62, %63, %64, %65, %66, %67, %68, %69, %70, %71, %72, %73, %74, %75, %76, %77, %78, %79, %80, %81, %82, %83, %84, %85, %86, %87, %88, %89, %90, %91, %92, %93, %94, %95, %96, %97, %98, %99, %100, %101, %102, %103, %104, %105, %106, %107, %108, %109, %110, %111, %112, %113, %114, %115, %116, %117, %118, %119}, %120, %121, p, 1, 1, 0, 1;\n}\n"
    : "+f"(d[0]), "+f"(d[1]), "+f"(d[2]), "+f"(d[3]), "+f"(d[4]), "+f"(d[5]), "+f"(d[6]), "+f"(d[7]), "+f"(d[8]), "+f"(d[9]), "+f"(d[10]), "+f"(d[11]), "+f"(d[12]), "+f"(d[13]), "+f"(d[14]), "+f"(d[15]), "+f"(d[16]), "+f"(d[17]), "+f"(d[18]), "+f"(d[19]), "+f"(d[20]), "+f"(d[21]), "+f"(d[22]), "+f"(d[23]), "+f"(d[24]), "+f"(d[25]), "+f"(d[26]), "+f"(d[27]), "+f"(d[28]), "+f"(d[29]), "+f"(d[30]), "+f"(d[31]), "+f"(d[32]), "+f"(d[33]), "+f"(d[34]), "+f"(d[35]), "+f"(d[36]), "+f"(d[37]), "+f"(d[38]), "+f"(d[39]), "+f"(d[40]), "+f"(d[41]), "+f"(d[42]), "+f"(d[43]), "+f"(d[44]), "+f"(d[45]), "+f"(d[46]), "+f"(d[47]), "+f"(d[48]), "+f"(d[49]), "+f"(d[50]), "+f"(d[51]), "+f"(d[52]), "+f"(d[53]), "+f"(d[54]), "+f"(d[55]), "+f"(d[56]), "+f"(d[57]), "+f"(d[58]), "+f"(d[59]), "+f"(d[60]), "+f"(d[61]), "+f"(d[62]), "+f"(d[63]), "+f"(d[64]), "+f"(d[65]), "+f"(d[66]), "+f"(d[67]), "+f"(d[68]), "+f"(d[69]), "+f"(d[70]), "+f"(d[71]), "+f"(d[72]), "+f"(d[73]), "+f"(d[74]), "+f"(d[75]), "+f"(d[76]), "+f"(d[77]), "+f"(d[78]), "+f"(d[79]), "+f"(d[80]), "+f"(d[81]), "+f"(d[82]), "+f"(d[83]), "+f"(d[84]), "+f"(d[85]), "+f"(d[86]), "+f"(d[87]), "+f"(d[88]), "+f"(d[89]), "+f"(d[90]), "+f"(d[91]), "+f"(d[92]), "+f"(d[93]), "+f"(d[94]), "+f"(d[95]), "+f"(d[96]), "+f"(d[97]), "+f"(d[98]), "+f"(d[99]), "+f"(d[100]), "+f"(d[101]), "+f"(d[102]), "+f"(d[103]), "+f"(d[104]), "+f"(d[105]), "+f"(d[106]), "+f"(d[107]), "+f"(d[108]), "+f"(d[109]), "+f"(d[110]), "+f"(d[111]), "+f"(d[112]), "+f"(d[113]), "+f"(d[114]), "+f"(d[115]), "+f"(d[116]), "+f"(d[117]), "+f"(d[118]), "+f"(d[119])
    : "l"(a), "l"(b), "r"(sc));
}
__device__ __forceinline__ void wg_ss_n88_ta1_tb1(float* d, uint64_t a, uint64_t b, int sc) {
  asm volatile("{\n.reg .pred p;\nsetp.ne.b32 p, %46, 0;\nwgmma.mma_async.sync.aligned.m64n88k16.f32.bf16.bf16 {%0, %1, %2, %3, %4, %5, %6, %7, %8, %9, %10, %11, %12, %13, %14, %15, %16, %17, %18, %19, %20, %21, %22, %23, %24, %25, %26, %27, %28, %29, %30, %31, %32, %33, %34, %35, %36, %37, %38, %39, %40, %41, %42, %43}, %44, %45, p, 1, 1, 1, 1;\n}\n"
    : "+f"(d[0]), "+f"(d[1]), "+f"(d[2]), "+f"(d[3]), "+f"(d[4]), "+f"(d[5]), "+f"(d[6]), "+f"(d[7]), "+f"(d[8]), "+f"(d[9]), "+f"(d[10]), "+f"(d[11]), "+f"(d[12]), "+f"(d[13]), "+f"(d[14]), "+f"(d[15]), "+f"(d[16]), "+f"(d[17]), "+f"(d[18]), "+f"(d[19]), "+f"(d[20]), "+f"(d[21]), "+f"(d[22]), "+f"(d[23]), "+f"(d[24]), "+f"(d[25]), "+f"(d[26]), "+f"(d[27]), "+f"(d[28]), "+f"(d[29]), "+f"(d[30]), "+f"(d[31]), "+f"(d[32]), "+f"(d[33]), "+f"(d[34]), "+f"(d[35]), "+f"(d[36]), "+f"(d[37]), "+f"(d[38]), "+f"(d[39]), "+f"(d[40]), "+f"(d[41]), "+f"(d[42]), "+f"(d[43])
    : "l"(a), "l"(b), "r"(sc));
}
__device__ __forceinline__ void wg_rs_n160_tb1(float* d, const uint32_t* a, uint64_t b, int sc) {
  asm volatile("{\n.reg .pred p;\nsetp.ne.b32 p, %85, 0;\nwgmma.mma_async.sync.aligned.m64n160k16.f32.bf16.bf16 {%0, %1, %2, %3, %4, %5, %6, %7, %8, %9, %10, %11, %12, %13, %14, %15, %16, %17, %18, %19, %20, %21, %22, %23, %24, %25, %26, %27, %28, %29, %30, %31, %32, %33, %34, %35, %36, %37, %38, %39, %40, %41, %42, %43, %44, %45, %46, %47, %48, %49, %50, %51, %52, %53, %54, %55, %56, %57, %58, %59, %60, %61, %62, %63, %64, %65, %66, %67, %68, %69, %70, %71, %72, %73, %74, %75, %76, %77, %78, %79}, {%80, %81, %82, %83}, %84, p, 1, 1, 1;\n}\n"
    : "+f"(d[0]), "+f"(d[1]), "+f"(d[2]), "+f"(d[3]), "+f"(d[4]), "+f"(d[5]), "+f"(d[6]), "+f"(d[7]), "+f"(d[8]), "+f"(d[9]), "+f"(d[10]), "+f"(d[11]), "+f"(d[12]), "+f"(d[13]), "+f"(d[14]), "+f"(d[15]), "+f"(d[16]), "+f"(d[17]), "+f"(d[18]), "+f"(d[19]), "+f"(d[20]), "+f"(d[21]), "+f"(d[22]), "+f"(d[23]), "+f"(d[24]), "+f"(d[25]), "+f"(d[26]), "+f"(d[27]), "+f"(d[28]), "+f"(d[29]), "+f"(d[30]), "+f"(d[31]), "+f"(d[32]), "+f"(d[33]), "+f"(d[34]), "+f"(d[35]), "+f"(d[36]), "+f"(d[37]), "+f"(d[38]), "+f"(d[39]), "+f"(d[40]), "+f"(d[41]), "+f"(d[42]), "+f"(d[43]), "+f"(d[44]), "+f"(d[45]), "+f"(d[46]), "+f"(d[47]), "+f"(d[48]), "+f"(d[49]), "+f"(d[50]), "+f"(d[51]), "+f"(d[52]), "+f"(d[53]), "+f"(d[54]), "+f"(d[55]), "+f"(d[56]), "+f"(d[57]), "+f"(d[58]), "+f"(d[59]), "+f"(d[60]), "+f"(d[61]), "+f"(d[62]), "+f"(d[63]), "+f"(d[64]), "+f"(d[65]), "+f"(d[66]), "+f"(d[67]), "+f"(d[68]), "+f"(d[69]), "+f"(d[70]), "+f"(d[71]), "+f"(d[72]), "+f"(d[73]), "+f"(d[74]), "+f"(d[75]), "+f"(d[76]), "+f"(d[77]), "+f"(d[78]), "+f"(d[79])
    : "r"(a[0]), "r"(a[1]), "r"(a[2]), "r"(a[3]), "l"(b), "r"(sc));
}
__device__ __forceinline__ void wg_ss_n112_ta0_tb1(float* d, uint64_t a, uint64_t b, int sc) {
  asm volatile("{\n.reg .pred p;\nsetp.ne.b32 p, %58, 0;\nwgmma.mma_async.sync.aligned.m64n112k16.f32.bf16.bf16 {%0, %1, %2, %3, %4, %5, %6, %7, %8, %9, %10, %11, %12, %13, %14, %15, %16, %17, %18, %19, %20, %21, %22, %23, %24, %25, %26, %27, %28, %29, %30, %31, %32, %33, %34, %35, %36, %37, %38, %39, %40, %41, %42, %43, %44, %45, %46, %47, %48, %49, %50, %51, %52, %53, %54, %55}, %56, %57, p, 1, 1, 0, 1;\n}\n"
    : "+f"(d[0]), "+f"(d[1]), "+f"(d[2]), "+f"(d[3]), "+f"(d[4]), "+f"(d[5]), "+f"(d[6]), "+f"(d[7]), "+f"(d[8]), "+f"(d[9]), "+f"(d[10]), "+f"(d[11]), "+f"(d[12]), "+f"(d[13]), "+f"(d[14]), "+f"(d[15]), "+f"(d[16]), "+f"(d[17]), "+f"(d[18]), "+f"(d[19]), "+f"(d[20]), "+f"(d[21]), "+f"(d[22]), "+f"(d[23]), "+f"(d[24]), "+f"(d[25]), "+f"(d[26]), "+f"(d[27]), "+f"(d[28]), "+f"(d[29]), "+f"(d[30]), "+f"(d[31]), "+f"(d[32]), "+f"(d[33]), "+f"(d[34]), "+f"(d[35]), "+f"(d[36]), "+f"(d[37]), "+f"(d[38]), "+f"(d[39]), "+f"(d[40]), "+f"(d[41]), "+f"(d[42]), "+f"(d[43]), "+f"(d[44]), "+f"(d[45]), "+f"(d[46]), "+f"(d[47]), "+f"(d[48]), "+f"(d[49]), "+f"(d[50]), "+f"(d[51]), "+f"(d[52]), "+f"(d[53]), "+f"(d[54]), "+f"(d[55])
    : "l"(a), "l"(b), "r"(sc));
}
__device__ __forceinline__ void wg_rs_n32_tb1(float* d, const uint32_t* a, uint64_t b, int sc) {
  asm volatile("{\n.reg .pred p;\nsetp.ne.b32 p, %21, 0;\nwgmma.mma_async.sync.aligned.m64n32k16.f32.bf16.bf16 {%0, %1, %2, %3, %4, %5, %6, %7, %8, %9, %10, %11, %12, %13, %14, %15}, {%16, %17, %18, %19}, %20, p, 1, 1, 1;\n}\n"
    : "+f"(d[0]), "+f"(d[1]), "+f"(d[2]), "+f"(d[3]), "+f"(d[4]), "+f"(d[5]), "+f"(d[6]), "+f"(d[7]), "+f"(d[8]), "+f"(d[9]), "+f"(d[10]), "+f"(d[11]), "+f"(d[12]), "+f"(d[13]), "+f"(d[14]), "+f"(d[15])
    : "r"(a[0]), "r"(a[1]), "r"(a[2]), "r"(a[3]), "l"(b), "r"(sc));
}
__device__ __forceinline__ void wg_ss_n32_ta1_tb1(float* d, uint64_t a, uint64_t b, int sc) {
  asm volatile("{\n.reg .pred p;\nsetp.ne.b32 p, %18, 0;\nwgmma.mma_async.sync.aligned.m64n32k16.f32.bf16.bf16 {%0, %1, %2, %3, %4, %5, %6, %7, %8, %9, %10, %11, %12, %13, %14, %15}, %16, %17, p, 1, 1, 1, 1;\n}\n"
    : "+f"(d[0]), "+f"(d[1]), "+f"(d[2]), "+f"(d[3]), "+f"(d[4]), "+f"(d[5]), "+f"(d[6]), "+f"(d[7]), "+f"(d[8]), "+f"(d[9]), "+f"(d[10]), "+f"(d[11]), "+f"(d[12]), "+f"(d[13]), "+f"(d[14]), "+f"(d[15])
    : "l"(a), "l"(b), "r"(sc));
}
__device__ __forceinline__ void wg_rs_n32_tb0(float* d, const uint32_t* a, uint64_t b, int sc) {
  asm volatile("{\n.reg .pred p;\nsetp.ne.b32 p, %21, 0;\nwgmma.mma_async.sync.aligned.m64n32k16.f32.bf16.bf16 {%0, %1, %2, %3, %4, %5, %6, %7, %8, %9, %10, %11, %12, %13, %14, %15}, {%16, %17, %18, %19}, %20, p, 1, 1, 0;\n}\n"
    : "+f"(d[0]), "+f"(d[1]), "+f"(d[2]), "+f"(d[3]), "+f"(d[4]), "+f"(d[5]), "+f"(d[6]), "+f"(d[7]), "+f"(d[8]), "+f"(d[9]), "+f"(d[10]), "+f"(d[11]), "+f"(d[12]), "+f"(d[13]), "+f"(d[14]), "+f"(d[15])
    : "r"(a[0]), "r"(a[1]), "r"(a[2]), "r"(a[3]), "l"(b), "r"(sc));
}
__device__ __forceinline__ void wg_rs_n40_tb0(float* d, const uint32_t* a, uint64_t b, int sc) {
  asm volatile("{\n.reg .pred p;\nsetp.ne.b32 p, %25, 0;\nwgmma.mma_async.sync.aligned.m64n40k16.f32.bf16.bf16 {%0, %1, %2, %3, %4, %5, %6, %7, %8, %9, %10, %11, %12, %13, %14, %15, %16, %17, %18, %19}, {%20, %21, %22, %23}, %24, p, 1, 1, 0;\n}\n"
    : "+f"(d[0]), "+f"(d[1]), "+f"(d[2]), "+f"(d[3]), "+f"(d[4]), "+f"(d[5]), "+f"(d[6]), "+f"(d[7]), "+f"(d[8]), "+f"(d[9]), "+f"(d[10]), "+f"(d[11]), "+f"(d[12]), "+f"(d[13]), "+f"(d[14]), "+f"(d[15]), "+f"(d[16]), "+f"(d[17]), "+f"(d[18]), "+f"(d[19])
    : "r"(a[0]), "r"(a[1]), "r"(a[2]), "r"(a[3]), "l"(b), "r"(sc));
}
__device__ __forceinline__ void wg_rs_n8_tb1(float* d, const uint32_t* a, uint64_t b, int sc) {
  asm volatile("{\n.reg .pred p;\nsetp.ne.b32 p, %9, 0;\nwgmma.mma_async.sync.aligned.m64n8k16.f32.bf16.bf16 {%0, %1, %2, %3}, {%4, %5, %6, %7}, %8, p, 1, 1, 1;\n}\n"
    : "+f"(d[0]), "+f"(d[1]), "+f"(d[2]), "+f"(d[3])
    : "r"(a[0]), "r"(a[1]), "r"(a[2]), "r"(a[3]), "l"(b), "r"(sc));
}
__device__ __forceinline__ void wg_ss_n40_ta0_tb0(float* d, uint64_t a, uint64_t b, int sc) {
  asm volatile("{\n.reg .pred p;\nsetp.ne.b32 p, %22, 0;\nwgmma.mma_async.sync.aligned.m64n40k16.f32.bf16.bf16 {%0, %1, %2, %3, %4, %5, %6, %7, %8, %9, %10, %11, %12, %13, %14, %15, %16, %17, %18, %19}, %20, %21, p, 1, 1, 0, 0;\n}\n"
    : "+f"(d[0]), "+f"(d[1]), "+f"(d[2]), "+f"(d[3]), "+f"(d[4]), "+f"(d[5]), "+f"(d[6]), "+f"(d[7]), "+f"(d[8]), "+f"(d[9]), "+f"(d[10]), "+f"(d[11]), "+f"(d[12]), "+f"(d[13]), "+f"(d[14]), "+f"(d[15]), "+f"(d[16]), "+f"(d[17]), "+f"(d[18]), "+f"(d[19])
    : "l"(a), "l"(b), "r"(sc));
}
__device__ __forceinline__ void wg_ss_n40_ta1_tb0(float* d, uint64_t a, uint64_t b, int sc) {
  asm volatile("{\n.reg .pred p;\nsetp.ne.b32 p, %22, 0;\nwgmma.mma_async.sync.aligned.m64n40k16.f32.bf16.bf16 {%0, %1, %2, %3, %4, %5, %6, %7, %8, %9, %10, %11, %12, %13, %14, %15, %16, %17, %18, %19}, %20, %21, p, 1, 1, 1, 0;\n}\n"
    : "+f"(d[0]), "+f"(d[1]), "+f"(d[2]), "+f"(d[3]), "+f"(d[4]), "+f"(d[5]), "+f"(d[6]), "+f"(d[7]), "+f"(d[8]), "+f"(d[9]), "+f"(d[10]), "+f"(d[11]), "+f"(d[12]), "+f"(d[13]), "+f"(d[14]), "+f"(d[15]), "+f"(d[16]), "+f"(d[17]), "+f"(d[18]), "+f"(d[19])
    : "l"(a), "l"(b), "r"(sc));
}
__device__ __forceinline__ void wg_ss_n8_ta1_tb1(float* d, uint64_t a, uint64_t b, int sc) {
  asm volatile("{\n.reg .pred p;\nsetp.ne.b32 p, %6, 0;\nwgmma.mma_async.sync.aligned.m64n8k16.f32.bf16.bf16 {%0, %1, %2, %3}, %4, %5, p, 1, 1, 1, 1;\n}\n"
    : "+f"(d[0]), "+f"(d[1]), "+f"(d[2]), "+f"(d[3])
    : "l"(a), "l"(b), "r"(sc));
}

constexpr int O_WV = 0, O_WO = 81920, O_H = 163840, O_QK = 215040, O_SM = 228352, O_MISC = 230400;
constexpr int O_QM = O_QK + 1024, O_K = O_QK + 3072, O_OG = O_QK + 8192;
#define W0X 0
constexpr int SM_SLOT = W0X ? 1024 : 640;
constexpr int O_MAXS = O_MISC;
constexpr int O_BAR = O_MISC + 64;
constexpr int MB_XF = 0, MB_ML = 2, MB_MR = 3, MB_PF = 4, MB_SM = 5, MB_SX = 6, MB_OG = 7, MB_W = 10, MB_WC = 30;
constexpr int O_PROF = O_BAR + 8 * 40;
constexpr int REC_SMEM = O_PROF + 128;
constexpr int B_VOWN = 0, B_QK = 1, B_VGO = 2, B_SISS = 3, B_PM = 4, B_PX = 5, B_XGO = 6, B_ML = 7, B_WG2 = 8, B_VHALF = 9, B_VDONE = 10,
              B_MR = 11, B_SSENT = 12, B_SLD = 13, B_VEND = 14, B_XGO1 = 15;
#define TS0(idx) do {} while (0)
#define TS(idx) do {} while (0)
#define POLL_9 300
#define POLL_A 400
#define POLL_B 500
#define POLL_C 600
#define W_WIN 4
#define W_OPEN 16
#define V_OWN 4
#define V_S1 9
#define V_RS 3
#define V_S2 3
#define V_B 4
#define V_N1 0
#define SISS_K 3
#define V_K1 (V_OWN + V_RS + V_B + V_S1)
#define V_K2 ((V_K1 > 20 ? V_K1 : 20) + V_S2)
#define O_RSM 0x2AA0
#define FV 0
#define FP 1
#define O_B1 5
#define O_RS __builtin_popcount(O_RSM)
#define O_IDX(j) __builtin_popcount(O_RSM & ((1 << (j)) - 1))
constexpr float SCL = 0.07216878364870322f;
constexpr float SL2 = SCL * 1.4426950408889634f;
__device__ __forceinline__ constexpr int vord(int i) { return i < 4 ? 36 + i : i - 4; }
__device__ __forceinline__ constexpr uint32_t hoff(int k) { return ((k >> 2) * 5120 + (k & 3) * 32) >> 4; }
__device__ __forceinline__ constexpr int ar_chunk(int T) { return T == 9 ? 19 : (T % 3) * 8 + T / 3; }
__device__ __forceinline__ void fix_red(uint8_t* p, const float* a, float2 sc) {
  int v0 = __float2int_rn(a[0] * sc.x), v1 = __float2int_rn(a[1] * sc.y), v2 = __float2int_rn(a[2] * sc.x), v3 = __float2int_rn(a[3] * sc.y);
  red64(p, ((uint32_t)v0 << 7) | 1u, ((uint32_t)v2 << 3) + (uint32_t)(v0 >> 25));
  red64(p + 1024, ((uint32_t)v1 << 7) | 1u, ((uint32_t)v3 << 3) + (uint32_t)(v1 >> 25));
}
__device__ __forceinline__ float exp_row(float* t) {
  const float ml = fmaxf(fmaxf(fmaxf(fmaxf(t[0], t[1]), fmaxf(t[2], t[3])), fmaxf(fmaxf(t[4], t[5]), fmaxf(t[6], t[7]))), fmaxf(t[8], t[9]));
  const float m1 = __shfl_xor_sync(~0u, ml, 1), m2 = __shfl_xor_sync(~0u, ml, 2), m3 = __shfl_xor_sync(~0u, ml, 3);
  SCHED_FENCE();
#pragma unroll
  for (int k = 0; k < 10; k++) t[k] = ex2((t[k] - ml) * SL2);
  pin<10>(t);
  SCHED_FENCE();
  return ex2((ml - fmaxf(fmaxf(ml, m1), fmaxf(m2, m3))) * SL2);
}
#define ACC3(k, u, v) { t[k] += bflo(u) + bflo(v); t[k + 1] += bfhi(u) + bfhi(v); }

#define LBT 0
#define NLB 2
constexpr int LB_STAGE = 36864, LB_ST = 6 * LB_STAGE;
__device__ __forceinline__ void lb_role(const uint32_t sb, const CUtensorMap* tmx, uint32_t* __restrict__ flags, int layer) {
  const int tid = threadIdx.x, wid = __shfl_sync(~0u, tid >> 5, 0), wg = wid >> 2, w = wid & 3, lane = tid & 31, g = lane >> 2, i4 = lane & 3;
  const int cl = blockIdx.x / 3, rank = blockIdx.x - cl * 3;
  const uint32_t bar = sb + O_BAR;
  asm volatile("griddepcontrol.launch_dependents;");
  if (wid == 8) {
    if (lane < 14) mbar_init(bar + 8 * lane, lane >= 6 && lane < 12 ? 8 : 1);
    asm volatile("fence.mbarrier_init.release.cluster;" ::: "memory");
    fence_async();
  }
  __syncthreads();
  asm volatile("barrier.cluster.arrive.relaxed.aligned;" ::: "memory");
  if (wid == 8) {
    int st = 0; uint32_t ph = 1;
    const uint8_t* wsrc = g_w2 + rank * 286720;
    if (lane < 6) { mbar_expect(bar + 8 * lane, LB_STAGE); bulk_g2s(sb + lane * LB_STAGE + 8192, wsrc + lane * 28672, 28672, bar + 8 * lane); }
    if (layer == 1) wait_flag(flags + FL_R, 6);
#pragma unroll 1
    for (int tile = cl; tile < 32; tile += NLB) {
      wait_flag(flags + FL_O + (tile >> 1) * 8, 8);
      if (tile == cl + LBT * NLB && lane == 0) GTT(layer * 4 + 1, 11);
      fence_async_global();
#pragma unroll 1
      for (int kc = 0; kc < 10; kc++) {
        const bool pre = tile == cl && kc < 6;
        mbar_wait(bar + 8 * (6 + st), ph);
        if (lane == 0) {
          if (!pre) { mbar_expect(bar + 8 * st, LB_STAGE); bulk_g2s(sb + st * LB_STAGE + 8192, wsrc + kc * 28672, 28672, bar + 8 * st); }
          bulk_g2s(sb + st * LB_STAGE, g_oa + tile * 81920 + kc * 8192, 8192, bar + 8 * st);
        }
        __syncwarp();
        if (++st == 6) { st = 0; ph ^= 1; }
      }
      mbar_wait(bar + 8 * (6 + st), ph);
      if (lane == 0) { mbar_expect(bar + 8 * st, 64 * 464); tma2d(sb + st * LB_STAGE, tmx, rank * 224, tile * 64, bar + 8 * st); }
      __syncwarp();
      if (++st == 6) { st = 0; ph ^= 1; }
    }
    asm volatile("barrier.cluster.wait.aligned;" ::: "memory");
  } else if (wg < 2) {
    asm volatile("barrier.cluster.wait.aligned;" ::: "memory");
    const int u = 2 * rank + wg, nb = u == 5 ? 5 : 7;
    int st = 0; uint32_t ph = 0, it = 0;
#pragma unroll 1
    for (int tile = cl; tile < 32; tile += NLB, it++) {
      const int row0 = tile * 64 + 16 * w + g;
      float d[56];
      if (tid == 0) mbar_expect(bar + 8 * (12 + (it & 1)), 3072);
#pragma unroll 1
      for (int kc = 0; kc < 10; kc++) {
        const uint64_t da = mkdesc(SB0 + st * LB_STAGE, 1024, 128, 0), db = mkdesc(SB0 + st * LB_STAGE + 8192 + wg * 1792, 3584, 128, 0);
        mbar_wait(bar + 8 * st, ph);
        if (it == LBT && kc == 0) GT(layer * 4 + 1, 12);
        wg_fence();
#pragma unroll
        for (int k = 0; k < 4; k++) wg_ss_n112_ta0_tb1(d, da + k * 128, db + k * 448, kc | k);
        wg_commit();
        wg_wait<1>();
        if (kc > 0 && lane == 0) mbar_arrive(bar + 8 * (6 + (st == 0 ? 5 : st - 1)));
        if (++st == 6) { st = 0; ph ^= 1; }
      }
      wg_wait<0>();
      pin<56>(d);
      if (it == LBT) GT(layer * 4 + 1, 13);
      if (lane == 0) mbar_arrive(bar + 8 * (6 + (st == 0 ? 5 : st - 1)));
      mbar_wait(bar + 8 * st, ph);
      {
        const uint32_t x0 = sb + st * LB_STAGE + (16 * w + g) * 464 + wg * 224 + (layer ? 8 : 4) * i4, x1 = x0 + (layer ? 4 : 16);
#pragma unroll
        for (int j = 0; j < 28; j++) {
          const uint32_t v = lds1(((j & 2) ? x1 : x0) + (j >> 2) * 32 + (j & 1) * 3712);
          d[2 * j] += bflo(v); d[2 * j + 1] += bfhi(v);
        }
      }
      fence_async();
      __syncwarp();
      if (lane == 0) mbar_arrive(bar + 8 * (6 + st));
      if (++st == 6) { st = 0; ph ^= 1; }
      const float cnt = nb * 16.f;
      const uint32_t so = LB_ST + (it & 1) * 3072 + (16 * w + g) * 48;
#pragma unroll
      for (int h = 0; h < 2; h++) {
        float sum = 0.f;
#pragma unroll
        for (int j = 0; j < 14; j++) sum += d[4 * j + 2 * h] + d[4 * j + 2 * h + 1];
        sum += __shfl_xor_sync(~0u, sum, 1); sum += __shfl_xor_sync(~0u, sum, 2);
        const float mean = sum * rcp(cnt);
        float q = 0.f, q2 = 0.f;
#pragma unroll
        for (int j = 0; j < 14; j++) {
          const float a = d[4 * j + 2 * h] - mean, b = d[4 * j + 2 * h + 1] - mean;
          if (j < 10) q = fmaf(a, a, fmaf(b, b, q)); else q2 = fmaf(a, a, fmaf(b, b, q2));
        }
        if (nb == 7) q += q2;
        q += __shfl_xor_sync(~0u, q, 1); q += __shfl_xor_sync(~0u, q, 2);
        if (i4 < 3) { const uint32_t b = mapa(sb, i4); sta2f(b + so + h * 384 + u * 8, sum, q, b + O_BAR + 8 * (12 + (it & 1))); }
      }
      mbar_wait(bar + 8 * (12 + (it & 1)), (it >> 1) & 1);
      if (it == LBT) GT(layer * 4 + 1, 14);
#pragma unroll
      for (int h = 0; h < 2; h++) {
        const float4 x = lds4f(sb + so + h * 384), y = lds4f(sb + so + h * 384 + 16), z = lds4f(sb + so + h * 384 + 32);
        const float mu = (((x.x + x.z) + (y.x + y.z)) + (z.x + z.z)) * (1.f / DM);
        const float e0 = x.x * (1.f / 112.f) - mu, e1 = x.z * (1.f / 112.f) - mu, e2 = y.x * (1.f / 112.f) - mu, e3 = y.z * (1.f / 112.f) - mu;
        const float e4 = z.x * (1.f / 112.f) - mu, e5 = z.z * (1.f / 80.f) - mu;
        const float q = (((x.y + x.w) + (y.y + y.w)) + (z.y + z.w)) + 112.f * ((e0 * e0 + e1 * e1) + (e2 * e2 + e3 * e3) + e4 * e4) + 80.f * e5 * e5;
        const float rs = rsqrtf(q * (1.f / DM) + 1e-5f), sh = -mu * rs;
        const int tk = row0 + 8 * h;
        uint8_t* xp = g_xn + (tk >> 5) * 40960 + (tk & 31) * 128 + (i4 & 1) * 8;
#pragma unroll
        for (int j = 0; j < 7; j++) {
          if (j < nb) {
            const int b16 = u * 7 + j;
            const float* a = d + 8 * j + 2 * h;
            *(uint2*)(xp + (b16 >> 2) * 4096 + (((2 * (b16 & 3) + (i4 >> 1)) ^ g) << 4)) =
                make_uint2(pack2(fmaf(a[0], rs, sh), fmaf(a[1], rs, sh)), pack2(fmaf(a[4], rs, sh), fmaf(a[5], rs, sh)));
          }
        }
      }
      if (it == LBT) GT(layer * 4 + 1, 15);
      bar_arrive<1, 288>();
      bar_sync<2, 288>();
#pragma unroll
      for (int j = 0; j < 14; j++) {
        const float* a = d + 8 * (j >> 1) + 2 * (j & 1);
        if ((j >> 1) < nb) *(uint2*)(g_x + (row0 + 8 * (j & 1)) * DM + u * 112 + 4 * i4 + 16 * (j >> 1)) = make_uint2(pack2(a[0], a[1]), pack2(a[4], a[5]));
      }
      bar_arrive<3, 288>();
    }
  } else {
    asm volatile("barrier.cluster.wait.aligned;" ::: "memory");
    if (wid == 9) {
#pragma unroll 1
      for (int tile = cl; tile < 32; tile += NLB) {
        bar_sync<1, 288>();
        if (tile != cl) bar_arrive<2, 288>();
        if (lane == 0) { red_release(flags + FL_XN + tile * 8, 1); if (tile == cl + LBT * NLB) GTT(layer * 4 + 1, 9); }
        __syncwarp();
        if (tile == cl) bar_arrive<2, 288>();
        bar_sync<3, 288>();
        if (lane == 0) red_release(flags + FL_XN + tile * 8 + 1, 1);
        __syncwarp();
      }
    }
  }
  asm volatile("barrier.cluster.arrive.relaxed.aligned;\nbarrier.cluster.wait.aligned;" ::: "memory");
  GT(layer * 4 + 1, 10);
}

__global__ void __launch_bounds__(384, 1)
rec_kernel(const __grid_constant__ CUtensorMap tmq, const __grid_constant__ CUtensorMap tmk,
           const __grid_constant__ CUtensorMap tmv, const __grid_constant__ CUtensorMap tmo,
           const __grid_constant__ CUtensorMap tmx, const bf16* __restrict__ mem0, uint8_t* __restrict__ ar, uint32_t* __restrict__ flags, int layer) {
  extern __shared__ __align__(1024) uint8_t smem[];
  const uint32_t sb = smem_u32(smem);
  check_smem_base(sb);
  GT(layer * 4 + 1, 0);
  if (blockIdx.x < 3 * NLB) { lb_role(sb, &tmx, flags, layer); return; }
  const int bid = blockIdx.x - 3 * NLB;
  const int tid = threadIdx.x, wid = __shfl_sync(~0u, tid >> 5, 0), wg = wid >> 2, w = wid & 3;
  const int lane = __shfl_sync(~0u, tid & 31, tid & 31);
  const int head = bid / 3, rank = bid - head * 3;
  const int e0 = bid * 64;
  const uint32_t bar = sb + O_BAR;
  const uint32_t sb1 = mapa(sb, rank == 2 ? 0 : rank + 1), sb2 = mapa(sb, rank == 0 ? 2 : rank - 1);
  auto chunk_of = [&](int p) { const int c = 3 * rank + p; return p == 9 ? 9 : c >= 9 ? c - 9 : c; };

  auto load_piece = [&](int i) {
    if (lane == 0) mbar_expect(bar + 8 * (MB_W + i), 16384);
    __syncwarp();
    if (lane < 2) {
      if (i < 15) {
        const int m = i < 10 ? i & 1 : 0, p = (i < 10 ? i >> 1 : i - 10) * 2 + lane;
        tma5d(sb + m * 81920 + p * 8192, i >= 10 ? &tmv : m ? &tmk : &tmq, e0, chunk_of(p) * 4, bar + 8 * (MB_W + i));
      } else {
        const int p = (i - 15) * 2 + lane, k = p / 3, j = rank + p - 3 * k;
        tma2d(sb + O_WO + p * 8192, &tmo, p == 9 ? 576 : (rank * 3 + k) * 64, head * DH + (j >= 3 ? j - 3 : j) * 64, bar + 8 * (MB_W + i));
      }
    }
  };
  if (wid == 9) {
    mbar_init(bar + 8 * lane, (lane >= MB_WC || lane == MB_PF) ? 4 : 1);
    if (lane < 8) mbar_init(bar + 8 * (32 + lane), 4);
    asm volatile("fence.mbarrier_init.release.cluster;" ::: "memory");
    fence_async();
    __syncwarp();
#pragma unroll 1
    for (int i = 0; i < W_WIN; i++) load_piece(i);
  }
  __syncthreads();
  asm volatile("barrier.cluster.arrive.relaxed.aligned;" ::: "memory");

  if (wg < 2) {
    asm volatile("setmaxnreg.inc.sync.aligned.u32 208;");
    uint32_t a[40][4];
    const uint32_t swz = (lane & 7) * 128 + (((2 * w + ((lane >> 3) & 1)) ^ (lane & 7)) << 4);
    const uint32_t st_x = __shfl_sync(~0u, sb + O_QK + wg * 5120 + (lane >> 4) * 2048 + swz, lane);
    {
      const uint32_t la = sb + wg * 81920 + (lane >> 4) * 1024 + swz;
#pragma unroll
      for (int p = 0; p < 5; p++) {
        mbar_wait(bar + 8 * (MB_W + 2 * p + wg), 0);
#pragma unroll
        for (int k = 0; k < 8; k++) ldsm4t(a[p * 8 + k], la + (p * 8 + k) * 2048);
        fence_async();
        __syncwarp();
        mbar_arrive_elect(bar + 8 * (MB_WC + wg * 5 + p));
      }
    }
    GT(layer * 4 + 1, 5);
    asm volatile("barrier.cluster.wait.aligned;" ::: "memory");
    const uint32_t ld_m = __shfl_sync(~0u, sb + O_H + (lane & 7) * 128 + (((lane >> 3) ^ (lane & 7)) << 4), lane);

    for (int s = 0; s < NSEG; s++) {
      const uint32_t par = s & 1;
      if (wid == 4) TS0(0);
      if (wid == 0) TS(30);
      {
        float ax[16];
        constexpr uint64_t db = mkdesc(SB0 + O_H + 1024, 16, 1024, 1);
        mbar_waitf(bar + 8 * MB_XF, par);
        wg_fence();
#pragma unroll
        for (int k = 0; k < 20; k++) wg_rs_n32_tb0(ax, a[vord(k)], db + hoff(vord(k)), k);
        mbar_waitf(bar + 8 * (MB_XF + 1), par);
        wg_fence();
#pragma unroll
        for (int k = 20; k < 40; k++) wg_rs_n32_tb0(ax, a[vord(k)], db + hoff(vord(k)), 1);
        wg_commit();
        mbar_waitf(bar + 8 * MB_PF, par ^ 1);
        if (wid == 6 && lane == 0) { mbar_expect(bar + 8 * MB_SM, 2 * SM_SLOT + 48 + 48); mbar_expect(bar + 8 * MB_SX, 2 * (W0X ? 1664 : 2176)); }
        wg_wait<0>();
        pin<16>(ax);
        if (w == 0) TS(1 + 22 * wg);
        stsm4t(st_x, pack2(ax[0], ax[1]), pack2(ax[2], ax[3]), pack2(ax[4], ax[5]), pack2(ax[6], ax[7]));
        stsm4t(st_x + 4096, pack2(ax[8], ax[9]), pack2(ax[10], ax[11]), pack2(ax[12], ax[13]), pack2(ax[14], ax[15]));
        bar_arrive<B_VOWN, 384>();
      }
      {
        float c[4][4];
#pragma unroll
        for (int k = 0; k < 4; k++) c[k][0] = c[k][1] = c[k][2] = c[k][3] = 0.f;
        uint32_t b[3][2][4];
        const uint32_t ld_m2 = opaque(ld_m ^ 64);
        SCHED_FENCE();
#define MORD(j) ((j) == 0 ? 9 : (j) < 4 ? (j) - 1 : 3 + ((j) - 4) / 2 + 3 * ((j) & 1))
#pragma unroll
        for (int j = 0; j < 12; j++) {
          if (j < 10) {
            if (j == 0) { mbar_waitf(bar + 8 * MB_ML, par); if (wid == 0) TS(2); }
            if (j == 1) { bar_sync<B_ML, 352>(); if (wid == 0) TS(3); }
            if (j == 4) { bar_sync<B_MR, 288>(); if (wid == 0) TS(4); }
            ldsm4(b[j % 3][0], ld_m + MORD(j) * 5120);
            ldsm4(b[j % 3][1], ld_m2 + MORD(j) * 5120);
          }
          const int u = j - 2;
          if (u >= 0) {
#pragma unroll
            for (int k = 0; k < 4; k++) mma16816(c[k], a[4 * MORD(u) + k], b[u % 3][k >> 1][(k & 1) * 2], b[u % 3][k >> 1][(k & 1) * 2 + 1]);
          }
        }
        if (wid == 0) TS(31);
        if (V_N1 > 0) bar_arrive<B_VGO, 384>();
#pragma unroll
        for (int k = 0; k < 4; k++) c[0][k] = (c[0][k] + c[1][k]) + (c[2][k] + c[3][k]);
        stsm2t(st_x + 1024 - wg * 3072, pack2(c[0][0], c[0][1]), pack2(c[0][2], c[0][3]));
        fence_async();
      }
      if (wg == 0) {
        bar_sync<B_QK, 256>();
        float sv[20];
        {
          constexpr uint64_t da = mkdesc(SB0 + O_QK, 16, 1024, 1), db = mkdesc(SB0 + O_K, 16, 2048, 1);
          wg_fence();
#pragma unroll
          for (int k = 0; k < 4; k++) {
            wg_ss_n40_ta0_tb0(sv, da + 2 * k, db + 2 * k, k);
            if (V_B > 0 && k == SISS_K) bar_arrive<B_SISS, 256>();
          }
          wg_commit();
        }
        if (w == 0) TS(6);
        SCHED_FENCE();
        const uint32_t ln = opaque(lane);
        uint32_t m0, m1, m2, m3, m4;
        {
          const uint32_t a1 = opaque(sb1 + O_SM + SM_SLOT + ln * 16), a2 = opaque(sb2 + O_SM + ln * 16);
          const uint32_t a3 = opaque(sb1 + O_SM + SM_SLOT + 512 + ln * (W0X ? 16 : 4)), a4 = opaque(sb2 + O_SM + 512 + ln * (W0X ? 16 : 4));
          const uint32_t b1 = opaque(sb1 + O_BAR + 8 * MB_SM), b2 = opaque(sb2 + O_BAR + 8 * MB_SM);
          const uint32_t bt = opaque(mapa(sb, min(ln, 2u)) + O_BAR + 8 * MB_SM), at = opaque(bt + (O_MAXS + 48 - O_BAR - 8 * MB_SM));
          SCHED_FENCE();
          wg_wait<0>();
          pin<20>(sv);
          m0 = pack2(sv[2], sv[3]); m1 = pack2(sv[6], sv[7]); m2 = pack2(sv[10], sv[11]); m3 = pack2(sv[14], sv[15]); m4 = pack2(sv[18], sv[19]);
          if (w == 0) {
            sta4(a1, m0, m1, m2, m3, b1);
            sta4(a2, m0, m1, m2, m3, b2);
            if (W0X) {
              const uint32_t x0 = pack2(sv[0], sv[1]), x1 = pack2(sv[4], sv[5]);
              sta4(a3, m4, x0, x1, 0u, b1);
              sta4(a4, m4, x0, x1, 0u, b2);
            } else {
              sta1(a3, m4, b1);
              sta1(a4, m4, b2);
            }
          }
          sta1p(at, 0u, bt, ln < 3);
          bar_arrive<B_SSENT, 256>();
          SCHED_FENCE();
        }
        const uint32_t p0 = pack2(sv[0], sv[1]), p1 = pack2(sv[4], sv[5]), p2 = pack2(sv[8], sv[9]), p3 = pack2(sv[12], sv[13]), p4 = pack2(sv[16], sv[17]);
        const uint32_t ox = O_K + w * 2048 + ln * 16, ox2 = O_K + 8192 + ln * 4;
        uint4 xu = make_uint4(0, 0, 0, 0), xv = xu;
        {
          const uint32_t a1 = opaque(sb1 + ox + 512), a2 = opaque(sb2 + ox), b1 = opaque(sb1 + O_BAR + 8 * MB_SX), b2 = opaque(sb2 + O_BAR + 8 * MB_SX);
          if (w == 0) {
            TS(7);
            const uint32_t om = opaque(sb + O_SM + ln * 16), om2 = opaque(sb + O_SM + 512 + ln * 4);
            const uint32_t pa0 = ld_m + (O_QM - O_H), pa1 = (ld_m ^ 64) + (O_QM - O_H);
            float t[10] = {bflo(m0), bfhi(m0), bflo(m1), bfhi(m1), bflo(m2), bfhi(m2), bflo(m3), bfhi(m3), bflo(m4), bfhi(m4)};
            pin<10>(t);
            SCHED_FENCE();
            mbar_waitf(bar + 8 * MB_SM, par);
            const uint4 u = lds4(om), v = lds4(om + SM_SLOT);
            uint32_t u4, v4;
            if (W0X) {
              const uint4 x = lds4(om + 512), y = lds4(om + 512 + SM_SLOT);
              u4 = x.x; v4 = y.x; xu.x = x.y; xu.y = x.z; xv.x = y.y; xv.y = y.z;
            } else {
              u4 = lds1(om2); v4 = lds1(om2 + SM_SLOT);
              sta4(a1, p0, p1, p2, p3, b1);
              sta4(a2, p0, p1, p2, p3, b2);
            }
            bar_arrive<B_SLD, 256>();
            SCHED_FENCE();
            ACC3(0, u.x, v.x) ACC3(2, u.y, v.y) ACC3(4, u.z, v.z) ACC3(6, u.w, v.w) ACC3(8, u4, v4)
            TS(8);
            const float f = exp_row(t);
            stsm4(pa0, pack2(t[0] * f, t[1] * f), pack2(t[2] * f, t[3] * f), pack2(t[4] * f, t[5] * f), pack2(t[6] * f, t[7] * f));
            stsm1(pa1, pack2(t[8] * f, t[9] * f));
            bar_arrive<B_PM, 160>();
            TS(9);
          } else {
            const uint32_t a3 = opaque(sb1 + ox2 + 128), a4 = opaque(sb2 + ox2);
            SCHED_FENCE();
            mbar_waitf(bar + 8 * MB_SM, par);
            sta4(a1, p0, p1, p2, p3, b1);
            sta4(a2, p0, p1, p2, p3, b2);
            if (w == 3) { sta1(a3, p4, b1); sta1(a4, p4, b2); }
            bar_arrive<B_SLD, 256>();
          }
        }
        {
          float t[10] = {bflo(p0), bfhi(p0), bflo(p1), bfhi(p1), bflo(p2), bfhi(p2), bflo(p3), bfhi(p3), bflo(p4), bfhi(p4)};
          const int dq = 8 * w + (ln >> 2) - 2 * (ln & 3);
#pragma unroll
          for (int k = 1; k < 5; k++) {
            if (8 * (k - 1) > dq) t[2 * k] = -1e9f / SCL;
            if (8 * (k - 1) + 1 > dq) t[2 * k + 1] = -1e9f / SCL;
          }
          const int rr = 2 * w + (ln & 1);
          const uint32_t pa = sb + O_QK + ((ln >> 1) & 3) * 2048 + rr * 128;
          const uint32_t pa0 = opaque(pa + (((ln >> 3) ^ rr) << 4)), pa1 = opaque(pa0 ^ 64), l0 = opaque(sb + ox), l1 = opaque(sb + ox2);
          pin<10>(t);
          SCHED_FENCE();
          uint32_t u4 = 0, v4 = 0;
          if (W0X == 2 && w == 0) bar_sync<B_VEND, 256>();
          if (!W0X || w > 0) {
            mbar_waitf(bar + 8 * MB_SX, par);
            bar_sync<B_VEND, W0X == 1 ? 224 : 256>();
            xu = lds4(l0); xv = lds4(l0 + 512);
            if (w == 3) { u4 = lds1(l1); v4 = lds1(l1 + 128); }
          }
          ACC3(0, xu.x, xv.x) ACC3(2, xu.y, xv.y) ACC3(4, xu.z, xv.z) ACC3(6, xu.w, xv.w) ACC3(8, u4, v4)
          const float f = exp_row(t);
          const float sum = (((t[0] + t[1]) + (t[2] + t[3])) + ((t[4] + t[5]) + (t[6] + t[7])) + (t[8] + t[9])) * f;
          const float s1 = __shfl_xor_sync(~0u, sum, 1), s2 = __shfl_xor_sync(~0u, sum, 2), s3 = __shfl_xor_sync(~0u, sum, 3);
          const float inv = f * rcp((sum + s1) + (s2 + s3));
          stsm4(pa0, pack2(t[0] * inv, t[1] * inv), pack2(t[2] * inv, t[3] * inv), pack2(t[4] * inv, t[5] * inv), pack2(t[6] * inv, t[7] * inv));
          stsm2(pa1, pack2(t[8] * inv, t[9] * inv), 0u);
          fence_async();
        }
        bar_arrive<B_PX, 256>();
        if (w == 0) TS(10);
        bar_sync<B_XGO, 256>();
      } else {
        bar_arrive<B_QK, 256>();
        const int ln = opaque(lane);
        if (w == 2) {
          bar_sync<B_VHALF, 192>();
          if (ln == 0 && s > 0) { red_release(flags + FL_A + (e0 >> 10) * 8 + (s - 1) * 48, 1); }
          __syncwarp();
        }
        if (w == 3) {
          const int l = bid * 2 + ln, s2 = s + 2;
          if (ln < 2 && l < 160 && s2 < NSEG - 1) {
            const int tile = l >> 4;
            const uint8_t* p = ar + (s2 >> 2) * AR_GROUP + (s2 & 1) * 128 + ((s2 >> 1) & 1) * 512 + ar_chunk(tile) * 4096 +
                               ((l >> 3) & 1) * 16384 + (l & 1) * 256 + ((l >> 1) & 3) * 1024;
            asm volatile("prefetch.global.L2 [%0];" :: "l"(p));
          }
        }
        if (w == 0) {
          const bool more = s + 1 < NSEG;
          if (ln < 2 && more) mbar_expect(bar + 8 * (MB_XF + ln), 20480);
          const uint8_t* src = g_xn + (s + 1) * 40960 + chunk_of(ln) * 4096;
          if ((s & 1) && more) { wait_flag(flags + FL_XN + ((s + 1) >> 1) * 8, 3); fence_async_global(); }
          bar_sync<B_VHALF, 192>();
          if ((ln < 4 || ln == 9) && more) bulk_g2s(sb + O_H + ln * 5120 + 1024, src, 4096, bar + 8 * MB_XF);
          bar_sync<B_VDONE, 160>();
          if (ln >= 4 && ln < 9 && more) bulk_g2s(sb + O_H + ln * 5120 + 1024, src, 4096, bar + 8 * (MB_XF + 1));
        }
        bar_sync<B_XGO1, 256>();
      }
    }
  } else {
    asm volatile("setmaxnreg.dec.sync.aligned.u32 88;");
    asm volatile("barrier.cluster.wait.aligned;" ::: "memory");

    const int g = lane >> 2, i4 = lane & 3;
    const int myT = w == 0 ? 9 : rank * 3 + w - 1, myP = w == 0 ? 9 : w - 1;
    const int tok = 2 * ((lane >> 1) & 3) + ((lane >> 3) & 1);
    const uint32_t fw_off = sb + O_H + myP * 5120 + tok * 128 + (((2 * (lane >> 4) + (lane & 1)) ^ tok) << 4);
    const uint32_t prod_off = (w >> 1) * 16384 + (w & 1) * 2048 + ((g >> 1) & 1) * 256 + (i4 * 2 + (g >> 2)) * 16 + (g & 1) * 8;
    const uint32_t cons_off = ar_chunk(myT) * 4096 + (lane >> 3) * 1024 + (lane & 7) * 16;
    auto tile_off = [&](int k) { return (k * 8 + rank) * 4096; };
    constexpr uint32_t T9_OFF = ar_chunk(9) * 4096;

    uint32_t mx;
    auto forward = [&](const uint32_t* p) {
      const uint32_t c = O_H + myP * 5120, bo = O_BAR + 8 * MB_MR;
      sts4(fw_off, p[0], p[1], p[2], p[3]);
      sts4(fw_off ^ 64, p[4], p[5], p[6], p[7]);
      fence_async();
      __syncwarp();
      if (w == 0) mbar_arrive_elect(bar + 8 * MB_ML);
      else {
        bar_arrive<B_ML, 352>();
        bulk_s2c_elect<1024>(sb1 + c + 6 * 5120, sb1 + bo, sb2 + c + 3 * 5120, sb2 + bo, sb + c);
      }
      SCHED_FENCE();
      mx = 0;
#pragma unroll
      for (int k = 0; k < 8; k++) mx = __vmaxu2(mx, p[k] & 0x7FFF7FFFu);
    };
    auto send_max = [&]() {
      mx = max(mx & 0xFFFFu, mx >> 16);
      mx = __reduce_max_sync(~0u, mx);
      { const uint32_t b = mapa(sb, min(lane, 2)); sta1p(b + O_MAXS + (rank * 4 + w) * 4, mx << 16, b + O_BAR + 8 * MB_SM, lane < 3); }
    };
    auto arm = [&]() { if (lane == 0 && w < 2) mbar_expect(bar + 8 * (w == 0 ? MB_OG : MB_MR), w == 0 ? 2048 : 6144); };
    {
      arm();
      const uint32_t* mp = (const uint32_t*)(mem0 + tok * DM + myT * 64 + 16 * (lane >> 4) + 4 * (lane & 1));
      const uint32_t p[8] = {mp[0], mp[4], mp[1], mp[5], mp[16], mp[20], mp[17], mp[21]};
      forward(p);
    }
    if (w == 1) {
#pragma unroll 1
      for (int i = W_WIN; i < 20; i++) {
        if (i <= W_OPEN) mbar_wait(bar + 8 * (MB_W + i - W_WIN), 0);
        if (i >= 10) mbar_wait(bar + 8 * (MB_WC + i - 10), 0);
        load_piece(i);
      }
    }
    if (w == 0) {
      if (lane < 2) mbar_expect(bar + 8 * (MB_XF + lane), 20480);
      wait_flag<200>(flags + FL_XN, 3);
      fence_async_global();
      if (lane < 10) bulk_g2s(sb + O_H + lane * 5120 + 1024, g_xn + chunk_of(lane) * 4096, 4096, bar + 8 * (MB_XF + (lane >= 4 && lane < 9)));
      if (lane == 0) GTT(layer * 4 + 1, 4);
    }
    if (w == 2) {
      wait_flag<400>(flags + FL_X, 128);
      wait_flag<400>(g_zero + Z_FLAGS + FL_N, 4);
      const float sq = __ldcg((const float*)(g_zero + Z_NORM));
      float mx = 0.f;
#pragma unroll
      for (int k = 0; k < 5; k++) {
        const float4* p = (const float4*)g_nrm + k * 32 + lane;
        const float4 x = __ldcg(p), y = __ldcg(p + 160), z = __ldcg(p + 320), u = __ldcg(p + 480);
        mx = fmaxf(fmaxf(mx, fmaxf((x.x + y.x) + (z.x + u.x), (x.y + y.y) + (z.y + u.y))), fmaxf((x.z + y.z) + (z.z + u.z), (x.w + y.w) + (z.w + u.w)));
      }
#pragma unroll
      for (int o = 16; o; o >>= 1) mx = fmaxf(mx, __shfl_xor_sync(~0u, mx, o));
      sts1(sb + O_MAXS + 52, __float_as_uint(sqrt_approx(sq) * sqrt_approx(mx) * (25.2982213f * 1.1f)));
    }
    bar_sync<B_WG2, 128>();
    const float cbound = __uint_as_float(lds1(sb + O_MAXS + 52));
#pragma unroll 1
    for (int i = 10; i < 15; i++) mbar_wait(bar + 8 * (MB_W + i), 0);
    if (tid == 256) GTT(layer * 4 + 1, 7);

    const uint32_t la_w = sb + O_WV + ((lane >> 4) * 8 + (lane & 7)) * 128 + (((2 * w + ((lane >> 3) & 1)) ^ (lane & 7)) << 4);
    uint32_t af[V_RS][4];
#pragma unroll
    for (int k = 0; k < V_RS; k++) ldsm4t(af[k], la_w + vord(V_OWN + k) * 2048);
    const uint32_t pa0 = __shfl_sync(~0u, sb + O_QM + (lane & 7) * 128 + (((lane >> 3) ^ (lane & 7)) << 4), lane), pa1 = __shfl_sync(~0u, pa0 ^ 64, lane);
    uint32_t vf[10];
    uint4 oq0, oq1;
    uint8_t* op;
    auto pv_x = [&](int s) {
      float ox[16];
      const uint32_t vz[4] = {vf[8], vf[9], 0u, 0u};
      constexpr uint64_t dp = mkdesc(SB0 + O_QK, 16, 2048, 1);
      bar_sync<B_PX, 256>();
      wg_fence();
      wg_rs_n32_tb0(ox, vf, dp, 0);
      wg_rs_n32_tb0(ox, vf + 4, dp + 2, 1);
      wg_rs_n32_tb0(ox, vz, dp + 4, 1);
      wg_commit();
      const uint32_t ln = opaque(lane);
      op = g_ot + (size_t)s * (HE * 64) + (e0 + 16 * w) * 64 + (ln & 3) * 128 + (ln >> 2) * 16;
      wg_wait<0>();
      pin<16>(ox);
      oq0 = make_uint4(pack2(ox[0], ox[1]), pack2(ox[4], ox[5]), pack2(ox[8], ox[9]), pack2(ox[12], ox[13]));
      oq1 = make_uint4(pack2(ox[2], ox[3]), pack2(ox[6], ox[7]), pack2(ox[10], ox[11]), pack2(ox[14], ox[15]));
    };
    for (int s = 0;; s++) {
      const uint32_t par = s & 1;
      float sc1, isc, sum0, sum1;
      uint32_t ao[O_RS][4];
      {
        float av[20];
        constexpr uint64_t da = mkdesc(SB0 + O_WV, 1024, 1024, 1), db = mkdesc(SB0 + O_H, 16, 1024, 1);
#define V_RUN(k0, k1) wg_fence(); _Pragma("unroll") for (int k = k0; k < k1; k++) wg_ss_n40_ta1_tb0(av, da + vord(k) * 128, db + hoff(vord(k)), k);
        bar_sync<B_VOWN, 384>();
        V_RUN(0, V_OWN)
        if (w == 0) TS(29);
        SCHED_FENCE();
        if (w == 0) { mbar_waitf(bar + 8 * MB_MR, par); bar_arrive<B_MR, 288>(); SCHED_FENCE(); }
        send_max();
        if (V_N1 > 0) {
          bar_sync<B_VGO, 384>();
          wg_fence();
#pragma unroll
          for (int k = 0; k < V_N1; k++) wg_rs_n40_tb0(av, af[k], db + hoff(vord(V_OWN + k)), 1);
        }
        if (V_B > 0) {
          bar_sync<B_SISS, 256>();
          V_RUN(V_OWN + V_RS, V_OWN + V_RS + V_B)
        }
        bar_sync<B_SSENT, 256>();
        V_RUN(V_OWN + V_RS + V_B, V_K1)
        wg_fence();
#pragma unroll
        for (int k = V_N1; k < V_RS; k++) wg_rs_n40_tb0(av, af[k], db + hoff(vord(V_OWN + k)), 1);
        const uint32_t ln = opaque(lane);
        const uint32_t amx = opaque(sb + O_MAXS + 4 * min(ln, 11u));
        SCHED_FENCE();
        mbar_waitf(bar + 8 * MB_SM, par);
        const uint32_t mxl = lds1(amx);
        if (s == 0) {
#pragma unroll 1
          for (int i = 15; i < 20; i++) mbar_wait(bar + 8 * (MB_W + i), 0);
          asm volatile("griddepcontrol.launch_dependents;");
          if (tid == 256) GTT(layer * 4 + 1, 8);
        }
        bar_sync<B_SLD, 256>();
        V_RUN(V_K1, 20)
        wg_commit();
        V_RUN((V_K1 > 20 ? V_K1 : 20), V_K2)
        wg_commit();
        wg_wait<1>();
        bar_arrive<B_VHALF, 192>();
        V_RUN(V_K2, 40)
        wg_commit();
        SCHED_FENCE();
        if (w == 0) TS(12);
        {
          const float bnd = cbound * fmaxf(1.f, __uint_as_float(__reduce_max_sync(~0u, mxl)));
          const uint32_t eb = min(max(__float_as_uint(bnd) >> 23, 31u), 254u);
          sc1 = __uint_as_float(opaque((280u - eb) << 23));
          isc = __uint_as_float(opaque((eb - 29u) << 23));
        }
        const uint32_t o = O_OG + w * 256 + ln * 4;
        const uint32_t a0 = opaque(sb + o), a1 = opaque(sb1 + o + 4096), a2 = opaque(sb1 + o + 4096 + 128), a3 = opaque(sb2 + o + 2048), a4 = opaque(sb2 + o + 2048 + 128);
        const uint32_t b1 = opaque(sb1 + O_BAR + 8 * MB_OG), b2 = opaque(sb2 + O_BAR + 8 * MB_OG);
        const uint32_t c1 = opaque(0x3F803F80u);
        const uint32_t one[4] = {c1, c1, c1, c1};
        uint32_t pm[5];
        bar_arrive<B_VEND, W0X == 1 ? 224 : 256>();
        SCHED_FENCE();
        bar_sync<B_PM, 160>();
        ldsm4(pm, pa0);
        ldsm1(pm[4], pa1);
        SCHED_FENCE();
        wg_wait<0>();
        pin<20>(av);
        if (w == 0) TS(13);
#pragma unroll
        for (int j = 0; j < 16; j++) if ((O_RSM >> j) & 1) ldsm4t(ao[O_IDX(j)], la_w + O_WO + (1 + (j >> 3)) * 24576 + (4 + (j & 7)) * 2048);
#pragma unroll
        for (int k = 0; k < 10; k++) vf[k] = pack2(av[2 * k], av[2 * k + 1]);
        float o0[4] = {0.f, 0.f, 0.f, 0.f}, o1[4] = {0.f, 0.f, 0.f, 0.f}, o2[4] = {0.f, 0.f, 0.f, 0.f};
        float s0[4] = {0.f, 0.f, 0.f, 0.f}, s1[4] = {0.f, 0.f, 0.f, 0.f}, s2[4] = {0.f, 0.f, 0.f, 0.f};
        mma16816(o0, vf, pm[0], pm[1]);
        mma16816(o1, vf + 4, pm[2], pm[3]);
        mma1688(o2, vf[8], vf[9], pm[4]);
#define ONES_MMA mma16816(s0, one, pm[0], pm[1]); mma16816(s1, one, pm[2], pm[3]); mma1688(s2, c1, c1, pm[4]);
        if (FV == 0) { ONES_MMA }
        const uint32_t p0 = pack2(o0[0] + o1[0] + o2[0], o0[1] + o1[1] + o2[1]), p1 = pack2(o0[2] + o1[2] + o2[2], o0[3] + o1[3] + o2[3]);
        sta1(a1, p0, b1); sta1(a2, p1, b1);
        sta1(a3, p0, b2); sta1(a4, p1, b2);
        sts1(a0, p0); sts1(a0 + 128, p1);
        if (FV == 1) { SCHED_FENCE(); ONES_MMA }
        if (FV == 2) { fence_async(); SCHED_FENCE(); ONES_MMA }
        sum0 = s0[0] + s1[0] + s2[0]; sum1 = s0[1] + s1[1] + s2[1];
        if (FV != 2) fence_async();
      }
      if (s == NSEG - 1) break;
      uint8_t* arp;
      uint32_t t1;
      {
        bar_sync<B_WG2, 128>();
        float c9[4], ca[4], cb[4], cc[4];
        constexpr uint64_t da = mkdesc(SB0 + O_WO, 1024, 1024, 1), db = mkdesc(SB0 + O_OG, 128, 128, 0);
#define O_RUN(acc, tile, k0, k1) _Pragma("unroll") for (int k = k0; k < k1; k++) wg_ss_n8_ta1_tb1(acc, da + (tile) * 1536 + k * 128, db + (k >> 2) * 128 + (k & 3) * 16, k);
        wg_fence();
        O_RUN(c9, 3, 0, 4)
        wg_commit();
        if (w == 0) TS(14);
        O_RUN(ca, 0, 0, 4) O_RUN(cb, 1, 0, 2)
        wg_commit();
        SCHED_FENCE();
        arp = ar + (s >> 2) * AR_GROUP + (s & 1) * 128 + ((s >> 1) & 1) * 512;
        uint8_t* pp = arp + opaque(prod_off);
        const float2 sc = make_float2(sc1 * rcp(sum0), sc1 * rcp(sum1));
        wg_wait<1>();
        pin<4>(c9);
        fix_red(pp + T9_OFF, c9, sc);
        SCHED_FENCE();
        wg_fence();
        O_RUN(cb, 1, 2, 4) O_RUN(cc, 2, 0, 4)
        mbar_waitf(bar + 8 * MB_OG, par);
        wg_fence();
        O_RUN(ca, 0, 4, 12)
        wg_commit();
        bar_arrive<B_VDONE, 160>();
        if (w == 0) TS(15);
#define O_MIX(acc, j0, j1) _Pragma("unroll") for (int j = j0; j < j1; j++) { const int k = 4 + (j & 7); \
          if ((O_RSM >> j) & 1) wg_rs_n8_tb1(acc, ao[O_IDX(j) < O_RS ? O_IDX(j) : 0], db + (k >> 2) * 128 + (k & 3) * 16, 1); \
          else wg_ss_n8_ta1_tb1(acc, da + (1 + (j >> 3)) * 1536 + k * 128, db + (k >> 2) * 128 + (k & 3) * 16, 1); }
        O_MIX(cb, 0, O_B1)
        wg_commit();
        wg_wait<1>();
        pin<4>(ca);
        fix_red(pp + tile_off(0), ca, sc);
        SCHED_FENCE();
        if (w == 0) TS(16);
        wg_fence();
        O_MIX(cb, O_B1, 8)
        wg_commit();
        O_MIX(cc, 8, 16)
        wg_commit();
        bar_arrive<B_XGO1, 256>();
        bar_arrive<B_XGO, 256>();
        wg_wait<1>();
        pin<4>(cb);
        fix_red(pp + tile_off(1), cb, sc);
        SCHED_FENCE();
        wg_wait<0>();
        pin<4>(cc);
        fix_red(pp + tile_off(2), cc, sc);
        t1 = clk();
        if (w == 3) TS(17);
      }
      pv_x(s);
      mbar_arrive_elect(bar + 8 * MB_PF);
      if (w == 0) TS(28);
      {
        arm();
        const int dly = w == 0 ? POLL_9 : w == 1 ? POLL_A : w == 2 ? POLL_B : POLL_C;
        const uint32_t need = w == 0 ? 96 : 32;
        const uint8_t* cp = arp + opaque(cons_off);
        uint4 y[4];
        int it = 0;
        while ((int)(clk() - t1) < dly) {}
        if (w == 3) TS(18);
        y[0] = ld_poll(cp); y[1] = ld_poll(cp + 256); y[2] = ld_poll(cp + 16384); y[3] = ld_poll(cp + 16384 + 256);
        { const uint64_t pol = policy_evict_first(); stg4h(op, oq0, pol); stg4h(op + 512, oq1, pol); }
        const float isl = isc * 0.5f, bias = -(float)(need >> 3) * isl;
        while (true) {
          const uint32_t bad = ((y[0].x ^ need) | (y[0].z ^ need) | (y[1].x ^ need) | (y[1].z ^ need)) | ((y[2].x ^ need) | (y[2].z ^ need) | (y[3].x ^ need) | (y[3].z ^ need));
          if (!__any_sync(~0u, (bad & 127u) != 0)) break;
          if (++it > 2000000) __trap();
          y[0] = ld_poll(cp); y[1] = ld_poll(cp + 256); y[2] = ld_poll(cp + 16384); y[3] = ld_poll(cp + 16384 + 256);
        }
        uint32_t p[8];
#pragma unroll
        for (int k = 0; k < 4; k++) {
          p[2 * k] = pack2(fmaf((float)(int)__funnelshift_r(y[k].x, y[k].y, 3), isl, bias), fmaf((float)(int)__funnelshift_r(y[k].z, y[k].w, 3), isl, bias));
          p[2 * k + 1] = pack2((float)(int)y[k].y * isc, (float)(int)y[k].w * isc);
        }
        TS(19 + w);
        forward(p);
      }
    }
    bar_arrive<B_VDONE, 160>();
    bar_arrive<B_XGO1, 256>();
    bar_arrive<B_XGO, 256>();
    pv_x(NSEG - 1);
    { const uint64_t pol = policy_evict_first(); stg4h(op, oq0, pol); stg4h(op + 512, oq1, pol); }
    bar_sync<B_WG2, 128>();
    if (tid == 256) red_release(flags + FL_A + (e0 >> 10) * 8 + (NSEG - 1) * 48, 1);
    mbar_wait(bar + 8 * MB_OG, 1);
    __syncwarp();
  }
  asm volatile("barrier.cluster.arrive.relaxed.aligned;\nbarrier.cluster.wait.aligned;" ::: "memory");
  GT(layer * 4 + 1, 2);
  if (wid == 0) asm volatile("griddepcontrol.wait;" ::: "memory");
}

constexpr int P_B = 0, P_A = 131072, P_BAR = 196608, OPC_SMEM = P_BAR + 256;
#define PF_C 3
#define PF_S0 43
constexpr int OP_KR = 48;

__global__ void __launch_bounds__(384, 1)
opc_kernel(const __grid_constant__ CUtensorMap tmo, bf16* __restrict__ out, int layer,
           const bf16* __restrict__ Wq, const bf16* __restrict__ Wk, const bf16* __restrict__ Wv, const bf16* __restrict__ Wo) {
  extern __shared__ __align__(1024) uint8_t smem[];
  asm volatile("griddepcontrol.launch_dependents;");
  GT(layer * 4 + 2, 0);
  const uint32_t sb = smem_u32(smem);
  check_smem_base(sb);
  const int tid = threadIdx.x, wid = __shfl_sync(~0u, tid >> 5, 0), wg = wid >> 2, w = wid & 3, lane = tid & 31;
  const uint32_t bar = sb + P_BAR;
  uint32_t* flags = g_zero + Z_FLAGS + layer * FL_LAYER;
  float* acc = g_acc + layer * (S_TOK * DM);
  const uint64_t pol = policy_evict_first();
  if (wid == 0) {
    if (lane < 16) mbar_init(bar + 8 * lane, (lane == 8 || lane == 9) ? 8 : 1);
    fence_async();
  }
  __syncthreads();
  if (blockIdx.x < 30) {
    const int cg = blockIdx.x % 5, kg = blockIdx.x / 5;
    if (wg < 2) {
      asm volatile("setmaxnreg.inc.sync.aligned.u32 240;");
      uint32_t a[OP_KR][4];
      const uint32_t la = sb + P_B + ((lane >> 4) * 8 + (lane & 7)) * 128 + (((2 * w + ((lane >> 3) & 1)) ^ (lane & 7)) << 4);
      mbar_wait(bar + 80, 0);
#pragma unroll
      for (int k = 0; k < 32; k++) ldsm4t(a[k], la + wg * 65536 + k * 2048);
      bar_arrive<2, 288>();
      mbar_wait(bar + 88, 0);
#pragma unroll
      for (int k = 0; k < 16; k++) ldsm4t(a[32 + k], la + wg * 32768 + k * 2048);
      bar_arrive<3, 288>();
      mbar_wait(bar + 96, 0);
      float* ap = acc + (cg * 8 + wg * 4 + w) * 512 + lane * 4;
      for (int s = 0; s < NSEG; s++) {
        const int buf = s & 1;
        const uint32_t par = (s >> 1) & 1;
        float d[16];
        const uint64_t db = mkdesc(SB0 + P_B + buf * 65536, 512, 128, 0), da = mkdesc(SB0 + P_A + wg * 32768, 1024, 1024, 1);
        float* p = ap + s * (32 * DM);
        float* pz = ap + (s + 2) * (32 * DM) + kg * 128;
        if (kg < 4 && s + 2 < NSEG) { if (EVF) stg4h(pz, make_uint4(0, 0, 0, 0), pol); else stg4(pz, make_uint4(0, 0, 0, 0)); }
#pragma unroll
        for (int q = 0; q < 4; q++) {
          mbar_wait(bar + 8 * (buf * 4 + q), par);
          wg_fence();
#pragma unroll
          for (int k = 16 * q; k < 16 * q + 16; k++) {
            if (k < OP_KR) wg_rs_n32_tb1(d, a[k < OP_KR ? k : 0], db + k * 64, k);
            else wg_ss_n32_ta1_tb1(d, da + (k - OP_KR) * 128, db + k * 64, 1);
          }
        }
        wg_commit();
        wg_wait<0>();
        pin<16>(d);
        if (lane == 0) mbar_arrive(bar + 8 * (8 + buf));
        if (s == NSEG - 1) GT(layer * 4 + 2, 6);
        if (EVF) {
          red4fh(p, d[0], d[1], d[4], d[5], pol);
          red4fh(p + 128, d[8], d[9], d[12], d[13], pol);
          red4fh(p + 256, d[2], d[3], d[6], d[7], pol);
          red4fh(p + 384, d[10], d[11], d[14], d[15], pol);
        } else {
          red4f(p, d[0], d[1], d[4], d[5]);
          red4f(p + 128, d[8], d[9], d[12], d[13]);
          red4f(p + 256, d[2], d[3], d[6], d[7]);
          red4f(p + 384, d[10], d[11], d[14], d[15]);
        }
        bar_sync<1, 256>();
        if (tid == 0) { red_release(flags + FL_B + s * 8, 1); }
        __syncwarp();
      }
    } else {
      asm volatile("setmaxnreg.dec.sync.aligned.u32 24;");
      if (w == 0) {
        if (lane == 0) { mbar_expect(bar + 80, 131072); mbar_expect(bar + 96, 65536); mbar_expect(bar + 88, 65536); }
        __syncwarp();
        if (lane < 16) tma2d(sb + P_B + lane * 8192, &tmo, cg * 128 + (lane >> 3) * 64, kg * 1024 + (lane & 7) * 64, bar + 80);
        else if (lane < 24) tma2d(sb + P_B + lane * 8192, &tmo, cg * 128 + ((lane >> 2) & 1) * 64, kg * 1024 + 768 + (lane & 3) * 64, bar + 96);
        bar_sync<2, 288>();
        fence_async();
        if (lane < 8) tma2d(sb + P_B + lane * 8192, &tmo, cg * 128 + (lane >> 2) * 64, kg * 1024 + 512 + (lane & 3) * 64, bar + 88);
        bar_sync<3, 288>();
        for (int s = 0; s < NSEG; s++) {
          const int buf = s & 1;
          if (s >= 2) mbar_wait(bar + 8 * (8 + buf), ((s >> 1) & 1) ^ 1);
          if (s >= 2) wait_flag(flags + FL_B + (s - 2) * 8, 30);
          wait_flag(flags + FL_A + s * 48 + kg * 8, 16);
          fence_async_global();
          if (lane < 4) {
            mbar_expect(bar + 8 * (buf * 4 + lane), 16384);
            if (EVF) bulk_g2sh(sb + P_B + buf * 65536 + lane * 16384, g_ot + (size_t)s * (HE * 64) + kg * 65536 + lane * 16384, 16384, bar + 8 * (buf * 4 + lane), pol);
            else bulk_g2s(sb + P_B + buf * 65536 + lane * 16384, g_ot + (size_t)s * (HE * 64) + kg * 65536 + lane * 16384, 16384, bar + 8 * (buf * 4 + lane));
            if (s == NSEG - 1 && lane == 0) GTT(layer * 4 + 2, 5);
          }
          __syncwarp();
        }
      } else if (w == 1 && layer == 0) {
#pragma unroll 1
        for (int q = 4 * (4 - PF_C); q < 18; q++) {
          wait_flag(flags + FL_A + (PF_S0 + q) * 48 + kg * 8, 16);
          const int m = q >> 2;
          const uint8_t* W = m == 0 ? (const uint8_t*)Wo : m == 1 ? (const uint8_t*)Wv : m == 2 ? (const uint8_t*)Wk : m == 3 ? (const uint8_t*)Wq : (q & 1) ? g_w2 : g_w1;
          const int n = m < 4 ? 512 : (q & 1) ? 224 : 640, l0 = m < 4 ? blockIdx.x * 2048 + (q & 3) * 512 : blockIdx.x * n, lim = m < 4 ? 61440 : (q & 1) ? 6720 : 19200;
#pragma unroll 1
          for (int k = lane; k < n; k += 32) {
            if (l0 + k < lim) asm volatile("prefetch.global.L2 [%0];" :: "l"(W + (size_t)(l0 + k) * 128));
            __nanosleep(100);
          }
        }
      }
    }
  } else {
    constexpr int LD = 644;
    float* xs = (float*)smem;
    uint32_t par = 0;
    for (int task = blockIdx.x - 30; task < 2 * NSEG; task += 6, par ^= 1) {
      const int s = task >> 1, jj = task & 1;
      if (wid == 0) {
        wait_flag(flags + FL_XN + (task >> 2) * 8 + 1, 3);
        fence_async_global();
        if (lane == 0) { mbar_expect(bar, 20480); bulk_g2s(sb + 49152, g_x + task * 16 * DM, 20480, bar); }
      }
      if (wid == 1) { wait_flag(flags + FL_B + s * 8, 30); if (s == NSEG - 1 && lane == 0) GTT(layer * 4 + 2, 7); }
      __syncthreads();
      if (wid < 10) {
        float4 v[8];
#pragma unroll
        for (int k = 0; k < 8; k++) v[k] = EVF ? ldg4fh(acc + s * (32 * DM) + (wid * 8 + k) * 256 + jj * 128 + lane * 4, pol) : __ldcg((const float4*)(acc + s * (32 * DM) + (wid * 8 + k) * 256 + jj * 128 + lane * 4));
        float* xp = xs + (lane & 3) * 2 * LD + wid * 64 + (lane >> 2);
#pragma unroll
        for (int k = 0; k < 8; k++) { xp[k * 8] = v[k].x; xp[LD + k * 8] = v[k].y; xp[8 * LD + k * 8] = v[k].z; xp[9 * LD + k * 8] = v[k].w; }
      }
      mbar_wait(bar, par);
      __syncthreads();
      float v[2][20];
      const int pj = (lane & 24) + 2 * (lane & 3) + ((lane >> 2) & 1);
      const int tk0 = task * 16 + wid;
      if (wid < 8) {
        float sum[2] = {0.f, 0.f};
#pragma unroll
        for (int h = 0; h < 2; h++) {
#pragma unroll
          for (int k = 0; k < 10; k++) {
            const float2 u = *(const float2*)(xs + (wid + 8 * h) * LD + k * 64 + lane * 2);
            const uint32_t r = *(const uint32_t*)(smem + 49152 + (wid + 8 * h) * 1280 + k * 128 + pj * 4);
            v[h][2 * k] = u.x + bflo(r); v[h][2 * k + 1] = u.y + bfhi(r); sum[h] += v[h][2 * k] + v[h][2 * k + 1];
          }
        }
        if (!out) {
#pragma unroll
          for (int o = 16; o; o >>= 1) { sum[0] += __shfl_xor_sync(~0u, sum[0], o); sum[1] += __shfl_xor_sync(~0u, sum[1], o); }
          float q[2] = {0.f, 0.f};
#pragma unroll
          for (int h = 0; h < 2; h++) {
            sum[h] *= (1.f / DM);
#pragma unroll
            for (int k = 0; k < 20; k++) q[h] = fmaf(v[h][k] - sum[h], v[h][k] - sum[h], q[h]);
          }
#pragma unroll
          for (int o = 16; o; o >>= 1) { q[0] += __shfl_xor_sync(~0u, q[0], o); q[1] += __shfl_xor_sync(~0u, q[1], o); }
          uint8_t* xp = g_xt + (tk0 >> 7) * 163840 + (tk0 & 127) * 128 + (((lane >> 2) ^ (tk0 & 7)) << 4) + (lane & 3) * 4;
#pragma unroll
          for (int h = 0; h < 2; h++) {
            const float rs = rsqrtf(q[h] * (1.f / DM) + 1e-5f), sh = -sum[h] * rs;
#pragma unroll
            for (int k = 0; k < 10; k++) *(uint32_t*)(xp + h * 1024 + k * 16384) = pack2(fmaf(v[h][2 * k], rs, sh), fmaf(v[h][2 * k + 1], rs, sh));
          }
        }
      }
      fence_async();
      __syncthreads();
      if (!out) {
        if (tid == 352) red_release(flags + FL_LAYER + FL_T + (task >> 3) * 8, 1);
        __syncthreads();
      }
      if (wid < 8) {
        bf16* dst = out ? out + tk0 * DM + lane * 2 : g_x + tk0 * DM + pj * 2;
#pragma unroll
        for (int k = 0; k < 20; k++) *(uint32_t*)(dst + (k / 10) * 8 * DM + (k % 10) * 64) = pack2(v[k / 10][2 * (k % 10)], v[k / 10][2 * (k % 10) + 1]);
      }
    }
    __syncthreads();
    if (tid == 0 && !out) red_release(flags + FL_LAYER + FL_R, 1);
  }
  GT(layer * 4 + 2, 1);
  __syncwarp();
  asm volatile("griddepcontrol.wait;" ::: "memory");
  GT(layer * 4 + 2, 2);
}

constexpr int L_STAGE = 47104;
constexpr int L_KV = 0, L_B2 = 43008;
constexpr int L_BAR = 4 * L_STAGE;
constexpr int LA_SMEM = L_BAR + 256;
__device__ __forceinline__ float phi(float t) { return (fmaxf(t, 0.f) + 1e-6f) + ex2(fminf(t * 1.4426950408889634f, 0.f)); }
__device__ __forceinline__ void sqacc(uint32_t& h, uint32_t v) { asm("fma.rn.bf16x2 %0, %1, %1, %0;" : "+r"(h) : "r"(v)); }
__device__ __forceinline__ uint32_t phi2(float a, float b) { return pack2(phi(a), phi(b)); }
#define LA_LATE 6
#define PF_LB 1
#define PF_IL 1
#define PF_SLEEP1 400
#define RD1 0
#define PF_N0 2
#define PF_N1 0
#define PF_SLEEP 300

__global__ void __launch_bounds__(384, 1)
la_kernel(const bf16* __restrict__ Wq, const bf16* __restrict__ Wk, const bf16* __restrict__ Wv,
          const bf16* __restrict__ Wo, uint8_t* __restrict__ ar, int layer) {
  extern __shared__ __align__(1024) uint8_t smem[];
  const uint32_t sb = smem_u32(smem);
  check_smem_base(sb);
  const int tid = threadIdx.x, wid = __shfl_sync(~0u, tid >> 5, 0), wg = wid >> 2, w = wid & 3, lane = tid & 31, g = lane >> 2, i4 = lane & 3;
  const int cr = blockIdx.x & 1, hg = (blockIdx.x >> 1) & 7, tb = (blockIdx.x >> 4) * 2 + cr;
  const uint32_t bar = sb + L_BAR;
  uint32_t* flags = g_zero + Z_FLAGS + layer * FL_LAYER;
  asm volatile("griddepcontrol.launch_dependents;");
  GT(layer * 4, 0);
  if (wid == 0) {
    if (lane < 8) mbar_init(bar + 8 * lane, lane >= 4 ? (blockIdx.x < 128 ? 16 : 10) : 1);
    asm volatile("fence.mbarrier_init.release.cluster;" ::: "memory");
    fence_async();
  }
  if (blockIdx.x >= 128) {
    __syncthreads();
    const int q = blockIdx.x - 128;
    const uint8_t* src = (const uint8_t*)Wo + q * 1966080;
    if (wid == 11) {
#pragma unroll 1
      for (int it = 0; it < 48; it++) {
        const int st = it & 3;
        if (it >= 4) mbar_wait(bar + 8 * (4 + st), ((it >> 2) & 1) ^ 1);
        if (lane == 0) mbar_expect(bar + 8 * st, 40960);
        __syncwarp();
        if (lane < 4) bulk_g2s(sb + st * 40960 + lane * 10240, src + it * 40960 + lane * 10240, 10240, bar + 8 * st);
      }
    } else if (wid < 10) {
      float c[8] = {0.f, 0.f, 0.f, 0.f, 0.f, 0.f, 0.f, 0.f};
#pragma unroll 1
      for (int it = 0; it < 48; it++) {
        const int st = it & 3;
        mbar_wait(bar + 8 * st, (it >> 2) & 1);
        uint4 v[8];
#pragma unroll
        for (int k = 0; k < 8; k++) v[k] = lds4(sb + st * 40960 + k * 5120 + tid * 16);
        uint32_t h[4] = {0, 0, 0, 0};
#pragma unroll
        for (int k = 0; k < 8; k++) { sqacc(h[0], v[k].x); sqacc(h[1], v[k].y); sqacc(h[2], v[k].z); sqacc(h[3], v[k].w); }
        __syncwarp();
        if (lane == 0) mbar_arrive(bar + 8 * (4 + st));
#pragma unroll
        for (int k = 0; k < 4; k++) { c[2 * k] += bflo(h[k]); c[2 * k + 1] += bfhi(h[k]); }
      }
      float* red = (float*)(smem + 163840);
      *(float4*)(red + tid * 8) = make_float4(c[0], c[1], c[2], c[3]);
      *(float4*)(red + tid * 8 + 4) = make_float4(c[4], c[5], c[6], c[7]);
      bar_sync<1, 320>();
#pragma unroll
      for (int k = tid; k < DM; k += 320) g_nrm[q * DM + k] = (red[k] + red[DM + k]) + (red[2 * DM + k] + red[3 * DM + k]);
      asm volatile("griddepcontrol.wait;" ::: "memory");
      bar_sync<1, 320>();
      if (tid == 0) red_release(flags + FL_N, 1);
      GT(0, 2);
    }
    return;
  }
  __syncthreads();
  asm volatile("barrier.cluster.arrive.relaxed.aligned;" ::: "memory");
  if (layer == 0) asm volatile("griddepcontrol.wait;" ::: "memory");
  asm volatile("barrier.cluster.wait.aligned;" ::: "memory");
  if (wg == 2) {
    asm volatile("setmaxnreg.dec.sync.aligned.u32 40;");
    if (w == 0) {
      if (lane < 4) {
        mbar_expect(bar + 8 * lane, L_STAGE);
        bulk_g2s_mc(sb + lane * L_STAGE + 16384 + cr * 15360, g_w1 + (hg * 10 + lane) * 30720 + cr * 15360, 15360, bar + 8 * lane);
      }
      if (layer == 1) { if (LA_LATE) wait_flag(flags + FL_T + 15 * 8, LA_LATE); wait_flag(flags + FL_T + tb * 8, 8); fence_async_global(); }
      if (lane < 4) bulk_g2s(sb + lane * L_STAGE, g_xt + (tb * 10 + lane) * 16384, 16384, bar + 8 * lane);
#pragma unroll 1
      for (int kc = 4; kc < 10; kc++) {
        const int st = kc & 3;
        mbar_wait(bar + 8 * (4 + st), ((kc >> 2) & 1) ^ 1);
        if (lane == 0) {
          mbar_expect(bar + 8 * st, L_STAGE);
          bulk_g2s_mc(sb + st * L_STAGE + 16384 + cr * 15360, g_w1 + (hg * 10 + kc) * 30720 + cr * 15360, 15360, bar + 8 * st);
          bulk_g2s(sb + st * L_STAGE, g_xt + (tb * 10 + kc) * 16384, 16384, bar + 8 * st);
        }
        __syncwarp();
      }
    } else {
      const int t = tid - 288;
#pragma unroll 1
      for (int k = t; k < 768; k += 96) *(uint4*)(ar + blockIdx.x * 12288 + k * 16) = make_uint4(0, 0, 0, 0);
      if (layer == 0 || RD1) {
        float sv = 0.f;
        const uint4* pv = (const uint4*)((const uint8_t*)Wv + blockIdx.x * 61440) + t;
#pragma unroll 1
        for (int k = 0; k < 40; k += 5) {
          uint4 v[5];
#pragma unroll
          for (int j = 0; j < 5; j++) v[j] = __ldg(pv + (k + j) * 96);
          if (PF_IL && k < 25) {
            asm volatile("prefetch.global.L2 [%0];" :: "l"((const uint8_t*)Wq + blockIdx.x * 61440 + (k / 5) * 12288 + t * 128));
            if (PF_IL > 1) asm volatile("prefetch.global.L2 [%0];" :: "l"((const uint8_t*)Wk + blockIdx.x * 61440 + (k / 5) * 12288 + t * 128));
          }
#pragma unroll
          for (int j = 0; j < 5; j++) {
            sv = fmaf(bflo(v[j].x), bflo(v[j].x), fmaf(bfhi(v[j].x), bfhi(v[j].x), fmaf(bflo(v[j].y), bflo(v[j].y), fmaf(bfhi(v[j].y), bfhi(v[j].y), sv))));
            sv = fmaf(bflo(v[j].z), bflo(v[j].z), fmaf(bfhi(v[j].z), bfhi(v[j].z), fmaf(bflo(v[j].w), bflo(v[j].w), fmaf(bfhi(v[j].w), bfhi(v[j].w), sv))));
          }
        }
#pragma unroll
        for (int o = 16; o; o >>= 1) sv += __shfl_xor_sync(~0u, sv, o);
        if (lane == 0) atomicAdd((float*)(g_zero + Z_NORM + layer), sv);
      }
      if (layer == 1 && PF_LB) {
        const int l = blockIdx.x * 96 + t;
        if (l < 6720 + NLB * 640) asm volatile("prefetch.global.L2 [%0];" :: "l"(l < 6720 ? g_w2 + l * 128 : (const uint8_t*)g_x + (l - 6720) * 128));
      }
#pragma unroll 1
      for (int k = (layer && !RD1) ? 0 : 5 * PF_IL; k < 5 * (layer ? PF_N1 : PF_N0); k++) {
        const int m = k / 5;
        const bf16* W = m == 0 ? Wq : m == 1 ? Wk : m == 2 ? Wv : Wo;
        asm volatile("prefetch.global.L2 [%0];" :: "l"((const uint8_t*)W + blockIdx.x * 61440 + (k - m * 5) * 12288 + t * 128));
        __nanosleep(layer ? PF_SLEEP1 : PF_SLEEP);
      }
      if (t == 0) GTT(layer * 4, 14);
      bar_arrive<3, 352>();
    }
  } else {
    asm volatile("setmaxnreg.inc.sync.aligned.u32 232;");
    GT(layer * 4, 4);
    uint32_t pq[5][4];
    float* kv = (float*)(g_zero + Z_KV) + layer * KV_LAYER + hg * 1920;
    {
      float d[120];
#pragma unroll 1
      for (int kc = 0; kc < 10; kc++) {
        const int st = kc & 3;
        const uint64_t da = mkdesc(SB0 + st * L_STAGE + wg * 8192, 16, 1024, 1), db = mkdesc(SB0 + st * L_STAGE + 16384, 3840, 128, 0);
        mbar_wait(bar + 8 * st, (kc >> 2) & 1);
        wg_fence();
#pragma unroll
        for (int k = 0; k < 4; k++) wg_ss_n240_ta0_tb1(d, da + 2 * k, db + k * 480, kc | k);
        wg_commit();
        if (kc > 0) { wg_wait<1>(); if (lane < 2) mbar_arrive_cl(mapa(bar + 8 * (4 + ((kc - 1) & 3)), lane)); }
      }
      wg_wait<0>();
      pin<120>(d);
      GT(layer * 4, 5);
      bar_sync<1, 256>();
      const uint32_t kb = sb + L_KV + (wg * 8 + 2 * w + ((lane >> 3) & 1)) * 2688 + (lane >> 4) * 128 + (lane & 7) * 16;
#pragma unroll
      for (int j = 0; j < 5; j++) stsm4(kb + 1280 + j * 256, pack2(d[80 + 8 * j], d[81 + 8 * j]), pack2(d[82 + 8 * j], d[83 + 8 * j]), pack2(d[84 + 8 * j], d[85 + 8 * j]), pack2(d[86 + 8 * j], d[87 + 8 * j]));
      stsm2(kb + 2560, 0x3F803F80u, 0x3F803F80u);
#pragma unroll
      for (int j = 0; j < 5; j++) stsm4(kb + j * 256, phi2(d[40 + 8 * j], d[41 + 8 * j]), phi2(d[42 + 8 * j], d[43 + 8 * j]), phi2(d[44 + 8 * j], d[45 + 8 * j]), phi2(d[46 + 8 * j], d[47 + 8 * j]));
      fence_async();
      bar_sync<1, 256>();
      float e[44];
      {
        const uint64_t da = mkdesc(SB0 + L_KV + wg * 1024, 2688, 128, 0), db = mkdesc(SB0 + L_KV + 1280, 2688, 128, 0);
        wg_fence();
#pragma unroll
        for (int k = 0; k < 8; k++) wg_ss_n88_ta1_tb1(e, da + k * 336, db + k * 336, k);
        wg_commit();
        wg_wait<0>();
        pin<44>(e);
      }
#pragma unroll
      for (int h = 0; h < 2; h++) {
        const int row = wg * 64 + 16 * w + 8 * h + g;
        const int c = row < 80 ? 2 * i4 - (row / 20) * 20 : 100;
        float* dst = kv + row * 24 + c;
#pragma unroll
        for (int j = 0; j < 10; j++)
          asm volatile("{\n.reg .pred p;\nsetp.lt.u32 p, %3, 20;\n@p red.relaxed.gpu.global.add.v2.f32 [%0], {%1,%2};\n}" :: "l"(dst + 8 * j), "f"(e[4 * j + 2 * h]), "f"(e[4 * j + 2 * h + 1]), "r"(c + 8 * j) : "memory");
        asm volatile("{\n.reg .pred p;\nsetp.ne.u32 p, %2, 0;\n@p red.relaxed.gpu.global.add.f32 [%0], %1;\n}" :: "l"(kv + row * 24 + 20), "f"(e[40 + 2 * h]), "r"((int)(row < 80 && i4 == 0)) : "memory");
      }
      bar_sync<1, 256>();
      GT(layer * 4, 6);
      if (tid == 0) { red_release(flags + FL_KV + hg * 8, 1); }
      __syncwarp();
      pin<40>(d);
#pragma unroll
      for (int k = 0; k < 5; k++) {
        pq[k][0] = phi2(d[8 * k], d[8 * k + 1]); pq[k][1] = phi2(d[8 * k + 2], d[8 * k + 3]);
        pq[k][2] = phi2(d[8 * k + 4], d[8 * k + 5]); pq[k][3] = phi2(d[8 * k + 6], d[8 * k + 7]);
      }
    }
#pragma unroll 1
    for (int k = tid; k < 1600; k += 256) sts4(sb + L_B2 + k * 16, 0, 0, 0, 0);
    GT(layer * 4, 7);
    if (wid == 0) wait_flag(flags + FL_KV + hg * 8, 16);
    GT(layer * 4, 8);
    bar_sync<1, 256>();
    if (tid < 240) {
      const int dd = tid / 3, part = tid - dd * 3, n = (dd / 20) * 20 + 8 * part;
      const float4 v0 = __ldcg((const float4*)(kv + dd * 24 + 8 * part)), v1 = __ldcg((const float4*)(kv + dd * 24 + 8 * part + 4));
      const float z = __ldcg(kv + dd * 24 + 20);
      const uint32_t a = sb + L_B2 + (dd >> 3) * 2560 + (dd & 7) * 16, zz = pack2(z, z);
      const uint32_t a0 = a + (n >> 3) * 128 + (n & 7) * 2, a1 = a + ((n + 4) >> 3) * 128 + ((n + 4) & 7) * 2;
      sts2(a0, pack2(v0.x, v0.y), pack2(v0.z, v0.w)); sts2(a0 + 1280, zz, zz);
      if (part < 2) { sts2(a1, pack2(v1.x, v1.y), pack2(v1.z, v1.w)); sts2(a1 + 1280, zz, zz); }
    }
    fence_async();
    bar_sync<1, 256>();
    {
      float o[80];
      const uint64_t db = mkdesc(SB0 + L_B2, 2560, 128, 0);
      wg_fence();
#pragma unroll
      for (int k = 0; k < 5; k++) wg_rs_n160_tb1(o, pq[k], db + k * 320, k);
      wg_commit();
      wg_wait<0>();
      pin<80>(o);
      uint8_t* op = g_oa + (tb * 2 + wg) * 81920 + hg * 10240 + w * 256 + lane * 4;
#pragma unroll
      for (int j = 0; j < 20; j++) {
        const float inv = rcp(o[40 + 2 * j] + 1e-6f);
        *(uint32_t*)(op + (j >> 1) * 1024 + (j & 1) * 128) = pack2(o[2 * j] * inv, o[2 * j + 1] * inv);
      }
      GT(layer * 4, 9);
    }
    bar_sync<3, 352>();
    if (tid == 0) { red_release(flags + FL_O + tb * 8, 1); red_add(flags + FL_X, 1); }
    GT(layer * 4, 2);
    if (wid == 7) asm volatile("griddepcontrol.wait;" ::: "memory");
  }
}

__global__ void __launch_bounds__(256) prep_kernel(const bf16* __restrict__ x, const bf16* __restrict__ wqkv, const bf16* __restrict__ wo) {
  asm volatile("griddepcontrol.launch_dependents;");
  const int b = blockIdx.x, tid = threadIdx.x, lane = tid & 31;
  if (b < 160) GT(3, 0);
  if (b < 256) {
    const int row = b * 8 + (tid >> 5);
    float v[20], s = 0.f;
#pragma unroll
    for (int k = 0; k < 10; k++) { const uint32_t u = __ldg((const uint32_t*)(x + row * DM + k * 64 + lane * 2)); v[2 * k] = bflo(u); v[2 * k + 1] = bfhi(u); s += v[2 * k] + v[2 * k + 1]; }
#pragma unroll
    for (int o = 16; o; o >>= 1) s += __shfl_xor_sync(~0u, s, o);
    const float m = s * (1.f / DM);
    float q = 0.f;
#pragma unroll
    for (int k = 0; k < 20; k++) { v[k] -= m; q += v[k] * v[k]; }
#pragma unroll
    for (int o = 16; o; o >>= 1) q += __shfl_xor_sync(~0u, q, o);
    const float r = rsqrtf(q * (1.f / DM) + 1e-5f);
#pragma unroll
    for (int k = 0; k < 10; k++)
      *(uint32_t*)(g_xt + ((row >> 7) * 10 + k) * 16384 + (row & 127) * 128 + (((lane >> 2) ^ (row & 7)) << 4) + (lane & 3) * 4) = pack2(v[2 * k] * r, v[2 * k + 1] * r);
  } else if (b < 256 + 203) {
    uint4 v[4];
    const int u0 = (b - 256) * 1024 + tid;
#pragma unroll
    for (int it = 0; it < 4; it++) {
      const int u = u0 + it * 256, k8 = u & 7;
      const bf16* src;
      bool ok = true;
      if (b < 256 + 150) {
        const int nb = (u >> 3) % 30, kg = (u / 240) % 80, hg = u / 19200;
        src = wqkv + (kg * 8 + k8) * 1920 + (nb / 10) * 640 + hg * 80 + (nb % 10) * 8;
      } else {
        const int q = u - 153600, nb = (q >> 3) % 28, kg = (q / 224) % 80, c = (q / 17920) * 224 + nb * 8;
        ok = c < DM;
        src = wo + (kg * 8 + k8) * DM + (ok ? c : 0);
      }
      v[it] = __ldg((const uint4*)src);
      if (!ok) v[it] = make_uint4(0, 0, 0, 0);
    }
    uint8_t* dst = b < 256 + 150 ? g_w1 + u0 * 16 : g_w2 + (u0 - 153600) * 16;
#pragma unroll
    for (int it = 0; it < 4; it++) if (u0 + it * 256 < 207360) *(uint4*)(dst + it * 4096) = v[it];
  } else {
    const int t = (b - 459) * 256 + tid;
    for (int k = t; k < Z_END / 4; k += 16 * 256) ((uint4*)g_zero)[k] = make_uint4(0, 0, 0, 0);
    for (int k = t; k < 16 * DM; k += 16 * 256) { ((uint4*)g_acc)[k] = make_uint4(0, 0, 0, 0); ((uint4*)(g_acc + S_TOK * DM))[k] = make_uint4(0, 0, 0, 0); }
  }
  if (b < 160) GT(3, 2);
}

typedef CUresult (*EncodeFn)(CUtensorMap*, CUtensorMapDataType, cuuint32_t, void*, const cuuint64_t*, const cuuint64_t*, const cuuint32_t*,
                             const cuuint32_t*, CUtensorMapInterleave, CUtensorMapSwizzle, CUtensorMapL2promotion, CUtensorMapFloatOOBfill);
static void make_map(EncodeFn fn, CUtensorMap* m, const void* p, uint64_t cols, uint64_t rows, uint32_t bc, uint32_t br, CUtensorMapSwizzle sw) {
  cuuint64_t dims[2] = {cols, rows}; cuuint64_t strides[1] = {cols * 2}; cuuint32_t box[2] = {bc, br}; cuuint32_t es[2] = {1, 1};
  fn(m, CU_TENSOR_MAP_DATA_TYPE_BFLOAT16, 2, (void*)p, dims, strides, box, es, CU_TENSOR_MAP_INTERLEAVE_NONE, sw,
     CU_TENSOR_MAP_L2_PROMOTION_L2_128B, CU_TENSOR_MAP_FLOAT_OOB_FILL_NONE);
}

static void make_map_perm(EncodeFn fn, CUtensorMap* m, const void* p) {
  cuuint64_t dims[5] = {HE, 2, 2, 4, 40}; const cuuint64_t r = HE * 2; cuuint64_t strides[4] = {r, 8 * r, 2 * r, 16 * r};
  cuuint32_t box[5] = {64, 2, 2, 4, 4}; cuuint32_t es[5] = {1, 1, 1, 1, 1};
  fn(m, CU_TENSOR_MAP_DATA_TYPE_BFLOAT16, 5, (void*)p, dims, strides, box, es, CU_TENSOR_MAP_INTERLEAVE_NONE, CU_TENSOR_MAP_SWIZZLE_128B,
     CU_TENSOR_MAP_L2_PROMOTION_L2_128B, CU_TENSOR_MAP_FLOAT_OOB_FILL_NONE);
}

#define OPC_PDL 1
#define LA_PDL 1
#define REC_PDL 1
extern "C" void kernel_launch(void* const* d_in, const int* in_sizes, int n_in, void* d_out, int out_size) {
  const bf16* x = (const bf16*)d_in[0];
  const bf16* wqkv = (const bf16*)d_in[1];
  const bf16* wo_a = (const bf16*)d_in[2];
  const bf16* mem0 = (const bf16*)d_in[4];
  const bf16* Wq = (const bf16*)d_in[5];
  const bf16* Wk = (const bf16*)d_in[6];
  const bf16* Wv = (const bf16*)d_in[7];
  const bf16* Wo = (const bf16*)d_in[8];
  cudaStream_t st = cudaStreamPerThread;

  static EncodeFn enc = nullptr;
  static uint8_t* p_ar; static uint32_t* p_zero; static bf16* p_x;
  if (!enc) {
    cudaDriverEntryPointQueryResult qr;
    void* fn = nullptr;
    cudaGetDriverEntryPoint("cuTensorMapEncodeTiled", &fn, cudaEnableDefault, &qr);
    enc = (EncodeFn)fn;
    cudaFuncSetAttribute(rec_kernel, cudaFuncAttributeMaxDynamicSharedMemorySize, REC_SMEM);
    cudaFuncSetAttribute(opc_kernel, cudaFuncAttributeMaxDynamicSharedMemorySize, OPC_SMEM);
    cudaFuncSetAttribute(la_kernel, cudaFuncAttributeMaxDynamicSharedMemorySize, LA_SMEM);
    cudaGetSymbolAddress((void**)&p_ar, g_ar); p_ar = (uint8_t*)(((uintptr_t)p_ar + 32767) & ~(uintptr_t)32767);
    cudaGetSymbolAddress((void**)&p_zero, g_zero); cudaGetSymbolAddress((void**)&p_x, g_x);
  }
  CUtensorMap tmq, tmk, tmv, tmo, tmx[2];
  make_map_perm(enc, &tmq, Wq);
  make_map_perm(enc, &tmk, Wk);
  make_map_perm(enc, &tmv, Wv);
  make_map(enc, &tmo, Wo, DM, HE, 64, 64, CU_TENSOR_MAP_SWIZZLE_128B);
  make_map(enc, &tmx[0], x, DM, S_TOK, 232, 64, CU_TENSOR_MAP_SWIZZLE_NONE);
  make_map(enc, &tmx[1], p_x, DM, S_TOK, 232, 64, CU_TENSOR_MAP_SWIZZLE_NONE);

  cudaLaunchAttribute at[2];
  at[0].id = cudaLaunchAttributeProgrammaticStreamSerialization; at[0].val.programmaticStreamSerializationAllowed = 1;
  at[1].id = cudaLaunchAttributeClusterDimension; at[1].val.clusterDim.x = 3; at[1].val.clusterDim.y = 1; at[1].val.clusterDim.z = 1;
  cudaLaunchAttribute at2[2] = {at[1], at[0]};
  at2[0].val.clusterDim.x = 2;
  prep_kernel<<<475, 256, 0, st>>>(x, wqkv, wo_a);
  for (int l = 0; l < 2; l++) {
    cudaLaunchConfig_t cfg = {};
    cfg.blockDim = dim3(384); cfg.stream = st;
    cfg.gridDim = dim3(l == 0 ? 132 : 128); cfg.dynamicSmemBytes = LA_SMEM; cfg.attrs = at2; cfg.numAttrs = 1 + LA_PDL;
    cudaLaunchKernelEx(&cfg, la_kernel, Wq, Wk, Wv, Wo, p_ar + l * AR_LAYER, l);
    cfg.gridDim = dim3(96 + 3 * NLB); cfg.dynamicSmemBytes = REC_SMEM; cfg.attrs = at + 1 - REC_PDL; cfg.numAttrs = 1 + REC_PDL;
    cudaLaunchKernelEx(&cfg, rec_kernel, tmq, tmk, tmv, tmo, tmx[l], mem0, p_ar + l * AR_LAYER, p_zero + Z_FLAGS + l * FL_LAYER, l);
    cfg.gridDim = dim3(36); cfg.dynamicSmemBytes = OPC_SMEM; cfg.attrs = at; cfg.numAttrs = OPC_PDL;
    cudaLaunchKernelEx(&cfg, opc_kernel, tmo, l == 1 ? (bf16*)d_out : (bf16*)nullptr, l, Wq, Wk, Wv, Wo);
  }
}
```

```cpp
#include <cuda_runtime.h>
#include <cuda_bf16.h>
#include <cuda.h>
#include <stdint.h>

typedef __nv_bfloat16 bf16;
typedef unsigned long long u64;

constexpr int S_TOK = 2048, DM = 640, DH = 192, HE = 6144, NSEG = 64;

constexpr int AR_GROUP = 98304;
constexpr int AR_LAYER = 16 * AR_GROUP;
__device__ __align__(1024) uint8_t g_ar[2 * AR_LAYER + 32768];
__device__ __align__(1024) uint8_t g_xn[NSEG * 40960];
__device__ __align__(1024) uint8_t g_xt[S_TOK * DM * 2];
__device__ __align__(1024) uint8_t g_ot[NSEG * HE * 64];
__device__ __align__(1024) uint8_t g_oa[S_TOK * DM * 2];
__device__ __align__(1024) uint8_t g_w1[DM * 1920 * 2];
__device__ __align__(1024) uint8_t g_w2[DM * 672 * 2];
__device__ __align__(1024) float g_acc[2 * S_TOK * DM];
__device__ __align__(1024) bf16 g_x[S_TOK * DM];
constexpr int FL_A = 0, FL_B = 64 * 6 * 8, FL_KV = FL_B + 64 * 8, FL_O = FL_KV + 8 * 8, FL_T = FL_O + 16 * 8, FL_X = FL_T + 16 * 8, FL_N = FL_X + 8, FL_R = FL_N + 8, FL_XN = FL_R + 8, FL_LAYER = FL_XN + 32 * 8;
constexpr int Z_FLAGS = 0, Z_NORM = 2 * FL_LAYER, Z_KV = Z_NORM + 8, KV_LAYER = 8 * 80 * 24, Z_END = Z_KV + 2 * KV_LAYER;
__device__ __align__(128) uint32_t g_zero[Z_END];
__device__ __align__(128) float g_nrm[4 * DM];
#define GT(slot, k) do {} while (0)
#define GTT(slot, k) do {} while (0)

__device__ __forceinline__ uint32_t smem_u32(const void* p) { return (uint32_t)__cvta_generic_to_shared(p); }
__device__ __forceinline__ uint32_t mapa(uint32_t a, uint32_t r) { uint32_t o; asm("mapa.shared::cluster.u32 %0, %1, %2;" : "=r"(o) : "r"(a), "r"(r)); return o; }
__device__ __forceinline__ void mbar_init(uint32_t bar, uint32_t cnt) { asm volatile("mbarrier.init.shared::cta.b64 [%0], %1;" :: "r"(bar), "r"(cnt) : "memory"); }
__device__ __forceinline__ void mbar_expect(uint32_t bar, uint32_t tx) { asm volatile("mbarrier.arrive.expect_tx.shared::cta.b64 _, [%0], %1;" :: "r"(bar), "r"(tx) : "memory"); }
__device__ __forceinline__ void mbar_arrive(uint32_t bar) { asm volatile("mbarrier.arrive.shared::cta.b64 _, [%0];" :: "r"(bar) : "memory"); }
__device__ __forceinline__ void mbar_wait(uint32_t bar, uint32_t par) {
  asm volatile("{\n.reg .pred p;\n.reg .u32 c;\nmov.u32 c, 0;\n"
               "LW:\nmbarrier.try_wait.parity.shared::cta.b64 p, [%0], %1;\n@p bra LD;\n"
               "add.u32 c, c, 1;\nsetp.lt.u32 p, c, 4000000;\n@p bra LW;\ntrap;\nLD:\n}" :: "r"(bar), "r"(par) : "memory");
}
__device__ __forceinline__ void mbar_waitf(uint32_t bar, uint32_t par) {
  asm volatile("{\n.reg .pred p, q;\n.reg .u32 c;\nmov.u32 c, 0;\n"
               "LW:\nadd.u32 c, c, 1;\nsetp.lt.u32 q, c, 1000000;\nmbarrier.try_wait.parity.shared::cta.b64 p, [%0], %1;\n"
               "and.pred q, q, !p;\n@q bra LW;\n}" :: "r"(bar), "r"(par) : "memory");
}
template <int ID, int N> __device__ __forceinline__ void bar_sync() { asm volatile("barrier.sync %0, %1;" :: "n"(ID), "n"(N) : "memory"); }
template <int ID, int N> __device__ __forceinline__ void bar_arrive() { asm volatile("barrier.arrive %0, %1;" :: "n"(ID), "n"(N) : "memory"); }
__device__ __forceinline__ void fence_async() { asm volatile("fence.proxy.async.shared::cta;" ::: "memory"); }
__device__ __forceinline__ void cluster_sync() { asm volatile("barrier.cluster.arrive.aligned;\nbarrier.cluster.wait.aligned;" ::: "memory"); }
__device__ __forceinline__ void wg_fence() { asm volatile("wgmma.fence.sync.aligned;" ::: "memory"); }
__device__ __forceinline__ void wg_commit() { asm volatile("wgmma.commit_group.sync.aligned;" ::: "memory"); }
template <int N> __device__ __forceinline__ void wg_wait() { asm volatile("wgmma.wait_group.sync.aligned %0;" :: "n"(N) : "memory"); }
template <int N> __device__ __forceinline__ void pin(float* d) {
#pragma unroll
  for (int i = 0; i < N; i++) asm volatile("" : "+f"(d[i]) :: "memory");
}
__device__ __forceinline__ constexpr uint64_t mkdesc(uint32_t addr, uint32_t lbo, uint32_t sbo, int sw) {
  return (uint64_t)((addr & 0x3FFFF) >> 4) | ((uint64_t)(lbo >> 4) << 16) | ((uint64_t)(sbo >> 4) << 32) | ((uint64_t)sw << 62);
}
constexpr uint32_t SB0 = 1024;
__device__ __forceinline__ void check_smem_base(uint32_t sb) { if ((sb & 0x3FFFF) != SB0) __trap(); }
__device__ __forceinline__ uint32_t cta_rank() { uint32_t r; asm volatile("mov.u32 %0, %%cluster_ctarank;" : "=r"(r)); return r; }
__device__ __forceinline__ uint32_t opaque(uint32_t v) { uint32_t o; asm volatile("mov.u32 %0, %1;" : "=r"(o) : "r"(v)); return o; }
__device__ __forceinline__ uint32_t pack2(float lo, float hi) { uint32_t r; asm("cvt.rn.bf16x2.f32 %0, %1, %2;" : "=r"(r) : "f"(hi), "f"(lo)); return r; }
__device__ __forceinline__ void ldsm4(uint32_t* r, uint32_t a) { asm volatile("ldmatrix.sync.aligned.m8n8.x4.shared.b16 {%0,%1,%2,%3}, [%4];" : "=r"(r[0]), "=r"(r[1]), "=r"(r[2]), "=r"(r[3]) : "r"(a) : "memory"); }
__device__ __forceinline__ void ldsm4t(uint32_t* r, uint32_t a) { asm volatile("ldmatrix.sync.aligned.m8n8.x4.trans.shared.b16 {%0,%1,%2,%3}, [%4];" : "=r"(r[0]), "=r"(r[1]), "=r"(r[2]), "=r"(r[3]) : "r"(a) : "memory"); }
__device__ __forceinline__ void ldsm1(uint32_t& r, uint32_t a) { asm volatile("ldmatrix.sync.aligned.m8n8.x1.shared.b16 {%0}, [%1];" : "=r"(r) : "r"(a) : "memory"); }
__device__ __forceinline__ void stsm4(uint32_t a, uint32_t r0, uint32_t r1, uint32_t r2, uint32_t r3) { asm volatile("stmatrix.sync.aligned.m8n8.x4.shared.b16 [%0], {%1,%2,%3,%4};" :: "r"(a), "r"(r0), "r"(r1), "r"(r2), "r"(r3) : "memory"); }
__device__ __forceinline__ void stsm1(uint32_t a, uint32_t r0) { asm volatile("stmatrix.sync.aligned.m8n8.x1.shared.b16 [%0], {%1};" :: "r"(a), "r"(r0) : "memory"); }
__device__ __forceinline__ void stsm4t(uint32_t a, uint32_t r0, uint32_t r1, uint32_t r2, uint32_t r3) { asm volatile("stmatrix.sync.aligned.m8n8.x4.trans.shared.b16 [%0], {%1,%2,%3,%4};" :: "r"(a), "r"(r0), "r"(r1), "r"(r2), "r"(r3) : "memory"); }
__device__ __forceinline__ void stsm2t(uint32_t a, uint32_t r0, uint32_t r1) { asm volatile("stmatrix.sync.aligned.m8n8.x2.trans.shared.b16 [%0], {%1,%2};" :: "r"(a), "r"(r0), "r"(r1) : "memory"); }
__device__ __forceinline__ void mma16816(float* c, const uint32_t* a, uint32_t b0, uint32_t b1) {
  asm volatile("mma.sync.aligned.m16n8k16.row.col.f32.bf16.bf16.f32 {%0,%1,%2,%3}, {%4,%5,%6,%7}, {%8,%9}, {%0,%1,%2,%3};"
               : "+f"(c[0]), "+f"(c[1]), "+f"(c[2]), "+f"(c[3]) : "r"(a[0]), "r"(a[1]), "r"(a[2]), "r"(a[3]), "r"(b0), "r"(b1));
}
__device__ __forceinline__ void mma1688(float* c, uint32_t a0, uint32_t a1, uint32_t b0) {
  asm volatile("mma.sync.aligned.m16n8k8.row.col.f32.bf16.bf16.f32 {%0,%1,%2,%3}, {%4,%5}, {%6}, {%0,%1,%2,%3};"
               : "+f"(c[0]), "+f"(c[1]), "+f"(c[2]), "+f"(c[3]) : "r"(a0), "r"(a1), "r"(b0));
}
__device__ __forceinline__ void sta1(uint32_t a, uint32_t v, uint32_t bar) { asm volatile("st.async.weak.shared::cluster.mbarrier::complete_tx::bytes.b32 [%0], %1, [%2];" :: "r"(a), "r"(v), "r"(bar) : "memory"); }
__device__ __forceinline__ void sta1p(uint32_t a, uint32_t v, uint32_t bar, bool p) { asm volatile("{\n.reg .pred p;\nsetp.ne.b32 p, %3, 0;\n@p st.async.weak.shared::cluster.mbarrier::complete_tx::bytes.b32 [%0], %1, [%2];\n}" :: "r"(a), "r"(v), "r"(bar), "r"((int)p) : "memory"); }
__device__ __forceinline__ void sta2(uint32_t a, uint32_t v0, uint32_t v1, uint32_t bar) { asm volatile("st.async.weak.shared::cluster.mbarrier::complete_tx::bytes.v2.b32 [%0], {%1,%2}, [%3];" :: "r"(a), "r"(v0), "r"(v1), "r"(bar) : "memory"); }
__device__ __forceinline__ void sta4(uint32_t a, uint32_t v0, uint32_t v1, uint32_t v2, uint32_t v3, uint32_t bar) { asm volatile("st.async.weak.shared::cluster.mbarrier::complete_tx::bytes.v4.b32 [%0], {%1,%2,%3,%4}, [%5];" :: "r"(a), "r"(v0), "r"(v1), "r"(v2), "r"(v3), "r"(bar) : "memory"); }
__device__ __forceinline__ float bflo(uint32_t v) { return __uint_as_float(v << 16); }
__device__ __forceinline__ float bfhi(uint32_t v) { return __uint_as_float(v & 0xFFFF0000u); }
__device__ __forceinline__ void sta2f(uint32_t a, float v0, float v1, uint32_t bar) { asm volatile("st.async.weak.shared::cluster.mbarrier::complete_tx::bytes.v2.f32 [%0], {%1,%2}, [%3];" :: "r"(a), "f"(v0), "f"(v1), "r"(bar) : "memory"); }
__device__ __forceinline__ void sta4f(uint32_t a, float v0, float v1, float v2, float v3, uint32_t bar) { asm volatile("st.async.weak.shared::cluster.mbarrier::complete_tx::bytes.v4.f32 [%0], {%1,%2,%3,%4}, [%5];" :: "r"(a), "f"(v0), "f"(v1), "f"(v2), "f"(v3), "r"(bar) : "memory"); }
__device__ __forceinline__ float4 lds4f(uint32_t a) { float4 v; asm volatile("ld.shared.v4.f32 {%0,%1,%2,%3}, [%4];" : "=f"(v.x), "=f"(v.y), "=f"(v.z), "=f"(v.w) : "r"(a) : "memory"); return v; }
__device__ __forceinline__ float2 lds2f(uint32_t a) { float2 v; asm volatile("ld.shared.v2.f32 {%0,%1}, [%2];" : "=f"(v.x), "=f"(v.y) : "r"(a) : "memory"); return v; }
__device__ __forceinline__ uint4 lds4(uint32_t a) { uint4 v; asm volatile("ld.shared.v4.u32 {%0,%1,%2,%3}, [%4];" : "=r"(v.x), "=r"(v.y), "=r"(v.z), "=r"(v.w) : "r"(a) : "memory"); return v; }
__device__ __forceinline__ uint32_t lds1(uint32_t a) { uint32_t v; asm volatile("ld.shared.u32 %0, [%1];" : "=r"(v) : "r"(a) : "memory"); return v; }
__device__ __forceinline__ void stsm2(uint32_t a, uint32_t r0, uint32_t r1) { asm volatile("stmatrix.sync.aligned.m8n8.x2.shared.b16 [%0], {%1,%2};" :: "r"(a), "r"(r0), "r"(r1) : "memory"); }
__device__ __forceinline__ float rcp(float x) { float y; asm("rcp.approx.ftz.f32 %0, %1;" : "=f"(y) : "f"(x)); return y; }
__device__ __forceinline__ void sts4(uint32_t a, uint32_t v0, uint32_t v1, uint32_t v2, uint32_t v3) { asm volatile("st.shared.v4.u32 [%0], {%1,%2,%3,%4};" :: "r"(a), "r"(v0), "r"(v1), "r"(v2), "r"(v3) : "memory"); }
__device__ __forceinline__ void bulk_s2c(uint32_t dst, uint32_t src, uint32_t bytes, uint32_t bar) {
  asm volatile("cp.async.bulk.shared::cluster.shared::cta.mbarrier::complete_tx::bytes [%0], [%1], %2, [%3];" :: "r"(dst), "r"(src), "r"(bytes), "r"(bar) : "memory");
}
__device__ __forceinline__ void stg4(void* p, uint4 v) { asm volatile("st.global.v4.u32 [%0], {%1,%2,%3,%4};" :: "l"(p), "r"(v.x), "r"(v.y), "r"(v.z), "r"(v.w) : "memory"); }
__device__ __forceinline__ void red_add(uint32_t* p, uint32_t v) { asm volatile("red.relaxed.gpu.global.add.u32 [%0], %1;" :: "l"(p), "r"(v) : "memory"); }
__device__ __forceinline__ void red_release(uint32_t* p, uint32_t v) { asm volatile("red.release.gpu.global.add.u32 [%0], %1;" :: "l"(p), "r"(v) : "memory"); }
__device__ __forceinline__ void fence_async_global() { asm volatile("fence.proxy.async.global;" ::: "memory"); }
__device__ __forceinline__ uint64_t policy_evict_first() { uint64_t p; asm("createpolicy.fractional.L2::evict_first.b64 %0, 1.0;" : "=l"(p)); return p; }
__device__ __forceinline__ void stg4h(void* p, uint4 v, uint64_t pol) { asm volatile("st.global.L2::cache_hint.v4.u32 [%0], {%1,%2,%3,%4}, %5;" :: "l"(p), "r"(v.x), "r"(v.y), "r"(v.z), "r"(v.w), "l"(pol) : "memory"); }
__device__ __forceinline__ void red4fh(float* p, float a, float b, float c, float d, uint64_t pol) { asm volatile("red.relaxed.gpu.global.add.L2::cache_hint.v4.f32 [%0], {%1,%2,%3,%4}, %5;" :: "l"(p), "f"(a), "f"(b), "f"(c), "f"(d), "l"(pol) : "memory"); }
__device__ __forceinline__ float4 ldg4fh(const float* p, uint64_t pol) { float4 v; asm volatile("ld.global.cg.L2::cache_hint.v4.f32 {%0,%1,%2,%3}, [%4], %5;" : "=f"(v.x), "=f"(v.y), "=f"(v.z), "=f"(v.w) : "l"(p), "l"(pol) : "memory"); return v; }
__device__ __forceinline__ void bulk_g2sh(uint32_t dst, const void* src, uint32_t bytes, uint32_t bar, uint64_t pol) {
  asm volatile("cp.async.bulk.shared::cluster.global.mbarrier::complete_tx::bytes.L2::cache_hint [%0], [%1], %2, [%3], %4;" :: "r"(dst), "l"(src), "r"(bytes), "r"(bar), "l"(pol) : "memory");
}
#define EVF 1
__device__ __forceinline__ void red4f(float* p, float a, float b, float c, float d) { asm volatile("red.relaxed.gpu.global.add.v4.f32 [%0], {%1,%2,%3,%4};" :: "l"(p), "f"(a), "f"(b), "f"(c), "f"(d) : "memory"); }
template <int SLEEP = 20>
__device__ __forceinline__ void wait_flag(const uint32_t* p, uint32_t target) {
  uint32_t v; int it = 0;
  while (true) {
    asm volatile("ld.acquire.gpu.global.u32 %0, [%1];" : "=r"(v) : "l"(p) : "memory");
    if (__all_sync(~0u, v >= target)) break;
    if (++it > 4000000) __trap();
    __nanosleep(SLEEP);
  }
}
__device__ __forceinline__ void sts2(uint32_t a, uint32_t v0, uint32_t v1) { asm volatile("st.shared.v2.u32 [%0], {%1,%2};" :: "r"(a), "r"(v0), "r"(v1) : "memory"); }
__device__ __forceinline__ float sqrt_approx(float x) { float y; asm("sqrt.approx.f32 %0, %1;" : "=f"(y) : "f"(x)); return y; }
template <int BYTES> __device__ __forceinline__ void bulk_s2c_elect(uint32_t d1, uint32_t b1, uint32_t d2, uint32_t b2, uint32_t src) {
  asm volatile("{\n.reg .pred p;\nelect.sync _|p, 0xffffffff;\n"
               "@p cp.async.bulk.shared::cluster.shared::cta.mbarrier::complete_tx::bytes [%0], [%4], %5, [%1];\n"
               "@p cp.async.bulk.shared::cluster.shared::cta.mbarrier::complete_tx::bytes [%2], [%4], %5, [%3];\n}"
               :: "r"(d1), "r"(b1), "r"(d2), "r"(b2), "r"(src), "n"(BYTES) : "memory");
}
template <int BYTES> __device__ __forceinline__ void bulk_s2c_elect1(uint32_t d, uint32_t b, uint32_t src) {
  asm volatile("{\n.reg .pred p;\nelect.sync _|p, 0xffffffff;\n"
               "@p cp.async.bulk.shared::cluster.shared::cta.mbarrier::complete_tx::bytes [%0], [%2], %3, [%1];\n}" :: "r"(d), "r"(b), "r"(src), "n"(BYTES) : "memory");
}
template <int BYTES> __device__ __forceinline__ void bulk_g2s_elect(uint32_t d, const void* src, uint32_t b) {
  asm volatile("{\n.reg .pred p;\nelect.sync _|p, 0xffffffff;\n"
               "@p cp.async.bulk.shared::cluster.global.mbarrier::complete_tx::bytes [%0], [%1], %3, [%2];\n}" :: "r"(d), "l"(src), "r"(b), "n"(BYTES) : "memory");
}
__device__ __forceinline__ void mbar_arrive_elect(uint32_t bar) { asm volatile("{\n.reg .pred p;\nelect.sync _|p, 0xffffffff;\n@p mbarrier.arrive.shared::cta.b64 _, [%0];\n}" :: "r"(bar) : "memory"); }
__device__ __forceinline__ void cp16(uint32_t dst, const void* src) { asm volatile("cp.async.cg.shared.global [%0], [%1], 16;" :: "r"(dst), "l"(src) : "memory"); }
__device__ __forceinline__ void sts1(uint32_t a, uint32_t v) { asm volatile("st.shared.u32 [%0], %1;" :: "r"(a), "r"(v) : "memory"); }
__device__ __forceinline__ void bulk_g2s(uint32_t dst, const void* src, uint32_t bytes, uint32_t bar) {
  asm volatile("cp.async.bulk.shared::cluster.global.mbarrier::complete_tx::bytes [%0], [%1], %2, [%3];" :: "r"(dst), "l"(src), "r"(bytes), "r"(bar) : "memory");
}
__device__ __forceinline__ void bulk_g2s_mc(uint32_t dst, const void* src, uint32_t bytes, uint32_t bar) {
  asm volatile("cp.async.bulk.shared::cluster.global.mbarrier::complete_tx::bytes.multicast::cluster [%0], [%1], %2, [%3], %4;" :: "r"(dst), "l"(src), "r"(bytes), "r"(bar), "h"((uint16_t)3) : "memory");
}
__device__ __forceinline__ void mbar_arrive_cl(uint32_t bar) { asm volatile("mbarrier.arrive.shared::cluster.b64 _, [%0];" :: "r"(bar) : "memory"); }
__device__ __forceinline__ void mbar_arrive_clp(uint32_t bar, bool p) { asm volatile("{\n.reg .pred p;\nsetp.ne.b32 p, %1, 0;\n@p mbarrier.arrive.shared::cluster.b64 _, [%0];\n}" :: "r"(bar), "r"((int)p) : "memory"); }
__device__ __forceinline__ void tma2d(uint32_t dst, const CUtensorMap* m, int c0, int c1, uint32_t bar) {
  asm volatile("cp.async.bulk.tensor.2d.shared::cluster.global.mbarrier::complete_tx::bytes [%0], [%1, {%3, %4}], [%2];" :: "r"(dst), "l"((uint64_t)m), "r"(bar), "r"(c0), "r"(c1) : "memory");
}
__device__ __forceinline__ void tma5d(uint32_t dst, const CUtensorMap* m, int c0, int c4, uint32_t bar) {
  asm volatile("cp.async.bulk.tensor.5d.shared::cluster.global.mbarrier::complete_tx::bytes [%0], [%1, {%3, %5, %5, %5, %4}], [%2];" :: "r"(dst), "l"((uint64_t)m), "r"(bar), "r"(c0), "r"(c4), "r"(0) : "memory");
}
__device__ __forceinline__ void red64(void* p, uint32_t lo, uint32_t hi) { asm volatile("{\n.reg .b64 t;\nmov.b64 t, {%1,%2};\nred.relaxed.gpu.global.add.u64 [%0], t;\n}" :: "l"(p), "r"(lo), "r"(hi) : "memory"); }
__device__ __forceinline__ uint4 ld_poll(const void* p) {
  uint4 v;
  asm volatile("{\n.reg .b64 a, b;\nld.relaxed.gpu.global.v2.b64 {a, b}, [%4];\nmov.b64 {%0,%1}, a;\nmov.b64 {%2,%3}, b;\n}" : "=r"(v.x), "=r"(v.y), "=r"(v.z), "=r"(v.w) : "l"(p) : "memory");
  return v;
}
__device__ __forceinline__ uint32_t clk() { uint32_t c; asm volatile("mov.u32 %0, %%clock;" : "=r"(c) :: "memory"); return c; }
#define SCHED_FENCE() asm volatile("pmevent 0;" ::: "memory")
__device__ __forceinline__ float ex2(float x) { float y; asm("ex2.approx.ftz.f32 %0, %1;" : "=f"(y) : "f"(x)); return y; }

__device__ __forceinline__ void wg_ss_n240_ta0_tb1(float* d, uint64_t a, uint64_t b, int sc) {
  asm volatile("{\n.reg .pred p;\nsetp.ne.b32 p, %122, 0;\nwgmma.mma_async.sync.aligned.m64n240k16.f32.bf16.bf16 {%0, %1, %2, %3, %4, %5, %6, %7, %8, %9, %10, %11, %12, %13, %14, %15, %16, %17, %18, %19, %20, %21, %22, %23, %24, %25, %26, %27, %28, %29, %30, %31, %32, %33, %34, %35, %36, %37, %38, %39, %40, %41, %42, %43, %44, %45, %46, %47, %48, %49, %50, %51, %52, %53, %54, %55, %56, %57, %58, %59, %60, %61, %62, %63, %64, %65, %66, %67, %68, %69, %70, %71, %72, %73, %74, %75, %76, %77, %78, %79, %80, %81, %82, %83, %84, %85, %86, %87, %88, %89, %90, %91, %92, %93, %94, %95, %96, %97, %98, %99, %100, %101, %102, %103, %104, %105, %106, %107, %108, %109, %110, %111, %112, %113, %114, %115, %116, %117, %118, %119}, %120, %121, p, 1, 1, 0, 1;\n}\n"
    : "+f"(d[0]), "+f"(d[1]), "+f"(d[2]), "+f"(d[3]), "+f"(d[4]), "+f"(d[5]), "+f"(d[6]), "+f"(d[7]), "+f"(d[8]), "+f"(d[9]), "+f"(d[10]), "+f"(d[11]), "+f"(d[12]), "+f"(d[13]), "+f"(d[14]), "+f"(d[15]), "+f"(d[16]), "+f"(d[17]), "+f"(d[18]), "+f"(d[19]), "+f"(d[20]), "+f"(d[21]), "+f"(d[22]), "+f"(d[23]), "+f"(d[24]), "+f"(d[25]), "+f"(d[26]), "+f"(d[27]), "+f"(d[28]), "+f"(d[29]), "+f"(d[30]), "+f"(d[31]), "+f"(d[32]), "+f"(d[33]), "+f"(d[34]), "+f"(d[35]), "+f"(d[36]), "+f"(d[37]), "+f"(d[38]), "+f"(d[39]), "+f"(d[40]), "+f"(d[41]), "+f"(d[42]), "+f"(d[43]), "+f"(d[44]), "+f"(d[45]), "+f"(d[46]), "+f"(d[47]), "+f"(d[48]), "+f"(d[49]), "+f"(d[50]), "+f"(d[51]), "+f"(d[52]), "+f"(d[53]), "+f"(d[54]), "+f"(d[55]), "+f"(d[56]), "+f"(d[57]), "+f"(d[58]), "+f"(d[59]), "+f"(d[60]), "+f"(d[61]), "+f"(d[62]), "+f"(d[63]), "+f"(d[64]), "+f"(d[65]), "+f"(d[66]), "+f"(d[67]), "+f"(d[68]), "+f"(d[69]), "+f"(d[70]), "+f"(d[71]), "+f"(d[72]), "+f"(d[73]), "+f"(d[74]), "+f"(d[75]), "+f"(d[76]), "+f"(d[77]), "+f"(d[78]), "+f"(d[79]), "+f"(d[80]), "+f"(d[81]), "+f"(d[82]), "+f"(d[83]), "+f"(d[84]), "+f"(d[85]), "+f"(d[86]), "+f"(d[87]), "+f"(d[88]), "+f"(d[89]), "+f"(d[90]), "+f"(d[91]), "+f"(d[92]), "+f"(d[93]), "+f"(d[94]), "+f"(d[95]), "+f"(d[96]), "+f"(d[97]), "+f"(d[98]), "+f"(d[99]), "+f"(d[100]), "+f"(d[101]), "+f"(d[102]), "+f"(d[103]), "+f"(d[104]), "+f"(d[105]), "+f"(d[106]), "+f"(d[107]), "+f"(d[108]), "+f"(d[109]), "+f"(d[110]), "+f"(d[111]), "+f"(d[112]), "+f"(d[113]), "+f"(d[114]), "+f"(d[115]), "+f"(d[116]), "+f"(d[117]), "+f"(d[118]), "+f"(d[119])
    : "l"(a), "l"(b), "r"(sc));
}
__device__ __forceinline__ void wg_ss_n88_ta1_tb1(float* d, uint64_t a, uint64_t b, int sc) {
  asm volatile("{\n.reg .pred p;\nsetp.ne.b32 p, %46, 0;\nwgmma.mma_async.sync.aligned.m64n88k16.f32.bf16.bf16 {%0, %1, %2, %3, %4, %5, %6, %7, %8, %9, %10, %11, %12, %13, %14, %15, %16, %17, %18, %19, %20, %21, %22, %23, %24, %25, %26, %27, %28, %29, %30, %31, %32, %33, %34, %35, %36, %37, %38, %39, %40, %41, %42, %43}, %44, %45, p, 1, 1, 1, 1;\n}\n"
    : "+f"(d[0]), "+f"(d[1]), "+f"(d[2]), "+f"(d[3]), "+f"(d[4]), "+f"(d[5]), "+f"(d[6]), "+f"(d[7]), "+f"(d[8]), "+f"(d[9]), "+f"(d[10]), "+f"(d[11]), "+f"(d[12]), "+f"(d[13]), "+f"(d[14]), "+f"(d[15]), "+f"(d[16]), "+f"(d[17]), "+f"(d[18]), "+f"(d[19]), "+f"(d[20]), "+f"(d[21]), "+f"(d[22]), "+f"(d[23]), "+f"(d[24]), "+f"(d[25]), "+f"(d[26]), "+f"(d[27]), "+f"(d[28]), "+f"(d[29]), "+f"(d[30]), "+f"(d[31]), "+f"(d[32]), "+f"(d[33]), "+f"(d[34]), "+f"(d[35]), "+f"(d[36]), "+f"(d[37]), "+f"(d[38]), "+f"(d[39]), "+f"(d[40]), "+f"(d[41]), "+f"(d[42]), "+f"(d[43])
    : "l"(a), "l"(b), "r"(sc));
}
__device__ __forceinline__ void wg_rs_n160_tb1(float* d, const uint32_t* a, uint64_t b, int sc) {
  asm volatile("{\n.reg .pred p;\nsetp.ne.b32 p, %85, 0;\nwgmma.mma_async.sync.aligned.m64n160k16.f32.bf16.bf16 {%0, %1, %2, %3, %4, %5, %6, %7, %8, %9, %10, %11, %12, %13, %14, %15, %16, %17, %18, %19, %20, %21, %22, %23, %24, %25, %26, %27, %28, %29, %30, %31, %32, %33, %34, %35, %36, %37, %38, %39, %40, %41, %42, %43, %44, %45, %46, %47, %48, %49, %50, %51, %52, %53, %54, %55, %56, %57, %58, %59, %60, %61, %62, %63, %64, %65, %66, %67, %68, %69, %70, %71, %72, %73, %74, %75, %76, %77, %78, %79}, {%80, %81, %82, %83}, %84, p, 1, 1, 1;\n}\n"
    : "+f"(d[0]), "+f"(d[1]), "+f"(d[2]), "+f"(d[3]), "+f"(d[4]), "+f"(d[5]), "+f"(d[6]), "+f"(d[7]), "+f"(d[8]), "+f"(d[9]), "+f"(d[10]), "+f"(d[11]), "+f"(d[12]), "+f"(d[13]), "+f"(d[14]), "+f"(d[15]), "+f"(d[16]), "+f"(d[17]), "+f"(d[18]), "+f"(d[19]), "+f"(d[20]), "+f"(d[21]), "+f"(d[22]), "+f"(d[23]), "+f"(d[24]), "+f"(d[25]), "+f"(d[26]), "+f"(d[27]), "+f"(d[28]), "+f"(d[29]), "+f"(d[30]), "+f"(d[31]), "+f"(d[32]), "+f"(d[33]), "+f"(d[34]), "+f"(d[35]), "+f"(d[36]), "+f"(d[37]), "+f"(d[38]), "+f"(d[39]), "+f"(d[40]), "+f"(d[41]), "+f"(d[42]), "+f"(d[43]), "+f"(d[44]), "+f"(d[45]), "+f"(d[46]), "+f"(d[47]), "+f"(d[48]), "+f"(d[49]), "+f"(d[50]), "+f"(d[51]), "+f"(d[52]), "+f"(d[53]), "+f"(d[54]), "+f"(d[55]), "+f"(d[56]), "+f"(d[57]), "+f"(d[58]), "+f"(d[59]), "+f"(d[60]), "+f"(d[61]), "+f"(d[62]), "+f"(d[63]), "+f"(d[64]), "+f"(d[65]), "+f"(d[66]), "+f"(d[67]), "+f"(d[68]), "+f"(d[69]), "+f"(d[70]), "+f"(d[71]), "+f"(d[72]), "+f"(d[73]), "+f"(d[74]), "+f"(d[75]), "+f"(d[76]), "+f"(d[77]), "+f"(d[78]), "+f"(d[79])
    : "r"(a[0]), "r"(a[1]), "r"(a[2]), "r"(a[3]), "l"(b), "r"(sc));
}
__device__ __forceinline__ void wg_ss_n112_ta0_tb1(float* d, uint64_t a, uint64_t b, int sc) {
  asm volatile("{\n.reg .pred p;\nsetp.ne.b32 p, %58, 0;\nwgmma.mma_async.sync.aligned.m64n112k16.f32.bf16.bf16 {%0, %1, %2, %3, %4, %5, %6, %7, %8, %9, %10, %11, %12, %13, %14, %15, %16, %17, %18, %19, %20, %21, %22, %23, %24, %25, %26, %27, %28, %29, %30, %31, %32, %33, %34, %35, %36, %37, %38, %39, %40, %41, %42, %43, %44, %45, %46, %47, %48, %49, %50, %51, %52, %53, %54, %55}, %56, %57, p, 1, 1, 0, 1;\n}\n"
    : "+f"(d[0]), "+f"(d[1]), "+f"(d[2]), "+f"(d[3]), "+f"(d[4]), "+f"(d[5]), "+f"(d[6]), "+f"(d[7]), "+f"(d[8]), "+f"(d[9]), "+f"(d[10]), "+f"(d[11]), "+f"(d[12]), "+f"(d[13]), "+f"(d[14]), "+f"(d[15]), "+f"(d[16]), "+f"(d[17]), "+f"(d[18]), "+f"(d[19]), "+f"(d[20]), "+f"(d[21]), "+f"(d[22]), "+f"(d[23]), "+f"(d[24]), "+f"(d[25]), "+f"(d[26]), "+f"(d[27]), "+f"(d[28]), "+f"(d[29]), "+f"(d[30]), "+f"(d[31]), "+f"(d[32]), "+f"(d[33]), "+f"(d[34]), "+f"(d[35]), "+f"(d[36]), "+f"(d[37]), "+f"(d[38]), "+f"(d[39]), "+f"(d[40]), "+f"(d[41]), "+f"(d[42]), "+f"(d[43]), "+f"(d[44]), "+f"(d[45]), "+f"(d[46]), "+f"(d[47]), "+f"(d[48]), "+f"(d[49]), "+f"(d[50]), "+f"(d[51]), "+f"(d[52]), "+f"(d[53]), "+f"(d[54]), "+f"(d[55])
    : "l"(a), "l"(b), "r"(sc));
}
__device__ __forceinline__ void wg_rs_n32_tb1(float* d, const uint32_t* a, uint64_t b, int sc) {
  asm volatile("{\n.reg .pred p;\nsetp.ne.b32 p, %21, 0;\nwgmma.mma_async.sync.aligned.m64n32k16.f32.bf16.bf16 {%0, %1, %2, %3, %4, %5, %6, %7, %8, %9, %10, %11, %12, %13, %14, %15}, {%16, %17, %18, %19}, %20, p, 1, 1, 1;\n}\n"
    : "+f"(d[0]), "+f"(d[1]), "+f"(d[2]), "+f"(d[3]), "+f"(d[4]), "+f"(d[5]), "+f"(d[6]), "+f"(d[7]), "+f"(d[8]), "+f"(d[9]), "+f"(d[10]), "+f"(d[11]), "+f"(d[12]), "+f"(d[13]), "+f"(d[14]), "+f"(d[15])
    : "r"(a[0]), "r"(a[1]), "r"(a[2]), "r"(a[3]), "l"(b), "r"(sc));
}
__device__ __forceinline__ void wg_ss_n32_ta1_tb1(float* d, uint64_t a, uint64_t b, int sc) {
  asm volatile("{\n.reg .pred p;\nsetp.ne.b32 p, %18, 0;\nwgmma.mma_async.sync.aligned.m64n32k16.f32.bf16.bf16 {%0, %1, %2, %3, %4, %5, %6, %7, %8, %9, %10, %11, %12, %13, %14, %15}, %16, %17, p, 1, 1, 1, 1;\n}\n"
    : "+f"(d[0]), "+f"(d[1]), "+f"(d[2]), "+f"(d[3]), "+f"(d[4]), "+f"(d[5]), "+f"(d[6]), "+f"(d[7]), "+f"(d[8]), "+f"(d[9]), "+f"(d[10]), "+f"(d[11]), "+f"(d[12]), "+f"(d[13]), "+f"(d[14]), "+f"(d[15])
    : "l"(a), "l"(b), "r"(sc));
}
__device__ __forceinline__ void wg_rs_n32_tb0(float* d, const uint32_t* a, uint64_t b, int sc) {
  asm volatile("{\n.reg .pred p;\nsetp.ne.b32 p, %21, 0;\nwgmma.mma_async.sync.aligned.m64n32k16.f32.bf16.bf16 {%0, %1, %2, %3, %4, %5, %6, %7, %8, %9, %10, %11, %12, %13, %14, %15}, {%16, %17, %18, %19}, %20, p, 1, 1, 0;\n}\n"
    : "+f"(d[0]), "+f"(d[1]), "+f"(d[2]), "+f"(d[3]), "+f"(d[4]), "+f"(d[5]), "+f"(d[6]), "+f"(d[7]), "+f"(d[8]), "+f"(d[9]), "+f"(d[10]), "+f"(d[11]), "+f"(d[12]), "+f"(d[13]), "+f"(d[14]), "+f"(d[15])
    : "r"(a[0]), "r"(a[1]), "r"(a[2]), "r"(a[3]), "l"(b), "r"(sc));
}
__device__ __forceinline__ void wg_rs_n40_tb0(float* d, const uint32_t* a, uint64_t b, int sc) {
  asm volatile("{\n.reg .pred p;\nsetp.ne.b32 p, %25, 0;\nwgmma.mma_async.sync.aligned.m64n40k16.f32.bf16.bf16 {%0, %1, %2, %3, %4, %5, %6, %7, %8, %9, %10, %11, %12, %13, %14, %15, %16, %17, %18, %19}, {%20, %21, %22, %23}, %24, p, 1, 1, 0;\n}\n"
    : "+f"(d[0]), "+f"(d[1]), "+f"(d[2]), "+f"(d[3]), "+f"(d[4]), "+f"(d[5]), "+f"(d[6]), "+f"(d[7]), "+f"(d[8]), "+f"(d[9]), "+f"(d[10]), "+f"(d[11]), "+f"(d[12]), "+f"(d[13]), "+f"(d[14]), "+f"(d[15]), "+f"(d[16]), "+f"(d[17]), "+f"(d[18]), "+f"(d[19])
    : "r"(a[0]), "r"(a[1]), "r"(a[2]), "r"(a[3]), "l"(b), "r"(sc));
}
__device__ __forceinline__ void wg_rs_n8_tb1(float* d, const uint32_t* a, uint64_t b, int sc) {
  asm volatile("{\n.reg .pred p;\nsetp.ne.b32 p, %9, 0;\nwgmma.mma_async.sync.aligned.m64n8k16.f32.bf16.bf16 {%0, %1, %2, %3}, {%4, %5, %6, %7}, %8, p, 1, 1, 1;\n}\n"
    : "+f"(d[0]), "+f"(d[1]), "+f"(d[2]), "+f"(d[3])
    : "r"(a[0]), "r"(a[1]), "r"(a[2]), "r"(a[3]), "l"(b), "r"(sc));
}
__device__ __forceinline__ void wg_ss_n40_ta0_tb0(float* d, uint64_t a, uint64_t b, int sc) {
  asm volatile("{\n.reg .pred p;\nsetp.ne.b32 p, %22, 0;\nwgmma.mma_async.sync.aligned.m64n40k16.f32.bf16.bf16 {%0, %1, %2, %3, %4, %5, %6, %7, %8, %9, %10, %11, %12, %13, %14, %15, %16, %17, %18, %19}, %20, %21, p, 1, 1, 0, 0;\n}\n"
    : "+f"(d[0]), "+f"(d[1]), "+f"(d[2]), "+f"(d[3]), "+f"(d[4]), "+f"(d[5]), "+f"(d[6]), "+f"(d[7]), "+f"(d[8]), "+f"(d[9]), "+f"(d[10]), "+f"(d[11]), "+f"(d[12]), "+f"(d[13]), "+f"(d[14]), "+f"(d[15]), "+f"(d[16]), "+f"(d[17]), "+f"(d[18]), "+f"(d[19])
    : "l"(a), "l"(b), "r"(sc));
}
__device__ __forceinline__ void wg_ss_n40_ta1_tb0(float* d, uint64_t a, uint64_t b, int sc) {
  asm volatile("{\n.reg .pred p;\nsetp.ne.b32 p, %22, 0;\nwgmma.mma_async.sync.aligned.m64n40k16.f32.bf16.bf16 {%0, %1, %2, %3, %4, %5, %6, %7, %8, %9, %10, %11, %12, %13, %14, %15, %16, %17, %18, %19}, %20, %21, p, 1, 1, 1, 0;\n}\n"
    : "+f"(d[0]), "+f"(d[1]), "+f"(d[2]), "+f"(d[3]), "+f"(d[4]), "+f"(d[5]), "+f"(d[6]), "+f"(d[7]), "+f"(d[8]), "+f"(d[9]), "+f"(d[10]), "+f"(d[11]), "+f"(d[12]), "+f"(d[13]), "+f"(d[14]), "+f"(d[15]), "+f"(d[16]), "+f"(d[17]), "+f"(d[18]), "+f"(d[19])
    : "l"(a), "l"(b), "r"(sc));
}
__device__ __forceinline__ void wg_ss_n8_ta1_tb1(float* d, uint64_t a, uint64_t b, int sc) {
  asm volatile("{\n.reg .pred p;\nsetp.ne.b32 p, %6, 0;\nwgmma.mma_async.sync.aligned.m64n8k16.f32.bf16.bf16 {%0, %1, %2, %3}, %4, %5, p, 1, 1, 1, 1;\n}\n"
    : "+f"(d[0]), "+f"(d[1]), "+f"(d[2]), "+f"(d[3])
    : "l"(a), "l"(b), "r"(sc));
}

constexpr int O_WV = 0, O_WO = 81920, O_H = 163840, O_QK = 215040, O_SM = 228352, O_MISC = 229632;
constexpr int O_QM = O_QK + 1024, O_K = O_QK + 3072, O_OG = O_QK + 8192;
constexpr int SM_SLOT = 640;
constexpr int O_MAXS = O_MISC;
constexpr int O_BAR = O_MISC + 64;
constexpr int MB_XF = 0, MB_ML = 2, MB_MR = 3, MB_PF = 4, MB_SM = 5, MB_SX = 6, MB_OG = 7, MB_W = 10, MB_WC = 30;
constexpr int O_PROF = O_BAR + 8 * 40;
constexpr int REC_SMEM = O_PROF + 128;
constexpr int B_VOWN = 0, B_QK = 1, B_SISS = 3, B_PM = 4, B_PX = 5, B_XGO = 6, B_ML = 7, B_WG2 = 8, B_VHALF = 9, B_VDONE = 10,
              B_MR = 11, B_SSENT = 12, B_SLD = 13, B_VEND = 14, B_XGO1 = 15;
#define TS0(idx) do {} while (0)
#define TS(idx) do {} while (0)
#define POLL_9 300
#define POLL_A 400
#define POLL_B 500
#define POLL_C 600
#define W_WIN 4
#define W_OPEN 16
#define V_OWN 6
#define V_S1 8
#define V_RS 3
#define V_S2 1
#define V_B 4
#define V_K1 (V_OWN + V_RS + V_B + V_S1)
#define V_K2 ((V_K1 > 20 ? V_K1 : 20) + V_S2)
#define O_RSM 0x2AA0
#define SSP 0
#define TOK 0
#define O_B1 5
#define O_RS __builtin_popcount(O_RSM)
#define O_IDX(j) __builtin_popcount(O_RSM & ((1 << (j)) - 1))
constexpr float SCL = 0.07216878364870322f;
constexpr float SL2 = SCL * 1.4426950408889634f;
__device__ __forceinline__ constexpr int vord(int i) { return i < 4 ? 36 + i : i - 4; }
__device__ __forceinline__ constexpr uint32_t hoff(int k) { return ((k >> 2) * 5120 + (k & 3) * 32) >> 4; }
__device__ __forceinline__ constexpr int ar_chunk(int T) { return T == 9 ? 19 : (T % 3) * 8 + T / 3; }
__device__ __forceinline__ void fix_red(uint8_t* p, const float* a, float2 sc) {
  int v0 = __float2int_rn(a[0] * sc.x), v1 = __float2int_rn(a[1] * sc.y), v2 = __float2int_rn(a[2] * sc.x), v3 = __float2int_rn(a[3] * sc.y);
  red64(p, ((uint32_t)v0 << 7) | 1u, ((uint32_t)v2 << 3) + (uint32_t)(v0 >> 25));
  red64(p + 1024, ((uint32_t)v1 << 7) | 1u, ((uint32_t)v3 << 3) + (uint32_t)(v1 >> 25));
}
__device__ __forceinline__ float exp_row(float* t) {
  const float ml = fmaxf(fmaxf(fmaxf(fmaxf(t[0], t[1]), fmaxf(t[2], t[3])), fmaxf(fmaxf(t[4], t[5]), fmaxf(t[6], t[7]))), fmaxf(t[8], t[9]));
  const float m1 = __shfl_xor_sync(~0u, ml, 1), m2 = __shfl_xor_sync(~0u, ml, 2), m3 = __shfl_xor_sync(~0u, ml, 3);
  SCHED_FENCE();
#pragma unroll
  for (int k = 0; k < 10; k++) t[k] = ex2((t[k] - ml) * SL2);
  pin<10>(t);
  SCHED_FENCE();
  return ex2((ml - fmaxf(fmaxf(ml, m1), fmaxf(m2, m3))) * SL2);
}
#define ACC3(k, u, v) { t[k] += bflo(u) + bflo(v); t[k + 1] += bfhi(u) + bfhi(v); }

#define LBT 0
#define NLB 2
constexpr int LB_STAGE = 36864, LB_ST = 6 * LB_STAGE;
__device__ __forceinline__ void lb_role(const uint32_t sb, const CUtensorMap* tmx, uint32_t* __restrict__ flags, int layer) {
  const int tid = threadIdx.x, wid = __shfl_sync(~0u, tid >> 5, 0), wg = wid >> 2, w = wid & 3, lane = tid & 31, g = lane >> 2, i4 = lane & 3;
  const int cl = blockIdx.x / 3, rank = blockIdx.x - cl * 3;
  const uint32_t bar = sb + O_BAR;
  asm volatile("griddepcontrol.launch_dependents;");
  if (wid == 8) {
    if (lane < 14) mbar_init(bar + 8 * lane, lane >= 6 && lane < 12 ? 8 : 1);
    asm volatile("fence.mbarrier_init.release.cluster;" ::: "memory");
    fence_async();
  }
  __syncthreads();
  asm volatile("barrier.cluster.arrive.relaxed.aligned;" ::: "memory");
  if (wid == 8) {
    int st = 0; uint32_t ph = 1;
    const uint8_t* wsrc = g_w2 + rank * 286720;
    if (lane < 6) { mbar_expect(bar + 8 * lane, LB_STAGE); bulk_g2s(sb + lane * LB_STAGE + 8192, wsrc + lane * 28672, 28672, bar + 8 * lane); }
    if (layer == 1) wait_flag(flags + FL_R, 6);
#pragma unroll 1
    for (int tile = cl; tile < 32; tile += NLB) {
      wait_flag(flags + FL_O + (tile >> 1) * 8, 8);
      if (tile == cl + LBT * NLB && lane == 0) GTT(layer * 4 + 1, 11);
      fence_async_global();
#pragma unroll 1
      for (int kc = 0; kc < 10; kc++) {
        const bool pre = tile == cl && kc < 6;
        mbar_wait(bar + 8 * (6 + st), ph);
        if (lane == 0) {
          if (!pre) { mbar_expect(bar + 8 * st, LB_STAGE); bulk_g2s(sb + st * LB_STAGE + 8192, wsrc + kc * 28672, 28672, bar + 8 * st); }
          bulk_g2s(sb + st * LB_STAGE, g_oa + tile * 81920 + kc * 8192, 8192, bar + 8 * st);
        }
        __syncwarp();
        if (++st == 6) { st = 0; ph ^= 1; }
      }
      mbar_wait(bar + 8 * (6 + st), ph);
      if (lane == 0) { mbar_expect(bar + 8 * st, 64 * 464); tma2d(sb + st * LB_STAGE, tmx, rank * 224, tile * 64, bar + 8 * st); }
      __syncwarp();
      if (++st == 6) { st = 0; ph ^= 1; }
    }
    asm volatile("barrier.cluster.wait.aligned;" ::: "memory");
  } else if (wg < 2) {
    asm volatile("barrier.cluster.wait.aligned;" ::: "memory");
    const int u = 2 * rank + wg, nb = u == 5 ? 5 : 7;
    int st = 0; uint32_t ph = 0, it = 0;
#pragma unroll 1
    for (int tile = cl; tile < 32; tile += NLB, it++) {
      const int row0 = tile * 64 + 16 * w + g;
      float d[56];
      if (tid == 0) mbar_expect(bar + 8 * (12 + (it & 1)), 3072);
#pragma unroll 1
      for (int kc = 0; kc < 10; kc++) {
        const uint64_t da = mkdesc(SB0 + st * LB_STAGE, 1024, 128, 0), db = mkdesc(SB0 + st * LB_STAGE + 8192 + wg * 1792, 3584, 128, 0);
        mbar_wait(bar + 8 * st, ph);
        if (it == LBT && kc == 0) GT(layer * 4 + 1, 12);
        wg_fence();
#pragma unroll
        for (int k = 0; k < 4; k++) wg_ss_n112_ta0_tb1(d, da + k * 128, db + k * 448, kc | k);
        wg_commit();
        wg_wait<1>();
        if (kc > 0 && lane == 0) mbar_arrive(bar + 8 * (6 + (st == 0 ? 5 : st - 1)));
        if (++st == 6) { st = 0; ph ^= 1; }
      }
      wg_wait<0>();
      pin<56>(d);
      if (it == LBT) GT(layer * 4 + 1, 13);
      if (lane == 0) mbar_arrive(bar + 8 * (6 + (st == 0 ? 5 : st - 1)));
      mbar_wait(bar + 8 * st, ph);
      {
        const uint32_t x0 = sb + st * LB_STAGE + (16 * w + g) * 464 + wg * 224 + (layer ? 8 : 4) * i4, x1 = x0 + (layer ? 4 : 16);
#pragma unroll
        for (int j = 0; j < 28; j++) {
          const uint32_t v = lds1(((j & 2) ? x1 : x0) + (j >> 2) * 32 + (j & 1) * 3712);
          d[2 * j] += bflo(v); d[2 * j + 1] += bfhi(v);
        }
      }
      fence_async();
      __syncwarp();
      if (lane == 0) mbar_arrive(bar + 8 * (6 + st));
      if (++st == 6) { st = 0; ph ^= 1; }
      const float cnt = nb * 16.f;
      const uint32_t so = LB_ST + (it & 1) * 3072 + (16 * w + g) * 48;
#pragma unroll
      for (int h = 0; h < 2; h++) {
        float sum = 0.f;
#pragma unroll
        for (int j = 0; j < 14; j++) sum += d[4 * j + 2 * h] + d[4 * j + 2 * h + 1];
        sum += __shfl_xor_sync(~0u, sum, 1); sum += __shfl_xor_sync(~0u, sum, 2);
        const float mean = sum * rcp(cnt);
        float q = 0.f, q2 = 0.f;
#pragma unroll
        for (int j = 0; j < 14; j++) {
          const float a = d[4 * j + 2 * h] - mean, b = d[4 * j + 2 * h + 1] - mean;
          if (j < 10) q = fmaf(a, a, fmaf(b, b, q)); else q2 = fmaf(a, a, fmaf(b, b, q2));
        }
        if (nb == 7) q += q2;
        q += __shfl_xor_sync(~0u, q, 1); q += __shfl_xor_sync(~0u, q, 2);
        if (i4 < 3) { const uint32_t b = mapa(sb, i4); sta2f(b + so + h * 384 + u * 8, sum, q, b + O_BAR + 8 * (12 + (it & 1))); }
      }
      mbar_wait(bar + 8 * (12 + (it & 1)), (it >> 1) & 1);
      if (it == LBT) GT(layer * 4 + 1, 14);
#pragma unroll
      for (int h = 0; h < 2; h++) {
        const float4 x = lds4f(sb + so + h * 384), y = lds4f(sb + so + h * 384 + 16), z = lds4f(sb + so + h * 384 + 32);
        const float mu = (((x.x + x.z) + (y.x + y.z)) + (z.x + z.z)) * (1.f / DM);
        const float e0 = x.x * (1.f / 112.f) - mu, e1 = x.z * (1.f / 112.f) - mu, e2 = y.x * (1.f / 112.f) - mu, e3 = y.z * (1.f / 112.f) - mu;
        const float e4 = z.x * (1.f / 112.f) - mu, e5 = z.z * (1.f / 80.f) - mu;
        const float q = (((x.y + x.w) + (y.y + y.w)) + (z.y + z.w)) + 112.f * ((e0 * e0 + e1 * e1) + (e2 * e2 + e3 * e3) + e4 * e4) + 80.f * e5 * e5;
        const float rs = rsqrtf(q * (1.f / DM) + 1e-5f), sh = -mu * rs;
        const int tk = row0 + 8 * h;
        uint8_t* xp = g_xn + (tk >> 5) * 40960 + (tk & 31) * 128 + (i4 & 1) * 8;
#pragma unroll
        for (int j = 0; j < 7; j++) {
          if (j < nb) {
            const int b16 = u * 7 + j;
            const float* a = d + 8 * j + 2 * h;
            *(uint2*)(xp + (b16 >> 2) * 4096 + (((2 * (b16 & 3) + (i4 >> 1)) ^ g) << 4)) =
                make_uint2(pack2(fmaf(a[0], rs, sh), fmaf(a[1], rs, sh)), pack2(fmaf(a[4], rs, sh), fmaf(a[5], rs, sh)));
          }
        }
      }
      if (it == LBT) GT(layer * 4 + 1, 15);
      bar_arrive<1, 288>();
      bar_sync<2, 288>();
#pragma unroll
      for (int j = 0; j < 14; j++) {
        const float* a = d + 8 * (j >> 1) + 2 * (j & 1);
        if ((j >> 1) < nb) *(uint2*)(g_x + (row0 + 8 * (j & 1)) * DM + u * 112 + 4 * i4 + 16 * (j >> 1)) = make_uint2(pack2(a[0], a[1]), pack2(a[4], a[5]));
      }
      bar_arrive<3, 288>();
    }
  } else {
    asm volatile("barrier.cluster.wait.aligned;" ::: "memory");
    if (wid == 9) {
#pragma unroll 1
      for (int tile = cl; tile < 32; tile += NLB) {
        bar_sync<1, 288>();
        if (tile != cl) bar_arrive<2, 288>();
        if (lane == 0) { red_release(flags + FL_XN + tile * 8, 1); if (tile == cl + LBT * NLB) GTT(layer * 4 + 1, 9); }
        __syncwarp();
        if (tile == cl) bar_arrive<2, 288>();
        bar_sync<3, 288>();
        if (lane == 0) red_release(flags + FL_XN + tile * 8 + 1, 1);
        __syncwarp();
      }
    }
  }
  asm volatile("barrier.cluster.arrive.relaxed.aligned;\nbarrier.cluster.wait.aligned;" ::: "memory");
  GT(layer * 4 + 1, 10);
}

__global__ void __launch_bounds__(384, 1)
rec_kernel(const __grid_constant__ CUtensorMap tmq, const __grid_constant__ CUtensorMap tmk,
           const __grid_constant__ CUtensorMap tmv, const __grid_constant__ CUtensorMap tmo,
           const __grid_constant__ CUtensorMap tmx, const bf16* __restrict__ mem0, uint8_t* __restrict__ ar, uint32_t* __restrict__ flags, int layer) {
  extern __shared__ __align__(1024) uint8_t smem[];
  const uint32_t sb = smem_u32(smem);
  check_smem_base(sb);
  GT(layer * 4 + 1, 0);
  if (blockIdx.x < 3 * NLB) { lb_role(sb, &tmx, flags, layer); return; }
  const int bid = blockIdx.x - 3 * NLB;
  const int tid = threadIdx.x, wid = __shfl_sync(~0u, tid >> 5, 0), wg = wid >> 2, w = wid & 3;
  const int lane = __shfl_sync(~0u, tid & 31, tid & 31);
  const int head = bid / 3, rank = bid - head * 3;
  const int e0 = bid * 64;
  const uint32_t bar = sb + O_BAR;
  const uint32_t sb1 = mapa(sb, rank == 2 ? 0 : rank + 1), sb2 = mapa(sb, rank == 0 ? 2 : rank - 1);
  auto chunk_of = [&](int p) { const int c = 3 * rank + p; return p == 9 ? 9 : c >= 9 ? c - 9 : c; };

  auto load_piece = [&](int i) {
    if (lane == 0) mbar_expect(bar + 8 * (MB_W + i), 16384);
    __syncwarp();
    if (lane < 2) {
      if (i < 15) {
        const int m = i < 10 ? i & 1 : 0, p = (i < 10 ? i >> 1 : i - 10) * 2 + lane;
        tma5d(sb + m * 81920 + p * 8192, i >= 10 ? &tmv : m ? &tmk : &tmq, e0, chunk_of(p) * 4, bar + 8 * (MB_W + i));
      } else {
        const int p = (i - 15) * 2 + lane, k = p / 3, j = rank + p - 3 * k;
        tma2d(sb + O_WO + p * 8192, &tmo, p == 9 ? 576 : (rank * 3 + k) * 64, head * DH + (j >= 3 ? j - 3 : j) * 64, bar + 8 * (MB_W + i));
      }
    }
  };
  if (wid == 9) {
    mbar_init(bar + 8 * lane, (lane >= MB_WC || lane == MB_PF) ? 4 : (TOK && lane == MB_SM) ? 13 : 1);
    if (lane < 8) mbar_init(bar + 8 * (32 + lane), 4);
    asm volatile("fence.mbarrier_init.release.cluster;" ::: "memory");
    fence_async();
    __syncwarp();
#pragma unroll 1
    for (int i = 0; i < W_WIN; i++) load_piece(i);
  }
  __syncthreads();
  asm volatile("barrier.cluster.arrive.relaxed.aligned;" ::: "memory");

  if (wg < 2) {
    asm volatile("setmaxnreg.inc.sync.aligned.u32 208;");
    uint32_t a[40][4];
    const uint32_t swz = (lane & 7) * 128 + (((2 * w + ((lane >> 3) & 1)) ^ (lane & 7)) << 4);
    const uint32_t st_x = __shfl_sync(~0u, sb + O_QK + wg * 5120 + (lane >> 4) * 2048 + swz, lane);
    {
      const uint32_t la = sb + wg * 81920 + (lane >> 4) * 1024 + swz;
#pragma unroll
      for (int p = 0; p < 5; p++) {
        mbar_wait(bar + 8 * (MB_W + 2 * p + wg), 0);
#pragma unroll
        for (int k = 0; k < 8; k++) ldsm4t(a[p * 8 + k], la + (p * 8 + k) * 2048);
        fence_async();
        __syncwarp();
        mbar_arrive_elect(bar + 8 * (MB_WC + wg * 5 + p));
      }
    }
    GT(layer * 4 + 1, 5);
    asm volatile("barrier.cluster.wait.aligned;" ::: "memory");
    const uint32_t ld_m = __shfl_sync(~0u, sb + O_H + (lane & 7) * 128 + (((lane >> 3) ^ (lane & 7)) << 4), lane);

    for (int s = 0; s < NSEG; s++) {
      const uint32_t par = s & 1;
      if (wid == 4) TS0(0);
      if (wid == 0) TS(30);
      {
        float ax[16];
        constexpr uint64_t db = mkdesc(SB0 + O_H + 1024, 16, 1024, 1);
        mbar_waitf(bar + 8 * MB_XF, par);
        wg_fence();
#pragma unroll
        for (int k = 0; k < 20; k++) wg_rs_n32_tb0(ax, a[vord(k)], db + hoff(vord(k)), k);
        mbar_waitf(bar + 8 * (MB_XF + 1), par);
        wg_fence();
#pragma unroll
        for (int k = 20; k < 40; k++) wg_rs_n32_tb0(ax, a[vord(k)], db + hoff(vord(k)), 1);
        wg_commit();
        mbar_waitf(bar + 8 * MB_PF, par ^ 1);
        if (wid == 6 && lane == 0) { mbar_expect(bar + 8 * MB_SM, 2 * SM_SLOT + 48 + (TOK ? 0 : 48)); mbar_expect(bar + 8 * MB_SX, 2 * 2176); }
        wg_wait<0>();
        pin<16>(ax);
        if (w == 0) TS(1 + 22 * wg);
        stsm4t(st_x, pack2(ax[0], ax[1]), pack2(ax[2], ax[3]), pack2(ax[4], ax[5]), pack2(ax[6], ax[7]));
        stsm4t(st_x + 4096, pack2(ax[8], ax[9]), pack2(ax[10], ax[11]), pack2(ax[12], ax[13]), pack2(ax[14], ax[15]));
        bar_arrive<B_VOWN, 384>();
      }
      {
        float c[4][4];
#pragma unroll
        for (int k = 0; k < 4; k++) c[k][0] = c[k][1] = c[k][2] = c[k][3] = 0.f;
        uint32_t b[3][2][4];
        const uint32_t ld_m2 = opaque(ld_m ^ 64);
        SCHED_FENCE();
#define MORD(j) ((j) == 0 ? 9 : (j) < 4 ? (j) - 1 : 3 + ((j) - 4) / 2 + 3 * ((j) & 1))
#pragma unroll
        for (int j = 0; j < 12; j++) {
          if (j < 10) {
            if (j == 0) { mbar_waitf(bar + 8 * MB_ML, par); if (wid == 0) TS(2); }
            if (j == 1) { bar_sync<B_ML, 352>(); if (wid == 0) TS(3); }
            if (j == 4) { bar_sync<B_MR, 288>(); if (wid == 0) TS(4); }
            ldsm4(b[j % 3][0], ld_m + MORD(j) * 5120);
            ldsm4(b[j % 3][1], ld_m2 + MORD(j) * 5120);
          }
          const int u = j - 2;
          if (u >= 0) {
#pragma unroll
            for (int k = 0; k < 4; k++) mma16816(c[k], a[4 * MORD(u) + k], b[u % 3][k >> 1][(k & 1) * 2], b[u % 3][k >> 1][(k & 1) * 2 + 1]);
          }
        }
        if (wid == 0) TS(31);
#pragma unroll
        for (int k = 0; k < 4; k++) c[0][k] = (c[0][k] + c[1][k]) + (c[2][k] + c[3][k]);
        stsm2t(st_x + 1024 - wg * 3072, pack2(c[0][0], c[0][1]), pack2(c[0][2], c[0][3]));
        fence_async();
      }
      if (wg == 0) {
        bar_sync<B_QK, 256>();
        float sv[20];
        {
          constexpr uint64_t da = mkdesc(SB0 + O_QK, 16, 1024, 1), db = mkdesc(SB0 + O_K, 16, 2048, 1);
          wg_fence();
#pragma unroll
          for (int k = 0; k < 4; k++) wg_ss_n40_ta0_tb0(sv, da + 2 * k, db + 2 * k, k);
          bar_arrive<B_SISS, 256>();
          wg_commit();
        }
        if (w == 0) TS(6);
        SCHED_FENCE();
        const uint32_t ln = opaque(lane);
        uint32_t m0, m1, m2, m3, m4;
        {
          const uint32_t a1 = opaque(sb1 + O_SM + SM_SLOT + ln * 16), a2 = opaque(sb2 + O_SM + ln * 16);
          const uint32_t a3 = opaque(sb1 + O_SM + SM_SLOT + 512 + ln * 4), a4 = opaque(sb2 + O_SM + 512 + ln * 4);
          const uint32_t b1 = opaque(sb1 + O_BAR + 8 * MB_SM), b2 = opaque(sb2 + O_BAR + 8 * MB_SM);
          const uint32_t bt = opaque(mapa(sb, min(ln, 2u)) + O_BAR + 8 * MB_SM), at = opaque(bt + (O_MAXS + 48 - O_BAR - 8 * MB_SM));
          SCHED_FENCE();
          wg_wait<0>();
          pin<20>(sv);
#define TOKEN { if (TOK) mbar_arrive_clp(bt, ln < 3); else sta1p(at, 0u, bt, ln < 3); }
          if (SSP >= 1) TOKEN
          if (SSP == 3) { bar_arrive<B_SSENT, 256>(); SCHED_FENCE(); }
          m0 = pack2(sv[2], sv[3]); m1 = pack2(sv[6], sv[7]); m2 = pack2(sv[10], sv[11]); m3 = pack2(sv[14], sv[15]); m4 = pack2(sv[18], sv[19]);
          if (SSP == 2) { SCHED_FENCE(); bar_arrive<B_SSENT, 256>(); }
          if (w == 0) {
            sta4(a1, m0, m1, m2, m3, b1);
            sta4(a2, m0, m1, m2, m3, b2);
            sta1(a3, m4, b1);
            sta1(a4, m4, b2);
          }
          if (SSP == 0) TOKEN
          if (SSP < 2) bar_arrive<B_SSENT, 256>();
          SCHED_FENCE();
        }
        const uint32_t p0 = pack2(sv[0], sv[1]), p1 = pack2(sv[4], sv[5]), p2 = pack2(sv[8], sv[9]), p3 = pack2(sv[12], sv[13]), p4 = pack2(sv[16], sv[17]);
        const uint32_t ox = O_K + w * 2048 + ln * 16, ox2 = O_K + 8192 + ln * 4;
        {
          const uint32_t a1 = opaque(sb1 + ox + 512), a2 = opaque(sb2 + ox), b1 = opaque(sb1 + O_BAR + 8 * MB_SX), b2 = opaque(sb2 + O_BAR + 8 * MB_SX);
          if (w == 0) {
            TS(7);
            const uint32_t om = opaque(sb + O_SM + ln * 16), om2 = opaque(sb + O_SM + 512 + ln * 4);
            const uint32_t pa0 = ld_m + (O_QM - O_H), pa1 = (ld_m ^ 64) + (O_QM - O_H);
            float t[10] = {bflo(m0), bfhi(m0), bflo(m1), bfhi(m1), bflo(m2), bfhi(m2), bflo(m3), bfhi(m3), bflo(m4), bfhi(m4)};
            pin<10>(t);
            SCHED_FENCE();
            mbar_waitf(bar + 8 * MB_SM, par);
            const uint4 u = lds4(om), v = lds4(om + SM_SLOT);
            const uint32_t u4 = lds1(om2), v4 = lds1(om2 + SM_SLOT);
            sta4(a1, p0, p1, p2, p3, b1);
            sta4(a2, p0, p1, p2, p3, b2);
            bar_arrive<B_SLD, 256>();
            SCHED_FENCE();
            ACC3(0, u.x, v.x) ACC3(2, u.y, v.y) ACC3(4, u.z, v.z) ACC3(6, u.w, v.w) ACC3(8, u4, v4)
            TS(8);
            const float f = exp_row(t);
            stsm4(pa0, pack2(t[0] * f, t[1] * f), pack2(t[2] * f, t[3] * f), pack2(t[4] * f, t[5] * f), pack2(t[6] * f, t[7] * f));
            stsm1(pa1, pack2(t[8] * f, t[9] * f));
            bar_arrive<B_PM, 160>();
            TS(9);
          } else {
            const uint32_t a3 = opaque(sb1 + ox2 + 128), a4 = opaque(sb2 + ox2);
            SCHED_FENCE();
            mbar_waitf(bar + 8 * MB_SM, par);
            sta4(a1, p0, p1, p2, p3, b1);
            sta4(a2, p0, p1, p2, p3, b2);
            if (w == 3) { sta1(a3, p4, b1); sta1(a4, p4, b2); }
            bar_arrive<B_SLD, 256>();
          }
        }
        {
          float t[10] = {bflo(p0), bfhi(p0), bflo(p1), bfhi(p1), bflo(p2), bfhi(p2), bflo(p3), bfhi(p3), bflo(p4), bfhi(p4)};
          const int dq = 8 * w + (ln >> 2) - 2 * (ln & 3);
#pragma unroll
          for (int k = 1; k < 5; k++) {
            if (8 * (k - 1) > dq) t[2 * k] = -1e9f / SCL;
            if (8 * (k - 1) + 1 > dq) t[2 * k + 1] = -1e9f / SCL;
          }
          const int rr = 2 * w + (ln & 1);
          const uint32_t pa = sb + O_QK + ((ln >> 1) & 3) * 2048 + rr * 128;
          const uint32_t pa0 = opaque(pa + (((ln >> 3) ^ rr) << 4)), pa1 = opaque(pa0 ^ 64), l0 = opaque(sb + ox), l1 = opaque(sb + ox2);
          pin<10>(t);
          SCHED_FENCE();
          mbar_waitf(bar + 8 * MB_SX, par);
          bar_sync<B_VEND, 256>();
          const uint4 u = lds4(l0), v = lds4(l0 + 512);
          uint32_t u4 = 0, v4 = 0;
          if (w == 3) { u4 = lds1(l1); v4 = lds1(l1 + 128); }
          ACC3(0, u.x, v.x) ACC3(2, u.y, v.y) ACC3(4, u.z, v.z) ACC3(6, u.w, v.w) ACC3(8, u4, v4)
          const float f = exp_row(t);
          const float sum = (((t[0] + t[1]) + (t[2] + t[3])) + ((t[4] + t[5]) + (t[6] + t[7])) + (t[8] + t[9])) * f;
          const float s1 = __shfl_xor_sync(~0u, sum, 1), s2 = __shfl_xor_sync(~0u, sum, 2), s3 = __shfl_xor_sync(~0u, sum, 3);
          const float inv = f * rcp((sum + s1) + (s2 + s3));
          stsm4(pa0, pack2(t[0] * inv, t[1] * inv), pack2(t[2] * inv, t[3] * inv), pack2(t[4] * inv, t[5] * inv), pack2(t[6] * inv, t[7] * inv));
          stsm2(pa1, pack2(t[8] * inv, t[9] * inv), 0u);
          fence_async();
        }
        bar_arrive<B_PX, 256>();
        if (w == 0) TS(10);
        bar_sync<B_XGO, 256>();
      } else {
        bar_arrive<B_QK, 256>();
        const int ln = opaque(lane);
        if (w == 2) {
          bar_sync<B_VHALF, 192>();
          if (ln == 0 && s > 0) { red_release(flags + FL_A + (e0 >> 10) * 8 + (s - 1) * 48, 1); }
          __syncwarp();
        }
        if (w == 3) {
          const int l = bid * 2 + ln, s2 = s + 2;
          if (ln < 2 && l < 160 && s2 < NSEG - 1) {
            const int tile = l >> 4;
            const uint8_t* p = ar + (s2 >> 2) * AR_GROUP + (s2 & 1) * 128 + ((s2 >> 1) & 1) * 512 + ar_chunk(tile) * 4096 +
                               ((l >> 3) & 1) * 16384 + (l & 1) * 256 + ((l >> 1) & 3) * 1024;
            asm volatile("prefetch.global.L2 [%0];" :: "l"(p));
          }
        }
        if (w == 0) {
          const bool more = s + 1 < NSEG;
          if (ln < 2 && more) mbar_expect(bar + 8 * (MB_XF + ln), 20480);
          const uint8_t* src = g_xn + (s + 1) * 40960;
          if ((s & 1) && more) { wait_flag(flags + FL_XN + ((s + 1) >> 1) * 8, 3); fence_async_global(); }
          bar_sync<B_VHALF, 192>();
          if (more) {
#pragma unroll
            for (int q = 0; q < 5; q++) { const int p = q == 0 ? 9 : q - 1; bulk_g2s_elect<4096>(sb + O_H + p * 5120 + 1024, src + chunk_of(p) * 4096, bar + 8 * MB_XF); }
          }
          bar_sync<B_VDONE, 160>();
          if (more) {
#pragma unroll
            for (int p = 4; p < 9; p++) bulk_g2s_elect<4096>(sb + O_H + p * 5120 + 1024, src + chunk_of(p) * 4096, bar + 8 * (MB_XF + 1));
          }
        }
        bar_sync<B_XGO1, 256>();
      }
    }
  } else {
    asm volatile("setmaxnreg.dec.sync.aligned.u32 88;");
    asm volatile("barrier.cluster.wait.aligned;" ::: "memory");

    const int g = lane >> 2, i4 = lane & 3;
    const int myT = w == 0 ? 9 : rank * 3 + w - 1, myP = w == 0 ? 9 : w - 1;
    const int tok = 2 * ((lane >> 1) & 3) + ((lane >> 3) & 1);
    const uint32_t fw_off = sb + O_H + myP * 5120 + tok * 128 + (((2 * (lane >> 4) + (lane & 1)) ^ tok) << 4);
    const uint32_t prod_off = (w >> 1) * 16384 + (w & 1) * 2048 + ((g >> 1) & 1) * 256 + (i4 * 2 + (g >> 2)) * 16 + (g & 1) * 8;
    const uint32_t cons_off = ar_chunk(myT) * 4096 + (lane >> 3) * 1024 + (lane & 7) * 16;
    auto tile_off = [&](int k) { return (k * 8 + rank) * 4096; };
    constexpr uint32_t T9_OFF = ar_chunk(9) * 4096;

    uint32_t p[8];
    auto forward = [&]() {
      const uint32_t c = O_H + myP * 5120, bo = O_BAR + 8 * MB_MR;
      sts4(fw_off, p[0], p[1], p[2], p[3]);
      sts4(fw_off ^ 64, p[4], p[5], p[6], p[7]);
      if (w == 0) {
        __syncwarp();
        mbar_arrive_elect(bar + 8 * MB_ML);
        fence_async();
      } else {
        bar_arrive<B_ML, 352>();
        fence_async();
        __syncwarp();
        bulk_s2c_elect1<1024>(sb1 + c + 6 * 5120, sb1 + bo, sb + c);
        bulk_s2c_elect1<1024>(sb2 + c + 3 * 5120, sb2 + bo, sb + c);
      }
    };
    auto send_max = [&]() {
      uint32_t mx = 0;
#pragma unroll
      for (int k = 0; k < 8; k++) mx = __vmaxu2(mx, p[k] & 0x7FFF7FFFu);
      mx = max(mx & 0xFFFFu, mx >> 16);
      mx = __reduce_max_sync(~0u, mx);
      { const uint32_t b = mapa(sb, min(lane, 2)); sta1p(b + O_MAXS + (rank * 4 + w) * 4, mx << 16, b + O_BAR + 8 * MB_SM, lane < 3); }
    };
    auto arm = [&]() { if (lane == 0 && w < 2) mbar_expect(bar + 8 * (w == 0 ? MB_OG : MB_MR), w == 0 ? 2048 : 6144); };
    {
      arm();
      const uint32_t* mp = (const uint32_t*)(mem0 + tok * DM + myT * 64 + 16 * (lane >> 4) + 4 * (lane & 1));
      p[0] = mp[0]; p[1] = mp[4]; p[2] = mp[1]; p[3] = mp[5]; p[4] = mp[16]; p[5] = mp[20]; p[6] = mp[17]; p[7] = mp[21];
      forward();
    }
    if (w == 1) {
#pragma unroll 1
      for (int i = W_WIN; i < 20; i++) {
        if (i <= W_OPEN) mbar_wait(bar + 8 * (MB_W + i - W_WIN), 0);
        if (i >= 10) mbar_wait(bar + 8 * (MB_WC + i - 10), 0);
        load_piece(i);
      }
    }
    if (w == 0) {
      if (lane < 2) mbar_expect(bar + 8 * (MB_XF + lane), 20480);
      wait_flag<200>(flags + FL_XN, 3);
      fence_async_global();
      if (lane < 10) bulk_g2s(sb + O_H + lane * 5120 + 1024, g_xn + chunk_of(lane) * 4096, 4096, bar + 8 * (MB_XF + (lane >= 4 && lane < 9)));
      if (lane == 0) GTT(layer * 4 + 1, 4);
    }
    if (w == 2) {
      wait_flag<400>(flags + FL_X, 128);
      wait_flag<400>(g_zero + Z_FLAGS + FL_N, 4);
      const float sq = __ldcg((const float*)(g_zero + Z_NORM));
      float mx = 0.f;
#pragma unroll
      for (int k = 0; k < 5; k++) {
        const float4* p = (const float4*)g_nrm + k * 32 + lane;
        const float4 x = __ldcg(p), y = __ldcg(p + 160), z = __ldcg(p + 320), u = __ldcg(p + 480);
        mx = fmaxf(fmaxf(mx, fmaxf((x.x + y.x) + (z.x + u.x), (x.y + y.y) + (z.y + u.y))), fmaxf((x.z + y.z) + (z.z + u.z), (x.w + y.w) + (z.w + u.w)));
      }
#pragma unroll
      for (int o = 16; o; o >>= 1) mx = fmaxf(mx, __shfl_xor_sync(~0u, mx, o));
      sts1(sb + O_MAXS + 52, __float_as_uint(sqrt_approx(sq) * sqrt_approx(mx) * (25.2982213f * 1.1f)));
    }
    bar_sync<B_WG2, 128>();
    const float cbound = __uint_as_float(lds1(sb + O_MAXS + 52));
#pragma unroll 1
    for (int i = 10; i < 15; i++) mbar_wait(bar + 8 * (MB_W + i), 0);
    if (tid == 256) GTT(layer * 4 + 1, 7);

    const uint32_t la_w = sb + O_WV + ((lane >> 4) * 8 + (lane & 7)) * 128 + (((2 * w + ((lane >> 3) & 1)) ^ (lane & 7)) << 4);
    uint32_t af[V_RS][4];
#pragma unroll
    for (int k = 0; k < V_RS; k++) ldsm4t(af[k], la_w + vord(V_OWN + k) * 2048);
    const uint32_t pa0 = __shfl_sync(~0u, sb + O_QM + (lane & 7) * 128 + (((lane >> 3) ^ (lane & 7)) << 4), lane), pa1 = __shfl_sync(~0u, pa0 ^ 64, lane);
    uint32_t vf[10];
    uint4 oq0, oq1;
    uint8_t* op;
    auto pv_x = [&](int s) {
      float ox[16];
      const uint32_t vz[4] = {vf[8], vf[9], 0u, 0u};
      constexpr uint64_t dp = mkdesc(SB0 + O_QK, 16, 2048, 1);
      bar_sync<B_PX, 256>();
      wg_fence();
      wg_rs_n32_tb0(ox, vf, dp, 0);
      wg_rs_n32_tb0(ox, vf + 4, dp + 2, 1);
      wg_rs_n32_tb0(ox, vz, dp + 4, 1);
      wg_commit();
      const uint32_t ln = opaque(lane);
      op = g_ot + (size_t)s * (HE * 64) + (e0 + 16 * w) * 64 + (ln & 3) * 128 + (ln >> 2) * 16;
      wg_wait<0>();
      pin<16>(ox);
      oq0 = make_uint4(pack2(ox[0], ox[1]), pack2(ox[4], ox[5]), pack2(ox[8], ox[9]), pack2(ox[12], ox[13]));
      oq1 = make_uint4(pack2(ox[2], ox[3]), pack2(ox[6], ox[7]), pack2(ox[10], ox[11]), pack2(ox[14], ox[15]));
    };
    for (int s = 0;; s++) {
      const uint32_t par = s & 1;
      float sc1, isc, sum0, sum1;
      uint32_t ao[O_RS][4];
      {
        float av[20];
        constexpr uint64_t da = mkdesc(SB0 + O_WV, 1024, 1024, 1), db = mkdesc(SB0 + O_H, 16, 1024, 1);
#define V_RUN(k0, k1) wg_fence(); _Pragma("unroll") for (int k = k0; k < k1; k++) wg_ss_n40_ta1_tb0(av, da + vord(k) * 128, db + hoff(vord(k)), k);
        bar_sync<B_VOWN, 384>();
        V_RUN(0, V_OWN)
        if (w == 0) TS(29);
        SCHED_FENCE();
        if (w == 0) { mbar_waitf(bar + 8 * MB_MR, par); bar_arrive<B_MR, 288>(); SCHED_FENCE(); }
        send_max();
        bar_sync<B_SISS, 256>();
        V_RUN(V_OWN + V_RS, V_OWN + V_RS + V_B)
        if (s == 0) {
#pragma unroll 1
          for (int i = 15; i < 20; i++) mbar_wait(bar + 8 * (MB_W + i), 0);
          asm volatile("griddepcontrol.launch_dependents;");
          if (tid == 256) GTT(layer * 4 + 1, 8);
        }
        bar_sync<B_SSENT, 256>();
        V_RUN(V_OWN + V_RS + V_B, V_K1)
        wg_fence();
#pragma unroll
        for (int k = 0; k < V_RS; k++) wg_rs_n40_tb0(av, af[k], db + hoff(vord(V_OWN + k)), 1);
        if (V_K1 >= 20) wg_commit();
        const uint32_t ln = opaque(lane);
        const uint32_t amx = opaque(sb + O_MAXS + 4 * min(ln, 11u));
        SCHED_FENCE();
        mbar_waitf(bar + 8 * MB_SM, par);
        const uint32_t mxl = lds1(amx);
        if (V_S2 == 0) { wg_wait<0>(); bar_arrive<B_VHALF, 192>(); }
        bar_sync<B_SLD, 256>();
        if (V_K1 < 20) { V_RUN(V_K1, 20) wg_commit(); }
        if (V_S2 > 0) {
          V_RUN((V_K1 > 20 ? V_K1 : 20), V_K2)
          wg_commit();
          wg_wait<1>();
          bar_arrive<B_VHALF, 192>();
        }
        V_RUN(V_K2, 40)
        wg_commit();
        SCHED_FENCE();
        if (w == 0) TS(12);
        {
          const float bnd = cbound * fmaxf(1.f, __uint_as_float(__reduce_max_sync(~0u, mxl)));
          const uint32_t eb = min(max(__float_as_uint(bnd) >> 23, 31u), 254u);
          sc1 = __uint_as_float(opaque((280u - eb) << 23));
          isc = __uint_as_float(opaque((eb - 29u) << 23));
        }
        const uint32_t o = O_OG + w * 256 + ln * 4;
        const uint32_t a0 = opaque(sb + o), a1 = opaque(sb1 + o + 4096), a2 = opaque(sb1 + o + 4096 + 128), a3 = opaque(sb2 + o + 2048), a4 = opaque(sb2 + o + 2048 + 128);
        const uint32_t b1 = opaque(sb1 + O_BAR + 8 * MB_OG), b2 = opaque(sb2 + O_BAR + 8 * MB_OG);
        const uint32_t c1 = opaque(0x3F803F80u);
        const uint32_t one[4] = {c1, c1, c1, c1};
        uint32_t pm[5];
        bar_arrive<B_VEND, 256>();
        SCHED_FENCE();
        bar_sync<B_PM, 160>();
        ldsm4(pm, pa0);
        ldsm1(pm[4], pa1);
        SCHED_FENCE();
        wg_wait<0>();
        pin<20>(av);
        if (w == 0) TS(13);
#pragma unroll
        for (int j = 0; j < 16; j++) if ((O_RSM >> j) & 1) ldsm4t(ao[O_IDX(j)], la_w + O_WO + (1 + (j >> 3)) * 24576 + (4 + (j & 7)) * 2048);
#pragma unroll
        for (int k = 0; k < 10; k++) vf[k] = pack2(av[2 * k], av[2 * k + 1]);
        float o0[4] = {0.f, 0.f, 0.f, 0.f}, o1[4] = {0.f, 0.f, 0.f, 0.f}, o2[4] = {0.f, 0.f, 0.f, 0.f};
        float s0[4] = {0.f, 0.f, 0.f, 0.f}, s1[4] = {0.f, 0.f, 0.f, 0.f}, s2[4] = {0.f, 0.f, 0.f, 0.f};
        mma16816(o0, vf, pm[0], pm[1]);
        mma16816(o1, vf + 4, pm[2], pm[3]);
        mma1688(o2, vf[8], vf[9], pm[4]);
        mma16816(s0, one, pm[0], pm[1]);
        mma16816(s1, one, pm[2], pm[3]);
        mma1688(s2, c1, c1, pm[4]);
        const uint32_t p0 = pack2(o0[0] + o1[0] + o2[0], o0[1] + o1[1] + o2[1]), p1 = pack2(o0[2] + o1[2] + o2[2], o0[3] + o1[3] + o2[3]);
        sta1(a1, p0, b1); sta1(a2, p1, b1);
        sta1(a3, p0, b2); sta1(a4, p1, b2);
        sts1(a0, p0); sts1(a0 + 128, p1);
        sum0 = s0[0] + s1[0] + s2[0]; sum1 = s0[1] + s1[1] + s2[1];
        fence_async();
      }
      if (s == NSEG - 1) break;
      uint8_t* arp;
      uint32_t t1;
      {
        bar_sync<B_WG2, 128>();
        float c9[4], ca[4], cb[4], cc[4];
        constexpr uint64_t da = mkdesc(SB0 + O_WO, 1024, 1024, 1), db = mkdesc(SB0 + O_OG, 128, 128, 0);
#define O_RUN(acc, tile, k0, k1) _Pragma("unroll") for (int k = k0; k < k1; k++) wg_ss_n8_ta1_tb1(acc, da + (tile) * 1536 + k * 128, db + (k >> 2) * 128 + (k & 3) * 16, k);
        wg_fence();
        O_RUN(c9, 3, 0, 4)
        wg_commit();
        if (w == 0) TS(14);
        O_RUN(ca, 0, 0, 4) O_RUN(cb, 1, 0, 2)
        wg_commit();
        SCHED_FENCE();
        arp = ar + (s >> 2) * AR_GROUP + (s & 1) * 128 + ((s >> 1) & 1) * 512;
        uint8_t* pp = arp + opaque(prod_off);
        const float2 sc = make_float2(sc1 * rcp(sum0), sc1 * rcp(sum1));
        wg_wait<1>();
        pin<4>(c9);
        fix_red(pp + T9_OFF, c9, sc);
        SCHED_FENCE();
        wg_fence();
        O_RUN(cb, 1, 2, 4) O_RUN(cc, 2, 0, 4)
        mbar_waitf(bar + 8 * MB_OG, par);
        wg_fence();
        O_RUN(ca, 0, 4, 12)
        wg_commit();
        if (w == 0) TS(15);
#define O_MIX(acc, j0, j1) _Pragma("unroll") for (int j = j0; j < j1; j++) { const int k = 4 + (j & 7); \
          if ((O_RSM >> j) & 1) wg_rs_n8_tb1(acc, ao[O_IDX(j) < O_RS ? O_IDX(j) : 0], db + (k >> 2) * 128 + (k & 3) * 16, 1); \
          else wg_ss_n8_ta1_tb1(acc, da + (1 + (j >> 3)) * 1536 + k * 128, db + (k >> 2) * 128 + (k & 3) * 16, 1); }
        O_MIX(cb, 0, O_B1)
        wg_commit();
        wg_wait<1>();
        pin<4>(ca);
        fix_red(pp + tile_off(0), ca, sc);
        SCHED_FENCE();
        if (w == 0) TS(16);
        bar_arrive<B_VDONE, 160>();
        wg_fence();
        O_MIX(cb, O_B1, 8)
        wg_commit();
        O_MIX(cc, 8, 16)
        wg_commit();
        bar_arrive<B_XGO1, 256>();
        bar_arrive<B_XGO, 256>();
        wg_wait<1>();
        pin<4>(cb);
        uint8_t* pb = pp + tile_off(1);
        fix_red(pb, cb, sc);
        wg_wait<0>();
        pin<4>(cc);
        fix_red(pb + 32768, cc, sc);
        t1 = clk();
        if (w == 3) TS(17);
      }
      pv_x(s);
      mbar_arrive_elect(bar + 8 * MB_PF);
      if (w == 0) TS(28);
      {
        arm();
        const int dly = w == 0 ? POLL_9 : w == 1 ? POLL_A : w == 2 ? POLL_B : POLL_C;
        const uint32_t need = w == 0 ? 96 : 32;
        const uint8_t* cp = arp + opaque(cons_off);
        uint4 y[4];
        int it = 0;
        while ((int)(clk() - t1) < dly) {}
        if (w == 3) TS(18);
        y[0] = ld_poll(cp); y[1] = ld_poll(cp + 256); y[2] = ld_poll(cp + 16384); y[3] = ld_poll(cp + 16384 + 256);
        { const uint64_t pol = policy_evict_first(); stg4h(op, oq0, pol); stg4h(op + 512, oq1, pol); }
        const float isl = isc * 0.5f, bias = -(float)(need >> 3) * isl;
        while (true) {
          const uint32_t bad = ((y[0].x ^ need) | (y[0].z ^ need) | (y[1].x ^ need) | (y[1].z ^ need)) | ((y[2].x ^ need) | (y[2].z ^ need) | (y[3].x ^ need) | (y[3].z ^ need));
          if (!__any_sync(~0u, (bad & 127u) != 0)) break;
          if (++it > 2000000) __trap();
          y[0] = ld_poll(cp); y[1] = ld_poll(cp + 256); y[2] = ld_poll(cp + 16384); y[3] = ld_poll(cp + 16384 + 256);
        }
#pragma unroll
        for (int k = 0; k < 4; k++) {
          p[2 * k] = pack2(fmaf((float)(int)__funnelshift_r(y[k].x, y[k].y, 3), isl, bias), fmaf((float)(int)__funnelshift_r(y[k].z, y[k].w, 3), isl, bias));
          p[2 * k + 1] = pack2((float)(int)y[k].y * isc, (float)(int)y[k].w * isc);
        }
        TS(19 + w);
        forward();
      }
    }
    bar_arrive<B_VDONE, 160>();
    bar_arrive<B_XGO1, 256>();
    bar_arrive<B_XGO, 256>();
    pv_x(NSEG - 1);
    { const uint64_t pol = policy_evict_first(); stg4h(op, oq0, pol); stg4h(op + 512, oq1, pol); }
    bar_sync<B_WG2, 128>();
    if (tid == 256) red_release(flags + FL_A + (e0 >> 10) * 8 + (NSEG - 1) * 48, 1);
    mbar_wait(bar + 8 * MB_OG, 1);
    __syncwarp();
  }
  asm volatile("barrier.cluster.arrive.relaxed.aligned;\nbarrier.cluster.wait.aligned;" ::: "memory");
  GT(layer * 4 + 1, 2);
  if (wid == 0) asm volatile("griddepcontrol.wait;" ::: "memory");
}

constexpr int P_B = 0, P_A = 131072, P_BAR = 196608, OPC_SMEM = P_BAR + 256;
#define PF_C 3
#define PF_S0 43
constexpr int OP_KR = 48;

__global__ void __launch_bounds__(384, 1)
opc_kernel(const __grid_constant__ CUtensorMap tmo, bf16* __restrict__ out, int layer,
           const bf16* __restrict__ Wq, const bf16* __restrict__ Wk, const bf16* __restrict__ Wv, const bf16* __restrict__ Wo) {
  extern __shared__ __align__(1024) uint8_t smem[];
  asm volatile("griddepcontrol.launch_dependents;");
  GT(layer * 4 + 2, 0);
  const uint32_t sb = smem_u32(smem);
  check_smem_base(sb);
  const int tid = threadIdx.x, wid = __shfl_sync(~0u, tid >> 5, 0), wg = wid >> 2, w = wid & 3, lane = tid & 31;
  const uint32_t bar = sb + P_BAR;
  uint32_t* flags = g_zero + Z_FLAGS + layer * FL_LAYER;
  float* acc = g_acc + layer * (S_TOK * DM);
  const uint64_t pol = policy_evict_first();
  if (wid == 0) {
    if (lane < 16) mbar_init(bar + 8 * lane, (lane == 8 || lane == 9) ? 8 : 1);
    fence_async();
  }
  __syncthreads();
  if (blockIdx.x < 30) {
    const int cg = blockIdx.x % 5, kg = blockIdx.x / 5;
    if (wg < 2) {
      asm volatile("setmaxnreg.inc.sync.aligned.u32 240;");
      uint32_t a[OP_KR][4];
      const uint32_t la = sb + P_B + ((lane >> 4) * 8 + (lane & 7)) * 128 + (((2 * w + ((lane >> 3) & 1)) ^ (lane & 7)) << 4);
      mbar_wait(bar + 80, 0);
#pragma unroll
      for (int k = 0; k < 32; k++) ldsm4t(a[k], la + wg * 65536 + k * 2048);
      bar_arrive<2, 288>();
      mbar_wait(bar + 88, 0);
#pragma unroll
      for (int k = 0; k < 16; k++) ldsm4t(a[32 + k], la + wg * 32768 + k * 2048);
      bar_arrive<3, 288>();
      mbar_wait(bar + 96, 0);
      float* ap = acc + (cg * 8 + wg * 4 + w) * 512 + lane * 4;
      for (int s = 0; s < NSEG; s++) {
        const int buf = s & 1;
        const uint32_t par = (s >> 1) & 1;
        float d[16];
        const uint64_t db = mkdesc(SB0 + P_B + buf * 65536, 512, 128, 0), da = mkdesc(SB0 + P_A + wg * 32768, 1024, 1024, 1);
        float* p = ap + s * (32 * DM);
        float* pz = ap + (s + 2) * (32 * DM) + kg * 128;
        if (kg < 4 && s + 2 < NSEG) { if (EVF) stg4h(pz, make_uint4(0, 0, 0, 0), pol); else stg4(pz, make_uint4(0, 0, 0, 0)); }
#pragma unroll
        for (int q = 0; q < 4; q++) {
          mbar_wait(bar + 8 * (buf * 4 + q), par);
          wg_fence();
#pragma unroll
          for (int k = 16 * q; k < 16 * q + 16; k++) {
            if (k < OP_KR) wg_rs_n32_tb1(d, a[k < OP_KR ? k : 0], db + k * 64, k);
            else wg_ss_n32_ta1_tb1(d, da + (k - OP_KR) * 128, db + k * 64, 1);
          }
        }
        wg_commit();
        wg_wait<0>();
        pin<16>(d);
        if (lane == 0) mbar_arrive(bar + 8 * (8 + buf));
        if (s == NSEG - 1) GT(layer * 4 + 2, 6);
        if (EVF) {
          red4fh(p, d[0], d[1], d[4], d[5], pol);
          red4fh(p + 128, d[8], d[9], d[12], d[13], pol);
          red4fh(p + 256, d[2], d[3], d[6], d[7], pol);
          red4fh(p + 384, d[10], d[11], d[14], d[15], pol);
        } else {
          red4f(p, d[0], d[1], d[4], d[5]);
          red4f(p + 128, d[8], d[9], d[12], d[13]);
          red4f(p + 256, d[2], d[3], d[6], d[7]);
          red4f(p + 384, d[10], d[11], d[14], d[15]);
        }
        bar_sync<1, 256>();
        if (tid == 0) { red_release(flags + FL_B + s * 8, 1); }
        __syncwarp();
      }
    } else {
      asm volatile("setmaxnreg.dec.sync.aligned.u32 24;");
      if (w == 0) {
        if (lane == 0) { mbar_expect(bar + 80, 131072); mbar_expect(bar + 96, 65536); mbar_expect(bar + 88, 65536); }
        __syncwarp();
        if (lane < 16) tma2d(sb + P_B + lane * 8192, &tmo, cg * 128 + (lane >> 3) * 64, kg * 1024 + (lane & 7) * 64, bar + 80);
        else if (lane < 24) tma2d(sb + P_B + lane * 8192, &tmo, cg * 128 + ((lane >> 2) & 1) * 64, kg * 1024 + 768 + (lane & 3) * 64, bar + 96);
        bar_sync<2, 288>();
        fence_async();
        if (lane < 8) tma2d(sb + P_B + lane * 8192, &tmo, cg * 128 + (lane >> 2) * 64, kg * 1024 + 512 + (lane & 3) * 64, bar + 88);
        bar_sync<3, 288>();
        for (int s = 0; s < NSEG; s++) {
          const int buf = s & 1;
          if (s >= 2) mbar_wait(bar + 8 * (8 + buf), ((s >> 1) & 1) ^ 1);
          if (s >= 2) wait_flag(flags + FL_B + (s - 2) * 8, 30);
          wait_flag(flags + FL_A + s * 48 + kg * 8, 16);
          fence_async_global();
          if (lane < 4) {
            mbar_expect(bar + 8 * (buf * 4 + lane), 16384);
            if (EVF) bulk_g2sh(sb + P_B + buf * 65536 + lane * 16384, g_ot + (size_t)s * (HE * 64) + kg * 65536 + lane * 16384, 16384, bar + 8 * (buf * 4 + lane), pol);
            else bulk_g2s(sb + P_B + buf * 65536 + lane * 16384, g_ot + (size_t)s * (HE * 64) + kg * 65536 + lane * 16384, 16384, bar + 8 * (buf * 4 + lane));
            if (s == NSEG - 1 && lane == 0) GTT(layer * 4 + 2, 5);
          }
          __syncwarp();
        }
      } else if (w == 1 && layer == 0) {
#pragma unroll 1
        for (int q = 4 * (4 - PF_C); q < 18; q++) {
          wait_flag(flags + FL_A + (PF_S0 + q) * 48 + kg * 8, 16);
          const int m = q >> 2;
          const uint8_t* W = m == 0 ? (const uint8_t*)Wo : m == 1 ? (const uint8_t*)Wv : m == 2 ? (const uint8_t*)Wk : m == 3 ? (const uint8_t*)Wq : (q & 1) ? g_w2 : g_w1;
          const int n = m < 4 ? 512 : (q & 1) ? 224 : 640, l0 = m < 4 ? blockIdx.x * 2048 + (q & 3) * 512 : blockIdx.x * n, lim = m < 4 ? 61440 : (q & 1) ? 6720 : 19200;
#pragma unroll 1
          for (int k = lane; k < n; k += 32) {
            if (l0 + k < lim) asm volatile("prefetch.global.L2 [%0];" :: "l"(W + (size_t)(l0 + k) * 128));
            __nanosleep(100);
          }
        }
      }
    }
  } else {
    constexpr int LD = 644;
    float* xs = (float*)smem;
    uint32_t par = 0;
    for (int task = blockIdx.x - 30; task < 2 * NSEG; task += 6, par ^= 1) {
      const int s = task >> 1, jj = task & 1;
      if (wid == 0) {
        wait_flag(flags + FL_XN + (task >> 2) * 8 + 1, 3);
        fence_async_global();
        if (lane == 0) { mbar_expect(bar, 20480); bulk_g2s(sb + 49152, g_x + task * 16 * DM, 20480, bar); }
      }
      if (wid == 1) { wait_flag(flags + FL_B + s * 8, 30); if (s == NSEG - 1 && lane == 0) GTT(layer * 4 + 2, 7); }
      __syncthreads();
      if (wid < 10) {
        float4 v[8];
#pragma unroll
        for (int k = 0; k < 8; k++) v[k] = EVF ? ldg4fh(acc + s * (32 * DM) + (wid * 8 + k) * 256 + jj * 128 + lane * 4, pol) : __ldcg((const float4*)(acc + s * (32 * DM) + (wid * 8 + k) * 256 + jj * 128 + lane * 4));
        float* xp = xs + (lane & 3) * 2 * LD + wid * 64 + (lane >> 2);
#pragma unroll
        for (int k = 0; k < 8; k++) { xp[k * 8] = v[k].x; xp[LD + k * 8] = v[k].y; xp[8 * LD + k * 8] = v[k].z; xp[9 * LD + k * 8] = v[k].w; }
      }
      mbar_wait(bar, par);
      __syncthreads();
      float v[2][20];
      const int pj = (lane & 24) + 2 * (lane & 3) + ((lane >> 2) & 1);
      const int tk0 = task * 16 + wid;
      if (wid < 8) {
        float sum[2] = {0.f, 0.f};
#pragma unroll
        for (int h = 0; h < 2; h++) {
#pragma unroll
          for (int k = 0; k < 10; k++) {
            const float2 u = *(const float2*)(xs + (wid + 8 * h) * LD + k * 64 + lane * 2);
            const uint32_t r = *(const uint32_t*)(smem + 49152 + (wid + 8 * h) * 1280 + k * 128 + pj * 4);
            v[h][2 * k] = u.x + bflo(r); v[h][2 * k + 1] = u.y + bfhi(r); sum[h] += v[h][2 * k] + v[h][2 * k + 1];
          }
        }
        if (!out) {
#pragma unroll
          for (int o = 16; o; o >>= 1) { sum[0] += __shfl_xor_sync(~0u, sum[0], o); sum[1] += __shfl_xor_sync(~0u, sum[1], o); }
          float q[2] = {0.f, 0.f};
#pragma unroll
          for (int h = 0; h < 2; h++) {
            sum[h] *= (1.f / DM);
#pragma unroll
            for (int k = 0; k < 20; k++) q[h] = fmaf(v[h][k] - sum[h], v[h][k] - sum[h], q[h]);
          }
#pragma unroll
          for (int o = 16; o; o >>= 1) { q[0] += __shfl_xor_sync(~0u, q[0], o); q[1] += __shfl_xor_sync(~0u, q[1], o); }
          uint8_t* xp = g_xt + (tk0 >> 7) * 163840 + (tk0 & 127) * 128 + (((lane >> 2) ^ (tk0 & 7)) << 4) + (lane & 3) * 4;
#pragma unroll
          for (int h = 0; h < 2; h++) {
            const float rs = rsqrtf(q[h] * (1.f / DM) + 1e-5f), sh = -sum[h] * rs;
#pragma unroll
            for (int k = 0; k < 10; k++) *(uint32_t*)(xp + h * 1024 + k * 16384) = pack2(fmaf(v[h][2 * k], rs, sh), fmaf(v[h][2 * k + 1], rs, sh));
          }
        }
      }
      fence_async();
      __syncthreads();
      if (!out) {
        if (tid == 352) red_release(flags + FL_LAYER + FL_T + (task >> 3) * 8, 1);
        __syncthreads();
      }
      if (wid < 8) {
        bf16* dst = out ? out + tk0 * DM + lane * 2 : g_x + tk0 * DM + pj * 2;
#pragma unroll
        for (int k = 0; k < 20; k++) *(uint32_t*)(dst + (k / 10) * 8 * DM + (k % 10) * 64) = pack2(v[k / 10][2 * (k % 10)], v[k / 10][2 * (k % 10) + 1]);
      }
    }
    __syncthreads();
    if (tid == 0 && !out) red_release(flags + FL_LAYER + FL_R, 1);
  }
  GT(layer * 4 + 2, 1);
  __syncwarp();
  asm volatile("griddepcontrol.wait;" ::: "memory");
  GT(layer * 4 + 2, 2);
}

constexpr int L_STAGE = 47104;
constexpr int L_KV = 0, L_B2 = 43008;
constexpr int L_BAR = 4 * L_STAGE;
constexpr int LA_SMEM = L_BAR + 256;
__device__ __forceinline__ float phi(float t) { return (fmaxf(t, 0.f) + 1e-6f) + ex2(fminf(t * 1.4426950408889634f, 0.f)); }
__device__ __forceinline__ void sqacc(uint32_t& h, uint32_t v) { asm("fma.rn.bf16x2 %0, %1, %1, %0;" : "+r"(h) : "r"(v)); }
__device__ __forceinline__ uint32_t phi2(float a, float b) { return pack2(phi(a), phi(b)); }
#define LA_LATE 6
#define PF_LB 1
#define PF_IL 1
#define PF_SLEEP1 400
#define RD1 0
#define PF_N0 2
#define PF_N1 0
#define PF_SLEEP 300

__global__ void __launch_bounds__(384, 1)
la_kernel(const bf16* __restrict__ Wq, const bf16* __restrict__ Wk, const bf16* __restrict__ Wv,
          const bf16* __restrict__ Wo, uint8_t* __restrict__ ar, int layer) {
  extern __shared__ __align__(1024) uint8_t smem[];
  const uint32_t sb = smem_u32(smem);
  check_smem_base(sb);
  const int tid = threadIdx.x, wid = __shfl_sync(~0u, tid >> 5, 0), wg = wid >> 2, w = wid & 3, lane = tid & 31, g = lane >> 2, i4 = lane & 3;
  const int cr = blockIdx.x & 1, hg = (blockIdx.x >> 1) & 7, tb = (blockIdx.x >> 4) * 2 + cr;
  const uint32_t bar = sb + L_BAR;
  uint32_t* flags = g_zero + Z_FLAGS + layer * FL_LAYER;
  asm volatile("griddepcontrol.launch_dependents;");
  GT(layer * 4, 0);
  if (wid == 0) {
    if (lane < 8) mbar_init(bar + 8 * lane, lane >= 4 ? (blockIdx.x < 128 ? 16 : 10) : 1);
    asm volatile("fence.mbarrier_init.release.cluster;" ::: "memory");
    fence_async();
  }
  if (blockIdx.x >= 128) {
    __syncthreads();
    const int q = blockIdx.x - 128;
    const uint8_t* src = (const uint8_t*)Wo + q * 1966080;
    if (wid == 11) {
#pragma unroll 1
      for (int it = 0; it < 48; it++) {
        const int st = it & 3;
        if (it >= 4) mbar_wait(bar + 8 * (4 + st), ((it >> 2) & 1) ^ 1);
        if (lane == 0) mbar_expect(bar + 8 * st, 40960);
        __syncwarp();
        if (lane < 4) bulk_g2s(sb + st * 40960 + lane * 10240, src + it * 40960 + lane * 10240, 10240, bar + 8 * st);
      }
    } else if (wid < 10) {
      float c[8] = {0.f, 0.f, 0.f, 0.f, 0.f, 0.f, 0.f, 0.f};
#pragma unroll 1
      for (int it = 0; it < 48; it++) {
        const int st = it & 3;
        mbar_wait(bar + 8 * st, (it >> 2) & 1);
        uint4 v[8];
#pragma unroll
        for (int k = 0; k < 8; k++) v[k] = lds4(sb + st * 40960 + k * 5120 + tid * 16);
        uint32_t h[4] = {0, 0, 0, 0};
#pragma unroll
        for (int k = 0; k < 8; k++) { sqacc(h[0], v[k].x); sqacc(h[1], v[k].y); sqacc(h[2], v[k].z); sqacc(h[3], v[k].w); }
        __syncwarp();
        if (lane == 0) mbar_arrive(bar + 8 * (4 + st));
#pragma unroll
        for (int k = 0; k < 4; k++) { c[2 * k] += bflo(h[k]); c[2 * k + 1] += bfhi(h[k]); }
      }
      float* red = (float*)(smem + 163840);
      *(float4*)(red + tid * 8) = make_float4(c[0], c[1], c[2], c[3]);
      *(float4*)(red + tid * 8 + 4) = make_float4(c[4], c[5], c[6], c[7]);
      bar_sync<1, 320>();
#pragma unroll
      for (int k = tid; k < DM; k += 320) g_nrm[q * DM + k] = (red[k] + red[DM + k]) + (red[2 * DM + k] + red[3 * DM + k]);
      asm volatile("griddepcontrol.wait;" ::: "memory");
      bar_sync<1, 320>();
      if (tid == 0) red_release(flags + FL_N, 1);
      GT(0, 2);
    }
    return;
  }
  __syncthreads();
  asm volatile("barrier.cluster.arrive.relaxed.aligned;" ::: "memory");
  if (layer == 0) asm volatile("griddepcontrol.wait;" ::: "memory");
  asm volatile("barrier.cluster.wait.aligned;" ::: "memory");
  if (wg == 2) {
    asm volatile("setmaxnreg.dec.sync.aligned.u32 40;");
    if (w == 0) {
      if (lane < 4) {
        mbar_expect(bar + 8 * lane, L_STAGE);
        bulk_g2s_mc(sb + lane * L_STAGE + 16384 + cr * 15360, g_w1 + (hg * 10 + lane) * 30720 + cr * 15360, 15360, bar + 8 * lane);
      }
      if (layer == 1) { if (LA_LATE) wait_flag(flags + FL_T + 15 * 8, LA_LATE); wait_flag(flags + FL_T + tb * 8, 8); fence_async_global(); }
      if (lane < 4) bulk_g2s(sb + lane * L_STAGE, g_xt + (tb * 10 + lane) * 16384, 16384, bar + 8 * lane);
#pragma unroll 1
      for (int kc = 4; kc < 10; kc++) {
        const int st = kc & 3;
        mbar_wait(bar + 8 * (4 + st), ((kc >> 2) & 1) ^ 1);
        if (lane == 0) {
          mbar_expect(bar + 8 * st, L_STAGE);
          bulk_g2s_mc(sb + st * L_STAGE + 16384 + cr * 15360, g_w1 + (hg * 10 + kc) * 30720 + cr * 15360, 15360, bar + 8 * st);
          bulk_g2s(sb + st * L_STAGE, g_xt + (tb * 10 + kc) * 16384, 16384, bar + 8 * st);
        }
        __syncwarp();
      }
    } else {
      const int t = tid - 288;
#pragma unroll 1
      for (int k = t; k < 768; k += 96) *(uint4*)(ar + blockIdx.x * 12288 + k * 16) = make_uint4(0, 0, 0, 0);
      if (layer == 0 || RD1) {
        float sv = 0.f;
        const uint4* pv = (const uint4*)((const uint8_t*)Wv + blockIdx.x * 61440) + t;
#pragma unroll 1
        for (int k = 0; k < 40; k += 5) {
          uint4 v[5];
#pragma unroll
          for (int j = 0; j < 5; j++) v[j] = __ldg(pv + (k + j) * 96);
          if (PF_IL && k < 25) {
            asm volatile("prefetch.global.L2 [%0];" :: "l"((const uint8_t*)Wq + blockIdx.x * 61440 + (k / 5) * 12288 + t * 128));
            if (PF_IL > 1) asm volatile("prefetch.global.L2 [%0];" :: "l"((const uint8_t*)Wk + blockIdx.x * 61440 + (k / 5) * 12288 + t * 128));
          }
#pragma unroll
          for (int j = 0; j < 5; j++) {
            sv = fmaf(bflo(v[j].x), bflo(v[j].x), fmaf(bfhi(v[j].x), bfhi(v[j].x), fmaf(bflo(v[j].y), bflo(v[j].y), fmaf(bfhi(v[j].y), bfhi(v[j].y), sv))));
            sv = fmaf(bflo(v[j].z), bflo(v[j].z), fmaf(bfhi(v[j].z), bfhi(v[j].z), fmaf(bflo(v[j].w), bflo(v[j].w), fmaf(bfhi(v[j].w), bfhi(v[j].w), sv))));
          }
        }
#pragma unroll
        for (int o = 16; o; o >>= 1) sv += __shfl_xor_sync(~0u, sv, o);
        if (lane == 0) atomicAdd((float*)(g_zero + Z_NORM + layer), sv);
      }
      if (layer == 1 && PF_LB) {
        const int l = blockIdx.x * 96 + t;
        if (l < 6720 + NLB * 640) asm volatile("prefetch.global.L2 [%0];" :: "l"(l < 6720 ? g_w2 + l * 128 : (const uint8_t*)g_x + (l - 6720) * 128));
      }
#pragma unroll 1
      for (int k = (layer && !RD1) ? 0 : 5 * PF_IL; k < 5 * (layer ? PF_N1 : PF_N0); k++) {
        const int m = k / 5;
        const bf16* W = m == 0 ? Wq : m == 1 ? Wk : m == 2 ? Wv : Wo;
        asm volatile("prefetch.global.L2 [%0];" :: "l"((const uint8_t*)W + blockIdx.x * 61440 + (k - m * 5) * 12288 + t * 128));
        __nanosleep(layer ? PF_SLEEP1 : PF_SLEEP);
      }
      if (t == 0) GTT(layer * 4, 14);
      bar_arrive<3, 352>();
    }
  } else {
    asm volatile("setmaxnreg.inc.sync.aligned.u32 232;");
    GT(layer * 4, 4);
    uint32_t pq[5][4];
    float* kv = (float*)(g_zero + Z_KV) + layer * KV_LAYER + hg * 1920;
    {
      float d[120];
#pragma unroll 1
      for (int kc = 0; kc < 10; kc++) {
        const int st = kc & 3;
        const uint64_t da = mkdesc(SB0 + st * L_STAGE + wg * 8192, 16, 1024, 1), db = mkdesc(SB0 + st * L_STAGE + 16384, 3840, 128, 0);
        mbar_wait(bar + 8 * st, (kc >> 2) & 1);
        wg_fence();
#pragma unroll
        for (int k = 0; k < 4; k++) wg_ss_n240_ta0_tb1(d, da + 2 * k, db + k * 480, kc | k);
        wg_commit();
        if (kc > 0) { wg_wait<1>(); if (lane < 2) mbar_arrive_cl(mapa(bar + 8 * (4 + ((kc - 1) & 3)), lane)); }
      }
      wg_wait<0>();
      pin<120>(d);
      GT(layer * 4, 5);
      bar_sync<1, 256>();
      const uint32_t kb = sb + L_KV + (wg * 8 + 2 * w + ((lane >> 3) & 1)) * 2688 + (lane >> 4) * 128 + (lane & 7) * 16;
#pragma unroll
      for (int j = 0; j < 5; j++) stsm4(kb + 1280 + j * 256, pack2(d[80 + 8 * j], d[81 + 8 * j]), pack2(d[82 + 8 * j], d[83 + 8 * j]), pack2(d[84 + 8 * j], d[85 + 8 * j]), pack2(d[86 + 8 * j], d[87 + 8 * j]));
      stsm2(kb + 2560, 0x3F803F80u, 0x3F803F80u);
#pragma unroll
      for (int j = 0; j < 5; j++) stsm4(kb + j * 256, phi2(d[40 + 8 * j], d[41 + 8 * j]), phi2(d[42 + 8 * j], d[43 + 8 * j]), phi2(d[44 + 8 * j], d[45 + 8 * j]), phi2(d[46 + 8 * j], d[47 + 8 * j]));
      fence_async();
      bar_sync<1, 256>();
      float e[44];
      {
        const uint64_t da = mkdesc(SB0 + L_KV + wg * 1024, 2688, 128, 0), db = mkdesc(SB0 + L_KV + 1280, 2688, 128, 0);
        wg_fence();
#pragma unroll
        for (int k = 0; k < 8; k++) wg_ss_n88_ta1_tb1(e, da + k * 336, db + k * 336, k);
        wg_commit();
        wg_wait<0>();
        pin<44>(e);
      }
#pragma unroll
      for (int h = 0; h < 2; h++) {
        const int row = wg * 64 + 16 * w + 8 * h + g;
        const int c = row < 80 ? 2 * i4 - (row / 20) * 20 : 100;
        float* dst = kv + row * 24 + c;
#pragma unroll
        for (int j = 0; j < 10; j++)
          asm volatile("{\n.reg .pred p;\nsetp.lt.u32 p, %3, 20;\n@p red.relaxed.gpu.global.add.v2.f32 [%0], {%1,%2};\n}" :: "l"(dst + 8 * j), "f"(e[4 * j + 2 * h]), "f"(e[4 * j + 2 * h + 1]), "r"(c + 8 * j) : "memory");
        asm volatile("{\n.reg .pred p;\nsetp.ne.u32 p, %2, 0;\n@p red.relaxed.gpu.global.add.f32 [%0], %1;\n}" :: "l"(kv + row * 24 + 20), "f"(e[40 + 2 * h]), "r"((int)(row < 80 && i4 == 0)) : "memory");
      }
      bar_sync<1, 256>();
      GT(layer * 4, 6);
      if (tid == 0) { red_release(flags + FL_KV + hg * 8, 1); }
      __syncwarp();
      pin<40>(d);
#pragma unroll
      for (int k = 0; k < 5; k++) {
        pq[k][0] = phi2(d[8 * k], d[8 * k + 1]); pq[k][1] = phi2(d[8 * k + 2], d[8 * k + 3]);
        pq[k][2] = phi2(d[8 * k + 4], d[8 * k + 5]); pq[k][3] = phi2(d[8 * k + 6], d[8 * k + 7]);
      }
    }
#pragma unroll 1
    for (int k = tid; k < 1600; k += 256) sts4(sb + L_B2 + k * 16, 0, 0, 0, 0);
    GT(layer * 4, 7);
    if (wid == 0) wait_flag(flags + FL_KV + hg * 8, 16);
    GT(layer * 4, 8);
    bar_sync<1, 256>();
    if (tid < 240) {
      const int dd = tid / 3, part = tid - dd * 3, n = (dd / 20) * 20 + 8 * part;
      const float4 v0 = __ldcg((const float4*)(kv + dd * 24 + 8 * part)), v1 = __ldcg((const float4*)(kv + dd * 24 + 8 * part + 4));
      const float z = __ldcg(kv + dd * 24 + 20);
      const uint32_t a = sb + L_B2 + (dd >> 3) * 2560 + (dd & 7) * 16, zz = pack2(z, z);
      const uint32_t a0 = a + (n >> 3) * 128 + (n & 7) * 2, a1 = a + ((n + 4) >> 3) * 128 + ((n + 4) & 7) * 2;
      sts2(a0, pack2(v0.x, v0.y), pack2(v0.z, v0.w)); sts2(a0 + 1280, zz, zz);
      if (part < 2) { sts2(a1, pack2(v1.x, v1.y), pack2(v1.z, v1.w)); sts2(a1 + 1280, zz, zz); }
    }
    fence_async();
    bar_sync<1, 256>();
    {
      float o[80];
      const uint64_t db = mkdesc(SB0 + L_B2, 2560, 128, 0);
      wg_fence();
#pragma unroll
      for (int k = 0; k < 5; k++) wg_rs_n160_tb1(o, pq[k], db + k * 320, k);
      wg_commit();
      wg_wait<0>();
      pin<80>(o);
      uint8_t* op = g_oa + (tb * 2 + wg) * 81920 + hg * 10240 + w * 256 + lane * 4;
#pragma unroll
      for (int j = 0; j < 20; j++) {
        const float inv = rcp(o[40 + 2 * j] + 1e-6f);
        *(uint32_t*)(op + (j >> 1) * 1024 + (j & 1) * 128) = pack2(o[2 * j] * inv, o[2 * j + 1] * inv);
      }
      GT(layer * 4, 9);
    }
    bar_sync<3, 352>();
    if (tid == 0) { red_release(flags + FL_O + tb * 8, 1); red_add(flags + FL_X, 1); }
    GT(layer * 4, 2);
    if (wid == 7) asm volatile("griddepcontrol.wait;" ::: "memory");
  }
}

__global__ void __launch_bounds__(256) prep_kernel(const bf16* __restrict__ x, const bf16* __restrict__ wqkv, const bf16* __restrict__ wo) {
  asm volatile("griddepcontrol.launch_dependents;");
  const int b = blockIdx.x, tid = threadIdx.x, lane = tid & 31;
  if (b < 160) GT(3, 0);
  if (b < 256) {
    const int row = b * 8 + (tid >> 5);
    float v[20], s = 0.f;
#pragma unroll
    for (int k = 0; k < 10; k++) { const uint32_t u = __ldg((const uint32_t*)(x + row * DM + k * 64 + lane * 2)); v[2 * k] = bflo(u); v[2 * k + 1] = bfhi(u); s += v[2 * k] + v[2 * k + 1]; }
#pragma unroll
    for (int o = 16; o; o >>= 1) s += __shfl_xor_sync(~0u, s, o);
    const float m = s * (1.f / DM);
    float q = 0.f;
#pragma unroll
    for (int k = 0; k < 20; k++) { v[k] -= m; q += v[k] * v[k]; }
#pragma unroll
    for (int o = 16; o; o >>= 1) q += __shfl_xor_sync(~0u, q, o);
    const float r = rsqrtf(q * (1.f / DM) + 1e-5f);
#pragma unroll
    for (int k = 0; k < 10; k++)
      *(uint32_t*)(g_xt + ((row >> 7) * 10 + k) * 16384 + (row & 127) * 128 + (((lane >> 2) ^ (row & 7)) << 4) + (lane & 3) * 4) = pack2(v[2 * k] * r, v[2 * k + 1] * r);
  } else if (b < 256 + 203) {
    uint4 v[4];
    const int u0 = (b - 256) * 1024 + tid;
#pragma unroll
    for (int it = 0; it < 4; it++) {
      const int u = u0 + it * 256, k8 = u & 7;
      const bf16* src;
      bool ok = true;
      if (b < 256 + 150) {
        const int nb = (u >> 3) % 30, kg = (u / 240) % 80, hg = u / 19200;
        src = wqkv + (kg * 8 + k8) * 1920 + (nb / 10) * 640 + hg * 80 + (nb % 10) * 8;
      } else {
        const int q = u - 153600, nb = (q >> 3) % 28, kg = (q / 224) % 80, c = (q / 17920) * 224 + nb * 8;
        ok = c < DM;
        src = wo + (kg * 8 + k8) * DM + (ok ? c : 0);
      }
      v[it] = __ldg((const uint4*)src);
      if (!ok) v[it] = make_uint4(0, 0, 0, 0);
    }
    uint8_t* dst = b < 256 + 150 ? g_w1 + u0 * 16 : g_w2 + (u0 - 153600) * 16;
#pragma unroll
    for (int it = 0; it < 4; it++) if (u0 + it * 256 < 207360) *(uint4*)(dst + it * 4096) = v[it];
  } else {
    const int t = (b - 459) * 256 + tid;
    for (int k = t; k < Z_END / 4; k += 16 * 256) ((uint4*)g_zero)[k] = make_uint4(0, 0, 0, 0);
    for (int k = t; k < 16 * DM; k += 16 * 256) { ((uint4*)g_acc)[k] = make_uint4(0, 0, 0, 0); ((uint4*)(g_acc + S_TOK * DM))[k] = make_uint4(0, 0, 0, 0); }
  }
  if (b < 160) GT(3, 2);
}

typedef CUresult (*EncodeFn)(CUtensorMap*, CUtensorMapDataType, cuuint32_t, void*, const cuuint64_t*, const cuuint64_t*, const cuuint32_t*,
                             const cuuint32_t*, CUtensorMapInterleave, CUtensorMapSwizzle, CUtensorMapL2promotion, CUtensorMapFloatOOBfill);
static void make_map(EncodeFn fn, CUtensorMap* m, const void* p, uint64_t cols, uint64_t rows, uint32_t bc, uint32_t br, CUtensorMapSwizzle sw) {
  cuuint64_t dims[2] = {cols, rows}; cuuint64_t strides[1] = {cols * 2}; cuuint32_t box[2] = {bc, br}; cuuint32_t es[2] = {1, 1};
  fn(m, CU_TENSOR_MAP_DATA_TYPE_BFLOAT16, 2, (void*)p, dims, strides, box, es, CU_TENSOR_MAP_INTERLEAVE_NONE, sw,
     CU_TENSOR_MAP_L2_PROMOTION_L2_128B, CU_TENSOR_MAP_FLOAT_OOB_FILL_NONE);
}

static void make_map_perm(EncodeFn fn, CUtensorMap* m, const void* p) {
  cuuint64_t dims[5] = {HE, 2, 2, 4, 40}; const cuuint64_t r = HE * 2; cuuint64_t strides[4] = {r, 8 * r, 2 * r, 16 * r};
  cuuint32_t box[5] = {64, 2, 2, 4, 4}; cuuint32_t es[5] = {1, 1, 1, 1, 1};
  fn(m, CU_TENSOR_MAP_DATA_TYPE_BFLOAT16, 5, (void*)p, dims, strides, box, es, CU_TENSOR_MAP_INTERLEAVE_NONE, CU_TENSOR_MAP_SWIZZLE_128B,
     CU_TENSOR_MAP_L2_PROMOTION_L2_128B, CU_TENSOR_MAP_FLOAT_OOB_FILL_NONE);
}

#define OPC_PDL 1
#define LA_PDL 1
#define REC_PDL 1
extern "C" void kernel_launch(void* const* d_in, const int* in_sizes, int n_in, void* d_out, int out_size) {
  const bf16* x = (const bf16*)d_in[0];
  const bf16* wqkv = (const bf16*)d_in[1];
  const bf16* wo_a = (const bf16*)d_in[2];
  const bf16* mem0 = (const bf16*)d_in[4];
  const bf16* Wq = (const bf16*)d_in[5];
  const bf16* Wk = (const bf16*)d_in[6];
  const bf16* Wv = (const bf16*)d_in[7];
  const bf16* Wo = (const bf16*)d_in[8];
  cudaStream_t st = cudaStreamPerThread;

  static EncodeFn enc = nullptr;
  static uint8_t* p_ar; static uint32_t* p_zero; static bf16* p_x;
  if (!enc) {
    cudaDriverEntryPointQueryResult qr;
    void* fn = nullptr;
    cudaGetDriverEntryPoint("cuTensorMapEncodeTiled", &fn, cudaEnableDefault, &qr);
    enc = (EncodeFn)fn;
    cudaFuncSetAttribute(rec_kernel, cudaFuncAttributeMaxDynamicSharedMemorySize, REC_SMEM);
    cudaFuncSetAttribute(opc_kernel, cudaFuncAttributeMaxDynamicSharedMemorySize, OPC_SMEM);
    cudaFuncSetAttribute(la_kernel, cudaFuncAttributeMaxDynamicSharedMemorySize, LA_SMEM);
    cudaGetSymbolAddress((void**)&p_ar, g_ar); p_ar = (uint8_t*)(((uintptr_t)p_ar + 32767) & ~(uintptr_t)32767);
    cudaGetSymbolAddress((void**)&p_zero, g_zero); cudaGetSymbolAddress((void**)&p_x, g_x);
  }
  CUtensorMap tmq, tmk, tmv, tmo, tmx[2];
  make_map_perm(enc, &tmq, Wq);
  make_map_perm(enc, &tmk, Wk);
  make_map_perm(enc, &tmv, Wv);
  make_map(enc, &tmo, Wo, DM, HE, 64, 64, CU_TENSOR_MAP_SWIZZLE_128B);
  make_map(enc, &tmx[0], x, DM, S_TOK, 232, 64, CU_TENSOR_MAP_SWIZZLE_NONE);
  make_map(enc, &tmx[1], p_x, DM, S_TOK, 232, 64, CU_TENSOR_MAP_SWIZZLE_NONE);

  cudaLaunchAttribute at[2];
  at[0].id = cudaLaunchAttributeProgrammaticStreamSerialization; at[0].val.programmaticStreamSerializationAllowed = 1;
  at[1].id = cudaLaunchAttributeClusterDimension; at[1].val.clusterDim.x = 3; at[1].val.clusterDim.y = 1; at[1].val.clusterDim.z = 1;
  cudaLaunchAttribute at2[2] = {at[1], at[0]};
  at2[0].val.clusterDim.x = 2;
  prep_kernel<<<475, 256, 0, st>>>(x, wqkv, wo_a);
  for (int l = 0; l < 2; l++) {
    cudaLaunchConfig_t cfg = {};
    cfg.blockDim = dim3(384); cfg.stream = st;
    cfg.gridDim = dim3(l == 0 ? 132 : 128); cfg.dynamicSmemBytes = LA_SMEM; cfg.attrs = at2; cfg.numAttrs = 1 + LA_PDL;
    cudaLaunchKernelEx(&cfg, la_kernel, Wq, Wk, Wv, Wo, p_ar + l * AR_LAYER, l);
    cfg.gridDim = dim3(96 + 3 * NLB); cfg.dynamicSmemBytes = REC_SMEM; cfg.attrs = at + 1 - REC_PDL; cfg.numAttrs = 1 + REC_PDL;
    cudaLaunchKernelEx(&cfg, rec_kernel, tmq, tmk, tmv, tmo, tmx[l], mem0, p_ar + l * AR_LAYER, p_zero + Z_FLAGS + l * FL_LAYER, l);
    cfg.gridDim = dim3(36); cfg.dynamicSmemBytes = OPC_SMEM; cfg.attrs = at; cfg.numAttrs = OPC_PDL;
    cudaLaunchKernelEx(&cfg, opc_kernel, tmo, l == 1 ? (bf16*)d_out : (bf16*)nullptr, l, Wq, Wk, Wv, Wo);
  }
}
```

```cpp
#include <cuda_runtime.h>
#include <cuda_bf16.h>
#include <cuda.h>
#include <stdint.h>

typedef __nv_bfloat16 bf16;
typedef unsigned long long u64;

constexpr int S_TOK = 2048, DM = 640, DH = 192, HE = 6144, NSEG = 64;

constexpr int AR_GROUP = 98304;
constexpr int AR_LAYER = 16 * AR_GROUP;
__device__ __align__(1024) uint8_t g_ar[2 * AR_LAYER + 32768];
__device__ __align__(1024) uint8_t g_xn[NSEG * 40960];
__device__ __align__(1024) uint8_t g_xt[S_TOK * DM * 2];
__device__ __align__(1024) uint8_t g_ot[NSEG * HE * 64];
__device__ __align__(1024) uint8_t g_oa[S_TOK * DM * 2];
__device__ __align__(1024) uint8_t g_w1[DM * 1920 * 2];
__device__ __align__(1024) uint8_t g_w2[DM * 672 * 2];
__device__ __align__(1024) float g_acc[2 * S_TOK * DM];
__device__ __align__(1024) bf16 g_x[S_TOK * DM];
constexpr int FL_A = 0, FL_B = 64 * 6 * 8, FL_KV = FL_B + 64 * 8, FL_O = FL_KV + 8 * 8, FL_T = FL_O + 16 * 8, FL_X = FL_T + 16 * 8, FL_N = FL_X + 8, FL_R = FL_N + 8, FL_XN = FL_R + 8, FL_LAYER = FL_XN + 32 * 8;
constexpr int Z_FLAGS = 0, Z_NORM = 2 * FL_LAYER, Z_KV = Z_NORM + 8, KV_LAYER = 8 * 80 * 24, Z_END = Z_KV + 2 * KV_LAYER;
__device__ __align__(128) uint32_t g_zero[Z_END];
__device__ __align__(128) float g_nrm[4 * DM];
#define GT(slot, k) do {} while (0)
#define GTT(slot, k) do {} while (0)

__device__ __forceinline__ uint32_t smem_u32(const void* p) { return (uint32_t)__cvta_generic_to_shared(p); }
__device__ __forceinline__ uint32_t mapa(uint32_t a, uint32_t r) { uint32_t o; asm("mapa.shared::cluster.u32 %0, %1, %2;" : "=r"(o) : "r"(a), "r"(r)); return o; }
__device__ __forceinline__ void mbar_init(uint32_t bar, uint32_t cnt) { asm volatile("mbarrier.init.shared::cta.b64 [%0], %1;" :: "r"(bar), "r"(cnt) : "memory"); }
__device__ __forceinline__ void mbar_expect(uint32_t bar, uint32_t tx) { asm volatile("mbarrier.arrive.expect_tx.shared::cta.b64 _, [%0], %1;" :: "r"(bar), "r"(tx) : "memory"); }
__device__ __forceinline__ void mbar_arrive(uint32_t bar) { asm volatile("mbarrier.arrive.shared::cta.b64 _, [%0];" :: "r"(bar) : "memory"); }
__device__ __forceinline__ void mbar_wait(uint32_t bar, uint32_t par) {
  asm volatile("{\n.reg .pred p;\n.reg .u32 c;\nmov.u32 c, 0;\n"
               "LW:\nmbarrier.try_wait.parity.shared::cta.b64 p, [%0], %1;\n@p bra LD;\n"
               "add.u32 c, c, 1;\nsetp.lt.u32 p, c, 4000000;\n@p bra LW;\ntrap;\nLD:\n}" :: "r"(bar), "r"(par) : "memory");
}
__device__ __forceinline__ void mbar_waitf(uint32_t bar, uint32_t par) {
  asm volatile("{\n.reg .pred p, q;\n.reg .u32 c;\nmov.u32 c, 0;\n"
               "LW:\nadd.u32 c, c, 1;\nsetp.lt.u32 q, c, 1000000;\nmbarrier.try_wait.parity.shared::cta.b64 p, [%0], %1;\n"
               "and.pred q, q, !p;\n@q bra LW;\n}" :: "r"(bar), "r"(par) : "memory");
}
template <int ID, int N> __device__ __forceinline__ void bar_sync() { asm volatile("barrier.sync %0, %1;" :: "n"(ID), "n"(N) : "memory"); }
template <int ID, int N> __device__ __forceinline__ void bar_arrive() { asm volatile("barrier.arrive %0, %1;" :: "n"(ID), "n"(N) : "memory"); }
__device__ __forceinline__ void fence_async() { asm volatile("fence.proxy.async.shared::cta;" ::: "memory"); }
__device__ __forceinline__ void cluster_sync() { asm volatile("barrier.cluster.arrive.aligned;\nbarrier.cluster.wait.aligned;" ::: "memory"); }
__device__ __forceinline__ void wg_fence() { asm volatile("wgmma.fence.sync.aligned;" ::: "memory"); }
__device__ __forceinline__ void wg_commit() { asm volatile("wgmma.commit_group.sync.aligned;" ::: "memory"); }
template <int N> __device__ __forceinline__ void wg_wait() { asm volatile("wgmma.wait_group.sync.aligned %0;" :: "n"(N) : "memory"); }
template <int N> __device__ __forceinline__ void pin(float* d) {
#pragma unroll
  for (int i = 0; i < N; i++) asm volatile("" : "+f"(d[i]) :: "memory");
}
__device__ __forceinline__ constexpr uint64_t mkdesc(uint32_t addr, uint32_t lbo, uint32_t sbo, int sw) {
  return (uint64_t)((addr & 0x3FFFF) >> 4) | ((uint64_t)(lbo >> 4) << 16) | ((uint64_t)(sbo >> 4) << 32) | ((uint64_t)sw << 62);
}
constexpr uint32_t SB0 = 1024;
__device__ __forceinline__ void check_smem_base(uint32_t sb) { if ((sb & 0x3FFFF) != SB0) __trap(); }
__device__ __forceinline__ uint32_t cta_rank() { uint32_t r; asm volatile("mov.u32 %0, %%cluster_ctarank;" : "=r"(r)); return r; }
__device__ __forceinline__ uint32_t opaque(uint32_t v) { uint32_t o; asm volatile("mov.u32 %0, %1;" : "=r"(o) : "r"(v)); return o; }
__device__ __forceinline__ uint32_t pack2(float lo, float hi) { uint32_t r; asm("cvt.rn.bf16x2.f32 %0, %1, %2;" : "=r"(r) : "f"(hi), "f"(lo)); return r; }
__device__ __forceinline__ void ldsm4(uint32_t* r, uint32_t a) { asm volatile("ldmatrix.sync.aligned.m8n8.x4.shared.b16 {%0,%1,%2,%3}, [%4];" : "=r"(r[0]), "=r"(r[1]), "=r"(r[2]), "=r"(r[3]) : "r"(a) : "memory"); }
__device__ __forceinline__ void ldsm4t(uint32_t* r, uint32_t a) { asm volatile("ldmatrix.sync.aligned.m8n8.x4.trans.shared.b16 {%0,%1,%2,%3}, [%4];" : "=r"(r[0]), "=r"(r[1]), "=r"(r[2]), "=r"(r[3]) : "r"(a) : "memory"); }
__device__ __forceinline__ void ldsm1(uint32_t& r, uint32_t a) { asm volatile("ldmatrix.sync.aligned.m8n8.x1.shared.b16 {%0}, [%1];" : "=r"(r) : "r"(a) : "memory"); }
__device__ __forceinline__ void stsm4(uint32_t a, uint32_t r0, uint32_t r1, uint32_t r2, uint32_t r3) { asm volatile("stmatrix.sync.aligned.m8n8.x4.shared.b16 [%0], {%1,%2,%3,%4};" :: "r"(a), "r"(r0), "r"(r1), "r"(r2), "r"(r3) : "memory"); }
__device__ __forceinline__ void stsm1(uint32_t a, uint32_t r0) { asm volatile("stmatrix.sync.aligned.m8n8.x1.shared.b16 [%0], {%1};" :: "r"(a), "r"(r0) : "memory"); }
__device__ __forceinline__ void stsm4t(uint32_t a, uint32_t r0, uint32_t r1, uint32_t r2, uint32_t r3) { asm volatile("stmatrix.sync.aligned.m8n8.x4.trans.shared.b16 [%0], {%1,%2,%3,%4};" :: "r"(a), "r"(r0), "r"(r1), "r"(r2), "r"(r3) : "memory"); }
__device__ __forceinline__ void stsm2t(uint32_t a, uint32_t r0, uint32_t r1) { asm volatile("stmatrix.sync.aligned.m8n8.x2.trans.shared.b16 [%0], {%1,%2};" :: "r"(a), "r"(r0), "r"(r1) : "memory"); }
__device__ __forceinline__ void mma16816(float* c, const uint32_t* a, uint32_t b0, uint32_t b1) {
  asm volatile("mma.sync.aligned.m16n8k16.row.col.f32.bf16.bf16.f32 {%0,%1,%2,%3}, {%4,%5,%6,%7}, {%8,%9}, {%0,%1,%2,%3};"
               : "+f"(c[0]), "+f"(c[1]), "+f"(c[2]), "+f"(c[3]) : "r"(a[0]), "r"(a[1]), "r"(a[2]), "r"(a[3]), "r"(b0), "r"(b1));
}
__device__ __forceinline__ void mma1688(float* c, uint32_t a0, uint32_t a1, uint32_t b0) {
  asm volatile("mma.sync.aligned.m16n8k8.row.col.f32.bf16.bf16.f32 {%0,%1,%2,%3}, {%4,%5}, {%6}, {%0,%1,%2,%3};"
               : "+f"(c[0]), "+f"(c[1]), "+f"(c[2]), "+f"(c[3]) : "r"(a0), "r"(a1), "r"(b0));
}
__device__ __forceinline__ void sta1(uint32_t a, uint32_t v, uint32_t bar) { asm volatile("st.async.weak.shared::cluster.mbarrier::complete_tx::bytes.b32 [%0], %1, [%2];" :: "r"(a), "r"(v), "r"(bar) : "memory"); }
__device__ __forceinline__ void sta1p(uint32_t a, uint32_t v, uint32_t bar, bool p) { asm volatile("{\n.reg .pred p;\nsetp.ne.b32 p, %3, 0;\n@p st.async.weak.shared::cluster.mbarrier::complete_tx::bytes.b32 [%0], %1, [%2];\n}" :: "r"(a), "r"(v), "r"(bar), "r"((int)p) : "memory"); }
__device__ __forceinline__ void sta2(uint32_t a, uint32_t v0, uint32_t v1, uint32_t bar) { asm volatile("st.async.weak.shared::cluster.mbarrier::complete_tx::bytes.v2.b32 [%0], {%1,%2}, [%3];" :: "r"(a), "r"(v0), "r"(v1), "r"(bar) : "memory"); }
__device__ __forceinline__ void sta4(uint32_t a, uint32_t v0, uint32_t v1, uint32_t v2, uint32_t v3, uint32_t bar) { asm volatile("st.async.weak.shared::cluster.mbarrier::complete_tx::bytes.v4.b32 [%0], {%1,%2,%3,%4}, [%5];" :: "r"(a), "r"(v0), "r"(v1), "r"(v2), "r"(v3), "r"(bar) : "memory"); }
__device__ __forceinline__ float bflo(uint32_t v) { return __uint_as_float(v << 16); }
__device__ __forceinline__ float bfhi(uint32_t v) { return __uint_as_float(v & 0xFFFF0000u); }
__device__ __forceinline__ void sta2f(uint32_t a, float v0, float v1, uint32_t bar) { asm volatile("st.async.weak.shared::cluster.mbarrier::complete_tx::bytes.v2.f32 [%0], {%1,%2}, [%3];" :: "r"(a), "f"(v0), "f"(v1), "r"(bar) : "memory"); }
__device__ __forceinline__ void sta4f(uint32_t a, float v0, float v1, float v2, float v3, uint32_t bar) { asm volatile("st.async.weak.shared::cluster.mbarrier::complete_tx::bytes.v4.f32 [%0], {%1,%2,%3,%4}, [%5];" :: "r"(a), "f"(v0), "f"(v1), "f"(v2), "f"(v3), "r"(bar) : "memory"); }
__device__ __forceinline__ float4 lds4f(uint32_t a) { float4 v; asm volatile("ld.shared.v4.f32 {%0,%1,%2,%3}, [%4];" : "=f"(v.x), "=f"(v.y), "=f"(v.z), "=f"(v.w) : "r"(a) : "memory"); return v; }
__device__ __forceinline__ float2 lds2f(uint32_t a) { float2 v; asm volatile("ld.shared.v2.f32 {%0,%1}, [%2];" : "=f"(v.x), "=f"(v.y) : "r"(a) : "memory"); return v; }
__device__ __forceinline__ uint4 lds4(uint32_t a) { uint4 v; asm volatile("ld.shared.v4.u32 {%0,%1,%2,%3}, [%4];" : "=r"(v.x), "=r"(v.y), "=r"(v.z), "=r"(v.w) : "r"(a) : "memory"); return v; }
__device__ __forceinline__ uint32_t lds1(uint32_t a) { uint32_t v; asm volatile("ld.shared.u32 %0, [%1];" : "=r"(v) : "r"(a) : "memory"); return v; }
__device__ __forceinline__ void stsm2(uint32_t a, uint32_t r0, uint32_t r1) { asm volatile("stmatrix.sync.aligned.m8n8.x2.shared.b16 [%0], {%1,%2};" :: "r"(a), "r"(r0), "r"(r1) : "memory"); }
__device__ __forceinline__ float rcp(float x) { float y; asm("rcp.approx.ftz.f32 %0, %1;" : "=f"(y) : "f"(x)); return y; }
__device__ __forceinline__ void sts4(uint32_t a, uint32_t v0, uint32_t v1, uint32_t v2, uint32_t v3) { asm volatile("st.shared.v4.u32 [%0], {%1,%2,%3,%4};" :: "r"(a), "r"(v0), "r"(v1), "r"(v2), "r"(v3) : "memory"); }
__device__ __forceinline__ void bulk_s2c(uint32_t dst, uint32_t src, uint32_t bytes, uint32_t bar) {
  asm volatile("cp.async.bulk.shared::cluster.shared::cta.mbarrier::complete_tx::bytes [%0], [%1], %2, [%3];" :: "r"(dst), "r"(src), "r"(bytes), "r"(bar) : "memory");
}
__device__ __forceinline__ void stg4(void* p, uint4 v) { asm volatile("st.global.v4.u32 [%0], {%1,%2,%3,%4};" :: "l"(p), "r"(v.x), "r"(v.y), "r"(v.z), "r"(v.w) : "memory"); }
__device__ __forceinline__ void red_add(uint32_t* p, uint32_t v) { asm volatile("red.relaxed.gpu.global.add.u32 [%0], %1;" :: "l"(p), "r"(v) : "memory"); }
__device__ __forceinline__ void red_release(uint32_t* p, uint32_t v) { asm volatile("red.release.gpu.global.add.u32 [%0], %1;" :: "l"(p), "r"(v) : "memory"); }
__device__ __forceinline__ void fence_async_global() { asm volatile("fence.proxy.async.global;" ::: "memory"); }
__device__ __forceinline__ uint64_t policy_evict_first() { uint64_t p; asm("createpolicy.fractional.L2::evict_first.b64 %0, 1.0;" : "=l"(p)); return p; }
__device__ __forceinline__ void stg4h(void* p, uint4 v, uint64_t pol) { asm volatile("st.global.L2::cache_hint.v4.u32 [%0], {%1,%2,%3,%4}, %5;" :: "l"(p), "r"(v.x), "r"(v.y), "r"(v.z), "r"(v.w), "l"(pol) : "memory"); }
__device__ __forceinline__ void red4fh(float* p, float a, float b, float c, float d, uint64_t pol) { asm volatile("red.relaxed.gpu.global.add.L2::cache_hint.v4.f32 [%0], {%1,%2,%3,%4}, %5;" :: "l"(p), "f"(a), "f"(b), "f"(c), "f"(d), "l"(pol) : "memory"); }
__device__ __forceinline__ float4 ldg4fh(const float* p, uint64_t pol) { float4 v; asm volatile("ld.global.cg.L2::cache_hint.v4.f32 {%0,%1,%2,%3}, [%4], %5;" : "=f"(v.x), "=f"(v.y), "=f"(v.z), "=f"(v.w) : "l"(p), "l"(pol) : "memory"); return v; }
__device__ __forceinline__ void bulk_g2sh(uint32_t dst, const void* src, uint32_t bytes, uint32_t bar, uint64_t pol) {
  asm volatile("cp.async.bulk.shared::cluster.global.mbarrier::complete_tx::bytes.L2::cache_hint [%0], [%1], %2, [%3], %4;" :: "r"(dst), "l"(src), "r"(bytes), "r"(bar), "l"(pol) : "memory");
}
#define EVF 1
__device__ __forceinline__ void red4f(float* p, float a, float b, float c, float d) { asm volatile("red.relaxed.gpu.global.add.v4.f32 [%0], {%1,%2,%3,%4};" :: "l"(p), "f"(a), "f"(b), "f"(c), "f"(d) : "memory"); }
template <int SLEEP = 20>
__device__ __forceinline__ void wait_flag(const uint32_t* p, uint32_t target) {
  uint32_t v; int it = 0;
  while (true) {
    asm volatile("ld.acquire.gpu.global.u32 %0, [%1];" : "=r"(v) : "l"(p) : "memory");
    if (__all_sync(~0u, v >= target)) break;
    if (++it > 4000000) __trap();
    __nanosleep(SLEEP);
  }
}
__device__ __forceinline__ void sts2(uint32_t a, uint32_t v0, uint32_t v1) { asm volatile("st.shared.v2.u32 [%0], {%1,%2};" :: "r"(a), "r"(v0), "r"(v1) : "memory"); }
__device__ __forceinline__ float sqrt_approx(float x) { float y; asm("sqrt.approx.f32 %0, %1;" : "=f"(y) : "f"(x)); return y; }
template <int BYTES> __device__ __forceinline__ void bulk_s2c_elect(uint32_t d1, uint32_t b1, uint32_t d2, uint32_t b2, uint32_t src) {
  asm volatile("{\n.reg .pred p;\nelect.sync _|p, 0xffffffff;\n"
               "@p cp.async.bulk.shared::cluster.shared::cta.mbarrier::complete_tx::bytes [%0], [%4], %5, [%1];\n"
               "@p cp.async.bulk.shared::cluster.shared::cta.mbarrier::complete_tx::bytes [%2], [%4], %5, [%3];\n}"
               :: "r"(d1), "r"(b1), "r"(d2), "r"(b2), "r"(src), "n"(BYTES) : "memory");
}
template <int BYTES> __device__ __forceinline__ void bulk_s2c_elect1(uint32_t d, uint32_t b, uint32_t src) {
  asm volatile("{\n.reg .pred p;\nelect.sync _|p, 0xffffffff;\n"
               "@p cp.async.bulk.shared::cluster.shared::cta.mbarrier::complete_tx::bytes [%0], [%2], %3, [%1];\n}" :: "r"(d), "r"(b), "r"(src), "n"(BYTES) : "memory");
}
template <int BYTES> __device__ __forceinline__ void bulk_g2s_elect(uint32_t d, const void* src, uint32_t b) {
  asm volatile("{\n.reg .pred p;\nelect.sync _|p, 0xffffffff;\n"
               "@p cp.async.bulk.shared::cluster.global.mbarrier::complete_tx::bytes [%0], [%1], %3, [%2];\n}" :: "r"(d), "l"(src), "r"(b), "n"(BYTES) : "memory");
}
__device__ __forceinline__ void mbar_arrive_elect(uint32_t bar) { asm volatile("{\n.reg .pred p;\nelect.sync _|p, 0xffffffff;\n@p mbarrier.arrive.shared::cta.b64 _, [%0];\n}" :: "r"(bar) : "memory"); }
__device__ __forceinline__ void cp16(uint32_t dst, const void* src) { asm volatile("cp.async.cg.shared.global [%0], [%1], 16;" :: "r"(dst), "l"(src) : "memory"); }
__device__ __forceinline__ void sts1(uint32_t a, uint32_t v) { asm volatile("st.shared.u32 [%0], %1;" :: "r"(a), "r"(v) : "memory"); }
__device__ __forceinline__ void bulk_g2s(uint32_t dst, const void* src, uint32_t bytes, uint32_t bar) {
  asm volatile("cp.async.bulk.shared::cluster.global.mbarrier::complete_tx::bytes [%0], [%1], %2, [%3];" :: "r"(dst), "l"(src), "r"(bytes), "r"(bar) : "memory");
}
__device__ __forceinline__ void bulk_g2s_mc(uint32_t dst, const void* src, uint32_t bytes, uint32_t bar) {
  asm volatile("cp.async.bulk.shared::cluster.global.mbarrier::complete_tx::bytes.multicast::cluster [%0], [%1], %2, [%3], %4;" :: "r"(dst), "l"(src), "r"(bytes), "r"(bar), "h"((uint16_t)3) : "memory");
}
__device__ __forceinline__ void mbar_arrive_cl(uint32_t bar) { asm volatile("mbarrier.arrive.shared::cluster.b64 _, [%0];" :: "r"(bar) : "memory"); }
__device__ __forceinline__ void mbar_arrive_clp(uint32_t bar, bool p) { asm volatile("{\n.reg .pred p;\nsetp.ne.b32 p, %1, 0;\n@p mbarrier.arrive.shared::cluster.b64 _, [%0];\n}" :: "r"(bar), "r"((int)p) : "memory"); }
__device__ __forceinline__ void tma2d(uint32_t dst, const CUtensorMap* m, int c0, int c1, uint32_t bar) {
  asm volatile("cp.async.bulk.tensor.2d.shared::cluster.global.mbarrier::complete_tx::bytes [%0], [%1, {%3, %4}], [%2];" :: "r"(dst), "l"((uint64_t)m), "r"(bar), "r"(c0), "r"(c1) : "memory");
}
__device__ __forceinline__ void tma5d(uint32_t dst, const CUtensorMap* m, int c0, int c4, uint32_t bar) {
  asm volatile("cp.async.bulk.tensor.5d.shared::cluster.global.mbarrier::complete_tx::bytes [%0], [%1, {%3, %5, %5, %5, %4}], [%2];" :: "r"(dst), "l"((uint64_t)m), "r"(bar), "r"(c0), "r"(c4), "r"(0) : "memory");
}
__device__ __forceinline__ void red64(void* p, uint32_t lo, uint32_t hi) { asm volatile("{\n.reg .b64 t;\nmov.b64 t, {%1,%2};\nred.relaxed.gpu.global.add.u64 [%0], t;\n}" :: "l"(p), "r"(lo), "r"(hi) : "memory"); }
__device__ __forceinline__ uint4 ld_poll(const void* p) {
  uint4 v;
  asm volatile("{\n.reg .b64 a, b;\nld.relaxed.gpu.global.v2.b64 {a, b}, [%4];\nmov.b64 {%0,%1}, a;\nmov.b64 {%2,%3}, b;\n}" : "=r"(v.x), "=r"(v.y), "=r"(v.z), "=r"(v.w) : "l"(p) : "memory");
  return v;
}
__device__ __forceinline__ uint32_t clk() { uint32_t c; asm volatile("mov.u32 %0, %%clock;" : "=r"(c) :: "memory"); return c; }
#define SCHED_FENCE() asm volatile("pmevent 0;" ::: "memory")
__device__ __forceinline__ float ex2(float x) { float y; asm("ex2.approx.ftz.f32 %0, %1;" : "=f"(y) : "f"(x)); return y; }

__device__ __forceinline__ void wg_ss_n240_ta0_tb1(float* d, uint64_t a, uint64_t b, int sc) {
  asm volatile("{\n.reg .pred p;\nsetp.ne.b32 p, %122, 0;\nwgmma.mma_async.sync.aligned.m64n240k16.f32.bf16.bf16 {%0, %1, %2, %3, %4, %5, %6, %7, %8, %9, %10, %11, %12, %13, %14, %15, %16, %17, %18, %19, %20, %21, %22, %23, %24, %25, %26, %27, %28, %29, %30, %31, %32, %33, %34, %35, %36, %37, %38, %39, %40, %41, %42, %43, %44, %45, %46, %47, %48, %49, %50, %51, %52, %53, %54, %55, %56, %57, %58, %59, %60, %61, %62, %63, %64, %65, %66, %67, %68, %69, %70, %71, %72, %73, %74, %75, %76, %77, %78, %79, %80, %81, %82, %83, %84, %85, %86, %87, %88, %89, %90, %91, %92, %93, %94, %95, %96, %97, %98, %99, %100, %101, %102, %103, %104, %105, %106, %107, %108, %109, %110, %111, %112, %113, %114, %115, %116, %117, %118, %119}, %120, %121, p, 1, 1, 0, 1;\n}\n"
    : "+f"(d[0]), "+f"(d[1]), "+f"(d[2]), "+f"(d[3]), "+f"(d[4]), "+f"(d[5]), "+f"(d[6]), "+f"(d[7]), "+f"(d[8]), "+f"(d[9]), "+f"(d[10]), "+f"(d[11]), "+f"(d[12]), "+f"(d[13]), "+f"(d[14]), "+f"(d[15]), "+f"(d[16]), "+f"(d[17]), "+f"(d[18]), "+f"(d[19]), "+f"(d[20]), "+f"(d[21]), "+f"(d[22]), "+f"(d[23]), "+f"(d[24]), "+f"(d[25]), "+f"(d[26]), "+f"(d[27]), "+f"(d[28]), "+f"(d[29]), "+f"(d[30]), "+f"(d[31]), "+f"(d[32]), "+f"(d[33]), "+f"(d[34]), "+f"(d[35]), "+f"(d[36]), "+f"(d[37]), "+f"(d[38]), "+f"(d[39]), "+f"(d[40]), "+f"(d[41]), "+f"(d[42]), "+f"(d[43]), "+f"(d[44]), "+f"(d[45]), "+f"(d[46]), "+f"(d[47]), "+f"(d[48]), "+f"(d[49]), "+f"(d[50]), "+f"(d[51]), "+f"(d[52]), "+f"(d[53]), "+f"(d[54]), "+f"(d[55]), "+f"(d[56]), "+f"(d[57]), "+f"(d[58]), "+f"(d[59]), "+f"(d[60]), "+f"(d[61]), "+f"(d[62]), "+f"(d[63]), "+f"(d[64]), "+f"(d[65]), "+f"(d[66]), "+f"(d[67]), "+f"(d[68]), "+f"(d[69]), "+f"(d[70]), "+f"(d[71]), "+f"(d[72]), "+f"(d[73]), "+f"(d[74]), "+f"(d[75]), "+f"(d[76]), "+f"(d[77]), "+f"(d[78]), "+f"(d[79]), "+f"(d[80]), "+f"(d[81]), "+f"(d[82]), "+f"(d[83]), "+f"(d[84]), "+f"(d[85]), "+f"(d[86]), "+f"(d[87]), "+f"(d[88]), "+f"(d[89]), "+f"(d[90]), "+f"(d[91]), "+f"(d[92]), "+f"(d[93]), "+f"(d[94]), "+f"(d[95]), "+f"(d[96]), "+f"(d[97]), "+f"(d[98]), "+f"(d[99]), "+f"(d[100]), "+f"(d[101]), "+f"(d[102]), "+f"(d[103]), "+f"(d[104]), "+f"(d[105]), "+f"(d[106]), "+f"(d[107]), "+f"(d[108]), "+f"(d[109]), "+f"(d[110]), "+f"(d[111]), "+f"(d[112]), "+f"(d[113]), "+f"(d[114]), "+f"(d[115]), "+f"(d[116]), "+f"(d[117]), "+f"(d[118]), "+f"(d[119])
    : "l"(a), "l"(b), "r"(sc));
}
__device__ __forceinline__ void wg_ss_n88_ta1_tb1(float* d, uint64_t a, uint64_t b, int sc) {
  asm volatile("{\n.reg .pred p;\nsetp.ne.b32 p, %46, 0;\nwgmma.mma_async.sync.aligned.m64n88k16.f32.bf16.bf16 {%0, %1, %2, %3, %4, %5, %6, %7, %8, %9, %10, %11, %12, %13, %14, %15, %16, %17, %18, %19, %20, %21, %22, %23, %24, %25, %26, %27, %28, %29, %30, %31, %32, %33, %34, %35, %36, %37, %38, %39, %40, %41, %42, %43}, %44, %45, p, 1, 1, 1, 1;\n}\n"
    : "+f"(d[0]), "+f"(d[1]), "+f"(d[2]), "+f"(d[3]), "+f"(d[4]), "+f"(d[5]), "+f"(d[6]), "+f"(d[7]), "+f"(d[8]), "+f"(d[9]), "+f"(d[10]), "+f"(d[11]), "+f"(d[12]), "+f"(d[13]), "+f"(d[14]), "+f"(d[15]), "+f"(d[16]), "+f"(d[17]), "+f"(d[18]), "+f"(d[19]), "+f"(d[20]), "+f"(d[21]), "+f"(d[22]), "+f"(d[23]), "+f"(d[24]), "+f"(d[25]), "+f"(d[26]), "+f"(d[27]), "+f"(d[28]), "+f"(d[29]), "+f"(d[30]), "+f"(d[31]), "+f"(d[32]), "+f"(d[33]), "+f"(d[34]), "+f"(d[35]), "+f"(d[36]), "+f"(d[37]), "+f"(d[38]), "+f"(d[39]), "+f"(d[40]), "+f"(d[41]), "+f"(d[42]), "+f"(d[43])
    : "l"(a), "l"(b), "r"(sc));
}
__device__ __forceinline__ void wg_rs_n160_tb1(float* d, const uint32_t* a, uint64_t b, int sc) {
  asm volatile("{\n.reg .pred p;\nsetp.ne.b32 p, %85, 0;\nwgmma.mma_async.sync.aligned.m64n160k16.f32.bf16.bf16 {%0, %1, %2, %3, %4, %5, %6, %7, %8, %9, %10, %11, %12, %13, %14, %15, %16, %17, %18, %19, %20, %21, %22, %23, %24, %25, %26, %27, %28, %29, %30, %31, %32, %33, %34, %35, %36, %37, %38, %39, %40, %41, %42, %43, %44, %45, %46, %47, %48, %49, %50, %51, %52, %53, %54, %55, %56, %57, %58, %59, %60, %61, %62, %63, %64, %65, %66, %67, %68, %69, %70, %71, %72, %73, %74, %75, %76, %77, %78, %79}, {%80, %81, %82, %83}, %84, p, 1, 1, 1;\n}\n"
    : "+f"(d[0]), "+f"(d[1]), "+f"(d[2]), "+f"(d[3]), "+f"(d[4]), "+f"(d[5]), "+f"(d[6]), "+f"(d[7]), "+f"(d[8]), "+f"(d[9]), "+f"(d[10]), "+f"(d[11]), "+f"(d[12]), "+f"(d[13]), "+f"(d[14]), "+f"(d[15]), "+f"(d[16]), "+f"(d[17]), "+f"(d[18]), "+f"(d[19]), "+f"(d[20]), "+f"(d[21]), "+f"(d[22]), "+f"(d[23]), "+f"(d[24]), "+f"(d[25]), "+f"(d[26]), "+f"(d[27]), "+f"(d[28]), "+f"(d[29]), "+f"(d[30]), "+f"(d[31]), "+f"(d[32]), "+f"(d[33]), "+f"(d[34]), "+f"(d[35]), "+f"(d[36]), "+f"(d[37]), "+f"(d[38]), "+f"(d[39]), "+f"(d[40]), "+f"(d[41]), "+f"(d[42]), "+f"(d[43]), "+f"(d[44]), "+f"(d[45]), "+f"(d[46]), "+f"(d[47]), "+f"(d[48]), "+f"(d[49]), "+f"(d[50]), "+f"(d[51]), "+f"(d[52]), "+f"(d[53]), "+f"(d[54]), "+f"(d[55]), "+f"(d[56]), "+f"(d[57]), "+f"(d[58]), "+f"(d[59]), "+f"(d[60]), "+f"(d[61]), "+f"(d[62]), "+f"(d[63]), "+f"(d[64]), "+f"(d[65]), "+f"(d[66]), "+f"(d[67]), "+f"(d[68]), "+f"(d[69]), "+f"(d[70]), "+f"(d[71]), "+f"(d[72]), "+f"(d[73]), "+f"(d[74]), "+f"(d[75]), "+f"(d[76]), "+f"(d[77]), "+f"(d[78]), "+f"(d[79])
    : "r"(a[0]), "r"(a[1]), "r"(a[2]), "r"(a[3]), "l"(b), "r"(sc));
}
__device__ __forceinline__ void wg_ss_n112_ta0_tb1(float* d, uint64_t a, uint64_t b, int sc) {
  asm volatile("{\n.reg .pred p;\nsetp.ne.b32 p, %58, 0;\nwgmma.mma_async.sync.aligned.m64n112k16.f32.bf16.bf16 {%0, %1, %2, %3, %4, %5, %6, %7, %8, %9, %10, %11, %12, %13, %14, %15, %16, %17, %18, %19, %20, %21, %22, %23, %24, %25, %26, %27, %28, %29, %30, %31, %32, %33, %34, %35, %36, %37, %38, %39, %40, %41, %42, %43, %44, %45, %46, %47, %48, %49, %50, %51, %52, %53, %54, %55}, %56, %57, p, 1, 1, 0, 1;\n}\n"
    : "+f"(d[0]), "+f"(d[1]), "+f"(d[2]), "+f"(d[3]), "+f"(d[4]), "+f"(d[5]), "+f"(d[6]), "+f"(d[7]), "+f"(d[8]), "+f"(d[9]), "+f"(d[10]), "+f"(d[11]), "+f"(d[12]), "+f"(d[13]), "+f"(d[14]), "+f"(d[15]), "+f"(d[16]), "+f"(d[17]), "+f"(d[18]), "+f"(d[19]), "+f"(d[20]), "+f"(d[21]), "+f"(d[22]), "+f"(d[23]), "+f"(d[24]), "+f"(d[25]), "+f"(d[26]), "+f"(d[27]), "+f"(d[28]), "+f"(d[29]), "+f"(d[30]), "+f"(d[31]), "+f"(d[32]), "+f"(d[33]), "+f"(d[34]), "+f"(d[35]), "+f"(d[36]), "+f"(d[37]), "+f"(d[38]), "+f"(d[39]), "+f"(d[40]), "+f"(d[41]), "+f"(d[42]), "+f"(d[43]), "+f"(d[44]), "+f"(d[45]), "+f"(d[46]), "+f"(d[47]), "+f"(d[48]), "+f"(d[49]), "+f"(d[50]), "+f"(d[51]), "+f"(d[52]), "+f"(d[53]), "+f"(d[54]), "+f"(d[55])
    : "l"(a), "l"(b), "r"(sc));
}
__device__ __forceinline__ void wg_rs_n32_tb1(float* d, const uint32_t* a, uint64_t b, int sc) {
  asm volatile("{\n.reg .pred p;\nsetp.ne.b32 p, %21, 0;\nwgmma.mma_async.sync.aligned.m64n32k16.f32.bf16.bf16 {%0, %1, %2, %3, %4, %5, %6, %7, %8, %9, %10, %11, %12, %13, %14, %15}, {%16, %17, %18, %19}, %20, p, 1, 1, 1;\n}\n"
    : "+f"(d[0]), "+f"(d[1]), "+f"(d[2]), "+f"(d[3]), "+f"(d[4]), "+f"(d[5]), "+f"(d[6]), "+f"(d[7]), "+f"(d[8]), "+f"(d[9]), "+f"(d[10]), "+f"(d[11]), "+f"(d[12]), "+f"(d[13]), "+f"(d[14]), "+f"(d[15])
    : "r"(a[0]), "r"(a[1]), "r"(a[2]), "r"(a[3]), "l"(b), "r"(sc));
}
__device__ __forceinline__ void wg_ss_n32_ta1_tb1(float* d, uint64_t a, uint64_t b, int sc) {
  asm volatile("{\n.reg .pred p;\nsetp.ne.b32 p, %18, 0;\nwgmma.mma_async.sync.aligned.m64n32k16.f32.bf16.bf16 {%0, %1, %2, %3, %4, %5, %6, %7, %8, %9, %10, %11, %12, %13, %14, %15}, %16, %17, p, 1, 1, 1, 1;\n}\n"
    : "+f"(d[0]), "+f"(d[1]), "+f"(d[2]), "+f"(d[3]), "+f"(d[4]), "+f"(d[5]), "+f"(d[6]), "+f"(d[7]), "+f"(d[8]), "+f"(d[9]), "+f"(d[10]), "+f"(d[11]), "+f"(d[12]), "+f"(d[13]), "+f"(d[14]), "+f"(d[15])
    : "l"(a), "l"(b), "r"(sc));
}
__device__ __forceinline__ void wg_rs_n32_tb0(float* d, const uint32_t* a, uint64_t b, int sc) {
  asm volatile("{\n.reg .pred p;\nsetp.ne.b32 p, %21, 0;\nwgmma.mma_async.sync.aligned.m64n32k16.f32.bf16.bf16 {%0, %1, %2, %3, %4, %5, %6, %7, %8, %9, %10, %11, %12, %13, %14, %15}, {%16, %17, %18, %19}, %20, p, 1, 1, 0;\n}\n"
    : "+f"(d[0]), "+f"(d[1]), "+f"(d[2]), "+f"(d[3]), "+f"(d[4]), "+f"(d[5]), "+f"(d[6]), "+f"(d[7]), "+f"(d[8]), "+f"(d[9]), "+f"(d[10]), "+f"(d[11]), "+f"(d[12]), "+f"(d[13]), "+f"(d[14]), "+f"(d[15])
    : "r"(a[0]), "r"(a[1]), "r"(a[2]), "r"(a[3]), "l"(b), "r"(sc));
}
__device__ __forceinline__ void wg_rs_n40_tb0(float* d, const uint32_t* a, uint64_t b, int sc) {
  asm volatile("{\n.reg .pred p;\nsetp.ne.b32 p, %25, 0;\nwgmma.mma_async.sync.aligned.m64n40k16.f32.bf16.bf16 {%0, %1, %2, %3, %4, %5, %6, %7, %8, %9, %10, %11, %12, %13, %14, %15, %16, %17, %18, %19}, {%20, %21, %22, %23}, %24, p, 1, 1, 0;\n}\n"
    : "+f"(d[0]), "+f"(d[1]), "+f"(d[2]), "+f"(d[3]), "+f"(d[4]), "+f"(d[5]), "+f"(d[6]), "+f"(d[7]), "+f"(d[8]), "+f"(d[9]), "+f"(d[10]), "+f"(d[11]), "+f"(d[12]), "+f"(d[13]), "+f"(d[14]), "+f"(d[15]), "+f"(d[16]), "+f"(d[17]), "+f"(d[18]), "+f"(d[19])
    : "r"(a[0]), "r"(a[1]), "r"(a[2]), "r"(a[3]), "l"(b), "r"(sc));
}
__device__ __forceinline__ void wg_rs_n8_tb1(float* d, const uint32_t* a, uint64_t b, int sc) {
  asm volatile("{\n.reg .pred p;\nsetp.ne.b32 p, %9, 0;\nwgmma.mma_async.sync.aligned.m64n8k16.f32.bf16.bf16 {%0, %1, %2, %3}, {%4, %5, %6, %7}, %8, p, 1, 1, 1;\n}\n"
    : "+f"(d[0]), "+f"(d[1]), "+f"(d[2]), "+f"(d[3])
    : "r"(a[0]), "r"(a[1]), "r"(a[2]), "r"(a[3]), "l"(b), "r"(sc));
}
__device__ __forceinline__ void wg_ss_n40_ta0_tb0(float* d, uint64_t a, uint64_t b, int sc) {
  asm volatile("{\n.reg .pred p;\nsetp.ne.b32 p, %22, 0;\nwgmma.mma_async.sync.aligned.m64n40k16.f32.bf16.bf16 {%0, %1, %2, %3, %4, %5, %6, %7, %8, %9, %10, %11, %12, %13, %14, %15, %16, %17, %18, %19}, %20, %21, p, 1, 1, 0, 0;\n}\n"
    : "+f"(d[0]), "+f"(d[1]), "+f"(d[2]), "+f"(d[3]), "+f"(d[4]), "+f"(d[5]), "+f"(d[6]), "+f"(d[7]), "+f"(d[8]), "+f"(d[9]), "+f"(d[10]), "+f"(d[11]), "+f"(d[12]), "+f"(d[13]), "+f"(d[14]), "+f"(d[15]), "+f"(d[16]), "+f"(d[17]), "+f"(d[18]), "+f"(d[19])
    : "l"(a), "l"(b), "r"(sc));
}
__device__ __forceinline__ void wg_ss_n40_ta1_tb0(float* d, uint64_t a, uint64_t b, int sc) {
  asm volatile("{\n.reg .pred p;\nsetp.ne.b32 p, %22, 0;\nwgmma.mma_async.sync.aligned.m64n40k16.f32.bf16.bf16 {%0, %1, %2, %3, %4, %5, %6, %7, %8, %9, %10, %11, %12, %13, %14, %15, %16, %17, %18, %19}, %20, %21, p, 1, 1, 1, 0;\n}\n"
    : "+f"(d[0]), "+f"(d[1]), "+f"(d[2]), "+f"(d[3]), "+f"(d[4]), "+f"(d[5]), "+f"(d[6]), "+f"(d[7]), "+f"(d[8]), "+f"(d[9]), "+f"(d[10]), "+f"(d[11]), "+f"(d[12]), "+f"(d[13]), "+f"(d[14]), "+f"(d[15]), "+f"(d[16]), "+f"(d[17]), "+f"(d[18]), "+f"(d[19])
    : "l"(a), "l"(b), "r"(sc));
}
__device__ __forceinline__ void wg_ss_n8_ta1_tb1(float* d, uint64_t a, uint64_t b, int sc) {
  asm volatile("{\n.reg .pred p;\nsetp.ne.b32 p, %6, 0;\nwgmma.mma_async.sync.aligned.m64n8k16.f32.bf16.bf16 {%0, %1, %2, %3}, %4, %5, p, 1, 1, 1, 1;\n}\n"
    : "+f"(d[0]), "+f"(d[1]), "+f"(d[2]), "+f"(d[3])
    : "l"(a), "l"(b), "r"(sc));
}

constexpr int O_WV = 0, O_WO = 81920, O_H = 163840, O_QK = 215040, O_SM = 228352, O_MISC = 229632;
constexpr int O_QM = O_QK + 1024, O_K = O_QK + 3072, O_OG = O_QK + 8192;
constexpr int SM_SLOT = 640;
constexpr int O_MAXS = O_MISC;
constexpr int O_BAR = O_MISC + 64;
constexpr int MB_XF = 0, MB_ML = 2, MB_MR = 3, MB_PF = 4, MB_SM = 5, MB_SX = 6, MB_OG = 7, MB_W = 10, MB_WC = 30;
constexpr int O_PROF = O_BAR + 8 * 40;
constexpr int REC_SMEM = O_PROF + 128;
constexpr int B_VOWN = 0, B_QK = 1, B_SISS = 3, B_PM = 4, B_PX = 5, B_XGO = 6, B_ML = 7, B_WG2 = 8, B_VHALF = 9, B_VDONE = 10,
              B_MR = 11, B_SSENT = 12, B_SLD = 13, B_VEND = 14, B_XGO1 = 15;
#define TS0(idx) do {} while (0)
#define TS(idx) do {} while (0)
#define POLL_9 300
#define POLL_A 400
#define POLL_B 500
#define POLL_C 600
#define W_WIN 4
#define W_OPEN 16
#define V_OWN 6
#define V_S1 7
#define V_RS 3
#define V_S2 1
#define V_B 5
#define V_K1 (V_OWN + V_RS + V_B + V_S1)
#define V_K2 ((V_K1 > 20 ? V_K1 : 20) + V_S2)
#define O_RSM 0x2AA0
#define XG1 16
#define XG0 0
#define SLDW 0
#define O_B1 5
#define O_RS __builtin_popcount(O_RSM)
#define O_IDX(j) __builtin_popcount(O_RSM & ((1 << (j)) - 1))
constexpr float SCL = 0.07216878364870322f;
constexpr float SL2 = SCL * 1.4426950408889634f;
__device__ __forceinline__ constexpr int vord(int i) { return i < 4 ? 36 + i : i - 4; }
__device__ __forceinline__ constexpr uint32_t hoff(int k) { return ((k >> 2) * 5120 + (k & 3) * 32) >> 4; }
__device__ __forceinline__ constexpr int ar_chunk(int T) { return T == 9 ? 19 : (T % 3) * 8 + T / 3; }
__device__ __forceinline__ void fix_red(uint8_t* p, const float* a, float2 sc) {
  int v0 = __float2int_rn(a[0] * sc.x), v1 = __float2int_rn(a[1] * sc.y), v2 = __float2int_rn(a[2] * sc.x), v3 = __float2int_rn(a[3] * sc.y);
  red64(p, ((uint32_t)v0 << 7) | 1u, ((uint32_t)v2 << 3) + (uint32_t)(v0 >> 25));
  red64(p + 1024, ((uint32_t)v1 << 7) | 1u, ((uint32_t)v3 << 3) + (uint32_t)(v1 >> 25));
}
__device__ __forceinline__ float exp_row(float* t) {
  const float ml = fmaxf(fmaxf(fmaxf(fmaxf(t[0], t[1]), fmaxf(t[2], t[3])), fmaxf(fmaxf(t[4], t[5]), fmaxf(t[6], t[7]))), fmaxf(t[8], t[9]));
  const float m1 = __shfl_xor_sync(~0u, ml, 1), m2 = __shfl_xor_sync(~0u, ml, 2), m3 = __shfl_xor_sync(~0u, ml, 3);
  SCHED_FENCE();
#pragma unroll
  for (int k = 0; k < 10; k++) t[k] = ex2((t[k] - ml) * SL2);
  pin<10>(t);
  SCHED_FENCE();
  return ex2((ml - fmaxf(fmaxf(ml, m1), fmaxf(m2, m3))) * SL2);
}
#define ACC3(k, u, v) { t[k] += bflo(u) + bflo(v); t[k + 1] += bfhi(u) + bfhi(v); }

#define LBT 0
#define NLB 2
constexpr int LB_STAGE = 36864, LB_ST = 6 * LB_STAGE;
__device__ __forceinline__ void lb_role(const uint32_t sb, const CUtensorMap* tmx, uint32_t* __restrict__ flags, int layer) {
  const int tid = threadIdx.x, wid = __shfl_sync(~0u, tid >> 5, 0), wg = wid >> 2, w = wid & 3, lane = tid & 31, g = lane >> 2, i4 = lane & 3;
  const int cl = blockIdx.x / 3, rank = blockIdx.x - cl * 3;
  const uint32_t bar = sb + O_BAR;
  asm volatile("griddepcontrol.launch_dependents;");
  if (wid == 8) {
    if (lane < 14) mbar_init(bar + 8 * lane, lane >= 6 && lane < 12 ? 8 : 1);
    asm volatile("fence.mbarrier_init.release.cluster;" ::: "memory");
    fence_async();
  }
  __syncthreads();
  asm volatile("barrier.cluster.arrive.relaxed.aligned;" ::: "memory");
  if (wid == 8) {
    int st = 0; uint32_t ph = 1;
    const uint8_t* wsrc = g_w2 + rank * 286720;
    if (lane < 6) { mbar_expect(bar + 8 * lane, LB_STAGE); bulk_g2s(sb + lane * LB_STAGE + 8192, wsrc + lane * 28672, 28672, bar + 8 * lane); }
    if (layer == 1) wait_flag(flags + FL_R, 6);
#pragma unroll 1
    for (int tile = cl; tile < 32; tile += NLB) {
      wait_flag(flags + FL_O + (tile >> 1) * 8, 8);
      if (tile == cl + LBT * NLB && lane == 0) GTT(layer * 4 + 1, 11);
      fence_async_global();
#pragma unroll 1
      for (int kc = 0; kc < 10; kc++) {
        const bool pre = tile == cl && kc < 6;
        mbar_wait(bar + 8 * (6 + st), ph);
        if (lane == 0) {
          if (!pre) { mbar_expect(bar + 8 * st, LB_STAGE); bulk_g2s(sb + st * LB_STAGE + 8192, wsrc + kc * 28672, 28672, bar + 8 * st); }
          bulk_g2s(sb + st * LB_STAGE, g_oa + tile * 81920 + kc * 8192, 8192, bar + 8 * st);
        }
        __syncwarp();
        if (++st == 6) { st = 0; ph ^= 1; }
      }
      mbar_wait(bar + 8 * (6 + st), ph);
      if (lane == 0) { mbar_expect(bar + 8 * st, 64 * 464); tma2d(sb + st * LB_STAGE, tmx, rank * 224, tile * 64, bar + 8 * st); }
      __syncwarp();
      if (++st == 6) { st = 0; ph ^= 1; }
    }
    asm volatile("barrier.cluster.wait.aligned;" ::: "memory");
  } else if (wg < 2) {
    asm volatile("barrier.cluster.wait.aligned;" ::: "memory");
    const int u = 2 * rank + wg, nb = u == 5 ? 5 : 7;
    int st = 0; uint32_t ph = 0, it = 0;
#pragma unroll 1
    for (int tile = cl; tile < 32; tile += NLB, it++) {
      const int row0 = tile * 64 + 16 * w + g;
      float d[56];
      if (tid == 0) mbar_expect(bar + 8 * (12 + (it & 1)), 3072);
#pragma unroll 1
      for (int kc = 0; kc < 10; kc++) {
        const uint64_t da = mkdesc(SB0 + st * LB_STAGE, 1024, 128, 0), db = mkdesc(SB0 + st * LB_STAGE + 8192 + wg * 1792, 3584, 128, 0);
        mbar_wait(bar + 8 * st, ph);
        if (it == LBT && kc == 0) GT(layer * 4 + 1, 12);
        wg_fence();
#pragma unroll
        for (int k = 0; k < 4; k++) wg_ss_n112_ta0_tb1(d, da + k * 128, db + k * 448, kc | k);
        wg_commit();
        wg_wait<1>();
        if (kc > 0 && lane == 0) mbar_arrive(bar + 8 * (6 + (st == 0 ? 5 : st - 1)));
        if (++st == 6) { st = 0; ph ^= 1; }
      }
      wg_wait<0>();
      pin<56>(d);
      if (it == LBT) GT(layer * 4 + 1, 13);
      if (lane == 0) mbar_arrive(bar + 8 * (6 + (st == 0 ? 5 : st - 1)));
      mbar_wait(bar + 8 * st, ph);
      {
        const uint32_t x0 = sb + st * LB_STAGE + (16 * w + g) * 464 + wg * 224 + (layer ? 8 : 4) * i4, x1 = x0 + (layer ? 4 : 16);
#pragma unroll
        for (int j = 0; j < 28; j++) {
          const uint32_t v = lds1(((j & 2) ? x1 : x0) + (j >> 2) * 32 + (j & 1) * 3712);
          d[2 * j] += bflo(v); d[2 * j + 1] += bfhi(v);
        }
      }
      fence_async();
      __syncwarp();
      if (lane == 0) mbar_arrive(bar + 8 * (6 + st));
      if (++st == 6) { st = 0; ph ^= 1; }
      const float cnt = nb * 16.f;
      const uint32_t so = LB_ST + (it & 1) * 3072 + (16 * w + g) * 48;
#pragma unroll
      for (int h = 0; h < 2; h++) {
        float sum = 0.f;
#pragma unroll
        for (int j = 0; j < 14; j++) sum += d[4 * j + 2 * h] + d[4 * j + 2 * h + 1];
        sum += __shfl_xor_sync(~0u, sum, 1); sum += __shfl_xor_sync(~0u, sum, 2);
        const float mean = sum * rcp(cnt);
        float q = 0.f, q2 = 0.f;
#pragma unroll
        for (int j = 0; j < 14; j++) {
          const float a = d[4 * j + 2 * h] - mean, b = d[4 * j + 2 * h + 1] - mean;
          if (j < 10) q = fmaf(a, a, fmaf(b, b, q)); else q2 = fmaf(a, a, fmaf(b, b, q2));
        }
        if (nb == 7) q += q2;
        q += __shfl_xor_sync(~0u, q, 1); q += __shfl_xor_sync(~0u, q, 2);
        if (i4 < 3) { const uint32_t b = mapa(sb, i4); sta2f(b + so + h * 384 + u * 8, sum, q, b + O_BAR + 8 * (12 + (it & 1))); }
      }
      mbar_wait(bar + 8 * (12 + (it & 1)), (it >> 1) & 1);
      if (it == LBT) GT(layer * 4 + 1, 14);
#pragma unroll
      for (int h = 0; h < 2; h++) {
        const float4 x = lds4f(sb + so + h * 384), y = lds4f(sb + so + h * 384 + 16), z = lds4f(sb + so + h * 384 + 32);
        const float mu = (((x.x + x.z) + (y.x + y.z)) + (z.x + z.z)) * (1.f / DM);
        const float e0 = x.x * (1.f / 112.f) - mu, e1 = x.z * (1.f / 112.f) - mu, e2 = y.x * (1.f / 112.f) - mu, e3 = y.z * (1.f / 112.f) - mu;
        const float e4 = z.x * (1.f / 112.f) - mu, e5 = z.z * (1.f / 80.f) - mu;
        const float q = (((x.y + x.w) + (y.y + y.w)) + (z.y + z.w)) + 112.f * ((e0 * e0 + e1 * e1) + (e2 * e2 + e3 * e3) + e4 * e4) + 80.f * e5 * e5;
        const float rs = rsqrtf(q * (1.f / DM) + 1e-5f), sh = -mu * rs;
        const int tk = row0 + 8 * h;
        uint8_t* xp = g_xn + (tk >> 5) * 40960 + (tk & 31) * 128 + (i4 & 1) * 8;
#pragma unroll
        for (int j = 0; j < 7; j++) {
          if (j < nb) {
            const int b16 = u * 7 + j;
            const float* a = d + 8 * j + 2 * h;
            *(uint2*)(xp + (b16 >> 2) * 4096 + (((2 * (b16 & 3) + (i4 >> 1)) ^ g) << 4)) =
                make_uint2(pack2(fmaf(a[0], rs, sh), fmaf(a[1], rs, sh)), pack2(fmaf(a[4], rs, sh), fmaf(a[5], rs, sh)));
          }
        }
      }
      if (it == LBT) GT(layer * 4 + 1, 15);
      bar_arrive<1, 288>();
      bar_sync<2, 288>();
#pragma unroll
      for (int j = 0; j < 14; j++) {
        const float* a = d + 8 * (j >> 1) + 2 * (j & 1);
        if ((j >> 1) < nb) *(uint2*)(g_x + (row0 + 8 * (j & 1)) * DM + u * 112 + 4 * i4 + 16 * (j >> 1)) = make_uint2(pack2(a[0], a[1]), pack2(a[4], a[5]));
      }
      bar_arrive<3, 288>();
    }
  } else {
    asm volatile("barrier.cluster.wait.aligned;" ::: "memory");
    if (wid == 9) {
#pragma unroll 1
      for (int tile = cl; tile < 32; tile += NLB) {
        bar_sync<1, 288>();
        if (tile != cl) bar_arrive<2, 288>();
        if (lane == 0) { red_release(flags + FL_XN + tile * 8, 1); if (tile == cl + LBT * NLB) GTT(layer * 4 + 1, 9); }
        __syncwarp();
        if (tile == cl) bar_arrive<2, 288>();
        bar_sync<3, 288>();
        if (lane == 0) red_release(flags + FL_XN + tile * 8 + 1, 1);
        __syncwarp();
      }
    }
  }
  asm volatile("barrier.cluster.arrive.relaxed.aligned;\nbarrier.cluster.wait.aligned;" ::: "memory");
  GT(layer * 4 + 1, 10);
}

__global__ void __launch_bounds__(384, 1)
rec_kernel(const __grid_constant__ CUtensorMap tmq, const __grid_constant__ CUtensorMap tmk,
           const __grid_constant__ CUtensorMap tmv, const __grid_constant__ CUtensorMap tmo,
           const __grid_constant__ CUtensorMap tmx, const bf16* __restrict__ mem0, uint8_t* __restrict__ ar, uint32_t* __restrict__ flags, int layer) {
  extern __shared__ __align__(1024) uint8_t smem[];
  const uint32_t sb = smem_u32(smem);
  check_smem_base(sb);
  GT(layer * 4 + 1, 0);
  if (blockIdx.x < 3 * NLB) { lb_role(sb, &tmx, flags, layer); return; }
  const int bid = blockIdx.x - 3 * NLB;
  const int tid = threadIdx.x, wid = __shfl_sync(~0u, tid >> 5, 0), wg = wid >> 2, w = wid & 3;
  const int lane = __shfl_sync(~0u, tid & 31, tid & 31);
  const int head = bid / 3, rank = bid - head * 3;
  const int e0 = bid * 64;
  const uint32_t bar = sb + O_BAR;
  const uint32_t sb1 = mapa(sb, rank == 2 ? 0 : rank + 1), sb2 = mapa(sb, rank == 0 ? 2 : rank - 1);
  auto chunk_of = [&](int p) { const int c = 3 * rank + p; return p == 9 ? 9 : c >= 9 ? c - 9 : c; };

  auto load_piece = [&](int i) {
    if (lane == 0) mbar_expect(bar + 8 * (MB_W + i), 16384);
    __syncwarp();
    if (lane < 2) {
      if (i < 15) {
        const int m = i < 10 ? i & 1 : 0, p = (i < 10 ? i >> 1 : i - 10) * 2 + lane;
        tma5d(sb + m * 81920 + p * 8192, i >= 10 ? &tmv : m ? &tmk : &tmq, e0, chunk_of(p) * 4, bar + 8 * (MB_W + i));
      } else {
        const int p = (i - 15) * 2 + lane, k = p / 3, j = rank + p - 3 * k;
        tma2d(sb + O_WO + p * 8192, &tmo, p == 9 ? 576 : (rank * 3 + k) * 64, head * DH + (j >= 3 ? j - 3 : j) * 64, bar + 8 * (MB_W + i));
      }
    }
  };
  if (wid == 9) {
    mbar_init(bar + 8 * lane, (lane >= MB_WC || lane == MB_PF) ? 4 : lane == MB_SM ? 13 : 1);
    if (lane < 8) mbar_init(bar + 8 * (32 + lane), 4);
    asm volatile("fence.mbarrier_init.release.cluster;" ::: "memory");
    fence_async();
    __syncwarp();
#pragma unroll 1
    for (int i = 0; i < W_WIN; i++) load_piece(i);
  }
  __syncthreads();
  asm volatile("barrier.cluster.arrive.relaxed.aligned;" ::: "memory");

  if (wg < 2) {
    asm volatile("setmaxnreg.inc.sync.aligned.u32 208;");
    uint32_t a[40][4];
    const uint32_t swz = (lane & 7) * 128 + (((2 * w + ((lane >> 3) & 1)) ^ (lane & 7)) << 4);
    const uint32_t st_x = __shfl_sync(~0u, sb + O_QK + wg * 5120 + (lane >> 4) * 2048 + swz, lane);
    {
      const uint32_t la = sb + wg * 81920 + (lane >> 4) * 1024 + swz;
#pragma unroll
      for (int p = 0; p < 5; p++) {
        mbar_wait(bar + 8 * (MB_W + 2 * p + wg), 0);
#pragma unroll
        for (int k = 0; k < 8; k++) ldsm4t(a[p * 8 + k], la + (p * 8 + k) * 2048);
        fence_async();
        __syncwarp();
        mbar_arrive_elect(bar + 8 * (MB_WC + wg * 5 + p));
      }
    }
    GT(layer * 4 + 1, 5);
    asm volatile("barrier.cluster.wait.aligned;" ::: "memory");
    const uint32_t ld_m = __shfl_sync(~0u, sb + O_H + (lane & 7) * 128 + (((lane >> 3) ^ (lane & 7)) << 4), lane);

    for (int s = 0; s < NSEG; s++) {
      const uint32_t par = s & 1;
      if (wid == 4) TS0(0);
      if (wid == 0) TS(30);
      {
        float ax[16];
        constexpr uint64_t db = mkdesc(SB0 + O_H + 1024, 16, 1024, 1);
        mbar_waitf(bar + 8 * MB_XF, par);
        wg_fence();
#pragma unroll
        for (int k = 0; k < 20; k++) wg_rs_n32_tb0(ax, a[vord(k)], db + hoff(vord(k)), k);
        mbar_waitf(bar + 8 * (MB_XF + 1), par);
        wg_fence();
#pragma unroll
        for (int k = 20; k < 40; k++) wg_rs_n32_tb0(ax, a[vord(k)], db + hoff(vord(k)), 1);
        wg_commit();
        mbar_waitf(bar + 8 * MB_PF, par ^ 1);
        if (wid == 6 && lane == 0) { mbar_expect(bar + 8 * MB_SM, 2 * SM_SLOT + 48); mbar_expect(bar + 8 * MB_SX, 2 * 2176); }
        wg_wait<0>();
        pin<16>(ax);
        if (w == 0) TS(1 + 22 * wg);
        stsm4t(st_x, pack2(ax[0], ax[1]), pack2(ax[2], ax[3]), pack2(ax[4], ax[5]), pack2(ax[6], ax[7]));
        stsm4t(st_x + 4096, pack2(ax[8], ax[9]), pack2(ax[10], ax[11]), pack2(ax[12], ax[13]), pack2(ax[14], ax[15]));
        bar_arrive<B_VOWN, 384>();
      }
      {
        float c[4][4];
#pragma unroll
        for (int k = 0; k < 4; k++) c[k][0] = c[k][1] = c[k][2] = c[k][3] = 0.f;
        uint32_t b[3][2][4];
        const uint32_t ld_m2 = opaque(ld_m ^ 64);
        SCHED_FENCE();
#define MORD(j) ((j) == 0 ? 9 : (j) < 4 ? (j) - 1 : 3 + ((j) - 4) / 2 + 3 * ((j) & 1))
#pragma unroll
        for (int j = 0; j < 12; j++) {
          if (j < 10) {
            if (j == 0) { mbar_waitf(bar + 8 * MB_ML, par); if (wid == 0) TS(2); }
            if (j == 1) { bar_sync<B_ML, 352>(); if (wid == 0) TS(3); }
            if (j == 4) { bar_sync<B_MR, 288>(); if (wid == 0) TS(4); }
            ldsm4(b[j % 3][0], ld_m + MORD(j) * 5120);
            ldsm4(b[j % 3][1], ld_m2 + MORD(j) * 5120);
          }
          const int u = j - 2;
          if (u >= 0) {
#pragma unroll
            for (int k = 0; k < 4; k++) mma16816(c[k], a[4 * MORD(u) + k], b[u % 3][k >> 1][(k & 1) * 2], b[u % 3][k >> 1][(k & 1) * 2 + 1]);
          }
        }
        if (wid == 0) TS(31);
#pragma unroll
        for (int k = 0; k < 4; k++) c[0][k] = (c[0][k] + c[1][k]) + (c[2][k] + c[3][k]);
        stsm2t(st_x + 1024 - wg * 3072, pack2(c[0][0], c[0][1]), pack2(c[0][2], c[0][3]));
        fence_async();
      }
      if (wg == 0) {
        bar_sync<B_QK, 256>();
        float sv[20];
        {
          constexpr uint64_t da = mkdesc(SB0 + O_QK, 16, 1024, 1), db = mkdesc(SB0 + O_K, 16, 2048, 1);
          wg_fence();
#pragma unroll
          for (int k = 0; k < 4; k++) wg_ss_n40_ta0_tb0(sv, da + 2 * k, db + 2 * k, k);
          bar_arrive<B_SISS, 256>();
          wg_commit();
        }
        if (w == 0) TS(6);
        SCHED_FENCE();
        const uint32_t ln = opaque(lane);
        uint32_t m0, m1, m2, m3, m4;
        {
          const uint32_t a1 = opaque(sb1 + O_SM + SM_SLOT + ln * 16), a2 = opaque(sb2 + O_SM + ln * 16);
          const uint32_t a3 = opaque(sb1 + O_SM + SM_SLOT + 512 + ln * 4), a4 = opaque(sb2 + O_SM + 512 + ln * 4);
          const uint32_t b1 = opaque(sb1 + O_BAR + 8 * MB_SM), b2 = opaque(sb2 + O_BAR + 8 * MB_SM);
          const uint32_t bt = opaque(mapa(sb, min(ln, 2u)) + O_BAR + 8 * MB_SM);
          SCHED_FENCE();
          wg_wait<0>();
          pin<20>(sv);
          m0 = pack2(sv[2], sv[3]); m1 = pack2(sv[6], sv[7]); m2 = pack2(sv[10], sv[11]); m3 = pack2(sv[14], sv[15]); m4 = pack2(sv[18], sv[19]);
          if (w == 0) {
            sta4(a1, m0, m1, m2, m3, b1);
            sta4(a2, m0, m1, m2, m3, b2);
            sta1(a3, m4, b1);
            sta1(a4, m4, b2);
          }
          mbar_arrive_clp(bt, ln < 3);
          bar_arrive<B_SSENT, 256>();
          SCHED_FENCE();
        }
        const uint32_t p0 = pack2(sv[0], sv[1]), p1 = pack2(sv[4], sv[5]), p2 = pack2(sv[8], sv[9]), p3 = pack2(sv[12], sv[13]), p4 = pack2(sv[16], sv[17]);
        const uint32_t ox = O_K + w * 2048 + ln * 16, ox2 = O_K + 8192 + ln * 4;
        {
          const uint32_t a1 = opaque(sb1 + ox + 512), a2 = opaque(sb2 + ox), b1 = opaque(sb1 + O_BAR + 8 * MB_SX), b2 = opaque(sb2 + O_BAR + 8 * MB_SX);
          if (w == 0) {
            TS(7);
            const uint32_t om = opaque(sb + O_SM + ln * 16), om2 = opaque(sb + O_SM + 512 + ln * 4);
            const uint32_t pa0 = ld_m + (O_QM - O_H), pa1 = (ld_m ^ 64) + (O_QM - O_H);
            float t[10] = {bflo(m0), bfhi(m0), bflo(m1), bfhi(m1), bflo(m2), bfhi(m2), bflo(m3), bfhi(m3), bflo(m4), bfhi(m4)};
            pin<10>(t);
            SCHED_FENCE();
            mbar_waitf(bar + 8 * MB_SM, par);
            const uint4 u = lds4(om), v = lds4(om + SM_SLOT);
            const uint32_t u4 = lds1(om2), v4 = lds1(om2 + SM_SLOT);
            sta4(a1, p0, p1, p2, p3, b1);
            sta4(a2, p0, p1, p2, p3, b2);
            bar_arrive<B_SLD, 256>();
            SCHED_FENCE();
            ACC3(0, u.x, v.x) ACC3(2, u.y, v.y) ACC3(4, u.z, v.z) ACC3(6, u.w, v.w) ACC3(8, u4, v4)
            TS(8);
            const float f = exp_row(t);
            stsm4(pa0, pack2(t[0] * f, t[1] * f), pack2(t[2] * f, t[3] * f), pack2(t[4] * f, t[5] * f), pack2(t[6] * f, t[7] * f));
            stsm1(pa1, pack2(t[8] * f, t[9] * f));
            bar_arrive<B_PM, 160>();
            TS(9);
          } else {
            const uint32_t a3 = opaque(sb1 + ox2 + 128), a4 = opaque(sb2 + ox2);
            SCHED_FENCE();
            mbar_waitf(bar + 8 * MB_SM, par);
            sta4(a1, p0, p1, p2, p3, b1);
            sta4(a2, p0, p1, p2, p3, b2);
            if (w == 3) { sta1(a3, p4, b1); sta1(a4, p4, b2); }
            bar_arrive<B_SLD, 256>();
          }
        }
        {
          float t[10] = {bflo(p0), bfhi(p0), bflo(p1), bfhi(p1), bflo(p2), bfhi(p2), bflo(p3), bfhi(p3), bflo(p4), bfhi(p4)};
          const int dq = 8 * w + (ln >> 2) - 2 * (ln & 3);
#pragma unroll
          for (int k = 1; k < 5; k++) {
            if (8 * (k - 1) > dq) t[2 * k] = -1e9f / SCL;
            if (8 * (k - 1) + 1 > dq) t[2 * k + 1] = -1e9f / SCL;
          }
          const int rr = 2 * w + (ln & 1);
          const uint32_t pa = sb + O_QK + ((ln >> 1) & 3) * 2048 + rr * 128;
          const uint32_t pa0 = opaque(pa + (((ln >> 3) ^ rr) << 4)), pa1 = opaque(pa0 ^ 64), l0 = opaque(sb + ox), l1 = opaque(sb + ox2);
          pin<10>(t);
          SCHED_FENCE();
          mbar_waitf(bar + 8 * MB_SX, par);
          bar_sync<B_VEND, 256>();
          const uint4 u = lds4(l0), v = lds4(l0 + 512);
          uint32_t u4 = 0, v4 = 0;
          if (w == 3) { u4 = lds1(l1); v4 = lds1(l1 + 128); }
          ACC3(0, u.x, v.x) ACC3(2, u.y, v.y) ACC3(4, u.z, v.z) ACC3(6, u.w, v.w) ACC3(8, u4, v4)
          const float f = exp_row(t);
          const float sum = (((t[0] + t[1]) + (t[2] + t[3])) + ((t[4] + t[5]) + (t[6] + t[7])) + (t[8] + t[9])) * f;
          const float s1 = __shfl_xor_sync(~0u, sum, 1), s2 = __shfl_xor_sync(~0u, sum, 2), s3 = __shfl_xor_sync(~0u, sum, 3);
          const float inv = f * rcp((sum + s1) + (s2 + s3));
          stsm4(pa0, pack2(t[0] * inv, t[1] * inv), pack2(t[2] * inv, t[3] * inv), pack2(t[4] * inv, t[5] * inv), pack2(t[6] * inv, t[7] * inv));
          stsm2(pa1, pack2(t[8] * inv, t[9] * inv), 0u);
          fence_async();
        }
        bar_arrive<B_PX, 256>();
        if (w == 0) TS(10);
        bar_sync<B_XGO, 256>();
      } else {
        bar_arrive<B_QK, 256>();
        const int ln = opaque(lane);
        if (w == 2) {
          bar_sync<B_VHALF, 192>();
          if (ln == 0 && s > 0) { red_release(flags + FL_A + (e0 >> 10) * 8 + (s - 1) * 48, 1); }
          __syncwarp();
        }
        if (w == 3) {
          const int l = bid * 2 + ln, s2 = s + 2;
          if (ln < 2 && l < 160 && s2 < NSEG - 1) {
            const int tile = l >> 4;
            const uint8_t* p = ar + (s2 >> 2) * AR_GROUP + (s2 & 1) * 128 + ((s2 >> 1) & 1) * 512 + ar_chunk(tile) * 4096 +
                               ((l >> 3) & 1) * 16384 + (l & 1) * 256 + ((l >> 1) & 3) * 1024;
            asm volatile("prefetch.global.L2 [%0];" :: "l"(p));
          }
        }
        if (w == 0) {
          const bool more = s + 1 < NSEG;
          if (ln < 2 && more) mbar_expect(bar + 8 * (MB_XF + ln), 20480);
          const uint8_t* src = g_xn + (s + 1) * 40960;
          if ((s & 1) && more) { wait_flag(flags + FL_XN + ((s + 1) >> 1) * 8, 3); fence_async_global(); }
          bar_sync<B_VHALF, 192>();
          if (more) {
#pragma unroll
            for (int q = 0; q < 5; q++) { const int p = q == 0 ? 9 : q - 1; bulk_g2s_elect<4096>(sb + O_H + p * 5120 + 1024, src + chunk_of(p) * 4096, bar + 8 * MB_XF); }
          }
          bar_sync<B_VDONE, 160>();
          if (more) {
#pragma unroll
            for (int p = 4; p < 9; p++) bulk_g2s_elect<4096>(sb + O_H + p * 5120 + 1024, src + chunk_of(p) * 4096, bar + 8 * (MB_XF + 1));
          }
        }
        bar_sync<B_XGO1, 256>();
      }
    }
  } else {
    asm volatile("setmaxnreg.dec.sync.aligned.u32 88;");
    asm volatile("barrier.cluster.wait.aligned;" ::: "memory");

    const int g = lane >> 2, i4 = lane & 3;
    const int myT = w == 0 ? 9 : rank * 3 + w - 1, myP = w == 0 ? 9 : w - 1;
    const int tok = 2 * ((lane >> 1) & 3) + ((lane >> 3) & 1);
    const uint32_t fw_off = sb + O_H + myP * 5120 + tok * 128 + (((2 * (lane >> 4) + (lane & 1)) ^ tok) << 4);
    const uint32_t prod_off = (w >> 1) * 16384 + (w & 1) * 2048 + ((g >> 1) & 1) * 256 + (i4 * 2 + (g >> 2)) * 16 + (g & 1) * 8;
    const uint32_t cons_off = ar_chunk(myT) * 4096 + (lane >> 3) * 1024 + (lane & 7) * 16;
    auto tile_off = [&](int k) { return (k * 8 + rank) * 4096; };
    constexpr uint32_t T9_OFF = ar_chunk(9) * 4096;

    uint32_t p[8];
    auto forward = [&]() {
      const uint32_t c = O_H + myP * 5120, bo = O_BAR + 8 * MB_MR;
      sts4(fw_off, p[0], p[1], p[2], p[3]);
      sts4(fw_off ^ 64, p[4], p[5], p[6], p[7]);
      if (w == 0) {
        __syncwarp();
        mbar_arrive_elect(bar + 8 * MB_ML);
        fence_async();
      } else {
        bar_arrive<B_ML, 352>();
        fence_async();
        __syncwarp();
        bulk_s2c_elect1<1024>(sb1 + c + 6 * 5120, sb1 + bo, sb + c);
        bulk_s2c_elect1<1024>(sb2 + c + 3 * 5120, sb2 + bo, sb + c);
      }
    };
    auto send_max = [&]() {
      uint32_t mx = 0;
#pragma unroll
      for (int k = 0; k < 8; k++) mx = __vmaxu2(mx, p[k] & 0x7FFF7FFFu);
      mx = max(mx & 0xFFFFu, mx >> 16);
      mx = __reduce_max_sync(~0u, mx);
      { const uint32_t b = mapa(sb, min(lane, 2)); sta1p(b + O_MAXS + (rank * 4 + w) * 4, mx << 16, b + O_BAR + 8 * MB_SM, lane < 3); }
    };
    auto arm = [&]() { if (lane == 0 && w < 2) mbar_expect(bar + 8 * (w == 0 ? MB_OG : MB_MR), w == 0 ? 2048 : 6144); };
    {
      arm();
      const uint32_t* mp = (const uint32_t*)(mem0 + tok * DM + myT * 64 + 16 * (lane >> 4) + 4 * (lane & 1));
      p[0] = mp[0]; p[1] = mp[4]; p[2] = mp[1]; p[3] = mp[5]; p[4] = mp[16]; p[5] = mp[20]; p[6] = mp[17]; p[7] = mp[21];
      forward();
    }
    if (w == 1) {
#pragma unroll 1
      for (int i = W_WIN; i < 20; i++) {
        if (i <= W_OPEN) mbar_wait(bar + 8 * (MB_W + i - W_WIN), 0);
        if (i >= 10) mbar_wait(bar + 8 * (MB_WC + i - 10), 0);
        load_piece(i);
      }
    }
    if (w == 0) {
      if (lane < 2) mbar_expect(bar + 8 * (MB_XF + lane), 20480);
      wait_flag<200>(flags + FL_XN, 3);
      fence_async_global();
      if (lane < 10) bulk_g2s(sb + O_H + lane * 5120 + 1024, g_xn + chunk_of(lane) * 4096, 4096, bar + 8 * (MB_XF + (lane >= 4 && lane < 9)));
      if (lane == 0) GTT(layer * 4 + 1, 4);
    }
    if (w == 2) {
      wait_flag<400>(flags + FL_X, 128);
      wait_flag<400>(g_zero + Z_FLAGS + FL_N, 4);
      const float sq = __ldcg((const float*)(g_zero + Z_NORM));
      float mx = 0.f;
#pragma unroll
      for (int k = 0; k < 5; k++) {
        const float4* p = (const float4*)g_nrm + k * 32 + lane;
        const float4 x = __ldcg(p), y = __ldcg(p + 160), z = __ldcg(p + 320), u = __ldcg(p + 480);
        mx = fmaxf(fmaxf(mx, fmaxf((x.x + y.x) + (z.x + u.x), (x.y + y.y) + (z.y + u.y))), fmaxf((x.z + y.z) + (z.z + u.z), (x.w + y.w) + (z.w + u.w)));
      }
#pragma unroll
      for (int o = 16; o; o >>= 1) mx = fmaxf(mx, __shfl_xor_sync(~0u, mx, o));
      sts1(sb + O_MAXS + 52, __float_as_uint(sqrt_approx(sq) * sqrt_approx(mx) * (25.2982213f * 1.1f)));
    }
    bar_sync<B_WG2, 128>();
    const float cbound = __uint_as_float(lds1(sb + O_MAXS + 52));
#pragma unroll 1
    for (int i = 10; i < 15; i++) mbar_wait(bar + 8 * (MB_W + i), 0);
    if (tid == 256) GTT(layer * 4 + 1, 7);

    const uint32_t la_w = sb + O_WV + ((lane >> 4) * 8 + (lane & 7)) * 128 + (((2 * w + ((lane >> 3) & 1)) ^ (lane & 7)) << 4);
    uint32_t af[V_RS][4];
#pragma unroll
    for (int k = 0; k < V_RS; k++) ldsm4t(af[k], la_w + vord(V_OWN + k) * 2048);
    const uint32_t pa0 = __shfl_sync(~0u, sb + O_QM + (lane & 7) * 128 + (((lane >> 3) ^ (lane & 7)) << 4), lane), pa1 = __shfl_sync(~0u, pa0 ^ 64, lane);
    uint32_t vf[10];
    uint4 oq0, oq1;
    uint8_t* op;
    auto pv_x = [&](int s) {
      float ox[16];
      const uint32_t vz[4] = {vf[8], vf[9], 0u, 0u};
      constexpr uint64_t dp = mkdesc(SB0 + O_QK, 16, 2048, 1);
      bar_sync<B_PX, 256>();
      wg_fence();
      wg_rs_n32_tb0(ox, vf, dp, 0);
      wg_rs_n32_tb0(ox, vf + 4, dp + 2, 1);
      wg_rs_n32_tb0(ox, vz, dp + 4, 1);
      wg_commit();
      if (XG0 == 1) { bar_arrive<B_XGO, 256>(); SCHED_FENCE(); }
      const uint32_t ln = opaque(lane);
      op = g_ot + (size_t)s * (HE * 64) + (e0 + 16 * w) * 64 + (ln & 3) * 128 + (ln >> 2) * 16;
      wg_wait<0>();
      pin<16>(ox);
      oq0 = make_uint4(pack2(ox[0], ox[1]), pack2(ox[4], ox[5]), pack2(ox[8], ox[9]), pack2(ox[12], ox[13]));
      oq1 = make_uint4(pack2(ox[2], ox[3]), pack2(ox[6], ox[7]), pack2(ox[10], ox[11]), pack2(ox[14], ox[15]));
    };
    for (int s = 0;; s++) {
      const uint32_t par = s & 1;
      float sc1, isc, sum0, sum1;
      uint32_t ao[O_RS][4];
      {
        float av[20];
        constexpr uint64_t da = mkdesc(SB0 + O_WV, 1024, 1024, 1), db = mkdesc(SB0 + O_H, 16, 1024, 1);
#define V_RUN(k0, k1) wg_fence(); _Pragma("unroll") for (int k = k0; k < k1; k++) wg_ss_n40_ta1_tb0(av, da + vord(k) * 128, db + hoff(vord(k)), k);
        bar_sync<B_VOWN, 384>();
        V_RUN(0, V_OWN)
        if (w == 0) TS(29);
        SCHED_FENCE();
        if (w == 0) { mbar_waitf(bar + 8 * MB_MR, par); bar_arrive<B_MR, 288>(); SCHED_FENCE(); }
        send_max();
        bar_sync<B_SISS, 256>();
        V_RUN(V_OWN + V_RS, V_OWN + V_RS + V_B)
        if (s == 0) {
#pragma unroll 1
          for (int i = 15; i < 20; i++) mbar_wait(bar + 8 * (MB_W + i), 0);
          asm volatile("griddepcontrol.launch_dependents;");
          if (tid == 256) GTT(layer * 4 + 1, 8);
        }
        bar_sync<B_SSENT, 256>();
        V_RUN(V_OWN + V_RS + V_B, V_K1)
        wg_fence();
#pragma unroll
        for (int k = 0; k < V_RS; k++) wg_rs_n40_tb0(av, af[k], db + hoff(vord(V_OWN + k)), 1);
        if (V_K1 >= 20) wg_commit();
        const uint32_t ln = opaque(lane);
        const uint32_t amx = opaque(sb + O_MAXS + 4 * min(ln, 11u));
        SCHED_FENCE();
        mbar_waitf(bar + 8 * MB_SM, par);
        const uint32_t mxl = lds1(amx);
        if (V_S2 == 0) { wg_wait<0>(); bar_arrive<B_VHALF, 192>(); }
        bar_sync<B_SLD, 256>();
        if (SLDW) { const uint32_t t2 = clk(); while ((int)(clk() - t2) < SLDW) {} }
        if (V_K1 < 20) { V_RUN(V_K1, 20) wg_commit(); }
        if (V_S2 > 0) {
          V_RUN((V_K1 > 20 ? V_K1 : 20), V_K2)
          wg_commit();
          wg_wait<1>();
          bar_arrive<B_VHALF, 192>();
        }
        V_RUN(V_K2, 40)
        wg_commit();
        SCHED_FENCE();
        if (w == 0) TS(12);
        {
          const float bnd = cbound * fmaxf(1.f, __uint_as_float(__reduce_max_sync(~0u, mxl)));
          const uint32_t eb = min(max(__float_as_uint(bnd) >> 23, 31u), 254u);
          sc1 = __uint_as_float(opaque((280u - eb) << 23));
          isc = __uint_as_float(opaque((eb - 29u) << 23));
        }
        const uint32_t o = O_OG + w * 256 + ln * 4;
        const uint32_t a0 = opaque(sb + o), a1 = opaque(sb1 + o + 4096), a2 = opaque(sb1 + o + 4096 + 128), a3 = opaque(sb2 + o + 2048), a4 = opaque(sb2 + o + 2048 + 128);
        const uint32_t b1 = opaque(sb1 + O_BAR + 8 * MB_OG), b2 = opaque(sb2 + O_BAR + 8 * MB_OG);
        const uint32_t c1 = opaque(0x3F803F80u);
        const uint32_t one[4] = {c1, c1, c1, c1};
        uint32_t pm[5];
        bar_arrive<B_VEND, 256>();
        SCHED_FENCE();
        bar_sync<B_PM, 160>();
        ldsm4(pm, pa0);
        ldsm1(pm[4], pa1);
        SCHED_FENCE();
        wg_wait<0>();
        pin<20>(av);
        if (w == 0) TS(13);
#pragma unroll
        for (int j = 0; j < 16; j++) if ((O_RSM >> j) & 1) ldsm4t(ao[O_IDX(j)], la_w + O_WO + (1 + (j >> 3)) * 24576 + (4 + (j & 7)) * 2048);
#pragma unroll
        for (int k = 0; k < 10; k++) vf[k] = pack2(av[2 * k], av[2 * k + 1]);
        float o0[4] = {0.f, 0.f, 0.f, 0.f}, o1[4] = {0.f, 0.f, 0.f, 0.f}, o2[4] = {0.f, 0.f, 0.f, 0.f};
        float s0[4] = {0.f, 0.f, 0.f, 0.f}, s1[4] = {0.f, 0.f, 0.f, 0.f}, s2[4] = {0.f, 0.f, 0.f, 0.f};
        mma16816(o0, vf, pm[0], pm[1]);
        mma16816(o1, vf + 4, pm[2], pm[3]);
        mma1688(o2, vf[8], vf[9], pm[4]);
        mma16816(s0, one, pm[0], pm[1]);
        mma16816(s1, one, pm[2], pm[3]);
        mma1688(s2, c1, c1, pm[4]);
        const uint32_t p0 = pack2(o0[0] + o1[0] + o2[0], o0[1] + o1[1] + o2[1]), p1 = pack2(o0[2] + o1[2] + o2[2], o0[3] + o1[3] + o2[3]);
        sta1(a1, p0, b1); sta1(a2, p1, b1);
        sta1(a3, p0, b2); sta1(a4, p1, b2);
        sts1(a0, p0); sts1(a0 + 128, p1);
        sum0 = s0[0] + s1[0] + s2[0]; sum1 = s0[1] + s1[1] + s2[1];
        fence_async();
      }
      if (s == NSEG - 1) break;
      uint8_t* arp;
      uint32_t t1;
      {
        bar_sync<B_WG2, 128>();
        float c9[4], ca[4], cb[4], cc[4];
        constexpr uint64_t da = mkdesc(SB0 + O_WO, 1024, 1024, 1), db = mkdesc(SB0 + O_OG, 128, 128, 0);
#define O_RUN(acc, tile, k0, k1) _Pragma("unroll") for (int k = k0; k < k1; k++) wg_ss_n8_ta1_tb1(acc, da + (tile) * 1536 + k * 128, db + (k >> 2) * 128 + (k & 3) * 16, k);
        wg_fence();
        O_RUN(c9, 3, 0, 4)
        wg_commit();
        if (w == 0) TS(14);
        O_RUN(ca, 0, 0, 4) O_RUN(cb, 1, 0, 2)
        wg_commit();
        SCHED_FENCE();
        arp = ar + (s >> 2) * AR_GROUP + (s & 1) * 128 + ((s >> 1) & 1) * 512;
        uint8_t* pp = arp + opaque(prod_off);
        const float2 sc = make_float2(sc1 * rcp(sum0), sc1 * rcp(sum1));
        wg_wait<1>();
        pin<4>(c9);
        fix_red(pp + T9_OFF, c9, sc);
        SCHED_FENCE();
        wg_fence();
        O_RUN(cb, 1, 2, 4) O_RUN(cc, 2, 0, 4)
        mbar_waitf(bar + 8 * MB_OG, par);
        wg_fence();
        O_RUN(ca, 0, 4, 12)
        wg_commit();
        if (w == 0) TS(15);
#define O_MIX(acc, j0, j1) _Pragma("unroll") for (int j = j0; j < j1; j++) { const int k = 4 + (j & 7); \
          if ((O_RSM >> j) & 1) wg_rs_n8_tb1(acc, ao[O_IDX(j) < O_RS ? O_IDX(j) : 0], db + (k >> 2) * 128 + (k & 3) * 16, 1); \
          else wg_ss_n8_ta1_tb1(acc, da + (1 + (j >> 3)) * 1536 + k * 128, db + (k >> 2) * 128 + (k & 3) * 16, 1); }
        O_MIX(cb, 0, O_B1)
        wg_commit();
        wg_wait<1>();
        pin<4>(ca);
        fix_red(pp + tile_off(0), ca, sc);
        SCHED_FENCE();
        if (w == 0) TS(16);
        bar_arrive<B_VDONE, 160>();
        wg_fence();
        O_MIX(cb, O_B1, 8)
        wg_commit();
        O_MIX(cc, 8, XG1)
        if (XG1 < 16) bar_arrive<B_XGO1, 256>();
        O_MIX(cc, XG1, 16)
        wg_commit();
        if (XG1 == 16) bar_arrive<B_XGO1, 256>();
        if (XG0 == 0) bar_arrive<B_XGO, 256>();
        wg_wait<1>();
        pin<4>(cb);
        uint8_t* pb = pp + tile_off(1);
        fix_red(pb, cb, sc);
        wg_wait<0>();
        pin<4>(cc);
        fix_red(pb + 32768, cc, sc);
        t1 = clk();
        if (w == 3) TS(17);
      }
      pv_x(s);
      mbar_arrive_elect(bar + 8 * MB_PF);
      if (w == 0) TS(28);
      {
        arm();
        const int dly = w == 0 ? POLL_9 : w == 1 ? POLL_A : w == 2 ? POLL_B : POLL_C;
        const uint32_t need = w == 0 ? 96 : 32;
        const uint8_t* cp = arp + opaque(cons_off);
        uint4 y[4];
        int it = 0;
        while ((int)(clk() - t1) < dly) {}
        if (w == 3) TS(18);
        y[0] = ld_poll(cp); y[1] = ld_poll(cp + 256); y[2] = ld_poll(cp + 16384); y[3] = ld_poll(cp + 16384 + 256);
        { const uint64_t pol = policy_evict_first(); stg4h(op, oq0, pol); stg4h(op + 512, oq1, pol); }
        const float isl = isc * 0.5f, bias = -(float)(need >> 3) * isl;
        while (true) {
          const uint32_t bad = ((y[0].x ^ need) | (y[0].z ^ need) | (y[1].x ^ need) | (y[1].z ^ need)) | ((y[2].x ^ need) | (y[2].z ^ need) | (y[3].x ^ need) | (y[3].z ^ need));
          if (!__any_sync(~0u, (bad & 127u) != 0)) break;
          if (++it > 2000000) __trap();
          y[0] = ld_poll(cp); y[1] = ld_poll(cp + 256); y[2] = ld_poll(cp + 16384); y[3] = ld_poll(cp + 16384 + 256);
        }
#pragma unroll
        for (int k = 0; k < 4; k++) {
          p[2 * k] = pack2(fmaf((float)(int)__funnelshift_r(y[k].x, y[k].y, 3), isl, bias), fmaf((float)(int)__funnelshift_r(y[k].z, y[k].w, 3), isl, bias));
          p[2 * k + 1] = pack2((float)(int)y[k].y * isc, (float)(int)y[k].w * isc);
        }
        TS(19 + w);
        forward();
      }
    }
    bar_arrive<B_VDONE, 160>();
    bar_arrive<B_XGO1, 256>();
    if (XG0 == 0) bar_arrive<B_XGO, 256>();
    pv_x(NSEG - 1);
    { const uint64_t pol = policy_evict_first(); stg4h(op, oq0, pol); stg4h(op + 512, oq1, pol); }
    bar_sync<B_WG2, 128>();
    if (tid == 256) red_release(flags + FL_A + (e0 >> 10) * 8 + (NSEG - 1) * 48, 1);
    mbar_wait(bar + 8 * MB_OG, 1);
    __syncwarp();
  }
  asm volatile("barrier.cluster.arrive.relaxed.aligned;\nbarrier.cluster.wait.aligned;" ::: "memory");
  GT(layer * 4 + 1, 2);
  if (wid == 0) asm volatile("griddepcontrol.wait;" ::: "memory");
}

constexpr int P_B = 0, P_A = 131072, P_BAR = 196608, OPC_SMEM = P_BAR + 256;
#define PF_C 3
#define PF_S0 43
constexpr int OP_KR = 48;

__global__ void __launch_bounds__(384, 1)
opc_kernel(const __grid_constant__ CUtensorMap tmo, bf16* __restrict__ out, int layer,
           const bf16* __restrict__ Wq, const bf16* __restrict__ Wk, const bf16* __restrict__ Wv, const bf16* __restrict__ Wo) {
  extern __shared__ __align__(1024) uint8_t smem[];
  asm volatile("griddepcontrol.launch_dependents;");
  GT(layer * 4 + 2, 0);
  const uint32_t sb = smem_u32(smem);
  check_smem_base(sb);
  const int tid = threadIdx.x, wid = __shfl_sync(~0u, tid >> 5, 0), wg = wid >> 2, w = wid & 3, lane = tid & 31;
  const uint32_t bar = sb + P_BAR;
  uint32_t* flags = g_zero + Z_FLAGS + layer * FL_LAYER;
  float* acc = g_acc + layer * (S_TOK * DM);
  const uint64_t pol = policy_evict_first();
  if (wid == 0) {
    if (lane < 16) mbar_init(bar + 8 * lane, (lane == 8 || lane == 9) ? 8 : 1);
    fence_async();
  }
  __syncthreads();
  if (blockIdx.x < 30) {
    const int cg = blockIdx.x % 5, kg = blockIdx.x / 5;
    if (wg < 2) {
      asm volatile("setmaxnreg.inc.sync.aligned.u32 240;");
      uint32_t a[OP_KR][4];
      const uint32_t la = sb + P_B + ((lane >> 4) * 8 + (lane & 7)) * 128 + (((2 * w + ((lane >> 3) & 1)) ^ (lane & 7)) << 4);
      mbar_wait(bar + 80, 0);
#pragma unroll
      for (int k = 0; k < 32; k++) ldsm4t(a[k], la + wg * 65536 + k * 2048);
      bar_arrive<2, 288>();
      mbar_wait(bar + 88, 0);
#pragma unroll
      for (int k = 0; k < 16; k++) ldsm4t(a[32 + k], la + wg * 32768 + k * 2048);
      bar_arrive<3, 288>();
      mbar_wait(bar + 96, 0);
      float* ap = acc + (cg * 8 + wg * 4 + w) * 512 + lane * 4;
      for (int s = 0; s < NSEG; s++) {
        const int buf = s & 1;
        const uint32_t par = (s >> 1) & 1;
        float d[16];
        const uint64_t db = mkdesc(SB0 + P_B + buf * 65536, 512, 128, 0), da = mkdesc(SB0 + P_A + wg * 32768, 1024, 1024, 1);
        float* p = ap + s * (32 * DM);
        float* pz = ap + (s + 2) * (32 * DM) + kg * 128;
        if (kg < 4 && s + 2 < NSEG) { if (EVF) stg4h(pz, make_uint4(0, 0, 0, 0), pol); else stg4(pz, make_uint4(0, 0, 0, 0)); }
#pragma unroll
        for (int q = 0; q < 4; q++) {
          mbar_wait(bar + 8 * (buf * 4 + q), par);
          wg_fence();
#pragma unroll
          for (int k = 16 * q; k < 16 * q + 16; k++) {
            if (k < OP_KR) wg_rs_n32_tb1(d, a[k < OP_KR ? k : 0], db + k * 64, k);
            else wg_ss_n32_ta1_tb1(d, da + (k - OP_KR) * 128, db + k * 64, 1);
          }
        }
        wg_commit();
        wg_wait<0>();
        pin<16>(d);
        if (lane == 0) mbar_arrive(bar + 8 * (8 + buf));
        if (s == NSEG - 1) GT(layer * 4 + 2, 6);
        if (EVF) {
          red4fh(p, d[0], d[1], d[4], d[5], pol);
          red4fh(p + 128, d[8], d[9], d[12], d[13], pol);
          red4fh(p + 256, d[2], d[3], d[6], d[7], pol);
          red4fh(p + 384, d[10], d[11], d[14], d[15], pol);
        } else {
          red4f(p, d[0], d[1], d[4], d[5]);
          red4f(p + 128, d[8], d[9], d[12], d[13]);
          red4f(p + 256, d[2], d[3], d[6], d[7]);
          red4f(p + 384, d[10], d[11], d[14], d[15]);
        }
        bar_sync<1, 256>();
        if (tid == 0) { red_release(flags + FL_B + s * 8, 1); }
        __syncwarp();
      }
    } else {
      asm volatile("setmaxnreg.dec.sync.aligned.u32 24;");
      if (w == 0) {
        if (lane == 0) { mbar_expect(bar + 80, 131072); mbar_expect(bar + 96, 65536); mbar_expect(bar + 88, 65536); }
        __syncwarp();
        if (lane < 16) tma2d(sb + P_B + lane * 8192, &tmo, cg * 128 + (lane >> 3) * 64, kg * 1024 + (lane & 7) * 64, bar + 80);
        else if (lane < 24) tma2d(sb + P_B + lane * 8192, &tmo, cg * 128 + ((lane >> 2) & 1) * 64, kg * 1024 + 768 + (lane & 3) * 64, bar + 96);
        bar_sync<2, 288>();
        fence_async();
        if (lane < 8) tma2d(sb + P_B + lane * 8192, &tmo, cg * 128 + (lane >> 2) * 64, kg * 1024 + 512 + (lane & 3) * 64, bar + 88);
        bar_sync<3, 288>();
        for (int s = 0; s < NSEG; s++) {
          const int buf = s & 1;
          if (s >= 2) mbar_wait(bar + 8 * (8 + buf), ((s >> 1) & 1) ^ 1);
          if (s >= 2) wait_flag(flags + FL_B + (s - 2) * 8, 30);
          wait_flag(flags + FL_A + s * 48 + kg * 8, 16);
          fence_async_global();
          if (lane < 4) {
            mbar_expect(bar + 8 * (buf * 4 + lane), 16384);
            if (EVF) bulk_g2sh(sb + P_B + buf * 65536 + lane * 16384, g_ot + (size_t)s * (HE * 64) + kg * 65536 + lane * 16384, 16384, bar + 8 * (buf * 4 + lane), pol);
            else bulk_g2s(sb + P_B + buf * 65536 + lane * 16384, g_ot + (size_t)s * (HE * 64) + kg * 65536 + lane * 16384, 16384, bar + 8 * (buf * 4 + lane));
            if (s == NSEG - 1 && lane == 0) GTT(layer * 4 + 2, 5);
          }
          __syncwarp();
        }
      } else if (w == 1 && layer == 0) {
#pragma unroll 1
        for (int q = 4 * (4 - PF_C); q < 18; q++) {
          wait_flag(flags + FL_A + (PF_S0 + q) * 48 + kg * 8, 16);
          const int m = q >> 2;
          const uint8_t* W = m == 0 ? (const uint8_t*)Wo : m == 1 ? (const uint8_t*)Wv : m == 2 ? (const uint8_t*)Wk : m == 3 ? (const uint8_t*)Wq : (q & 1) ? g_w2 : g_w1;
          const int n = m < 4 ? 512 : (q & 1) ? 224 : 640, l0 = m < 4 ? blockIdx.x * 2048 + (q & 3) * 512 : blockIdx.x * n, lim = m < 4 ? 61440 : (q & 1) ? 6720 : 19200;
#pragma unroll 1
          for (int k = lane; k < n; k += 32) {
            if (l0 + k < lim) asm volatile("prefetch.global.L2 [%0];" :: "l"(W + (size_t)(l0 + k) * 128));
            __nanosleep(100);
          }
        }
      }
    }
  } else {
    constexpr int LD = 644;
    float* xs = (float*)smem;
    uint32_t par = 0;
    for (int task = blockIdx.x - 30; task < 2 * NSEG; task += 6, par ^= 1) {
      const int s = task >> 1, jj = task & 1;
      if (wid == 0) {
        wait_flag(flags + FL_XN + (task >> 2) * 8 + 1, 3);
        fence_async_global();
        if (lane == 0) { mbar_expect(bar, 20480); bulk_g2s(sb + 49152, g_x + task * 16 * DM, 20480, bar); }
      }
      if (wid == 1) { wait_flag(flags + FL_B + s * 8, 30); if (s == NSEG - 1 && lane == 0) GTT(layer * 4 + 2, 7); }
      __syncthreads();
      if (wid < 10) {
        float4 v[8];
#pragma unroll
        for (int k = 0; k < 8; k++) v[k] = EVF ? ldg4fh(acc + s * (32 * DM) + (wid * 8 + k) * 256 + jj * 128 + lane * 4, pol) : __ldcg((const float4*)(acc + s * (32 * DM) + (wid * 8 + k) * 256 + jj * 128 + lane * 4));
        float* xp = xs + (lane & 3) * 2 * LD + wid * 64 + (lane >> 2);
#pragma unroll
        for (int k = 0; k < 8; k++) { xp[k * 8] = v[k].x; xp[LD + k * 8] = v[k].y; xp[8 * LD + k * 8] = v[k].z; xp[9 * LD + k * 8] = v[k].w; }
      }
      mbar_wait(bar, par);
      __syncthreads();
      float v[2][20];
      const int pj = (lane & 24) + 2 * (lane & 3) + ((lane >> 2) & 1);
      const int tk0 = task * 16 + wid;
      if (wid < 8) {
        float sum[2] = {0.f, 0.f};
#pragma unroll
        for (int h = 0; h < 2; h++) {
#pragma unroll
          for (int k = 0; k < 10; k++) {
            const float2 u = *(const float2*)(xs + (wid + 8 * h) * LD + k * 64 + lane * 2);
            const uint32_t r = *(const uint32_t*)(smem + 49152 + (wid + 8 * h) * 1280 + k * 128 + pj * 4);
            v[h][2 * k] = u.x + bflo(r); v[h][2 * k + 1] = u.y + bfhi(r); sum[h] += v[h][2 * k] + v[h][2 * k + 1];
          }
        }
        if (!out) {
#pragma unroll
          for (int o = 16; o; o >>= 1) { sum[0] += __shfl_xor_sync(~0u, sum[0], o); sum[1] += __shfl_xor_sync(~0u, sum[1], o); }
          float q[2] = {0.f, 0.f};
#pragma unroll
          for (int h = 0; h < 2; h++) {
            sum[h] *= (1.f / DM);
#pragma unroll
            for (int k = 0; k < 20; k++) q[h] = fmaf(v[h][k] - sum[h], v[h][k] - sum[h], q[h]);
          }
#pragma unroll
          for (int o = 16; o; o >>= 1) { q[0] += __shfl_xor_sync(~0u, q[0], o); q[1] += __shfl_xor_sync(~0u, q[1], o); }
          uint8_t* xp = g_xt + (tk0 >> 7) * 163840 + (tk0 & 127) * 128 + (((lane >> 2) ^ (tk0 & 7)) << 4) + (lane & 3) * 4;
#pragma unroll
          for (int h = 0; h < 2; h++) {
            const float rs = rsqrtf(q[h] * (1.f / DM) + 1e-5f), sh = -sum[h] * rs;
#pragma unroll
            for (int k = 0; k < 10; k++) *(uint32_t*)(xp + h * 1024 + k * 16384) = pack2(fmaf(v[h][2 * k], rs, sh), fmaf(v[h][2 * k + 1], rs, sh));
          }
        }
      }
      fence_async();
      __syncthreads();
      if (!out) {
        if (tid == 352) red_release(flags + FL_LAYER + FL_T + (task >> 3) * 8, 1);
        __syncthreads();
      }
      if (wid < 8) {
        bf16* dst = out ? out + tk0 * DM + lane * 2 : g_x + tk0 * DM + pj * 2;
#pragma unroll
        for (int k = 0; k < 20; k++) *(uint32_t*)(dst + (k / 10) * 8 * DM + (k % 10) * 64) = pack2(v[k / 10][2 * (k % 10)], v[k / 10][2 * (k % 10) + 1]);
      }
    }
    __syncthreads();
    if (tid == 0 && !out) red_release(flags + FL_LAYER + FL_R, 1);
  }
  GT(layer * 4 + 2, 1);
  __syncwarp();
  asm volatile("griddepcontrol.wait;" ::: "memory");
  GT(layer * 4 + 2, 2);
}

constexpr int L_STAGE = 47104;
constexpr int L_KV = 0, L_B2 = 43008;
constexpr int L_BAR = 4 * L_STAGE;
constexpr int LA_SMEM = L_BAR + 256;
__device__ __forceinline__ float phi(float t) { return (fmaxf(t, 0.f) + 1e-6f) + ex2(fminf(t * 1.4426950408889634f, 0.f)); }
__device__ __forceinline__ void sqacc(uint32_t& h, uint32_t v) { asm("fma.rn.bf16x2 %0, %1, %1, %0;" : "+r"(h) : "r"(v)); }
__device__ __forceinline__ uint32_t phi2(float a, float b) { return pack2(phi(a), phi(b)); }
#define LA_LATE 6
#define PF_LB 1
#define PF_IL 1
#define PF_SLEEP1 400
#define RD1 0
#define PF_N0 2
#define PF_N1 0
#define PF_SLEEP 300

__global__ void __launch_bounds__(384, 1)
la_kernel(const bf16* __restrict__ Wq, const bf16* __restrict__ Wk, const bf16* __restrict__ Wv,
          const bf16* __restrict__ Wo, uint8_t* __restrict__ ar, int layer) {
  extern __shared__ __align__(1024) uint8_t smem[];
  const uint32_t sb = smem_u32(smem);
  check_smem_base(sb);
  const int tid = threadIdx.x, wid = __shfl_sync(~0u, tid >> 5, 0), wg = wid >> 2, w = wid & 3, lane = tid & 31, g = lane >> 2, i4 = lane & 3;
  const int cr = blockIdx.x & 1, hg = (blockIdx.x >> 1) & 7, tb = (blockIdx.x >> 4) * 2 + cr;
  const uint32_t bar = sb + L_BAR;
  uint32_t* flags = g_zero + Z_FLAGS + layer * FL_LAYER;
  asm volatile("griddepcontrol.launch_dependents;");
  GT(layer * 4, 0);
  if (wid == 0) {
    if (lane < 8) mbar_init(bar + 8 * lane, lane >= 4 ? (blockIdx.x < 128 ? 16 : 10) : 1);
    asm volatile("fence.mbarrier_init.release.cluster;" ::: "memory");
    fence_async();
  }
  if (blockIdx.x >= 128) {
    __syncthreads();
    const int q = blockIdx.x - 128;
    const uint8_t* src = (const uint8_t*)Wo + q * 1966080;
    if (wid == 11) {
#pragma unroll 1
      for (int it = 0; it < 48; it++) {
        const int st = it & 3;
        if (it >= 4) mbar_wait(bar + 8 * (4 + st), ((it >> 2) & 1) ^ 1);
        if (lane == 0) mbar_expect(bar + 8 * st, 40960);
        __syncwarp();
        if (lane < 4) bulk_g2s(sb + st * 40960 + lane * 10240, src + it * 40960 + lane * 10240, 10240, bar + 8 * st);
      }
    } else if (wid < 10) {
      float c[8] = {0.f, 0.f, 0.f, 0.f, 0.f, 0.f, 0.f, 0.f};
#pragma unroll 1
      for (int it = 0; it < 48; it++) {
        const int st = it & 3;
        mbar_wait(bar + 8 * st, (it >> 2) & 1);
        uint4 v[8];
#pragma unroll
        for (int k = 0; k < 8; k++) v[k] = lds4(sb + st * 40960 + k * 5120 + tid * 16);
        uint32_t h[4] = {0, 0, 0, 0};
#pragma unroll
        for (int k = 0; k < 8; k++) { sqacc(h[0], v[k].x); sqacc(h[1], v[k].y); sqacc(h[2], v[k].z); sqacc(h[3], v[k].w); }
        __syncwarp();
        if (lane == 0) mbar_arrive(bar + 8 * (4 + st));
#pragma unroll
        for (int k = 0; k < 4; k++) { c[2 * k] += bflo(h[k]); c[2 * k + 1] += bfhi(h[k]); }
      }
      float* red = (float*)(smem + 163840);
      *(float4*)(red + tid * 8) = make_float4(c[0], c[1], c[2], c[3]);
      *(float4*)(red + tid * 8 + 4) = make_float4(c[4], c[5], c[6], c[7]);
      bar_sync<1, 320>();
#pragma unroll
      for (int k = tid; k < DM; k += 320) g_nrm[q * DM + k] = (red[k] + red[DM + k]) + (red[2 * DM + k] + red[3 * DM + k]);
      asm volatile("griddepcontrol.wait;" ::: "memory");
      bar_sync<1, 320>();
      if (tid == 0) red_release(flags + FL_N, 1);
      GT(0, 2);
    }
    return;
  }
  __syncthreads();
  asm volatile("barrier.cluster.arrive.relaxed.aligned;" ::: "memory");
  if (layer == 0) asm volatile("griddepcontrol.wait;" ::: "memory");
  asm volatile("barrier.cluster.wait.aligned;" ::: "memory");
  if (wg == 2) {
    asm volatile("setmaxnreg.dec.sync.aligned.u32 40;");
    if (w == 0) {
      if (lane < 4) {
        mbar_expect(bar + 8 * lane, L_STAGE);
        bulk_g2s_mc(sb + lane * L_STAGE + 16384 + cr * 15360, g_w1 + (hg * 10 + lane) * 30720 + cr * 15360, 15360, bar + 8 * lane);
      }
      if (layer == 1) { if (LA_LATE) wait_flag(flags + FL_T + 15 * 8, LA_LATE); wait_flag(flags + FL_T + tb * 8, 8); fence_async_global(); }
      if (lane < 4) bulk_g2s(sb + lane * L_STAGE, g_xt + (tb * 10 + lane) * 16384, 16384, bar + 8 * lane);
#pragma unroll 1
      for (int kc = 4; kc < 10; kc++) {
        const int st = kc & 3;
        mbar_wait(bar + 8 * (4 + st), ((kc >> 2) & 1) ^ 1);
        if (lane == 0) {
          mbar_expect(bar + 8 * st, L_STAGE);
          bulk_g2s_mc(sb + st * L_STAGE + 16384 + cr * 15360, g_w1 + (hg * 10 + kc) * 30720 + cr * 15360, 15360, bar + 8 * st);
          bulk_g2s(sb + st * L_STAGE, g_xt + (tb * 10 + kc) * 16384, 16384, bar + 8 * st);
        }
        __syncwarp();
      }
    } else {
      const int t = tid - 288;
#pragma unroll 1
      for (int k = t; k < 768; k += 96) *(uint4*)(ar + blockIdx.x * 12288 + k * 16) = make_uint4(0, 0, 0, 0);
      if (layer == 0 || RD1) {
        float sv = 0.f;
        const uint4* pv = (const uint4*)((const uint8_t*)Wv + blockIdx.x * 61440) + t;
#pragma unroll 1
        for (int k = 0; k < 40; k += 5) {
          uint4 v[5];
#pragma unroll
          for (int j = 0; j < 5; j++) v[j] = __ldg(pv + (k + j) * 96);
          if (PF_IL && k < 25) {
            asm volatile("prefetch.global.L2 [%0];" :: "l"((const uint8_t*)Wq + blockIdx.x * 61440 + (k / 5) * 12288 + t * 128));
            if (PF_IL > 1) asm volatile("prefetch.global.L2 [%0];" :: "l"((const uint8_t*)Wk + blockIdx.x * 61440 + (k / 5) * 12288 + t * 128));
          }
#pragma unroll
          for (int j = 0; j < 5; j++) {
            sv = fmaf(bflo(v[j].x), bflo(v[j].x), fmaf(bfhi(v[j].x), bfhi(v[j].x), fmaf(bflo(v[j].y), bflo(v[j].y), fmaf(bfhi(v[j].y), bfhi(v[j].y), sv))));
            sv = fmaf(bflo(v[j].z), bflo(v[j].z), fmaf(bfhi(v[j].z), bfhi(v[j].z), fmaf(bflo(v[j].w), bflo(v[j].w), fmaf(bfhi(v[j].w), bfhi(v[j].w), sv))));
          }
        }
#pragma unroll
        for (int o = 16; o; o >>= 1) sv += __shfl_xor_sync(~0u, sv, o);
        if (lane == 0) atomicAdd((float*)(g_zero + Z_NORM + layer), sv);
      }
      if (layer == 1 && PF_LB) {
        const int l = blockIdx.x * 96 + t;
        if (l < 6720 + NLB * 640) asm volatile("prefetch.global.L2 [%0];" :: "l"(l < 6720 ? g_w2 + l * 128 : (const uint8_t*)g_x + (l - 6720) * 128));
      }
#pragma unroll 1
      for (int k = (layer && !RD1) ? 0 : 5 * PF_IL; k < 5 * (layer ? PF_N1 : PF_N0); k++) {
        const int m = k / 5;
        const bf16* W = m == 0 ? Wq : m == 1 ? Wk : m == 2 ? Wv : Wo;
        asm volatile("prefetch.global.L2 [%0];" :: "l"((const uint8_t*)W + blockIdx.x * 61440 + (k - m * 5) * 12288 + t * 128));
        __nanosleep(layer ? PF_SLEEP1 : PF_SLEEP);
      }
      if (t == 0) GTT(layer * 4, 14);
      bar_arrive<3, 352>();
    }
  } else {
    asm volatile("setmaxnreg.inc.sync.aligned.u32 232;");
    GT(layer * 4, 4);
    uint32_t pq[5][4];
    float* kv = (float*)(g_zero + Z_KV) + layer * KV_LAYER + hg * 1920;
    {
      float d[120];
#pragma unroll 1
      for (int kc = 0; kc < 10; kc++) {
        const int st = kc & 3;
        const uint64_t da = mkdesc(SB0 + st * L_STAGE + wg * 8192, 16, 1024, 1), db = mkdesc(SB0 + st * L_STAGE + 16384, 3840, 128, 0);
        mbar_wait(bar + 8 * st, (kc >> 2) & 1);
        wg_fence();
#pragma unroll
        for (int k = 0; k < 4; k++) wg_ss_n240_ta0_tb1(d, da + 2 * k, db + k * 480, kc | k);
        wg_commit();
        if (kc > 0) { wg_wait<1>(); if (lane < 2) mbar_arrive_cl(mapa(bar + 8 * (4 + ((kc - 1) & 3)), lane)); }
      }
      wg_wait<0>();
      pin<120>(d);
      GT(layer * 4, 5);
      bar_sync<1, 256>();
      const uint32_t kb = sb + L_KV + (wg * 8 + 2 * w + ((lane >> 3) & 1)) * 2688 + (lane >> 4) * 128 + (lane & 7) * 16;
#pragma unroll
      for (int j = 0; j < 5; j++) stsm4(kb + 1280 + j * 256, pack2(d[80 + 8 * j], d[81 + 8 * j]), pack2(d[82 + 8 * j], d[83 + 8 * j]), pack2(d[84 + 8 * j], d[85 + 8 * j]), pack2(d[86 + 8 * j], d[87 + 8 * j]));
      stsm2(kb + 2560, 0x3F803F80u, 0x3F803F80u);
#pragma unroll
      for (int j = 0; j < 5; j++) stsm4(kb + j * 256, phi2(d[40 + 8 * j], d[41 + 8 * j]), phi2(d[42 + 8 * j], d[43 + 8 * j]), phi2(d[44 + 8 * j], d[45 + 8 * j]), phi2(d[46 + 8 * j], d[47 + 8 * j]));
      fence_async();
      bar_sync<1, 256>();
      float e[44];
      {
        const uint64_t da = mkdesc(SB0 + L_KV + wg * 1024, 2688, 128, 0), db = mkdesc(SB0 + L_KV + 1280, 2688, 128, 0);
        wg_fence();
#pragma unroll
        for (int k = 0; k < 8; k++) wg_ss_n88_ta1_tb1(e, da + k * 336, db + k * 336, k);
        wg_commit();
        wg_wait<0>();
        pin<44>(e);
      }
#pragma unroll
      for (int h = 0; h < 2; h++) {
        const int row = wg * 64 + 16 * w + 8 * h + g;
        const int c = row < 80 ? 2 * i4 - (row / 20) * 20 : 100;
        float* dst = kv + row * 24 + c;
#pragma unroll
        for (int j = 0; j < 10; j++)
          asm volatile("{\n.reg .pred p;\nsetp.lt.u32 p, %3, 20;\n@p red.relaxed.gpu.global.add.v2.f32 [%0], {%1,%2};\n}" :: "l"(dst + 8 * j), "f"(e[4 * j + 2 * h]), "f"(e[4 * j + 2 * h + 1]), "r"(c + 8 * j) : "memory");
        asm volatile("{\n.reg .pred p;\nsetp.ne.u32 p, %2, 0;\n@p red.relaxed.gpu.global.add.f32 [%0], %1;\n}" :: "l"(kv + row * 24 + 20), "f"(e[40 + 2 * h]), "r"((int)(row < 80 && i4 == 0)) : "memory");
      }
      bar_sync<1, 256>();
      GT(layer * 4, 6);
      if (tid == 0) { red_release(flags + FL_KV + hg * 8, 1); }
      __syncwarp();
      pin<40>(d);
#pragma unroll
      for (int k = 0; k < 5; k++) {
        pq[k][0] = phi2(d[8 * k], d[8 * k + 1]); pq[k][1] = phi2(d[8 * k + 2], d[8 * k + 3]);
        pq[k][2] = phi2(d[8 * k + 4], d[8 * k + 5]); pq[k][3] = phi2(d[8 * k + 6], d[8 * k + 7]);
      }
    }
#pragma unroll 1
    for (int k = tid; k < 1600; k += 256) sts4(sb + L_B2 + k * 16, 0, 0, 0, 0);
    GT(layer * 4, 7);
    if (wid == 0) wait_flag(flags + FL_KV + hg * 8, 16);
    GT(layer * 4, 8);
    bar_sync<1, 256>();
    if (tid < 240) {
      const int dd = tid / 3, part = tid - dd * 3, n = (dd / 20) * 20 + 8 * part;
      const float4 v0 = __ldcg((const float4*)(kv + dd * 24 + 8 * part)), v1 = __ldcg((const float4*)(kv + dd * 24 + 8 * part + 4));
      const float z = __ldcg(kv + dd * 24 + 20);
      const uint32_t a = sb + L_B2 + (dd >> 3) * 2560 + (dd & 7) * 16, zz = pack2(z, z);
      const uint32_t a0 = a + (n >> 3) * 128 + (n & 7) * 2, a1 = a + ((n + 4) >> 3) * 128 + ((n + 4) & 7) * 2;
      sts2(a0, pack2(v0.x, v0.y), pack2(v0.z, v0.w)); sts2(a0 + 1280, zz, zz);
      if (part < 2) { sts2(a1, pack2(v1.x, v1.y), pack2(v1.z, v1.w)); sts2(a1 + 1280, zz, zz); }
    }
    fence_async();
    bar_sync<1, 256>();
    {
      float o[80];
      const uint64_t db = mkdesc(SB0 + L_B2, 2560, 128, 0);
      wg_fence();
#pragma unroll
      for (int k = 0; k < 5; k++) wg_rs_n160_tb1(o, pq[k], db + k * 320, k);
      wg_commit();
      wg_wait<0>();
      pin<80>(o);
      uint8_t* op = g_oa + (tb * 2 + wg) * 81920 + hg * 10240 + w * 256 + lane * 4;
#pragma unroll
      for (int j = 0; j < 20; j++) {
        const float inv = rcp(o[40 + 2 * j] + 1e-6f);
        *(uint32_t*)(op + (j >> 1) * 1024 + (j & 1) * 128) = pack2(o[2 * j] * inv, o[2 * j + 1] * inv);
      }
      GT(layer * 4, 9);
    }
    bar_sync<3, 352>();
    if (tid == 0) { red_release(flags + FL_O + tb * 8, 1); red_add(flags + FL_X, 1); }
    GT(layer * 4, 2);
    if (wid == 7) asm volatile("griddepcontrol.wait;" ::: "memory");
  }
}

__global__ void __launch_bounds__(256) prep_kernel(const bf16* __restrict__ x, const bf16* __restrict__ wqkv, const bf16* __restrict__ wo) {
  asm volatile("griddepcontrol.launch_dependents;");
  const int b = blockIdx.x, tid = threadIdx.x, lane = tid & 31;
  if (b < 160) GT(3, 0);
  if (b < 256) {
    const int row = b * 8 + (tid >> 5);
    float v[20], s = 0.f;
#pragma unroll
    for (int k = 0; k < 10; k++) { const uint32_t u = __ldg((const uint32_t*)(x + row * DM + k * 64 + lane * 2)); v[2 * k] = bflo(u); v[2 * k + 1] = bfhi(u); s += v[2 * k] + v[2 * k + 1]; }
#pragma unroll
    for (int o = 16; o; o >>= 1) s += __shfl_xor_sync(~0u, s, o);
    const float m = s * (1.f / DM);
    float q = 0.f;
#pragma unroll
    for (int k = 0; k < 20; k++) { v[k] -= m; q += v[k] * v[k]; }
#pragma unroll
    for (int o = 16; o; o >>= 1) q += __shfl_xor_sync(~0u, q, o);
    const float r = rsqrtf(q * (1.f / DM) + 1e-5f);
#pragma unroll
    for (int k = 0; k < 10; k++)
      *(uint32_t*)(g_xt + ((row >> 7) * 10 + k) * 16384 + (row & 127) * 128 + (((lane >> 2) ^ (row & 7)) << 4) + (lane & 3) * 4) = pack2(v[2 * k] * r, v[2 * k + 1] * r);
  } else if (b < 256 + 203) {
    uint4 v[4];
    const int u0 = (b - 256) * 1024 + tid;
#pragma unroll
    for (int it = 0; it < 4; it++) {
      const int u = u0 + it * 256, k8 = u & 7;
      const bf16* src;
      bool ok = true;
      if (b < 256 + 150) {
        const int nb = (u >> 3) % 30, kg = (u / 240) % 80, hg = u / 19200;
        src = wqkv + (kg * 8 + k8) * 1920 + (nb / 10) * 640 + hg * 80 + (nb % 10) * 8;
      } else {
        const int q = u - 153600, nb = (q >> 3) % 28, kg = (q / 224) % 80, c = (q / 17920) * 224 + nb * 8;
        ok = c < DM;
        src = wo + (kg * 8 + k8) * DM + (ok ? c : 0);
      }
      v[it] = __ldg((const uint4*)src);
      if (!ok) v[it] = make_uint4(0, 0, 0, 0);
    }
    uint8_t* dst = b < 256 + 150 ? g_w1 + u0 * 16 : g_w2 + (u0 - 153600) * 16;
#pragma unroll
    for (int it = 0; it < 4; it++) if (u0 + it * 256 < 207360) *(uint4*)(dst + it * 4096) = v[it];
  } else {
    const int t = (b - 459) * 256 + tid;
    for (int k = t; k < Z_END / 4; k += 16 * 256) ((uint4*)g_zero)[k] = make_uint4(0, 0, 0, 0);
    for (int k = t; k < 16 * DM; k += 16 * 256) { ((uint4*)g_acc)[k] = make_uint4(0, 0, 0, 0); ((uint4*)(g_acc + S_TOK * DM))[k] = make_uint4(0, 0, 0, 0); }
  }
  if (b < 160) GT(3, 2);
}

typedef CUresult (*EncodeFn)(CUtensorMap*, CUtensorMapDataType, cuuint32_t, void*, const cuuint64_t*, const cuuint64_t*, const cuuint32_t*,
                             const cuuint32_t*, CUtensorMapInterleave, CUtensorMapSwizzle, CUtensorMapL2promotion, CUtensorMapFloatOOBfill);
static void make_map(EncodeFn fn, CUtensorMap* m, const void* p, uint64_t cols, uint64_t rows, uint32_t bc, uint32_t br, CUtensorMapSwizzle sw) {
  cuuint64_t dims[2] = {cols, rows}; cuuint64_t strides[1] = {cols * 2}; cuuint32_t box[2] = {bc, br}; cuuint32_t es[2] = {1, 1};
  fn(m, CU_TENSOR_MAP_DATA_TYPE_BFLOAT16, 2, (void*)p, dims, strides, box, es, CU_TENSOR_MAP_INTERLEAVE_NONE, sw,
     CU_TENSOR_MAP_L2_PROMOTION_L2_128B, CU_TENSOR_MAP_FLOAT_OOB_FILL_NONE);
}

static void make_map_perm(EncodeFn fn, CUtensorMap* m, const void* p) {
  cuuint64_t dims[5] = {HE, 2, 2, 4, 40}; const cuuint64_t r = HE * 2; cuuint64_t strides[4] = {r, 8 * r, 2 * r, 16 * r};
  cuuint32_t box[5] = {64, 2, 2, 4, 4}; cuuint32_t es[5] = {1, 1, 1, 1, 1};
  fn(m, CU_TENSOR_MAP_DATA_TYPE_BFLOAT16, 5, (void*)p, dims, strides, box, es, CU_TENSOR_MAP_INTERLEAVE_NONE, CU_TENSOR_MAP_SWIZZLE_128B,
     CU_TENSOR_MAP_L2_PROMOTION_L2_128B, CU_TENSOR_MAP_FLOAT_OOB_FILL_NONE);
}

#define OPC_PDL 1
#define LA_PDL 1
#define REC_PDL 1
extern "C" void kernel_launch(void* const* d_in, const int* in_sizes, int n_in, void* d_out, int out_size) {
  const bf16* x = (const bf16*)d_in[0];
  const bf16* wqkv = (const bf16*)d_in[1];
  const bf16* wo_a = (const bf16*)d_in[2];
  const bf16* mem0 = (const bf16*)d_in[4];
  const bf16* Wq = (const bf16*)d_in[5];
  const bf16* Wk = (const bf16*)d_in[6];
  const bf16* Wv = (const bf16*)d_in[7];
  const bf16* Wo = (const bf16*)d_in[8];
  cudaStream_t st = cudaStreamPerThread;

  static EncodeFn enc = nullptr;
  static uint8_t* p_ar; static uint32_t* p_zero; static bf16* p_x;
  if (!enc) {
    cudaDriverEntryPointQueryResult qr;
    void* fn = nullptr;
    cudaGetDriverEntryPoint("cuTensorMapEncodeTiled", &fn, cudaEnableDefault, &qr);
    enc = (EncodeFn)fn;
    cudaFuncSetAttribute(rec_kernel, cudaFuncAttributeMaxDynamicSharedMemorySize, REC_SMEM);
    cudaFuncSetAttribute(opc_kernel, cudaFuncAttributeMaxDynamicSharedMemorySize, OPC_SMEM);
    cudaFuncSetAttribute(la_kernel, cudaFuncAttributeMaxDynamicSharedMemorySize, LA_SMEM);
    cudaGetSymbolAddress((void**)&p_ar, g_ar); p_ar = (uint8_t*)(((uintptr_t)p_ar + 32767) & ~(uintptr_t)32767);
    cudaGetSymbolAddress((void**)&p_zero, g_zero); cudaGetSymbolAddress((void**)&p_x, g_x);
  }
  CUtensorMap tmq, tmk, tmv, tmo, tmx[2];
  make_map_perm(enc, &tmq, Wq);
  make_map_perm(enc, &tmk, Wk);
  make_map_perm(enc, &tmv, Wv);
  make_map(enc, &tmo, Wo, DM, HE, 64, 64, CU_TENSOR_MAP_SWIZZLE_128B);
  make_map(enc, &tmx[0], x, DM, S_TOK, 232, 64, CU_TENSOR_MAP_SWIZZLE_NONE);
  make_map(enc, &tmx[1], p_x, DM, S_TOK, 232, 64, CU_TENSOR_MAP_SWIZZLE_NONE);

  cudaLaunchAttribute at[2];
  at[0].id = cudaLaunchAttributeProgrammaticStreamSerialization; at[0].val.programmaticStreamSerializationAllowed = 1;
  at[1].id = cudaLaunchAttributeClusterDimension; at[1].val.clusterDim.x = 3; at[1].val.clusterDim.y = 1; at[1].val.clusterDim.z = 1;
  cudaLaunchAttribute at2[2] = {at[1], at[0]};
  at2[0].val.clusterDim.x = 2;
  prep_kernel<<<475, 256, 0, st>>>(x, wqkv, wo_a);
  for (int l = 0; l < 2; l++) {
    cudaLaunchConfig_t cfg = {};
    cfg.blockDim = dim3(384); cfg.stream = st;
    cfg.gridDim = dim3(l == 0 ? 132 : 128); cfg.dynamicSmemBytes = LA_SMEM; cfg.attrs = at2; cfg.numAttrs = 1 + LA_PDL;
    cudaLaunchKernelEx(&cfg, la_kernel, Wq, Wk, Wv, Wo, p_ar + l * AR_LAYER, l);
    cfg.gridDim = dim3(96 + 3 * NLB); cfg.dynamicSmemBytes = REC_SMEM; cfg.attrs = at + 1 - REC_PDL; cfg.numAttrs = 1 + REC_PDL;
    cudaLaunchKernelEx(&cfg, rec_kernel, tmq, tmk, tmv, tmo, tmx[l], mem0, p_ar + l * AR_LAYER, p_zero + Z_FLAGS + l * FL_LAYER, l);
    cfg.gridDim = dim3(36); cfg.dynamicSmemBytes = OPC_SMEM; cfg.attrs = at; cfg.numAttrs = OPC_PDL;
    cudaLaunchKernelEx(&cfg, opc_kernel, tmo, l == 1 ? (bf16*)d_out : (bf16*)nullptr, l, Wq, Wk, Wv, Wo);
  }
}
```

```cpp
#include <cuda_runtime.h>
#include <cuda_bf16.h>
#include <cuda.h>
#include <stdint.h>

typedef __nv_bfloat16 bf16;
typedef unsigned long long u64;

constexpr int S_TOK = 2048, DM = 640, DH = 192, HE = 6144, NSEG = 64;

constexpr int AR_GROUP = 98304;
constexpr int AR_LAYER = 16 * AR_GROUP;
__device__ __align__(1024) uint8_t g_ar[2 * AR_LAYER + 32768];
__device__ __align__(1024) uint8_t g_xn[NSEG * 40960];
__device__ __align__(1024) uint8_t g_xt[S_TOK * DM * 2];
__device__ __align__(1024) uint8_t g_ot[NSEG * HE * 64];
__device__ __align__(1024) uint8_t g_oa[S_TOK * DM * 2];
__device__ __align__(1024) uint8_t g_w1[DM * 1920 * 2];
__device__ __align__(1024) uint8_t g_w2[DM * 672 * 2];
__device__ __align__(1024) float g_acc[2 * S_TOK * DM];
__device__ __align__(1024) bf16 g_x[S_TOK * DM];
constexpr int FL_A = 0, FL_B = 64 * 6 * 8, FL_KV = FL_B + 64 * 8, FL_O = FL_KV + 8 * 8, FL_T = FL_O + 16 * 8, FL_X = FL_T + 16 * 8, FL_N = FL_X + 8, FL_R = FL_N + 8, FL_XN = FL_R + 8, FL_LAYER = FL_XN + 32 * 8;
constexpr int Z_FLAGS = 0, Z_NORM = 2 * FL_LAYER, Z_KV = Z_NORM + 8, KV_LAYER = 8 * 80 * 24, Z_END = Z_KV + 2 * KV_LAYER;
__device__ __align__(128) uint32_t g_zero[Z_END];
__device__ __align__(128) float g_nrm[4 * DM];
#define GT(slot, k) do {} while (0)
#define GTT(slot, k) do {} while (0)

__device__ __forceinline__ uint32_t smem_u32(const void* p) { return (uint32_t)__cvta_generic_to_shared(p); }
__device__ __forceinline__ uint32_t mapa(uint32_t a, uint32_t r) { uint32_t o; asm("mapa.shared::cluster.u32 %0, %1, %2;" : "=r"(o) : "r"(a), "r"(r)); return o; }
__device__ __forceinline__ void mbar_init(uint32_t bar, uint32_t cnt) { asm volatile("mbarrier.init.shared::cta.b64 [%0], %1;" :: "r"(bar), "r"(cnt) : "memory"); }
__device__ __forceinline__ void mbar_expect(uint32_t bar, uint32_t tx) { asm volatile("mbarrier.arrive.expect_tx.shared::cta.b64 _, [%0], %1;" :: "r"(bar), "r"(tx) : "memory"); }
__device__ __forceinline__ void mbar_arrive(uint32_t bar) { asm volatile("mbarrier.arrive.shared::cta.b64 _, [%0];" :: "r"(bar) : "memory"); }
__device__ __forceinline__ void mbar_wait(uint32_t bar, uint32_t par) {
  asm volatile("{\n.reg .pred p;\n.reg .u32 c;\nmov.u32 c, 0;\n"
               "LW:\nmbarrier.try_wait.parity.shared::cta.b64 p, [%0], %1;\n@p bra LD;\n"
               "add.u32 c, c, 1;\nsetp.lt.u32 p, c, 4000000;\n@p bra LW;\ntrap;\nLD:\n}" :: "r"(bar), "r"(par) : "memory");
}
__device__ __forceinline__ void mbar_waitf(uint32_t bar, uint32_t par) {
  asm volatile("{\n.reg .pred p, q;\n.reg .u32 c;\nmov.u32 c, 0;\n"
               "LW:\nadd.u32 c, c, 1;\nsetp.lt.u32 q, c, 1000000;\nmbarrier.try_wait.parity.shared::cta.b64 p, [%0], %1;\n"
               "and.pred q, q, !p;\n@q bra LW;\n}" :: "r"(bar), "r"(par) : "memory");
}
template <int ID, int N> __device__ __forceinline__ void bar_sync() { asm volatile("barrier.sync %0, %1;" :: "n"(ID), "n"(N) : "memory"); }
template <int ID, int N> __device__ __forceinline__ void bar_arrive() { asm volatile("barrier.arrive %0, %1;" :: "n"(ID), "n"(N) : "memory"); }
__device__ __forceinline__ void fence_async() { asm volatile("fence.proxy.async.shared::cta;" ::: "memory"); }
__device__ __forceinline__ void cluster_sync() { asm volatile("barrier.cluster.arrive.aligned;\nbarrier.cluster.wait.aligned;" ::: "memory"); }
__device__ __forceinline__ void wg_fence() { asm volatile("wgmma.fence.sync.aligned;" ::: "memory"); }
__device__ __forceinline__ void wg_commit() { asm volatile("wgmma.commit_group.sync.aligned;" ::: "memory"); }
template <int N> __device__ __forceinline__ void wg_wait() { asm volatile("wgmma.wait_group.sync.aligned %0;" :: "n"(N) : "memory"); }
template <int N> __device__ __forceinline__ void pin(float* d) {
#pragma unroll
  for (int i = 0; i < N; i++) asm volatile("" : "+f"(d[i]) :: "memory");
}
__device__ __forceinline__ constexpr uint64_t mkdesc(uint32_t addr, uint32_t lbo, uint32_t sbo, int sw) {
  return (uint64_t)((addr & 0x3FFFF) >> 4) | ((uint64_t)(lbo >> 4) << 16) | ((uint64_t)(sbo >> 4) << 32) | ((uint64_t)sw << 62);
}
constexpr uint32_t SB0 = 1024;
__device__ __forceinline__ void check_smem_base(uint32_t sb) { if ((sb & 0x3FFFF) != SB0) __trap(); }
__device__ __forceinline__ uint32_t cta_rank() { uint32_t r; asm volatile("mov.u32 %0, %%cluster_ctarank;" : "=r"(r)); return r; }
__device__ __forceinline__ uint32_t opaque(uint32_t v) { uint32_t o; asm volatile("mov.u32 %0, %1;" : "=r"(o) : "r"(v)); return o; }
__device__ __forceinline__ uint32_t pack2(float lo, float hi) { uint32_t r; asm("cvt.rn.bf16x2.f32 %0, %1, %2;" : "=r"(r) : "f"(hi), "f"(lo)); return r; }
__device__ __forceinline__ void ldsm4(uint32_t* r, uint32_t a) { asm volatile("ldmatrix.sync.aligned.m8n8.x4.shared.b16 {%0,%1,%2,%3}, [%4];" : "=r"(r[0]), "=r"(r[1]), "=r"(r[2]), "=r"(r[3]) : "r"(a) : "memory"); }
__device__ __forceinline__ void ldsm4t(uint32_t* r, uint32_t a) { asm volatile("ldmatrix.sync.aligned.m8n8.x4.trans.shared.b16 {%0,%1,%2,%3}, [%4];" : "=r"(r[0]), "=r"(r[1]), "=r"(r[2]), "=r"(r[3]) : "r"(a) : "memory"); }
__device__ __forceinline__ void ldsm1(uint32_t& r, uint32_t a) { asm volatile("ldmatrix.sync.aligned.m8n8.x1.shared.b16 {%0}, [%1];" : "=r"(r) : "r"(a) : "memory"); }
__device__ __forceinline__ void stsm4(uint32_t a, uint32_t r0, uint32_t r1, uint32_t r2, uint32_t r3) { asm volatile("stmatrix.sync.aligned.m8n8.x4.shared.b16 [%0], {%1,%2,%3,%4};" :: "r"(a), "r"(r0), "r"(r1), "r"(r2), "r"(r3) : "memory"); }
__device__ __forceinline__ void stsm1(uint32_t a, uint32_t r0) { asm volatile("stmatrix.sync.aligned.m8n8.x1.shared.b16 [%0], {%1};" :: "r"(a), "r"(r0) : "memory"); }
__device__ __forceinline__ void stsm4t(uint32_t a, uint32_t r0, uint32_t r1, uint32_t r2, uint32_t r3) { asm volatile("stmatrix.sync.aligned.m8n8.x4.trans.shared.b16 [%0], {%1,%2,%3,%4};" :: "r"(a), "r"(r0), "r"(r1), "r"(r2), "r"(r3) : "memory"); }
__device__ __forceinline__ void stsm2t(uint32_t a, uint32_t r0, uint32_t r1) { asm volatile("stmatrix.sync.aligned.m8n8.x2.trans.shared.b16 [%0], {%1,%2};" :: "r"(a), "r"(r0), "r"(r1) : "memory"); }
__device__ __forceinline__ void mma16816(float* c, const uint32_t* a, uint32_t b0, uint32_t b1) {
  asm volatile("mma.sync.aligned.m16n8k16.row.col.f32.bf16.bf16.f32 {%0,%1,%2,%3}, {%4,%5,%6,%7}, {%8,%9}, {%0,%1,%2,%3};"
               : "+f"(c[0]), "+f"(c[1]), "+f"(c[2]), "+f"(c[3]) : "r"(a[0]), "r"(a[1]), "r"(a[2]), "r"(a[3]), "r"(b0), "r"(b1));
}
__device__ __forceinline__ void mma1688(float* c, uint32_t a0, uint32_t a1, uint32_t b0) {
  asm volatile("mma.sync.aligned.m16n8k8.row.col.f32.bf16.bf16.f32 {%0,%1,%2,%3}, {%4,%5}, {%6}, {%0,%1,%2,%3};"
               : "+f"(c[0]), "+f"(c[1]), "+f"(c[2]), "+f"(c[3]) : "r"(a0), "r"(a1), "r"(b0));
}
__device__ __forceinline__ void sta1(uint32_t a, uint32_t v, uint32_t bar) { asm volatile("st.async.weak.shared::cluster.mbarrier::complete_tx::bytes.b32 [%0], %1, [%2];" :: "r"(a), "r"(v), "r"(bar) : "memory"); }
__device__ __forceinline__ void sta1p(uint32_t a, uint32_t v, uint32_t bar, bool p) { asm volatile("{\n.reg .pred p;\nsetp.ne.b32 p, %3, 0;\n@p st.async.weak.shared::cluster.mbarrier::complete_tx::bytes.b32 [%0], %1, [%2];\n}" :: "r"(a), "r"(v), "r"(bar), "r"((int)p) : "memory"); }
__device__ __forceinline__ void sta2(uint32_t a, uint32_t v0, uint32_t v1, uint32_t bar) { asm volatile("st.async.weak.shared::cluster.mbarrier::complete_tx::bytes.v2.b32 [%0], {%1,%2}, [%3];" :: "r"(a), "r"(v0), "r"(v1), "r"(bar) : "memory"); }
__device__ __forceinline__ void sta4(uint32_t a, uint32_t v0, uint32_t v1, uint32_t v2, uint32_t v3, uint32_t bar) { asm volatile("st.async.weak.shared::cluster.mbarrier::complete_tx::bytes.v4.b32 [%0], {%1,%2,%3,%4}, [%5];" :: "r"(a), "r"(v0), "r"(v1), "r"(v2), "r"(v3), "r"(bar) : "memory"); }
__device__ __forceinline__ float bflo(uint32_t v) { return __uint_as_float(v << 16); }
__device__ __forceinline__ float bfhi(uint32_t v) { return __uint_as_float(v & 0xFFFF0000u); }
__device__ __forceinline__ void sta2f(uint32_t a, float v0, float v1, uint32_t bar) { asm volatile("st.async.weak.shared::cluster.mbarrier::complete_tx::bytes.v2.f32 [%0], {%1,%2}, [%3];" :: "r"(a), "f"(v0), "f"(v1), "r"(bar) : "memory"); }
__device__ __forceinline__ void sta4f(uint32_t a, float v0, float v1, float v2, float v3, uint32_t bar) { asm volatile("st.async.weak.shared::cluster.mbarrier::complete_tx::bytes.v4.f32 [%0], {%1,%2,%3,%4}, [%5];" :: "r"(a), "f"(v0), "f"(v1), "f"(v2), "f"(v3), "r"(bar) : "memory"); }
__device__ __forceinline__ float4 lds4f(uint32_t a) { float4 v; asm volatile("ld.shared.v4.f32 {%0,%1,%2,%3}, [%4];" : "=f"(v.x), "=f"(v.y), "=f"(v.z), "=f"(v.w) : "r"(a) : "memory"); return v; }
__device__ __forceinline__ float2 lds2f(uint32_t a) { float2 v; asm volatile("ld.shared.v2.f32 {%0,%1}, [%2];" : "=f"(v.x), "=f"(v.y) : "r"(a) : "memory"); return v; }
__device__ __forceinline__ uint4 lds4(uint32_t a) { uint4 v; asm volatile("ld.shared.v4.u32 {%0,%1,%2,%3}, [%4];" : "=r"(v.x), "=r"(v.y), "=r"(v.z), "=r"(v.w) : "r"(a) : "memory"); return v; }
__device__ __forceinline__ uint32_t lds1(uint32_t a) { uint32_t v; asm volatile("ld.shared.u32 %0, [%1];" : "=r"(v) : "r"(a) : "memory"); return v; }
__device__ __forceinline__ void stsm2(uint32_t a, uint32_t r0, uint32_t r1) { asm volatile("stmatrix.sync.aligned.m8n8.x2.shared.b16 [%0], {%1,%2};" :: "r"(a), "r"(r0), "r"(r1) : "memory"); }
__device__ __forceinline__ float rcp(float x) { float y; asm("rcp.approx.ftz.f32 %0, %1;" : "=f"(y) : "f"(x)); return y; }
__device__ __forceinline__ void sts4(uint32_t a, uint32_t v0, uint32_t v1, uint32_t v2, uint32_t v3) { asm volatile("st.shared.v4.u32 [%0], {%1,%2,%3,%4};" :: "r"(a), "r"(v0), "r"(v1), "r"(v2), "r"(v3) : "memory"); }
__device__ __forceinline__ void bulk_s2c(uint32_t dst, uint32_t src, uint32_t bytes, uint32_t bar) {
  asm volatile("cp.async.bulk.shared::cluster.shared::cta.mbarrier::complete_tx::bytes [%0], [%1], %2, [%3];" :: "r"(dst), "r"(src), "r"(bytes), "r"(bar) : "memory");
}
__device__ __forceinline__ void stg4(void* p, uint4 v) { asm volatile("st.global.v4.u32 [%0], {%1,%2,%3,%4};" :: "l"(p), "r"(v.x), "r"(v.y), "r"(v.z), "r"(v.w) : "memory"); }
__device__ __forceinline__ void red_add(uint32_t* p, uint32_t v) { asm volatile("red.relaxed.gpu.global.add.u32 [%0], %1;" :: "l"(p), "r"(v) : "memory"); }
__device__ __forceinline__ void red_release(uint32_t* p, uint32_t v) { asm volatile("red.release.gpu.global.add.u32 [%0], %1;" :: "l"(p), "r"(v) : "memory"); }
__device__ __forceinline__ void fence_async_global() { asm volatile("fence.proxy.async.global;" ::: "memory"); }
__device__ __forceinline__ uint64_t policy_evict_first() { uint64_t p; asm("createpolicy.fractional.L2::evict_first.b64 %0, 1.0;" : "=l"(p)); return p; }
__device__ __forceinline__ void stg4h(void* p, uint4 v, uint64_t pol) { asm volatile("st.global.L2::cache_hint.v4.u32 [%0], {%1,%2,%3,%4}, %5;" :: "l"(p), "r"(v.x), "r"(v.y), "r"(v.z), "r"(v.w), "l"(pol) : "memory"); }
__device__ __forceinline__ void red4fh(float* p, float a, float b, float c, float d, uint64_t pol) { asm volatile("red.relaxed.gpu.global.add.L2::cache_hint.v4.f32 [%0], {%1,%2,%3,%4}, %5;" :: "l"(p), "f"(a), "f"(b), "f"(c), "f"(d), "l"(pol) : "memory"); }
__device__ __forceinline__ float4 ldg4fh(const float* p, uint64_t pol) { float4 v; asm volatile("ld.global.cg.L2::cache_hint.v4.f32 {%0,%1,%2,%3}, [%4], %5;" : "=f"(v.x), "=f"(v.y), "=f"(v.z), "=f"(v.w) : "l"(p), "l"(pol) : "memory"); return v; }
__device__ __forceinline__ void bulk_g2sh(uint32_t dst, const void* src, uint32_t bytes, uint32_t bar, uint64_t pol) {
  asm volatile("cp.async.bulk.shared::cluster.global.mbarrier::complete_tx::bytes.L2::cache_hint [%0], [%1], %2, [%3], %4;" :: "r"(dst), "l"(src), "r"(bytes), "r"(bar), "l"(pol) : "memory");
}
#define EVF 1
__device__ __forceinline__ void red4f(float* p, float a, float b, float c, float d) { asm volatile("red.relaxed.gpu.global.add.v4.f32 [%0], {%1,%2,%3,%4};" :: "l"(p), "f"(a), "f"(b), "f"(c), "f"(d) : "memory"); }
template <int SLEEP = 20>
__device__ __forceinline__ void wait_flag(const uint32_t* p, uint32_t target) {
  uint32_t v; int it = 0;
  while (true) {
    asm volatile("ld.acquire.gpu.global.u32 %0, [%1];" : "=r"(v) : "l"(p) : "memory");
    if (__all_sync(~0u, v >= target)) break;
    if (++it > 4000000) __trap();
    __nanosleep(SLEEP);
  }
}
__device__ __forceinline__ void sts2(uint32_t a, uint32_t v0, uint32_t v1) { asm volatile("st.shared.v2.u32 [%0], {%1,%2};" :: "r"(a), "r"(v0), "r"(v1) : "memory"); }
__device__ __forceinline__ float sqrt_approx(float x) { float y; asm("sqrt.approx.f32 %0, %1;" : "=f"(y) : "f"(x)); return y; }
template <int BYTES> __device__ __forceinline__ void bulk_s2c_elect(uint32_t d1, uint32_t b1, uint32_t d2, uint32_t b2, uint32_t src) {
  asm volatile("{\n.reg .pred p;\nelect.sync _|p, 0xffffffff;\n"
               "@p cp.async.bulk.shared::cluster.shared::cta.mbarrier::complete_tx::bytes [%0], [%4], %5, [%1];\n"
               "@p cp.async.bulk.shared::cluster.shared::cta.mbarrier::complete_tx::bytes [%2], [%4], %5, [%3];\n}"
               :: "r"(d1), "r"(b1), "r"(d2), "r"(b2), "r"(src), "n"(BYTES) : "memory");
}
template <int BYTES> __device__ __forceinline__ void bulk_s2c_elect1(uint32_t d, uint32_t b, uint32_t src) {
  asm volatile("{\n.reg .pred p;\nelect.sync _|p, 0xffffffff;\n"
               "@p cp.async.bulk.shared::cluster.shared::cta.mbarrier::complete_tx::bytes [%0], [%2], %3, [%1];\n}" :: "r"(d), "r"(b), "r"(src), "n"(BYTES) : "memory");
}
template <int BYTES> __device__ __forceinline__ void bulk_g2s_elect(uint32_t d, const void* src, uint32_t b) {
  asm volatile("{\n.reg .pred p;\nelect.sync _|p, 0xffffffff;\n"
               "@p cp.async.bulk.shared::cluster.global.mbarrier::complete_tx::bytes [%0], [%1], %3, [%2];\n}" :: "r"(d), "l"(src), "r"(b), "n"(BYTES) : "memory");
}
__device__ __forceinline__ void mbar_arrive_elect(uint32_t bar) { asm volatile("{\n.reg .pred p;\nelect.sync _|p, 0xffffffff;\n@p mbarrier.arrive.shared::cta.b64 _, [%0];\n}" :: "r"(bar) : "memory"); }
__device__ __forceinline__ void cp16(uint32_t dst, const void* src) { asm volatile("cp.async.cg.shared.global [%0], [%1], 16;" :: "r"(dst), "l"(src) : "memory"); }
__device__ __forceinline__ void sts1(uint32_t a, uint32_t v) { asm volatile("st.shared.u32 [%0], %1;" :: "r"(a), "r"(v) : "memory"); }
__device__ __forceinline__ void bulk_g2s(uint32_t dst, const void* src, uint32_t bytes, uint32_t bar) {
  asm volatile("cp.async.bulk.shared::cluster.global.mbarrier::complete_tx::bytes [%0], [%1], %2, [%3];" :: "r"(dst), "l"(src), "r"(bytes), "r"(bar) : "memory");
}
__device__ __forceinline__ void bulk_g2s_mc(uint32_t dst, const void* src, uint32_t bytes, uint32_t bar) {
  asm volatile("cp.async.bulk.shared::cluster.global.mbarrier::complete_tx::bytes.multicast::cluster [%0], [%1], %2, [%3], %4;" :: "r"(dst), "l"(src), "r"(bytes), "r"(bar), "h"((uint16_t)3) : "memory");
}
__device__ __forceinline__ void mbar_arrive_cl(uint32_t bar) { asm volatile("mbarrier.arrive.shared::cluster.b64 _, [%0];" :: "r"(bar) : "memory"); }
__device__ __forceinline__ void mbar_arrive_clp(uint32_t bar, bool p) { asm volatile("{\n.reg .pred p;\nsetp.ne.b32 p, %1, 0;\n@p mbarrier.arrive.shared::cluster.b64 _, [%0];\n}" :: "r"(bar), "r"((int)p) : "memory"); }
__device__ __forceinline__ void tma2d(uint32_t dst, const CUtensorMap* m, int c0, int c1, uint32_t bar) {
  asm volatile("cp.async.bulk.tensor.2d.shared::cluster.global.mbarrier::complete_tx::bytes [%0], [%1, {%3, %4}], [%2];" :: "r"(dst), "l"((uint64_t)m), "r"(bar), "r"(c0), "r"(c1) : "memory");
}
__device__ __forceinline__ void tma5d(uint32_t dst, const CUtensorMap* m, int c0, int c4, uint32_t bar) {
  asm volatile("cp.async.bulk.tensor.5d.shared::cluster.global.mbarrier::complete_tx::bytes [%0], [%1, {%3, %5, %5, %5, %4}], [%2];" :: "r"(dst), "l"((uint64_t)m), "r"(bar), "r"(c0), "r"(c4), "r"(0) : "memory");
}
__device__ __forceinline__ void red64(void* p, uint32_t lo, uint32_t hi) { asm volatile("{\n.reg .b64 t;\nmov.b64 t, {%1,%2};\nred.relaxed.gpu.global.add.u64 [%0], t;\n}" :: "l"(p), "r"(lo), "r"(hi) : "memory"); }
__device__ __forceinline__ uint4 ld_poll(const void* p) {
  uint4 v;
  asm volatile("{\n.reg .b64 a, b;\nld.relaxed.gpu.global.v2.b64 {a, b}, [%4];\nmov.b64 {%0,%1}, a;\nmov.b64 {%2,%3}, b;\n}" : "=r"(v.x), "=r"(v.y), "=r"(v.z), "=r"(v.w) : "l"(p) : "memory");
  return v;
}
__device__ __forceinline__ uint32_t clk() { uint32_t c; asm volatile("mov.u32 %0, %%clock;" : "=r"(c) :: "memory"); return c; }
#define SCHED_FENCE() asm volatile("pmevent 0;" ::: "memory")
__device__ __forceinline__ float ex2(float x) { float y; asm("ex2.approx.ftz.f32 %0, %1;" : "=f"(y) : "f"(x)); return y; }

__device__ __forceinline__ void wg_ss_n240_ta0_tb1(float* d, uint64_t a, uint64_t b, int sc) {
  asm volatile("{\n.reg .pred p;\nsetp.ne.b32 p, %122, 0;\nwgmma.mma_async.sync.aligned.m64n240k16.f32.bf16.bf16 {%0, %1, %2, %3, %4, %5, %6, %7, %8, %9, %10, %11, %12, %13, %14, %15, %16, %17, %18, %19, %20, %21, %22, %23, %24, %25, %26, %27, %28, %29, %30, %31, %32, %33, %34, %35, %36, %37, %38, %39, %40, %41, %42, %43, %44, %45, %46, %47, %48, %49, %50, %51, %52, %53, %54, %55, %56, %57, %58, %59, %60, %61, %62, %63, %64, %65, %66, %67, %68, %69, %70, %71, %72, %73, %74, %75, %76, %77, %78, %79, %80, %81, %82, %83, %84, %85, %86, %87, %88, %89, %90, %91, %92, %93, %94, %95, %96, %97, %98, %99, %100, %101, %102, %103, %104, %105, %106, %107, %108, %109, %110, %111, %112, %113, %114, %115, %116, %117, %118, %119}, %120, %121, p, 1, 1, 0, 1;\n}\n"
    : "+f"(d[0]), "+f"(d[1]), "+f"(d[2]), "+f"(d[3]), "+f"(d[4]), "+f"(d[5]), "+f"(d[6]), "+f"(d[7]), "+f"(d[8]), "+f"(d[9]), "+f"(d[10]), "+f"(d[11]), "+f"(d[12]), "+f"(d[13]), "+f"(d[14]), "+f"(d[15]), "+f"(d[16]), "+f"(d[17]), "+f"(d[18]), "+f"(d[19]), "+f"(d[20]), "+f"(d[21]), "+f"(d[22]), "+f"(d[23]), "+f"(d[24]), "+f"(d[25]), "+f"(d[26]), "+f"(d[27]), "+f"(d[28]), "+f"(d[29]), "+f"(d[30]), "+f"(d[31]), "+f"(d[32]), "+f"(d[33]), "+f"(d[34]), "+f"(d[35]), "+f"(d[36]), "+f"(d[37]), "+f"(d[38]), "+f"(d[39]), "+f"(d[40]), "+f"(d[41]), "+f"(d[42]), "+f"(d[43]), "+f"(d[44]), "+f"(d[45]), "+f"(d[46]), "+f"(d[47]), "+f"(d[48]), "+f"(d[49]), "+f"(d[50]), "+f"(d[51]), "+f"(d[52]), "+f"(d[53]), "+f"(d[54]), "+f"(d[55]), "+f"(d[56]), "+f"(d[57]), "+f"(d[58]), "+f"(d[59]), "+f"(d[60]), "+f"(d[61]), "+f"(d[62]), "+f"(d[63]), "+f"(d[64]), "+f"(d[65]), "+f"(d[66]), "+f"(d[67]), "+f"(d[68]), "+f"(d[69]), "+f"(d[70]), "+f"(d[71]), "+f"(d[72]), "+f"(d[73]), "+f"(d[74]), "+f"(d[75]), "+f"(d[76]), "+f"(d[77]), "+f"(d[78]), "+f"(d[79]), "+f"(d[80]), "+f"(d[81]), "+f"(d[82]), "+f"(d[83]), "+f"(d[84]), "+f"(d[85]), "+f"(d[86]), "+f"(d[87]), "+f"(d[88]), "+f"(d[89]), "+f"(d[90]), "+f"(d[91]), "+f"(d[92]), "+f"(d[93]), "+f"(d[94]), "+f"(d[95]), "+f"(d[96]), "+f"(d[97]), "+f"(d[98]), "+f"(d[99]), "+f"(d[100]), "+f"(d[101]), "+f"(d[102]), "+f"(d[103]), "+f"(d[104]), "+f"(d[105]), "+f"(d[106]), "+f"(d[107]), "+f"(d[108]), "+f"(d[109]), "+f"(d[110]), "+f"(d[111]), "+f"(d[112]), "+f"(d[113]), "+f"(d[114]), "+f"(d[115]), "+f"(d[116]), "+f"(d[117]), "+f"(d[118]), "+f"(d[119])
    : "l"(a), "l"(b), "r"(sc));
}
__device__ __forceinline__ void wg_ss_n88_ta1_tb1(float* d, uint64_t a, uint64_t b, int sc) {
  asm volatile("{\n.reg .pred p;\nsetp.ne.b32 p, %46, 0;\nwgmma.mma_async.sync.aligned.m64n88k16.f32.bf16.bf16 {%0, %1, %2, %3, %4, %5, %6, %7, %8, %9, %10, %11, %12, %13, %14, %15, %16, %17, %18, %19, %20, %21, %22, %23, %24, %25, %26, %27, %28, %29, %30, %31, %32, %33, %34, %35, %36, %37, %38, %39, %40, %41, %42, %43}, %44, %45, p, 1, 1, 1, 1;\n}\n"
    : "+f"(d[0]), "+f"(d[1]), "+f"(d[2]), "+f"(d[3]), "+f"(d[4]), "+f"(d[5]), "+f"(d[6]), "+f"(d[7]), "+f"(d[8]), "+f"(d[9]), "+f"(d[10]), "+f"(d[11]), "+f"(d[12]), "+f"(d[13]), "+f"(d[14]), "+f"(d[15]), "+f"(d[16]), "+f"(d[17]), "+f"(d[18]), "+f"(d[19]), "+f"(d[20]), "+f"(d[21]), "+f"(d[22]), "+f"(d[23]), "+f"(d[24]), "+f"(d[25]), "+f"(d[26]), "+f"(d[27]), "+f"(d[28]), "+f"(d[29]), "+f"(d[30]), "+f"(d[31]), "+f"(d[32]), "+f"(d[33]), "+f"(d[34]), "+f"(d[35]), "+f"(d[36]), "+f"(d[37]), "+f"(d[38]), "+f"(d[39]), "+f"(d[40]), "+f"(d[41]), "+f"(d[42]), "+f"(d[43])
    : "l"(a), "l"(b), "r"(sc));
}
__device__ __forceinline__ void wg_rs_n160_tb1(float* d, const uint32_t* a, uint64_t b, int sc) {
  asm volatile("{\n.reg .pred p;\nsetp.ne.b32 p, %85, 0;\nwgmma.mma_async.sync.aligned.m64n160k16.f32.bf16.bf16 {%0, %1, %2, %3, %4, %5, %6, %7, %8, %9, %10, %11, %12, %13, %14, %15, %16, %17, %18, %19, %20, %21, %22, %23, %24, %25, %26, %27, %28, %29, %30, %31, %32, %33, %34, %35, %36, %37, %38, %39, %40, %41, %42, %43, %44, %45, %46, %47, %48, %49, %50, %51, %52, %53, %54, %55, %56, %57, %58, %59, %60, %61, %62, %63, %64, %65, %66, %67, %68, %69, %70, %71, %72, %73, %74, %75, %76, %77, %78, %79}, {%80, %81, %82, %83}, %84, p, 1, 1, 1;\n}\n"
    : "+f"(d[0]), "+f"(d[1]), "+f"(d[2]), "+f"(d[3]), "+f"(d[4]), "+f"(d[5]), "+f"(d[6]), "+f"(d[7]), "+f"(d[8]), "+f"(d[9]), "+f"(d[10]), "+f"(d[11]), "+f"(d[12]), "+f"(d[13]), "+f"(d[14]), "+f"(d[15]), "+f"(d[16]), "+f"(d[17]), "+f"(d[18]), "+f"(d[19]), "+f"(d[20]), "+f"(d[21]), "+f"(d[22]), "+f"(d[23]), "+f"(d[24]), "+f"(d[25]), "+f"(d[26]), "+f"(d[27]), "+f"(d[28]), "+f"(d[29]), "+f"(d[30]), "+f"(d[31]), "+f"(d[32]), "+f"(d[33]), "+f"(d[34]), "+f"(d[35]), "+f"(d[36]), "+f"(d[37]), "+f"(d[38]), "+f"(d[39]), "+f"(d[40]), "+f"(d[41]), "+f"(d[42]), "+f"(d[43]), "+f"(d[44]), "+f"(d[45]), "+f"(d[46]), "+f"(d[47]), "+f"(d[48]), "+f"(d[49]), "+f"(d[50]), "+f"(d[51]), "+f"(d[52]), "+f"(d[53]), "+f"(d[54]), "+f"(d[55]), "+f"(d[56]), "+f"(d[57]), "+f"(d[58]), "+f"(d[59]), "+f"(d[60]), "+f"(d[61]), "+f"(d[62]), "+f"(d[63]), "+f"(d[64]), "+f"(d[65]), "+f"(d[66]), "+f"(d[67]), "+f"(d[68]), "+f"(d[69]), "+f"(d[70]), "+f"(d[71]), "+f"(d[72]), "+f"(d[73]), "+f"(d[74]), "+f"(d[75]), "+f"(d[76]), "+f"(d[77]), "+f"(d[78]), "+f"(d[79])
    : "r"(a[0]), "r"(a[1]), "r"(a[2]), "r"(a[3]), "l"(b), "r"(sc));
}
__device__ __forceinline__ void wg_ss_n112_ta0_tb1(float* d, uint64_t a, uint64_t b, int sc) {
  asm volatile("{\n.reg .pred p;\nsetp.ne.b32 p, %58, 0;\nwgmma.mma_async.sync.aligned.m64n112k16.f32.bf16.bf16 {%0, %1, %2, %3, %4, %5, %6, %7, %8, %9, %10, %11, %12, %13, %14, %15, %16, %17, %18, %19, %20, %21, %22, %23, %24, %25, %26, %27, %28, %29, %30, %31, %32, %33, %34, %35, %36, %37, %38, %39, %40, %41, %42, %43, %44, %45, %46, %47, %48, %49, %50, %51, %52, %53, %54, %55}, %56, %57, p, 1, 1, 0, 1;\n}\n"
    : "+f"(d[0]), "+f"(d[1]), "+f"(d[2]), "+f"(d[3]), "+f"(d[4]), "+f"(d[5]), "+f"(d[6]), "+f"(d[7]), "+f"(d[8]), "+f"(d[9]), "+f"(d[10]), "+f"(d[11]), "+f"(d[12]), "+f"(d[13]), "+f"(d[14]), "+f"(d[15]), "+f"(d[16]), "+f"(d[17]), "+f"(d[18]), "+f"(d[19]), "+f"(d[20]), "+f"(d[21]), "+f"(d[22]), "+f"(d[23]), "+f"(d[24]), "+f"(d[25]), "+f"(d[26]), "+f"(d[27]), "+f"(d[28]), "+f"(d[29]), "+f"(d[30]), "+f"(d[31]), "+f"(d[32]), "+f"(d[33]), "+f"(d[34]), "+f"(d[35]), "+f"(d[36]), "+f"(d[37]), "+f"(d[38]), "+f"(d[39]), "+f"(d[40]), "+f"(d[41]), "+f"(d[42]), "+f"(d[43]), "+f"(d[44]), "+f"(d[45]), "+f"(d[46]), "+f"(d[47]), "+f"(d[48]), "+f"(d[49]), "+f"(d[50]), "+f"(d[51]), "+f"(d[52]), "+f"(d[53]), "+f"(d[54]), "+f"(d[55])
    : "l"(a), "l"(b), "r"(sc));
}
__device__ __forceinline__ void wg_rs_n32_tb1(float* d, const uint32_t* a, uint64_t b, int sc) {
  asm volatile("{\n.reg .pred p;\nsetp.ne.b32 p, %21, 0;\nwgmma.mma_async.sync.aligned.m64n32k16.f32.bf16.bf16 {%0, %1, %2, %3, %4, %5, %6, %7, %8, %9, %10, %11, %12, %13, %14, %15}, {%16, %17, %18, %19}, %20, p, 1, 1, 1;\n}\n"
    : "+f"(d[0]), "+f"(d[1]), "+f"(d[2]), "+f"(d[3]), "+f"(d[4]), "+f"(d[5]), "+f"(d[6]), "+f"(d[7]), "+f"(d[8]), "+f"(d[9]), "+f"(d[10]), "+f"(d[11]), "+f"(d[12]), "+f"(d[13]), "+f"(d[14]), "+f"(d[15])
    : "r"(a[0]), "r"(a[1]), "r"(a[2]), "r"(a[3]), "l"(b), "r"(sc));
}
__device__ __forceinline__ void wg_ss_n32_ta1_tb1(float* d, uint64_t a, uint64_t b, int sc) {
  asm volatile("{\n.reg .pred p;\nsetp.ne.b32 p, %18, 0;\nwgmma.mma_async.sync.aligned.m64n32k16.f32.bf16.bf16 {%0, %1, %2, %3, %4, %5, %6, %7, %8, %9, %10, %11, %12, %13, %14, %15}, %16, %17, p, 1, 1, 1, 1;\n}\n"
    : "+f"(d[0]), "+f"(d[1]), "+f"(d[2]), "+f"(d[3]), "+f"(d[4]), "+f"(d[5]), "+f"(d[6]), "+f"(d[7]), "+f"(d[8]), "+f"(d[9]), "+f"(d[10]), "+f"(d[11]), "+f"(d[12]), "+f"(d[13]), "+f"(d[14]), "+f"(d[15])
    : "l"(a), "l"(b), "r"(sc));
}
__device__ __forceinline__ void wg_rs_n32_tb0(float* d, const uint32_t* a, uint64_t b, int sc) {
  asm volatile("{\n.reg .pred p;\nsetp.ne.b32 p, %21, 0;\nwgmma.mma_async.sync.aligned.m64n32k16.f32.bf16.bf16 {%0, %1, %2, %3, %4, %5, %6, %7, %8, %9, %10, %11, %12, %13, %14, %15}, {%16, %17, %18, %19}, %20, p, 1, 1, 0;\n}\n"
    : "+f"(d[0]), "+f"(d[1]), "+f"(d[2]), "+f"(d[3]), "+f"(d[4]), "+f"(d[5]), "+f"(d[6]), "+f"(d[7]), "+f"(d[8]), "+f"(d[9]), "+f"(d[10]), "+f"(d[11]), "+f"(d[12]), "+f"(d[13]), "+f"(d[14]), "+f"(d[15])
    : "r"(a[0]), "r"(a[1]), "r"(a[2]), "r"(a[3]), "l"(b), "r"(sc));
}
__device__ __forceinline__ void wg_rs_n40_tb0(float* d, const uint32_t* a, uint64_t b, int sc) {
  asm volatile("{\n.reg .pred p;\nsetp.ne.b32 p, %25, 0;\nwgmma.mma_async.sync.aligned.m64n40k16.f32.bf16.bf16 {%0, %1, %2, %3, %4, %5, %6, %7, %8, %9, %10, %11, %12, %13, %14, %15, %16, %17, %18, %19}, {%20, %21, %22, %23}, %24, p, 1, 1, 0;\n}\n"
    : "+f"(d[0]), "+f"(d[1]), "+f"(d[2]), "+f"(d[3]), "+f"(d[4]), "+f"(d[5]), "+f"(d[6]), "+f"(d[7]), "+f"(d[8]), "+f"(d[9]), "+f"(d[10]), "+f"(d[11]), "+f"(d[12]), "+f"(d[13]), "+f"(d[14]), "+f"(d[15]), "+f"(d[16]), "+f"(d[17]), "+f"(d[18]), "+f"(d[19])
    : "r"(a[0]), "r"(a[1]), "r"(a[2]), "r"(a[3]), "l"(b), "r"(sc));
}
__device__ __forceinline__ void wg_rs_n8_tb1(float* d, const uint32_t* a, uint64_t b, int sc) {
  asm volatile("{\n.reg .pred p;\nsetp.ne.b32 p, %9, 0;\nwgmma.mma_async.sync.aligned.m64n8k16.f32.bf16.bf16 {%0, %1, %2, %3}, {%4, %5, %6, %7}, %8, p, 1, 1, 1;\n}\n"
    : "+f"(d[0]), "+f"(d[1]), "+f"(d[2]), "+f"(d[3])
    : "r"(a[0]), "r"(a[1]), "r"(a[2]), "r"(a[3]), "l"(b), "r"(sc));
}
__device__ __forceinline__ void wg_ss_n40_ta0_tb0(float* d, uint64_t a, uint64_t b, int sc) {
  asm volatile("{\n.reg .pred p;\nsetp.ne.b32 p, %22, 0;\nwgmma.mma_async.sync.aligned.m64n40k16.f32.bf16.bf16 {%0, %1, %2, %3, %4, %5, %6, %7, %8, %9, %10, %11, %12, %13, %14, %15, %16, %17, %18, %19}, %20, %21, p, 1, 1, 0, 0;\n}\n"
    : "+f"(d[0]), "+f"(d[1]), "+f"(d[2]), "+f"(d[3]), "+f"(d[4]), "+f"(d[5]), "+f"(d[6]), "+f"(d[7]), "+f"(d[8]), "+f"(d[9]), "+f"(d[10]), "+f"(d[11]), "+f"(d[12]), "+f"(d[13]), "+f"(d[14]), "+f"(d[15]), "+f"(d[16]), "+f"(d[17]), "+f"(d[18]), "+f"(d[19])
    : "l"(a), "l"(b), "r"(sc));
}
__device__ __forceinline__ void wg_ss_n40_ta1_tb0(float* d, uint64_t a, uint64_t b, int sc) {
  asm volatile("{\n.reg .pred p;\nsetp.ne.b32 p, %22, 0;\nwgmma.mma_async.sync.aligned.m64n40k16.f32.bf16.bf16 {%0, %1, %2, %3, %4, %5, %6, %7, %8, %9, %10, %11, %12, %13, %14, %15, %16, %17, %18, %19}, %20, %21, p, 1, 1, 1, 0;\n}\n"
    : "+f"(d[0]), "+f"(d[1]), "+f"(d[2]), "+f"(d[3]), "+f"(d[4]), "+f"(d[5]), "+f"(d[6]), "+f"(d[7]), "+f"(d[8]), "+f"(d[9]), "+f"(d[10]), "+f"(d[11]), "+f"(d[12]), "+f"(d[13]), "+f"(d[14]), "+f"(d[15]), "+f"(d[16]), "+f"(d[17]), "+f"(d[18]), "+f"(d[19])
    : "l"(a), "l"(b), "r"(sc));
}
__device__ __forceinline__ void wg_ss_n8_ta1_tb1(float* d, uint64_t a, uint64_t b, int sc) {
  asm volatile("{\n.reg .pred p;\nsetp.ne.b32 p, %6, 0;\nwgmma.mma_async.sync.aligned.m64n8k16.f32.bf16.bf16 {%0, %1, %2, %3}, %4, %5, p, 1, 1, 1, 1;\n}\n"
    : "+f"(d[0]), "+f"(d[1]), "+f"(d[2]), "+f"(d[3])
    : "l"(a), "l"(b), "r"(sc));
}

constexpr int O_WV = 0, O_WO = 81920, O_H = 163840, O_QK = 215040, O_SM = 228352, O_MISC = 229632;
constexpr int O_QM = O_QK + 1024, O_K = O_QK + 3072, O_OG = O_QK + 8192;
constexpr int SM_SLOT = 640;
constexpr int O_MAXS = O_MISC;
constexpr int O_BAR = O_MISC + 64;
constexpr int MB_XF = 0, MB_ML = 2, MB_MR = 3, MB_PF = 4, MB_SM = 5, MB_SX = 6, MB_OG = 7, MB_W = 10, MB_WC = 30;
constexpr int O_PROF = O_BAR + 8 * 40;
constexpr int REC_SMEM = O_PROF + 128;
constexpr int B_VOWN = 0, B_QK = 1, B_OGO = 2, B_SISS = 3, B_PM = 4, B_PX = 5, B_XGO = 6, B_ML = 7, B_WG2 = 8, B_VHALF = 9, B_VDONE = 10,
              B_MR = 11, B_SSENT = 12, B_SLD = 13, B_VEND = 14, B_XGO1 = 15;
#define TS0(idx) do {} while (0)
#define TS(idx) do {} while (0)
#define POLL_9 300
#define POLL_A 400
#define POLL_B 500
#define POLL_C 600
#define W_WIN 4
#define W_OPEN 16
#define V_OWN 6
#define V_S1 7
#define V_RS 3
#define V_S2 1
#define V_B 5
#define V_K1 (V_OWN + V_RS + V_B + V_S1)
#define V_K2 ((V_K1 > 20 ? V_K1 : 20) + V_S2)
#define O_RSM 0x2AA0
#define PMW 0
#define OGB 0
#define O_B1 5
#define O_RS __builtin_popcount(O_RSM)
#define O_IDX(j) __builtin_popcount(O_RSM & ((1 << (j)) - 1))
constexpr float SCL = 0.07216878364870322f;
constexpr float SL2 = SCL * 1.4426950408889634f;
__device__ __forceinline__ constexpr int vord(int i) { return i < 4 ? 36 + i : i - 4; }
__device__ __forceinline__ constexpr uint32_t hoff(int k) { return ((k >> 2) * 5120 + (k & 3) * 32) >> 4; }
__device__ __forceinline__ constexpr int ar_chunk(int T) { return T == 9 ? 19 : (T % 3) * 8 + T / 3; }
__device__ __forceinline__ void fix_red(uint8_t* p, const float* a, float2 sc) {
  int v0 = __float2int_rn(a[0] * sc.x), v1 = __float2int_rn(a[1] * sc.y), v2 = __float2int_rn(a[2] * sc.x), v3 = __float2int_rn(a[3] * sc.y);
  red64(p, ((uint32_t)v0 << 7) | 1u, ((uint32_t)v2 << 3) + (uint32_t)(v0 >> 25));
  red64(p + 1024, ((uint32_t)v1 << 7) | 1u, ((uint32_t)v3 << 3) + (uint32_t)(v1 >> 25));
}
__device__ __forceinline__ float exp_row(float* t) {
  const float ml = fmaxf(fmaxf(fmaxf(fmaxf(t[0], t[1]), fmaxf(t[2], t[3])), fmaxf(fmaxf(t[4], t[5]), fmaxf(t[6], t[7]))), fmaxf(t[8], t[9]));
  const float m1 = __shfl_xor_sync(~0u, ml, 1), m2 = __shfl_xor_sync(~0u, ml, 2), m3 = __shfl_xor_sync(~0u, ml, 3);
  SCHED_FENCE();
#pragma unroll
  for (int k = 0; k < 10; k++) t[k] = ex2((t[k] - ml) * SL2);
  pin<10>(t);
  SCHED_FENCE();
  return ex2((ml - fmaxf(fmaxf(ml, m1), fmaxf(m2, m3))) * SL2);
}
#define ACC3(k, u, v) { t[k] += bflo(u) + bflo(v); t[k + 1] += bfhi(u) + bfhi(v); }

#define LBT 0
#define NLB 2
constexpr int LB_STAGE = 36864, LB_ST = 6 * LB_STAGE;
__device__ __forceinline__ void lb_role(const uint32_t sb, const CUtensorMap* tmx, uint32_t* __restrict__ flags, int layer) {
  const int tid = threadIdx.x, wid = __shfl_sync(~0u, tid >> 5, 0), wg = wid >> 2, w = wid & 3, lane = tid & 31, g = lane >> 2, i4 = lane & 3;
  const int cl = blockIdx.x / 3, rank = blockIdx.x - cl * 3;
  const uint32_t bar = sb + O_BAR;
  asm volatile("griddepcontrol.launch_dependents;");
  if (wid == 8) {
    if (lane < 14) mbar_init(bar + 8 * lane, lane >= 6 && lane < 12 ? 8 : 1);
    asm volatile("fence.mbarrier_init.release.cluster;" ::: "memory");
    fence_async();
  }
  __syncthreads();
  asm volatile("barrier.cluster.arrive.relaxed.aligned;" ::: "memory");
  if (wid == 8) {
    int st = 0; uint32_t ph = 1;
    const uint8_t* wsrc = g_w2 + rank * 286720;
    if (lane < 6) { mbar_expect(bar + 8 * lane, LB_STAGE); bulk_g2s(sb + lane * LB_STAGE + 8192, wsrc + lane * 28672, 28672, bar + 8 * lane); }
    if (layer == 1) wait_flag(flags + FL_R, 6);
#pragma unroll 1
    for (int tile = cl; tile < 32; tile += NLB) {
      wait_flag(flags + FL_O + (tile >> 1) * 8, 8);
      if (tile == cl + LBT * NLB && lane == 0) GTT(layer * 4 + 1, 11);
      fence_async_global();
#pragma unroll 1
      for (int kc = 0; kc < 10; kc++) {
        const bool pre = tile == cl && kc < 6;
        mbar_wait(bar + 8 * (6 + st), ph);
        if (lane == 0) {
          if (!pre) { mbar_expect(bar + 8 * st, LB_STAGE); bulk_g2s(sb + st * LB_STAGE + 8192, wsrc + kc * 28672, 28672, bar + 8 * st); }
          bulk_g2s(sb + st * LB_STAGE, g_oa + tile * 81920 + kc * 8192, 8192, bar + 8 * st);
        }
        __syncwarp();
        if (++st == 6) { st = 0; ph ^= 1; }
      }
      mbar_wait(bar + 8 * (6 + st), ph);
      if (lane == 0) { mbar_expect(bar + 8 * st, 64 * 464); tma2d(sb + st * LB_STAGE, tmx, rank * 224, tile * 64, bar + 8 * st); }
      __syncwarp();
      if (++st == 6) { st = 0; ph ^= 1; }
    }
    asm volatile("barrier.cluster.wait.aligned;" ::: "memory");
  } else if (wg < 2) {
    asm volatile("barrier.cluster.wait.aligned;" ::: "memory");
    const int u = 2 * rank + wg, nb = u == 5 ? 5 : 7;
    int st = 0; uint32_t ph = 0, it = 0;
#pragma unroll 1
    for (int tile = cl; tile < 32; tile += NLB, it++) {
      const int row0 = tile * 64 + 16 * w + g;
      float d[56];
      if (tid == 0) mbar_expect(bar + 8 * (12 + (it & 1)), 3072);
#pragma unroll 1
      for (int kc = 0; kc < 10; kc++) {
        const uint64_t da = mkdesc(SB0 + st * LB_STAGE, 1024, 128, 0), db = mkdesc(SB0 + st * LB_STAGE + 8192 + wg * 1792, 3584, 128, 0);
        mbar_wait(bar + 8 * st, ph);
        if (it == LBT && kc == 0) GT(layer * 4 + 1, 12);
        wg_fence();
#pragma unroll
        for (int k = 0; k < 4; k++) wg_ss_n112_ta0_tb1(d, da + k * 128, db + k * 448, kc | k);
        wg_commit();
        wg_wait<1>();
        if (kc > 0 && lane == 0) mbar_arrive(bar + 8 * (6 + (st == 0 ? 5 : st - 1)));
        if (++st == 6) { st = 0; ph ^= 1; }
      }
      wg_wait<0>();
      pin<56>(d);
      if (it == LBT) GT(layer * 4 + 1, 13);
      if (lane == 0) mbar_arrive(bar + 8 * (6 + (st == 0 ? 5 : st - 1)));
      mbar_wait(bar + 8 * st, ph);
      {
        const uint32_t x0 = sb + st * LB_STAGE + (16 * w + g) * 464 + wg * 224 + (layer ? 8 : 4) * i4, x1 = x0 + (layer ? 4 : 16);
#pragma unroll
        for (int j = 0; j < 28; j++) {
          const uint32_t v = lds1(((j & 2) ? x1 : x0) + (j >> 2) * 32 + (j & 1) * 3712);
          d[2 * j] += bflo(v); d[2 * j + 1] += bfhi(v);
        }
      }
      fence_async();
      __syncwarp();
      if (lane == 0) mbar_arrive(bar + 8 * (6 + st));
      if (++st == 6) { st = 0; ph ^= 1; }
      const float cnt = nb * 16.f;
      const uint32_t so = LB_ST + (it & 1) * 3072 + (16 * w + g) * 48;
#pragma unroll
      for (int h = 0; h < 2; h++) {
        float sum = 0.f;
#pragma unroll
        for (int j = 0; j < 14; j++) sum += d[4 * j + 2 * h] + d[4 * j + 2 * h + 1];
        sum += __shfl_xor_sync(~0u, sum, 1); sum += __shfl_xor_sync(~0u, sum, 2);
        const float mean = sum * rcp(cnt);
        float q = 0.f, q2 = 0.f;
#pragma unroll
        for (int j = 0; j < 14; j++) {
          const float a = d[4 * j + 2 * h] - mean, b = d[4 * j + 2 * h + 1] - mean;
          if (j < 10) q = fmaf(a, a, fmaf(b, b, q)); else q2 = fmaf(a, a, fmaf(b, b, q2));
        }
        if (nb == 7) q += q2;
        q += __shfl_xor_sync(~0u, q, 1); q += __shfl_xor_sync(~0u, q, 2);
        if (i4 < 3) { const uint32_t b = mapa(sb, i4); sta2f(b + so + h * 384 + u * 8, sum, q, b + O_BAR + 8 * (12 + (it & 1))); }
      }
      mbar_wait(bar + 8 * (12 + (it & 1)), (it >> 1) & 1);
      if (it == LBT) GT(layer * 4 + 1, 14);
#pragma unroll
      for (int h = 0; h < 2; h++) {
        const float4 x = lds4f(sb + so + h * 384), y = lds4f(sb + so + h * 384 + 16), z = lds4f(sb + so + h * 384 + 32);
        const float mu = (((x.x + x.z) + (y.x + y.z)) + (z.x + z.z)) * (1.f / DM);
        const float e0 = x.x * (1.f / 112.f) - mu, e1 = x.z * (1.f / 112.f) - mu, e2 = y.x * (1.f / 112.f) - mu, e3 = y.z * (1.f / 112.f) - mu;
        const float e4 = z.x * (1.f / 112.f) - mu, e5 = z.z * (1.f / 80.f) - mu;
        const float q = (((x.y + x.w) + (y.y + y.w)) + (z.y + z.w)) + 112.f * ((e0 * e0 + e1 * e1) + (e2 * e2 + e3 * e3) + e4 * e4) + 80.f * e5 * e5;
        const float rs = rsqrtf(q * (1.f / DM) + 1e-5f), sh = -mu * rs;
        const int tk = row0 + 8 * h;
        uint8_t* xp = g_xn + (tk >> 5) * 40960 + (tk & 31) * 128 + (i4 & 1) * 8;
#pragma unroll
        for (int j = 0; j < 7; j++) {
          if (j < nb) {
            const int b16 = u * 7 + j;
            const float* a = d + 8 * j + 2 * h;
            *(uint2*)(xp + (b16 >> 2) * 4096 + (((2 * (b16 & 3) + (i4 >> 1)) ^ g) << 4)) =
                make_uint2(pack2(fmaf(a[0], rs, sh), fmaf(a[1], rs, sh)), pack2(fmaf(a[4], rs, sh), fmaf(a[5], rs, sh)));
          }
        }
      }
      if (it == LBT) GT(layer * 4 + 1, 15);
      bar_arrive<1, 288>();
      bar_sync<2, 288>();
#pragma unroll
      for (int j = 0; j < 14; j++) {
        const float* a = d + 8 * (j >> 1) + 2 * (j & 1);
        if ((j >> 1) < nb) *(uint2*)(g_x + (row0 + 8 * (j & 1)) * DM + u * 112 + 4 * i4 + 16 * (j >> 1)) = make_uint2(pack2(a[0], a[1]), pack2(a[4], a[5]));
      }
      bar_arrive<3, 288>();
    }
  } else {
    asm volatile("barrier.cluster.wait.aligned;" ::: "memory");
    if (wid == 9) {
#pragma unroll 1
      for (int tile = cl; tile < 32; tile += NLB) {
        bar_sync<1, 288>();
        if (tile != cl) bar_arrive<2, 288>();
        if (lane == 0) { red_release(flags + FL_XN + tile * 8, 1); if (tile == cl + LBT * NLB) GTT(layer * 4 + 1, 9); }
        __syncwarp();
        if (tile == cl) bar_arrive<2, 288>();
        bar_sync<3, 288>();
        if (lane == 0) red_release(flags + FL_XN + tile * 8 + 1, 1);
        __syncwarp();
      }
    }
  }
  asm volatile("barrier.cluster.arrive.relaxed.aligned;\nbarrier.cluster.wait.aligned;" ::: "memory");
  GT(layer * 4 + 1, 10);
}

__global__ void __launch_bounds__(384, 1)
rec_kernel(const __grid_constant__ CUtensorMap tmq, const __grid_constant__ CUtensorMap tmk,
           const __grid_constant__ CUtensorMap tmv, const __grid_constant__ CUtensorMap tmo,
           const __grid_constant__ CUtensorMap tmx, const bf16* __restrict__ mem0, uint8_t* __restrict__ ar, uint32_t* __restrict__ flags, int layer) {
  extern __shared__ __align__(1024) uint8_t smem[];
  const uint32_t sb = smem_u32(smem);
  check_smem_base(sb);
  GT(layer * 4 + 1, 0);
  if (blockIdx.x < 3 * NLB) { lb_role(sb, &tmx, flags, layer); return; }
  const int bid = blockIdx.x - 3 * NLB;
  const int tid = threadIdx.x, wid = __shfl_sync(~0u, tid >> 5, 0), wg = wid >> 2, w = wid & 3;
  const int lane = __shfl_sync(~0u, tid & 31, tid & 31);
  const int head = bid / 3, rank = bid - head * 3;
  const int e0 = bid * 64;
  const uint32_t bar = sb + O_BAR;
  const uint32_t sb1 = mapa(sb, rank == 2 ? 0 : rank + 1), sb2 = mapa(sb, rank == 0 ? 2 : rank - 1);
  auto chunk_of = [&](int p) { const int c = 3 * rank + p; return p == 9 ? 9 : c >= 9 ? c - 9 : c; };

  auto load_piece = [&](int i) {
    if (lane == 0) mbar_expect(bar + 8 * (MB_W + i), 16384);
    __syncwarp();
    if (lane < 2) {
      if (i < 15) {
        const int m = i < 10 ? i & 1 : 0, p = (i < 10 ? i >> 1 : i - 10) * 2 + lane;
        tma5d(sb + m * 81920 + p * 8192, i >= 10 ? &tmv : m ? &tmk : &tmq, e0, chunk_of(p) * 4, bar + 8 * (MB_W + i));
      } else {
        const int p = (i - 15) * 2 + lane, k = p / 3, j = rank + p - 3 * k;
        tma2d(sb + O_WO + p * 8192, &tmo, p == 9 ? 576 : (rank * 3 + k) * 64, head * DH + (j >= 3 ? j - 3 : j) * 64, bar + 8 * (MB_W + i));
      }
    }
  };
  if (wid == 9) {
    mbar_init(bar + 8 * lane, (lane >= MB_WC || lane == MB_PF) ? 4 : lane == MB_SM ? 13 : 1);
    if (lane < 8) mbar_init(bar + 8 * (32 + lane), 4);
    asm volatile("fence.mbarrier_init.release.cluster;" ::: "memory");
    fence_async();
    __syncwarp();
#pragma unroll 1
    for (int i = 0; i < W_WIN; i++) load_piece(i);
  }
  __syncthreads();
  asm volatile("barrier.cluster.arrive.relaxed.aligned;" ::: "memory");

  if (wg < 2) {
    asm volatile("setmaxnreg.inc.sync.aligned.u32 208;");
    uint32_t a[40][4];
    const uint32_t swz = (lane & 7) * 128 + (((2 * w + ((lane >> 3) & 1)) ^ (lane & 7)) << 4);
    const uint32_t st_x = __shfl_sync(~0u, sb + O_QK + wg * 5120 + (lane >> 4) * 2048 + swz, lane);
    {
      const uint32_t la = sb + wg * 81920 + (lane >> 4) * 1024 + swz;
#pragma unroll
      for (int p = 0; p < 5; p++) {
        mbar_wait(bar + 8 * (MB_W + 2 * p + wg), 0);
#pragma unroll
        for (int k = 0; k < 8; k++) ldsm4t(a[p * 8 + k], la + (p * 8 + k) * 2048);
        fence_async();
        __syncwarp();
        mbar_arrive_elect(bar + 8 * (MB_WC + wg * 5 + p));
      }
    }
    GT(layer * 4 + 1, 5);
    asm volatile("barrier.cluster.wait.aligned;" ::: "memory");
    const uint32_t ld_m = __shfl_sync(~0u, sb + O_H + (lane & 7) * 128 + (((lane >> 3) ^ (lane & 7)) << 4), lane);

    for (int s = 0; s < NSEG; s++) {
      const uint32_t par = s & 1;
      if (wid == 4) TS0(0);
      if (wid == 0) TS(30);
      {
        float ax[16];
        constexpr uint64_t db = mkdesc(SB0 + O_H + 1024, 16, 1024, 1);
        mbar_waitf(bar + 8 * MB_XF, par);
        wg_fence();
#pragma unroll
        for (int k = 0; k < 20; k++) wg_rs_n32_tb0(ax, a[vord(k)], db + hoff(vord(k)), k);
        mbar_waitf(bar + 8 * (MB_XF + 1), par);
        wg_fence();
#pragma unroll
        for (int k = 20; k < 40; k++) wg_rs_n32_tb0(ax, a[vord(k)], db + hoff(vord(k)), 1);
        wg_commit();
        mbar_waitf(bar + 8 * MB_PF, par ^ 1);
        if (wid == 6 && lane == 0) { mbar_expect(bar + 8 * MB_SM, 2 * SM_SLOT + 48); mbar_expect(bar + 8 * MB_SX, 2 * 2176); }
        wg_wait<0>();
        pin<16>(ax);
        if (w == 0) TS(1 + 22 * wg);
        stsm4t(st_x, pack2(ax[0], ax[1]), pack2(ax[2], ax[3]), pack2(ax[4], ax[5]), pack2(ax[6], ax[7]));
        stsm4t(st_x + 4096, pack2(ax[8], ax[9]), pack2(ax[10], ax[11]), pack2(ax[12], ax[13]), pack2(ax[14], ax[15]));
        bar_arrive<B_VOWN, 384>();
      }
      {
        float c[4][4];
#pragma unroll
        for (int k = 0; k < 4; k++) c[k][0] = c[k][1] = c[k][2] = c[k][3] = 0.f;
        uint32_t b[3][2][4];
        const uint32_t ld_m2 = opaque(ld_m ^ 64);
        SCHED_FENCE();
#define MORD(j) ((j) == 0 ? 9 : (j) < 4 ? (j) - 1 : 3 + ((j) - 4) / 2 + 3 * ((j) & 1))
#pragma unroll
        for (int j = 0; j < 12; j++) {
          if (j < 10) {
            if (j == 0) { mbar_waitf(bar + 8 * MB_ML, par); if (wid == 0) TS(2); }
            if (j == 1) { bar_sync<B_ML, 352>(); if (wid == 0) TS(3); }
            if (j == 4) { bar_sync<B_MR, 288>(); if (wid == 0) TS(4); }
            ldsm4(b[j % 3][0], ld_m + MORD(j) * 5120);
            ldsm4(b[j % 3][1], ld_m2 + MORD(j) * 5120);
          }
          const int u = j - 2;
          if (u >= 0) {
#pragma unroll
            for (int k = 0; k < 4; k++) mma16816(c[k], a[4 * MORD(u) + k], b[u % 3][k >> 1][(k & 1) * 2], b[u % 3][k >> 1][(k & 1) * 2 + 1]);
          }
        }
        if (wid == 0) TS(31);
#pragma unroll
        for (int k = 0; k < 4; k++) c[0][k] = (c[0][k] + c[1][k]) + (c[2][k] + c[3][k]);
        stsm2t(st_x + 1024 - wg * 3072, pack2(c[0][0], c[0][1]), pack2(c[0][2], c[0][3]));
        fence_async();
      }
      if (wg == 0) {
        bar_sync<B_QK, 256>();
        float sv[20];
        {
          constexpr uint64_t da = mkdesc(SB0 + O_QK, 16, 1024, 1), db = mkdesc(SB0 + O_K, 16, 2048, 1);
          wg_fence();
#pragma unroll
          for (int k = 0; k < 4; k++) wg_ss_n40_ta0_tb0(sv, da + 2 * k, db + 2 * k, k);
          bar_arrive<B_SISS, 256>();
          wg_commit();
        }
        if (w == 0) TS(6);
        SCHED_FENCE();
        const uint32_t ln = opaque(lane);
        uint32_t m0, m1, m2, m3, m4;
        {
          const uint32_t a1 = opaque(sb1 + O_SM + SM_SLOT + ln * 16), a2 = opaque(sb2 + O_SM + ln * 16);
          const uint32_t a3 = opaque(sb1 + O_SM + SM_SLOT + 512 + ln * 4), a4 = opaque(sb2 + O_SM + 512 + ln * 4);
          const uint32_t b1 = opaque(sb1 + O_BAR + 8 * MB_SM), b2 = opaque(sb2 + O_BAR + 8 * MB_SM);
          const uint32_t bt = opaque(mapa(sb, min(ln, 2u)) + O_BAR + 8 * MB_SM);
          SCHED_FENCE();
          wg_wait<0>();
          pin<20>(sv);
          m0 = pack2(sv[2], sv[3]); m1 = pack2(sv[6], sv[7]); m2 = pack2(sv[10], sv[11]); m3 = pack2(sv[14], sv[15]); m4 = pack2(sv[18], sv[19]);
          if (w == 0) {
            sta4(a1, m0, m1, m2, m3, b1);
            sta4(a2, m0, m1, m2, m3, b2);
            sta1(a3, m4, b1);
            sta1(a4, m4, b2);
          }
          mbar_arrive_clp(bt, ln < 3);
          bar_arrive<B_SSENT, 256>();
          SCHED_FENCE();
        }
        const uint32_t p0 = pack2(sv[0], sv[1]), p1 = pack2(sv[4], sv[5]), p2 = pack2(sv[8], sv[9]), p3 = pack2(sv[12], sv[13]), p4 = pack2(sv[16], sv[17]);
        const uint32_t ox = O_K + w * 2048 + ln * 16, ox2 = O_K + 8192 + ln * 4;
        {
          const uint32_t a1 = opaque(sb1 + ox + 512), a2 = opaque(sb2 + ox), b1 = opaque(sb1 + O_BAR + 8 * MB_SX), b2 = opaque(sb2 + O_BAR + 8 * MB_SX);
          if (w == 0) {
            TS(7);
            const uint32_t om = opaque(sb + O_SM + ln * 16), om2 = opaque(sb + O_SM + 512 + ln * 4);
            const uint32_t pa0 = ld_m + (O_QM - O_H), pa1 = (ld_m ^ 64) + (O_QM - O_H);
            float t[10] = {bflo(m0), bfhi(m0), bflo(m1), bfhi(m1), bflo(m2), bfhi(m2), bflo(m3), bfhi(m3), bflo(m4), bfhi(m4)};
            pin<10>(t);
            SCHED_FENCE();
            mbar_waitf(bar + 8 * MB_SM, par);
            const uint4 u = lds4(om), v = lds4(om + SM_SLOT);
            const uint32_t u4 = lds1(om2), v4 = lds1(om2 + SM_SLOT);
            sta4(a1, p0, p1, p2, p3, b1);
            sta4(a2, p0, p1, p2, p3, b2);
            bar_arrive<B_SLD, 256>();
            SCHED_FENCE();
            ACC3(0, u.x, v.x) ACC3(2, u.y, v.y) ACC3(4, u.z, v.z) ACC3(6, u.w, v.w) ACC3(8, u4, v4)
            TS(8);
            const float f = exp_row(t);
            stsm4(pa0, pack2(t[0] * f, t[1] * f), pack2(t[2] * f, t[3] * f), pack2(t[4] * f, t[5] * f), pack2(t[6] * f, t[7] * f));
            stsm1(pa1, pack2(t[8] * f, t[9] * f));
            bar_arrive<B_PM, 160>();
            TS(9);
          } else {
            const uint32_t a3 = opaque(sb1 + ox2 + 128), a4 = opaque(sb2 + ox2);
            SCHED_FENCE();
            mbar_waitf(bar + 8 * MB_SM, par);
            sta4(a1, p0, p1, p2, p3, b1);
            sta4(a2, p0, p1, p2, p3, b2);
            if (w == 3) { sta1(a3, p4, b1); sta1(a4, p4, b2); }
            bar_arrive<B_SLD, 256>();
          }
        }
        {
          float t[10] = {bflo(p0), bfhi(p0), bflo(p1), bfhi(p1), bflo(p2), bfhi(p2), bflo(p3), bfhi(p3), bflo(p4), bfhi(p4)};
          const int dq = 8 * w + (ln >> 2) - 2 * (ln & 3);
#pragma unroll
          for (int k = 1; k < 5; k++) {
            if (8 * (k - 1) > dq) t[2 * k] = -1e9f / SCL;
            if (8 * (k - 1) + 1 > dq) t[2 * k + 1] = -1e9f / SCL;
          }
          const int rr = 2 * w + (ln & 1);
          const uint32_t pa = sb + O_QK + ((ln >> 1) & 3) * 2048 + rr * 128;
          const uint32_t pa0 = opaque(pa + (((ln >> 3) ^ rr) << 4)), pa1 = opaque(pa0 ^ 64), l0 = opaque(sb + ox), l1 = opaque(sb + ox2);
          pin<10>(t);
          SCHED_FENCE();
          mbar_waitf(bar + 8 * MB_SX, par);
          bar_sync<B_VEND, 256>();
          const uint4 u = lds4(l0), v = lds4(l0 + 512);
          uint32_t u4 = 0, v4 = 0;
          if (w == 3) { u4 = lds1(l1); v4 = lds1(l1 + 128); }
          ACC3(0, u.x, v.x) ACC3(2, u.y, v.y) ACC3(4, u.z, v.z) ACC3(6, u.w, v.w) ACC3(8, u4, v4)
          const float f = exp_row(t);
          const float sum = (((t[0] + t[1]) + (t[2] + t[3])) + ((t[4] + t[5]) + (t[6] + t[7])) + (t[8] + t[9])) * f;
          const float s1 = __shfl_xor_sync(~0u, sum, 1), s2 = __shfl_xor_sync(~0u, sum, 2), s3 = __shfl_xor_sync(~0u, sum, 3);
          const float inv = f * rcp((sum + s1) + (s2 + s3));
          stsm4(pa0, pack2(t[0] * inv, t[1] * inv), pack2(t[2] * inv, t[3] * inv), pack2(t[4] * inv, t[5] * inv), pack2(t[6] * inv, t[7] * inv));
          stsm2(pa1, pack2(t[8] * inv, t[9] * inv), 0u);
          fence_async();
        }
        bar_arrive<B_PX, 256>();
        if (w == 0) TS(10);
        bar_sync<B_XGO, 256>();
      } else {
        bar_arrive<B_QK, 256>();
        const int ln = opaque(lane);
        if (OGB == 1 && w == 1 && s + 1 < NSEG) {
          bar_sync<B_OGO, 160>();
          bulk_s2c_elect1<1024>(sb1 + O_OG + 4096, sb1 + O_BAR + 8 * MB_OG, sb + O_OG);
          bulk_s2c_elect1<1024>(sb2 + O_OG + 2048, sb2 + O_BAR + 8 * MB_OG, sb + O_OG);
        }
        if (w == 2) {
          bar_sync<B_VHALF, 192>();
          if (ln == 0 && s > 0) { red_release(flags + FL_A + (e0 >> 10) * 8 + (s - 1) * 48, 1); }
          __syncwarp();
        }
        if (w == 3) {
          const int l = bid * 2 + ln, s2 = s + 2;
          if (ln < 2 && l < 160 && s2 < NSEG - 1) {
            const int tile = l >> 4;
            const uint8_t* p = ar + (s2 >> 2) * AR_GROUP + (s2 & 1) * 128 + ((s2 >> 1) & 1) * 512 + ar_chunk(tile) * 4096 +
                               ((l >> 3) & 1) * 16384 + (l & 1) * 256 + ((l >> 1) & 3) * 1024;
            asm volatile("prefetch.global.L2 [%0];" :: "l"(p));
          }
        }
        if (w == 0) {
          const bool more = s + 1 < NSEG;
          if (ln < 2 && more) mbar_expect(bar + 8 * (MB_XF + ln), 20480);
          const uint8_t* src = g_xn + (s + 1) * 40960;
          if ((s & 1) && more) { wait_flag(flags + FL_XN + ((s + 1) >> 1) * 8, 3); fence_async_global(); }
          bar_sync<B_VHALF, 192>();
          if (more) {
#pragma unroll
            for (int q = 0; q < 5; q++) { const int p = q == 0 ? 9 : q - 1; bulk_g2s_elect<4096>(sb + O_H + p * 5120 + 1024, src + chunk_of(p) * 4096, bar + 8 * MB_XF); }
          }
          bar_sync<B_VDONE, 160>();
          if (more) {
#pragma unroll
            for (int p = 4; p < 9; p++) bulk_g2s_elect<4096>(sb + O_H + p * 5120 + 1024, src + chunk_of(p) * 4096, bar + 8 * (MB_XF + 1));
          }
        }
        bar_sync<B_XGO1, 256>();
      }
    }
  } else {
    asm volatile("setmaxnreg.dec.sync.aligned.u32 88;");
    asm volatile("barrier.cluster.wait.aligned;" ::: "memory");

    const int g = lane >> 2, i4 = lane & 3;
    const int myT = w == 0 ? 9 : rank * 3 + w - 1, myP = w == 0 ? 9 : w - 1;
    const int tok = 2 * ((lane >> 1) & 3) + ((lane >> 3) & 1);
    const uint32_t fw_off = sb + O_H + myP * 5120 + tok * 128 + (((2 * (lane >> 4) + (lane & 1)) ^ tok) << 4);
    const uint32_t prod_off = (w >> 1) * 16384 + (w & 1) * 2048 + ((g >> 1) & 1) * 256 + (i4 * 2 + (g >> 2)) * 16 + (g & 1) * 8;
    const uint32_t cons_off = ar_chunk(myT) * 4096 + (lane >> 3) * 1024 + (lane & 7) * 16;
    auto tile_off = [&](int k) { return (k * 8 + rank) * 4096; };
    constexpr uint32_t T9_OFF = ar_chunk(9) * 4096;

    uint32_t p[8];
    auto forward = [&]() {
      const uint32_t c = O_H + myP * 5120, bo = O_BAR + 8 * MB_MR;
      sts4(fw_off, p[0], p[1], p[2], p[3]);
      sts4(fw_off ^ 64, p[4], p[5], p[6], p[7]);
      if (w == 0) {
        __syncwarp();
        mbar_arrive_elect(bar + 8 * MB_ML);
        fence_async();
      } else {
        bar_arrive<B_ML, 352>();
        fence_async();
        __syncwarp();
        bulk_s2c_elect1<1024>(sb1 + c + 6 * 5120, sb1 + bo, sb + c);
        bulk_s2c_elect1<1024>(sb2 + c + 3 * 5120, sb2 + bo, sb + c);
      }
    };
    auto send_max = [&]() {
      uint32_t mx = 0;
#pragma unroll
      for (int k = 0; k < 8; k++) mx = __vmaxu2(mx, p[k] & 0x7FFF7FFFu);
      mx = max(mx & 0xFFFFu, mx >> 16);
      mx = __reduce_max_sync(~0u, mx);
      { const uint32_t b = mapa(sb, min(lane, 2)); sta1p(b + O_MAXS + (rank * 4 + w) * 4, mx << 16, b + O_BAR + 8 * MB_SM, lane < 3); }
    };
    auto arm = [&]() { if (lane == 0 && w < 2) mbar_expect(bar + 8 * (w == 0 ? MB_OG : MB_MR), w == 0 ? 2048 : 6144); };
    {
      arm();
      const uint32_t* mp = (const uint32_t*)(mem0 + tok * DM + myT * 64 + 16 * (lane >> 4) + 4 * (lane & 1));
      p[0] = mp[0]; p[1] = mp[4]; p[2] = mp[1]; p[3] = mp[5]; p[4] = mp[16]; p[5] = mp[20]; p[6] = mp[17]; p[7] = mp[21];
      forward();
    }
    if (w == 1) {
#pragma unroll 1
      for (int i = W_WIN; i < 20; i++) {
        if (i <= W_OPEN) mbar_wait(bar + 8 * (MB_W + i - W_WIN), 0);
        if (i >= 10) mbar_wait(bar + 8 * (MB_WC + i - 10), 0);
        load_piece(i);
      }
    }
    if (w == 0) {
      if (lane < 2) mbar_expect(bar + 8 * (MB_XF + lane), 20480);
      wait_flag<200>(flags + FL_XN, 3);
      fence_async_global();
      if (lane < 10) bulk_g2s(sb + O_H + lane * 5120 + 1024, g_xn + chunk_of(lane) * 4096, 4096, bar + 8 * (MB_XF + (lane >= 4 && lane < 9)));
      if (lane == 0) GTT(layer * 4 + 1, 4);
    }
    if (w == 2) {
      wait_flag<400>(flags + FL_X, 128);
      wait_flag<400>(g_zero + Z_FLAGS + FL_N, 4);
      const float sq = __ldcg((const float*)(g_zero + Z_NORM));
      float mx = 0.f;
#pragma unroll
      for (int k = 0; k < 5; k++) {
        const float4* p = (const float4*)g_nrm + k * 32 + lane;
        const float4 x = __ldcg(p), y = __ldcg(p + 160), z = __ldcg(p + 320), u = __ldcg(p + 480);
        mx = fmaxf(fmaxf(mx, fmaxf((x.x + y.x) + (z.x + u.x), (x.y + y.y) + (z.y + u.y))), fmaxf((x.z + y.z) + (z.z + u.z), (x.w + y.w) + (z.w + u.w)));
      }
#pragma unroll
      for (int o = 16; o; o >>= 1) mx = fmaxf(mx, __shfl_xor_sync(~0u, mx, o));
      sts1(sb + O_MAXS + 52, __float_as_uint(sqrt_approx(sq) * sqrt_approx(mx) * (25.2982213f * 1.1f)));
    }
    bar_sync<B_WG2, 128>();
    const float cbound = __uint_as_float(lds1(sb + O_MAXS + 52));
#pragma unroll 1
    for (int i = 10; i < 15; i++) mbar_wait(bar + 8 * (MB_W + i), 0);
    if (tid == 256) GTT(layer * 4 + 1, 7);

    const uint32_t la_w = sb + O_WV + ((lane >> 4) * 8 + (lane & 7)) * 128 + (((2 * w + ((lane >> 3) & 1)) ^ (lane & 7)) << 4);
    uint32_t af[V_RS][4];
#pragma unroll
    for (int k = 0; k < V_RS; k++) ldsm4t(af[k], la_w + vord(V_OWN + k) * 2048);
    const uint32_t pa0 = __shfl_sync(~0u, sb + O_QM + (lane & 7) * 128 + (((lane >> 3) ^ (lane & 7)) << 4), lane), pa1 = __shfl_sync(~0u, pa0 ^ 64, lane);
    uint32_t vf[10];
    uint4 oq0, oq1;
    uint8_t* op;
    auto pv_x = [&](int s) {
      float ox[16];
      const uint32_t vz[4] = {vf[8], vf[9], 0u, 0u};
      constexpr uint64_t dp = mkdesc(SB0 + O_QK, 16, 2048, 1);
      bar_sync<B_PX, 256>();
      wg_fence();
      wg_rs_n32_tb0(ox, vf, dp, 0);
      wg_rs_n32_tb0(ox, vf + 4, dp + 2, 1);
      wg_rs_n32_tb0(ox, vz, dp + 4, 1);
      wg_commit();
      const uint32_t ln = opaque(lane);
      op = g_ot + (size_t)s * (HE * 64) + (e0 + 16 * w) * 64 + (ln & 3) * 128 + (ln >> 2) * 16;
      wg_wait<0>();
      pin<16>(ox);
      oq0 = make_uint4(pack2(ox[0], ox[1]), pack2(ox[4], ox[5]), pack2(ox[8], ox[9]), pack2(ox[12], ox[13]));
      oq1 = make_uint4(pack2(ox[2], ox[3]), pack2(ox[6], ox[7]), pack2(ox[10], ox[11]), pack2(ox[14], ox[15]));
    };
    for (int s = 0;; s++) {
      const uint32_t par = s & 1;
      float sc1, isc, sum0, sum1;
      uint32_t ao[O_RS][4];
      {
        float av[20];
        constexpr uint64_t da = mkdesc(SB0 + O_WV, 1024, 1024, 1), db = mkdesc(SB0 + O_H, 16, 1024, 1);
#define V_RUN(k0, k1) wg_fence(); _Pragma("unroll") for (int k = k0; k < k1; k++) wg_ss_n40_ta1_tb0(av, da + vord(k) * 128, db + hoff(vord(k)), k);
        bar_sync<B_VOWN, 384>();
        V_RUN(0, V_OWN)
        if (w == 0) TS(29);
        SCHED_FENCE();
        if (w == 0) { mbar_waitf(bar + 8 * MB_MR, par); bar_arrive<B_MR, 288>(); SCHED_FENCE(); }
        send_max();
        bar_sync<B_SISS, 256>();
        V_RUN(V_OWN + V_RS, V_OWN + V_RS + V_B)
        if (s == 0) {
#pragma unroll 1
          for (int i = 15; i < 20; i++) mbar_wait(bar + 8 * (MB_W + i), 0);
          asm volatile("griddepcontrol.launch_dependents;");
          if (tid == 256) GTT(layer * 4 + 1, 8);
        }
        bar_sync<B_SSENT, 256>();
        V_RUN(V_OWN + V_RS + V_B, V_K1)
        wg_fence();
#pragma unroll
        for (int k = 0; k < V_RS; k++) wg_rs_n40_tb0(av, af[k], db + hoff(vord(V_OWN + k)), 1);
        if (V_K1 >= 20) wg_commit();
        const uint32_t ln = opaque(lane);
        const uint32_t amx = opaque(sb + O_MAXS + 4 * min(ln, 11u));
        SCHED_FENCE();
        mbar_waitf(bar + 8 * MB_SM, par);
        const uint32_t mxl = lds1(amx);
        if (V_S2 == 0) { wg_wait<0>(); bar_arrive<B_VHALF, 192>(); }
        bar_sync<B_SLD, 256>();
        if (V_K1 < 20) { V_RUN(V_K1, 20) wg_commit(); }
        if (V_S2 > 0) {
          V_RUN((V_K1 > 20 ? V_K1 : 20), V_K2)
          wg_commit();
          wg_wait<1>();
          bar_arrive<B_VHALF, 192>();
        }
        V_RUN(V_K2, 40)
        wg_commit();
        SCHED_FENCE();
        if (w == 0) TS(12);
        {
          const float bnd = cbound * fmaxf(1.f, __uint_as_float(__reduce_max_sync(~0u, mxl)));
          const uint32_t eb = min(max(__float_as_uint(bnd) >> 23, 31u), 254u);
          sc1 = __uint_as_float(opaque((280u - eb) << 23));
          isc = __uint_as_float(opaque((eb - 29u) << 23));
        }
        const uint32_t o = O_OG + w * 256 + ln * 4;
        const uint32_t a0 = opaque(sb + o), a1 = opaque(sb1 + o + 4096), a2 = opaque(sb1 + o + 4096 + 128), a3 = opaque(sb2 + o + 2048), a4 = opaque(sb2 + o + 2048 + 128);
        const uint32_t b1 = opaque(sb1 + O_BAR + 8 * MB_OG), b2 = opaque(sb2 + O_BAR + 8 * MB_OG), a5 = opaque(sb + O_OG + w * 256 + (ln & 15) * 16);
        const uint32_t c1 = opaque(0x3F803F80u);
        const uint32_t one[4] = {c1, c1, c1, c1};
        uint32_t pm[5];
        bar_arrive<B_VEND, 256>();
        SCHED_FENCE();
        bar_sync<B_PM, 160>();
        ldsm4(pm, pa0);
        ldsm1(pm[4], pa1);
        SCHED_FENCE();
        wg_wait<0>();
        pin<20>(av);
        if (w == 0) TS(13);
        if (PMW) {
          asm volatile("and.b32 %0, %0, 0x7FFFFFFF;\nand.b32 %1, %1, 0x7FFFFFFF;" : "+r"(pm[4]), "+r"(pm[3]));
          if (PMW == 2) { vf[0] = pack2(av[0], av[1]); vf[1] = pack2(av[2], av[3]); vf[2] = pack2(av[4], av[5]); vf[3] = pack2(av[6], av[7]); asm volatile("" : "+r"(vf[0]), "+r"(vf[1]), "+r"(vf[2]), "+r"(vf[3])); }
          SCHED_FENCE();
        }
#pragma unroll
        for (int j = 0; j < 16; j++) if ((O_RSM >> j) & 1) ldsm4t(ao[O_IDX(j)], la_w + O_WO + (1 + (j >> 3)) * 24576 + (4 + (j & 7)) * 2048);
#pragma unroll
        for (int k = (PMW == 2 ? 4 : 0); k < 10; k++) vf[k] = pack2(av[2 * k], av[2 * k + 1]);
        float o0[4] = {0.f, 0.f, 0.f, 0.f}, o1[4] = {0.f, 0.f, 0.f, 0.f}, o2[4] = {0.f, 0.f, 0.f, 0.f};
        float s0[4] = {0.f, 0.f, 0.f, 0.f}, s1[4] = {0.f, 0.f, 0.f, 0.f}, s2[4] = {0.f, 0.f, 0.f, 0.f};
        mma16816(o0, vf, pm[0], pm[1]);
        mma16816(o1, vf + 4, pm[2], pm[3]);
        mma1688(o2, vf[8], vf[9], pm[4]);
        mma16816(s0, one, pm[0], pm[1]);
        mma16816(s1, one, pm[2], pm[3]);
        mma1688(s2, c1, c1, pm[4]);
        const uint32_t p0 = pack2(o0[0] + o1[0] + o2[0], o0[1] + o1[1] + o2[1]), p1 = pack2(o0[2] + o1[2] + o2[2], o0[3] + o1[3] + o2[3]);
        if (OGB == 1) stsm2(a5, p0, p1);
        if (OGB == 2) { sts1(a0, p0); sts1(a0 + 128, p1); }
        if (OGB == 3) stsm2(a5, p0, p1);
        if (OGB != 1) { sta1(a1, p0, b1); sta1(a2, p1, b1); sta1(a3, p0, b2); sta1(a4, p1, b2); }
        if (OGB == 0) { sts1(a0, p0); sts1(a0 + 128, p1); }
        if (OGB == 4) stsm2(a5, p0, p1);
        sum0 = s0[0] + s1[0] + s2[0]; sum1 = s0[1] + s1[1] + s2[1];
        fence_async();
      }
      if (s == NSEG - 1) break;
      uint8_t* arp;
      uint32_t t1;
      {
        if (OGB == 1) bar_sync<B_OGO, 160>(); else bar_sync<B_WG2, 128>();
        float c9[4], ca[4], cb[4], cc[4];
        constexpr uint64_t da = mkdesc(SB0 + O_WO, 1024, 1024, 1), db = mkdesc(SB0 + O_OG, 128, 128, 0);
#define O_RUN(acc, tile, k0, k1) _Pragma("unroll") for (int k = k0; k < k1; k++) wg_ss_n8_ta1_tb1(acc, da + (tile) * 1536 + k * 128, db + (k >> 2) * 128 + (k & 3) * 16, k);
        wg_fence();
        O_RUN(c9, 3, 0, 4)
        wg_commit();
        if (w == 0) TS(14);
        O_RUN(ca, 0, 0, 4) O_RUN(cb, 1, 0, 2)
        wg_commit();
        SCHED_FENCE();
        arp = ar + (s >> 2) * AR_GROUP + (s & 1) * 128 + ((s >> 1) & 1) * 512;
        uint8_t* pp = arp + opaque(prod_off);
        const float2 sc = make_float2(sc1 * rcp(sum0), sc1 * rcp(sum1));
        wg_wait<1>();
        pin<4>(c9);
        fix_red(pp + T9_OFF, c9, sc);
        SCHED_FENCE();
        wg_fence();
        O_RUN(cb, 1, 2, 4) O_RUN(cc, 2, 0, 4)
        mbar_waitf(bar + 8 * MB_OG, par);
        wg_fence();
        O_RUN(ca, 0, 4, 12)
        wg_commit();
        if (w == 0) TS(15);
#define O_MIX(acc, j0, j1) _Pragma("unroll") for (int j = j0; j < j1; j++) { const int k = 4 + (j & 7); \
          if ((O_RSM >> j) & 1) wg_rs_n8_tb1(acc, ao[O_IDX(j) < O_RS ? O_IDX(j) : 0], db + (k >> 2) * 128 + (k & 3) * 16, 1); \
          else wg_ss_n8_ta1_tb1(acc, da + (1 + (j >> 3)) * 1536 + k * 128, db + (k >> 2) * 128 + (k & 3) * 16, 1); }
        O_MIX(cb, 0, O_B1)
        wg_commit();
        wg_wait<1>();
        pin<4>(ca);
        fix_red(pp + tile_off(0), ca, sc);
        SCHED_FENCE();
        if (w == 0) TS(16);
        bar_arrive<B_VDONE, 160>();
        wg_fence();
        O_MIX(cb, O_B1, 8)
        wg_commit();
        O_MIX(cc, 8, 16)
        wg_commit();
        bar_arrive<B_XGO1, 256>();
        bar_arrive<B_XGO, 256>();
        wg_wait<1>();
        pin<4>(cb);
        uint8_t* pb = pp + tile_off(1);
        fix_red(pb, cb, sc);
        wg_wait<0>();
        pin<4>(cc);
        fix_red(pb + 32768, cc, sc);
        t1 = clk();
        if (w == 3) TS(17);
      }
      pv_x(s);
      mbar_arrive_elect(bar + 8 * MB_PF);
      if (w == 0) TS(28);
      {
        arm();
        const int dly = w == 0 ? POLL_9 : w == 1 ? POLL_A : w == 2 ? POLL_B : POLL_C;
        const uint32_t need = w == 0 ? 96 : 32;
        const uint8_t* cp = arp + opaque(cons_off);
        uint4 y[4];
        int it = 0;
        while ((int)(clk() - t1) < dly) {}
        if (w == 3) TS(18);
        y[0] = ld_poll(cp); y[1] = ld_poll(cp + 256); y[2] = ld_poll(cp + 16384); y[3] = ld_poll(cp + 16384 + 256);
        { const uint64_t pol = policy_evict_first(); stg4h(op, oq0, pol); stg4h(op + 512, oq1, pol); }
        const float isl = isc * 0.5f, bias = -(float)(need >> 3) * isl;
        while (true) {
          const uint32_t bad = ((y[0].x ^ need) | (y[0].z ^ need) | (y[1].x ^ need) | (y[1].z ^ need)) | ((y[2].x ^ need) | (y[2].z ^ need) | (y[3].x ^ need) | (y[3].z ^ need));
          if (!__any_sync(~0u, (bad & 127u) != 0)) break;
          if (++it > 2000000) __trap();
          y[0] = ld_poll(cp); y[1] = ld_poll(cp + 256); y[2] = ld_poll(cp + 16384); y[3] = ld_poll(cp + 16384 + 256);
        }
#pragma unroll
        for (int k = 0; k < 4; k++) {
          p[2 * k] = pack2(fmaf((float)(int)__funnelshift_r(y[k].x, y[k].y, 3), isl, bias), fmaf((float)(int)__funnelshift_r(y[k].z, y[k].w, 3), isl, bias));
          p[2 * k + 1] = pack2((float)(int)y[k].y * isc, (float)(int)y[k].w * isc);
        }
        TS(19 + w);
        forward();
      }
    }
    bar_arrive<B_VDONE, 160>();
    bar_arrive<B_XGO1, 256>();
    bar_arrive<B_XGO, 256>();
    pv_x(NSEG - 1);
    { const uint64_t pol = policy_evict_first(); stg4h(op, oq0, pol); stg4h(op + 512, oq1, pol); }
    bar_sync<B_WG2, 128>();
    if (tid == 256) red_release(flags + FL_A + (e0 >> 10) * 8 + (NSEG - 1) * 48, 1);
    if (OGB != 1) mbar_wait(bar + 8 * MB_OG, 1);
    __syncwarp();
  }
  asm volatile("barrier.cluster.arrive.relaxed.aligned;\nbarrier.cluster.wait.aligned;" ::: "memory");
  GT(layer * 4 + 1, 2);
  if (wid == 0) asm volatile("griddepcontrol.wait;" ::: "memory");
}

constexpr int P_B = 0, P_A = 131072, P_BAR = 196608, OPC_SMEM = P_BAR + 256;
#define PF_C 3
#define PF_S0 43
constexpr int OP_KR = 48;

__global__ void __launch_bounds__(384, 1)
opc_kernel(const __grid_constant__ CUtensorMap tmo, bf16* __restrict__ out, int layer,
           const bf16* __restrict__ Wq, const bf16* __restrict__ Wk, const bf16* __restrict__ Wv, const bf16* __restrict__ Wo) {
  extern __shared__ __align__(1024) uint8_t smem[];
  asm volatile("griddepcontrol.launch_dependents;");
  GT(layer * 4 + 2, 0);
  const uint32_t sb = smem_u32(smem);
  check_smem_base(sb);
  const int tid = threadIdx.x, wid = __shfl_sync(~0u, tid >> 5, 0), wg = wid >> 2, w = wid & 3, lane = tid & 31;
  const uint32_t bar = sb + P_BAR;
  uint32_t* flags = g_zero + Z_FLAGS + layer * FL_LAYER;
  float* acc = g_acc + layer * (S_TOK * DM);
  const uint64_t pol = policy_evict_first();
  if (wid == 0) {
    if (lane < 16) mbar_init(bar + 8 * lane, (lane == 8 || lane == 9) ? 8 : 1);
    fence_async();
  }
  __syncthreads();
  if (blockIdx.x < 30) {
    const int cg = blockIdx.x % 5, kg = blockIdx.x / 5;
    if (wg < 2) {
      asm volatile("setmaxnreg.inc.sync.aligned.u32 240;");
      uint32_t a[OP_KR][4];
      const uint32_t la = sb + P_B + ((lane >> 4) * 8 + (lane & 7)) * 128 + (((2 * w + ((lane >> 3) & 1)) ^ (lane & 7)) << 4);
      mbar_wait(bar + 80, 0);
#pragma unroll
      for (int k = 0; k < 32; k++) ldsm4t(a[k], la + wg * 65536 + k * 2048);
      bar_arrive<2, 288>();
      mbar_wait(bar + 88, 0);
#pragma unroll
      for (int k = 0; k < 16; k++) ldsm4t(a[32 + k], la + wg * 32768 + k * 2048);
      bar_arrive<3, 288>();
      mbar_wait(bar + 96, 0);
      float* ap = acc + (cg * 8 + wg * 4 + w) * 512 + lane * 4;
      for (int s = 0; s < NSEG; s++) {
        const int buf = s & 1;
        const uint32_t par = (s >> 1) & 1;
        float d[16];
        const uint64_t db = mkdesc(SB0 + P_B + buf * 65536, 512, 128, 0), da = mkdesc(SB0 + P_A + wg * 32768, 1024, 1024, 1);
        float* p = ap + s * (32 * DM);
        float* pz = ap + (s + 2) * (32 * DM) + kg * 128;
        if (kg < 4 && s + 2 < NSEG) { if (EVF) stg4h(pz, make_uint4(0, 0, 0, 0), pol); else stg4(pz, make_uint4(0, 0, 0, 0)); }
#pragma unroll
        for (int q = 0; q < 4; q++) {
          mbar_wait(bar + 8 * (buf * 4 + q), par);
          wg_fence();
#pragma unroll
          for (int k = 16 * q; k < 16 * q + 16; k++) {
            if (k < OP_KR) wg_rs_n32_tb1(d, a[k < OP_KR ? k : 0], db + k * 64, k);
            else wg_ss_n32_ta1_tb1(d, da + (k - OP_KR) * 128, db + k * 64, 1);
          }
        }
        wg_commit();
        wg_wait<0>();
        pin<16>(d);
        if (lane == 0) mbar_arrive(bar + 8 * (8 + buf));
        if (s == NSEG - 1) GT(layer * 4 + 2, 6);
        if (EVF) {
          red4fh(p, d[0], d[1], d[4], d[5], pol);
          red4fh(p + 128, d[8], d[9], d[12], d[13], pol);
          red4fh(p + 256, d[2], d[3], d[6], d[7], pol);
          red4fh(p + 384, d[10], d[11], d[14], d[15], pol);
        } else {
          red4f(p, d[0], d[1], d[4], d[5]);
          red4f(p + 128, d[8], d[9], d[12], d[13]);
          red4f(p + 256, d[2], d[3], d[6], d[7]);
          red4f(p + 384, d[10], d[11], d[14], d[15]);
        }
        bar_sync<1, 256>();
        if (tid == 0) { red_release(flags + FL_B + s * 8, 1); }
        __syncwarp();
      }
    } else {
      asm volatile("setmaxnreg.dec.sync.aligned.u32 24;");
      if (w == 0) {
        if (lane == 0) { mbar_expect(bar + 80, 131072); mbar_expect(bar + 96, 65536); mbar_expect(bar + 88, 65536); }
        __syncwarp();
        if (lane < 16) tma2d(sb + P_B + lane * 8192, &tmo, cg * 128 + (lane >> 3) * 64, kg * 1024 + (lane & 7) * 64, bar + 80);
        else if (lane < 24) tma2d(sb + P_B + lane * 8192, &tmo, cg * 128 + ((lane >> 2) & 1) * 64, kg * 1024 + 768 + (lane & 3) * 64, bar + 96);
        bar_sync<2, 288>();
        fence_async();
        if (lane < 8) tma2d(sb + P_B + lane * 8192, &tmo, cg * 128 + (lane >> 2) * 64, kg * 1024 + 512 + (lane & 3) * 64, bar + 88);
        bar_sync<3, 288>();
        for (int s = 0; s < NSEG; s++) {
          const int buf = s & 1;
          if (s >= 2) mbar_wait(bar + 8 * (8 + buf), ((s >> 1) & 1) ^ 1);
          if (s >= 2) wait_flag(flags + FL_B + (s - 2) * 8, 30);
          wait_flag(flags + FL_A + s * 48 + kg * 8, 16);
          fence_async_global();
          if (lane < 4) {
            mbar_expect(bar + 8 * (buf * 4 + lane), 16384);
            if (EVF) bulk_g2sh(sb + P_B + buf * 65536 + lane * 16384, g_ot + (size_t)s * (HE * 64) + kg * 65536 + lane * 16384, 16384, bar + 8 * (buf * 4 + lane), pol);
            else bulk_g2s(sb + P_B + buf * 65536 + lane * 16384, g_ot + (size_t)s * (HE * 64) + kg * 65536 + lane * 16384, 16384, bar + 8 * (buf * 4 + lane));
            if (s == NSEG - 1 && lane == 0) GTT(layer * 4 + 2, 5);
          }
          __syncwarp();
        }
      } else if (w == 1 && layer == 0) {
#pragma unroll 1
        for (int q = 4 * (4 - PF_C); q < 18; q++) {
          wait_flag(flags + FL_A + (PF_S0 + q) * 48 + kg * 8, 16);
          const int m = q >> 2;
          const uint8_t* W = m == 0 ? (const uint8_t*)Wo : m == 1 ? (const uint8_t*)Wv : m == 2 ? (const uint8_t*)Wk : m == 3 ? (const uint8_t*)Wq : (q & 1) ? g_w2 : g_w1;
          const int n = m < 4 ? 512 : (q & 1) ? 224 : 640, l0 = m < 4 ? blockIdx.x * 2048 + (q & 3) * 512 : blockIdx.x * n, lim = m < 4 ? 61440 : (q & 1) ? 6720 : 19200;
#pragma unroll 1
          for (int k = lane; k < n; k += 32) {
            if (l0 + k < lim) asm volatile("prefetch.global.L2 [%0];" :: "l"(W + (size_t)(l0 + k) * 128));
            __nanosleep(100);
          }
        }
      }
    }
  } else {
    constexpr int LD = 644;
    float* xs = (float*)smem;
    uint32_t par = 0;
    for (int task = blockIdx.x - 30; task < 2 * NSEG; task += 6, par ^= 1) {
      const int s = task >> 1, jj = task & 1;
      if (wid == 0) {
        wait_flag(flags + FL_XN + (task >> 2) * 8 + 1, 3);
        fence_async_global();
        if (lane == 0) { mbar_expect(bar, 20480); bulk_g2s(sb + 49152, g_x + task * 16 * DM, 20480, bar); }
      }
      if (wid == 1) { wait_flag(flags + FL_B + s * 8, 30); if (s == NSEG - 1 && lane == 0) GTT(layer * 4 + 2, 7); }
      __syncthreads();
      if (wid < 10) {
        float4 v[8];
#pragma unroll
        for (int k = 0; k < 8; k++) v[k] = EVF ? ldg4fh(acc + s * (32 * DM) + (wid * 8 + k) * 256 + jj * 128 + lane * 4, pol) : __ldcg((const float4*)(acc + s * (32 * DM) + (wid * 8 + k) * 256 + jj * 128 + lane * 4));
        float* xp = xs + (lane & 3) * 2 * LD + wid * 64 + (lane >> 2);
#pragma unroll
        for (int k = 0; k < 8; k++) { xp[k * 8] = v[k].x; xp[LD + k * 8] = v[k].y; xp[8 * LD + k * 8] = v[k].z; xp[9 * LD + k * 8] = v[k].w; }
      }
      mbar_wait(bar, par);
      __syncthreads();
      float v[2][20];
      const int pj = (lane & 24) + 2 * (lane & 3) + ((lane >> 2) & 1);
      const int tk0 = task * 16 + wid;
      if (wid < 8) {
        float sum[2] = {0.f, 0.f};
#pragma unroll
        for (int h = 0; h < 2; h++) {
#pragma unroll
          for (int k = 0; k < 10; k++) {
            const float2 u = *(const float2*)(xs + (wid + 8 * h) * LD + k * 64 + lane * 2);
            const uint32_t r = *(const uint32_t*)(smem + 49152 + (wid + 8 * h) * 1280 + k * 128 + pj * 4);
            v[h][2 * k] = u.x + bflo(r); v[h][2 * k + 1] = u.y + bfhi(r); sum[h] += v[h][2 * k] + v[h][2 * k + 1];
          }
        }
        if (!out) {
#pragma unroll
          for (int o = 16; o; o >>= 1) { sum[0] += __shfl_xor_sync(~0u, sum[0], o); sum[1] += __shfl_xor_sync(~0u, sum[1], o); }
          float q[2] = {0.f, 0.f};
#pragma unroll
          for (int h = 0; h < 2; h++) {
            sum[h] *= (1.f / DM);
#pragma unroll
            for (int k = 0; k < 20; k++) q[h] = fmaf(v[h][k] - sum[h], v[h][k] - sum[h], q[h]);
          }
#pragma unroll
          for (int o = 16; o; o >>= 1) { q[0] += __shfl_xor_sync(~0u, q[0], o); q[1] += __shfl_xor_sync(~0u, q[1], o); }
          uint8_t* xp = g_xt + (tk0 >> 7) * 163840 + (tk0 & 127) * 128 + (((lane >> 2) ^ (tk0 & 7)) << 4) + (lane & 3) * 4;
#pragma unroll
          for (int h = 0; h < 2; h++) {
            const float rs = rsqrtf(q[h] * (1.f / DM) + 1e-5f), sh = -sum[h] * rs;
#pragma unroll
            for (int k = 0; k < 10; k++) *(uint32_t*)(xp + h * 1024 + k * 16384) = pack2(fmaf(v[h][2 * k], rs, sh), fmaf(v[h][2 * k + 1], rs, sh));
          }
        }
      }
      fence_async();
      __syncthreads();
      if (!out) {
        if (tid == 352) red_release(flags + FL_LAYER + FL_T + (task >> 3) * 8, 1);
        __syncthreads();
      }
      if (wid < 8) {
        bf16* dst = out ? out + tk0 * DM + lane * 2 : g_x + tk0 * DM + pj * 2;
#pragma unroll
        for (int k = 0; k < 20; k++) *(uint32_t*)(dst + (k / 10) * 8 * DM + (k % 10) * 64) = pack2(v[k / 10][2 * (k % 10)], v[k / 10][2 * (k % 10) + 1]);
      }
    }
    __syncthreads();
    if (tid == 0 && !out) red_release(flags + FL_LAYER + FL_R, 1);
  }
  GT(layer * 4 + 2, 1);
  __syncwarp();
  asm volatile("griddepcontrol.wait;" ::: "memory");
  GT(layer * 4 + 2, 2);
}

constexpr int L_STAGE = 47104;
constexpr int L_KV = 0, L_B2 = 43008;
constexpr int L_BAR = 4 * L_STAGE;
constexpr int LA_SMEM = L_BAR + 256;
__device__ __forceinline__ float phi(float t) { return (fmaxf(t, 0.f) + 1e-6f) + ex2(fminf(t * 1.4426950408889634f, 0.f)); }
__device__ __forceinline__ void sqacc(uint32_t& h, uint32_t v) { asm("fma.rn.bf16x2 %0, %1, %1, %0;" : "+r"(h) : "r"(v)); }
__device__ __forceinline__ uint32_t phi2(float a, float b) { return pack2(phi(a), phi(b)); }
#define LA_LATE 6
#define PF_LB 1
#define PF_IL 1
#define PF_SLEEP1 400
#define RD1 0
#define PF_N0 2
#define PF_N1 0
#define PF_SLEEP 300

__global__ void __launch_bounds__(384, 1)
la_kernel(const bf16* __restrict__ Wq, const bf16* __restrict__ Wk, const bf16* __restrict__ Wv,
          const bf16* __restrict__ Wo, uint8_t* __restrict__ ar, int layer) {
  extern __shared__ __align__(1024) uint8_t smem[];
  const uint32_t sb = smem_u32(smem);
  check_smem_base(sb);
  const int tid = threadIdx.x, wid = __shfl_sync(~0u, tid >> 5, 0), wg = wid >> 2, w = wid & 3, lane = tid & 31, g = lane >> 2, i4 = lane & 3;
  const int cr = blockIdx.x & 1, hg = (blockIdx.x >> 1) & 7, tb = (blockIdx.x >> 4) * 2 + cr;
  const uint32_t bar = sb + L_BAR;
  uint32_t* flags = g_zero + Z_FLAGS + layer * FL_LAYER;
  asm volatile("griddepcontrol.launch_dependents;");
  GT(layer * 4, 0);
  if (wid == 0) {
    if (lane < 8) mbar_init(bar + 8 * lane, lane >= 4 ? (blockIdx.x < 128 ? 16 : 10) : 1);
    asm volatile("fence.mbarrier_init.release.cluster;" ::: "memory");
    fence_async();
  }
  if (blockIdx.x >= 128) {
    __syncthreads();
    const int q = blockIdx.x - 128;
    const uint8_t* src = (const uint8_t*)Wo + q * 1966080;
    if (wid == 11) {
#pragma unroll 1
      for (int it = 0; it < 48; it++) {
        const int st = it & 3;
        if (it >= 4) mbar_wait(bar + 8 * (4 + st), ((it >> 2) & 1) ^ 1);
        if (lane == 0) mbar_expect(bar + 8 * st, 40960);
        __syncwarp();
        if (lane < 4) bulk_g2s(sb + st * 40960 + lane * 10240, src + it * 40960 + lane * 10240, 10240, bar + 8 * st);
      }
    } else if (wid < 10) {
      float c[8] = {0.f, 0.f, 0.f, 0.f, 0.f, 0.f, 0.f, 0.f};
#pragma unroll 1
      for (int it = 0; it < 48; it++) {
        const int st = it & 3;
        mbar_wait(bar + 8 * st, (it >> 2) & 1);
        uint4 v[8];
#pragma unroll
        for (int k = 0; k < 8; k++) v[k] = lds4(sb + st * 40960 + k * 5120 + tid * 16);
        uint32_t h[4] = {0, 0, 0, 0};
#pragma unroll
        for (int k = 0; k < 8; k++) { sqacc(h[0], v[k].x); sqacc(h[1], v[k].y); sqacc(h[2], v[k].z); sqacc(h[3], v[k].w); }
        __syncwarp();
        if (lane == 0) mbar_arrive(bar + 8 * (4 + st));
#pragma unroll
        for (int k = 0; k < 4; k++) { c[2 * k] += bflo(h[k]); c[2 * k + 1] += bfhi(h[k]); }
      }
      float* red = (float*)(smem + 163840);
      *(float4*)(red + tid * 8) = make_float4(c[0], c[1], c[2], c[3]);
      *(float4*)(red + tid * 8 + 4) = make_float4(c[4], c[5], c[6], c[7]);
      bar_sync<1, 320>();
#pragma unroll
      for (int k = tid; k < DM; k += 320) g_nrm[q * DM + k] = (red[k] + red[DM + k]) + (red[2 * DM + k] + red[3 * DM + k]);
      asm volatile("griddepcontrol.wait;" ::: "memory");
      bar_sync<1, 320>();
      if (tid == 0) red_release(flags + FL_N, 1);
      GT(0, 2);
    }
    return;
  }
  __syncthreads();
  asm volatile("barrier.cluster.arrive.relaxed.aligned;" ::: "memory");
  if (layer == 0) asm volatile("griddepcontrol.wait;" ::: "memory");
  asm volatile("barrier.cluster.wait.aligned;" ::: "memory");
  if (wg == 2) {
    asm volatile("setmaxnreg.dec.sync.aligned.u32 40;");
    if (w == 0) {
      if (lane < 4) {
        mbar_expect(bar + 8 * lane, L_STAGE);
        bulk_g2s_mc(sb + lane * L_STAGE + 16384 + cr * 15360, g_w1 + (hg * 10 + lane) * 30720 + cr * 15360, 15360, bar + 8 * lane);
      }
      if (layer == 1) { if (LA_LATE) wait_flag(flags + FL_T + 15 * 8, LA_LATE); wait_flag(flags + FL_T + tb * 8, 8); fence_async_global(); }
      if (lane < 4) bulk_g2s(sb + lane * L_STAGE, g_xt + (tb * 10 + lane) * 16384, 16384, bar + 8 * lane);
#pragma unroll 1
      for (int kc = 4; kc < 10; kc++) {
        const int st = kc & 3;
        mbar_wait(bar + 8 * (4 + st), ((kc >> 2) & 1) ^ 1);
        if (lane == 0) {
          mbar_expect(bar + 8 * st, L_STAGE);
          bulk_g2s_mc(sb + st * L_STAGE + 16384 + cr * 15360, g_w1 + (hg * 10 + kc) * 30720 + cr * 15360, 15360, bar + 8 * st);
          bulk_g2s(sb + st * L_STAGE, g_xt + (tb * 10 + kc) * 16384, 16384, bar + 8 * st);
        }
        __syncwarp();
      }
    } else {
      const int t = tid - 288;
#pragma unroll 1
      for (int k = t; k < 768; k += 96) *(uint4*)(ar + blockIdx.x * 12288 + k * 16) = make_uint4(0, 0, 0, 0);
      if (layer == 0 || RD1) {
        float sv = 0.f;
        const uint4* pv = (const uint4*)((const uint8_t*)Wv + blockIdx.x * 61440) + t;
#pragma unroll 1
        for (int k = 0; k < 40; k += 5) {
          uint4 v[5];
#pragma unroll
          for (int j = 0; j < 5; j++) v[j] = __ldg(pv + (k + j) * 96);
          if (PF_IL && k < 25) {
            asm volatile("prefetch.global.L2 [%0];" :: "l"((const uint8_t*)Wq + blockIdx.x * 61440 + (k / 5) * 12288 + t * 128));
            if (PF_IL > 1) asm volatile("prefetch.global.L2 [%0];" :: "l"((const uint8_t*)Wk + blockIdx.x * 61440 + (k / 5) * 12288 + t * 128));
          }
#pragma unroll
          for (int j = 0; j < 5; j++) {
            sv = fmaf(bflo(v[j].x), bflo(v[j].x), fmaf(bfhi(v[j].x), bfhi(v[j].x), fmaf(bflo(v[j].y), bflo(v[j].y), fmaf(bfhi(v[j].y), bfhi(v[j].y), sv))));
            sv = fmaf(bflo(v[j].z), bflo(v[j].z), fmaf(bfhi(v[j].z), bfhi(v[j].z), fmaf(bflo(v[j].w), bflo(v[j].w), fmaf(bfhi(v[j].w), bfhi(v[j].w), sv))));
          }
        }
#pragma unroll
        for (int o = 16; o; o >>= 1) sv += __shfl_xor_sync(~0u, sv, o);
        if (lane == 0) atomicAdd((float*)(g_zero + Z_NORM + layer), sv);
      }
      if (layer == 1 && PF_LB) {
        const int l = blockIdx.x * 96 + t;
        if (l < 6720 + NLB * 640) asm volatile("prefetch.global.L2 [%0];" :: "l"(l < 6720 ? g_w2 + l * 128 : (const uint8_t*)g_x + (l - 6720) * 128));
      }
#pragma unroll 1
      for (int k = (layer && !RD1) ? 0 : 5 * PF_IL; k < 5 * (layer ? PF_N1 : PF_N0); k++) {
        const int m = k / 5;
        const bf16* W = m == 0 ? Wq : m == 1 ? Wk : m == 2 ? Wv : Wo;
        asm volatile("prefetch.global.L2 [%0];" :: "l"((const uint8_t*)W + blockIdx.x * 61440 + (k - m * 5) * 12288 + t * 128));
        __nanosleep(layer ? PF_SLEEP1 : PF_SLEEP);
      }
      if (t == 0) GTT(layer * 4, 14);
      bar_arrive<3, 352>();
    }
  } else {
    asm volatile("setmaxnreg.inc.sync.aligned.u32 232;");
    GT(layer * 4, 4);
    uint32_t pq[5][4];
    float* kv = (float*)(g_zero + Z_KV) + layer * KV_LAYER + hg * 1920;
    {
      float d[120];
#pragma unroll 1
      for (int kc = 0; kc < 10; kc++) {
        const int st = kc & 3;
        const uint64_t da = mkdesc(SB0 + st * L_STAGE + wg * 8192, 16, 1024, 1), db = mkdesc(SB0 + st * L_STAGE + 16384, 3840, 128, 0);
        mbar_wait(bar + 8 * st, (kc >> 2) & 1);
        wg_fence();
#pragma unroll
        for (int k = 0; k < 4; k++) wg_ss_n240_ta0_tb1(d, da + 2 * k, db + k * 480, kc | k);
        wg_commit();
        if (kc > 0) { wg_wait<1>(); if (lane < 2) mbar_arrive_cl(mapa(bar + 8 * (4 + ((kc - 1) & 3)), lane)); }
      }
      wg_wait<0>();
      pin<120>(d);
      GT(layer * 4, 5);
      bar_sync<1, 256>();
      const uint32_t kb = sb + L_KV + (wg * 8 + 2 * w + ((lane >> 3) & 1)) * 2688 + (lane >> 4) * 128 + (lane & 7) * 16;
#pragma unroll
      for (int j = 0; j < 5; j++) stsm4(kb + 1280 + j * 256, pack2(d[80 + 8 * j], d[81 + 8 * j]), pack2(d[82 + 8 * j], d[83 + 8 * j]), pack2(d[84 + 8 * j], d[85 + 8 * j]), pack2(d[86 + 8 * j], d[87 + 8 * j]));
      stsm2(kb + 2560, 0x3F803F80u, 0x3F803F80u);
#pragma unroll
      for (int j = 0; j < 5; j++) stsm4(kb + j * 256, phi2(d[40 + 8 * j], d[41 + 8 * j]), phi2(d[42 + 8 * j], d[43 + 8 * j]), phi2(d[44 + 8 * j], d[45 + 8 * j]), phi2(d[46 + 8 * j], d[47 + 8 * j]));
      fence_async();
      bar_sync<1, 256>();
      float e[44];
      {
        const uint64_t da = mkdesc(SB0 + L_KV + wg * 1024, 2688, 128, 0), db = mkdesc(SB0 + L_KV + 1280, 2688, 128, 0);
        wg_fence();
#pragma unroll
        for (int k = 0; k < 8; k++) wg_ss_n88_ta1_tb1(e, da + k * 336, db + k * 336, k);
        wg_commit();
        wg_wait<0>();
        pin<44>(e);
      }
#pragma unroll
      for (int h = 0; h < 2; h++) {
        const int row = wg * 64 + 16 * w + 8 * h + g;
        const int c = row < 80 ? 2 * i4 - (row / 20) * 20 : 100;
        float* dst = kv + row * 24 + c;
#pragma unroll
        for (int j = 0; j < 10; j++)
          asm volatile("{\n.reg .pred p;\nsetp.lt.u32 p, %3, 20;\n@p red.relaxed.gpu.global.add.v2.f32 [%0], {%1,%2};\n}" :: "l"(dst + 8 * j), "f"(e[4 * j + 2 * h]), "f"(e[4 * j + 2 * h + 1]), "r"(c + 8 * j) : "memory");
        asm volatile("{\n.reg .pred p;\nsetp.ne.u32 p, %2, 0;\n@p red.relaxed.gpu.global.add.f32 [%0], %1;\n}" :: "l"(kv + row * 24 + 20), "f"(e[40 + 2 * h]), "r"((int)(row < 80 && i4 == 0)) : "memory");
      }
      bar_sync<1, 256>();
      GT(layer * 4, 6);
      if (tid == 0) { red_release(flags + FL_KV + hg * 8, 1); }
      __syncwarp();
      pin<40>(d);
#pragma unroll
      for (int k = 0; k < 5; k++) {
        pq[k][0] = phi2(d[8 * k], d[8 * k + 1]); pq[k][1] = phi2(d[8 * k + 2], d[8 * k + 3]);
        pq[k][2] = phi2(d[8 * k + 4], d[8 * k + 5]); pq[k][3] = phi2(d[8 * k + 6], d[8 * k + 7]);
      }
    }
#pragma unroll 1
    for (int k = tid; k < 1600; k += 256) sts4(sb + L_B2 + k * 16, 0, 0, 0, 0);
    GT(layer * 4, 7);
    if (wid == 0) wait_flag(flags + FL_KV + hg * 8, 16);
    GT(layer * 4, 8);
    bar_sync<1, 256>();
    if (tid < 240) {
      const int dd = tid / 3, part = tid - dd * 3, n = (dd / 20) * 20 + 8 * part;
      const float4 v0 = __ldcg((const float4*)(kv + dd * 24 + 8 * part)), v1 = __ldcg((const float4*)(kv + dd * 24 + 8 * part + 4));
      const float z = __ldcg(kv + dd * 24 + 20);
      const uint32_t a = sb + L_B2 + (dd >> 3) * 2560 + (dd & 7) * 16, zz = pack2(z, z);
      const uint32_t a0 = a + (n >> 3) * 128 + (n & 7) * 2, a1 = a + ((n + 4) >> 3) * 128 + ((n + 4) & 7) * 2;
      sts2(a0, pack2(v0.x, v0.y), pack2(v0.z, v0.w)); sts2(a0 + 1280, zz, zz);
      if (part < 2) { sts2(a1, pack2(v1.x, v1.y), pack2(v1.z, v1.w)); sts2(a1 + 1280, zz, zz); }
    }
    fence_async();
    bar_sync<1, 256>();
    {
      float o[80];
      const uint64_t db = mkdesc(SB0 + L_B2, 2560, 128, 0);
      wg_fence();
#pragma unroll
      for (int k = 0; k < 5; k++) wg_rs_n160_tb1(o, pq[k], db + k * 320, k);
      wg_commit();
      wg_wait<0>();
      pin<80>(o);
      uint8_t* op = g_oa + (tb * 2 + wg) * 81920 + hg * 10240 + w * 256 + lane * 4;
#pragma unroll
      for (int j = 0; j < 20; j++) {
        const float inv = rcp(o[40 + 2 * j] + 1e-6f);
        *(uint32_t*)(op + (j >> 1) * 1024 + (j & 1) * 128) = pack2(o[2 * j] * inv, o[2 * j + 1] * inv);
      }
      GT(layer * 4, 9);
    }
    bar_sync<3, 352>();
    if (tid == 0) { red_release(flags + FL_O + tb * 8, 1); red_add(flags + FL_X, 1); }
    GT(layer * 4, 2);
    if (wid == 7) asm volatile("griddepcontrol.wait;" ::: "memory");
  }
}

__global__ void __launch_bounds__(256) prep_kernel(const bf16* __restrict__ x, const bf16* __restrict__ wqkv, const bf16* __restrict__ wo) {
  asm volatile("griddepcontrol.launch_dependents;");
  const int b = blockIdx.x, tid = threadIdx.x, lane = tid & 31;
  if (b < 160) GT(3, 0);
  if (b < 256) {
    const int row = b * 8 + (tid >> 5);
    float v[20], s = 0.f;
#pragma unroll
    for (int k = 0; k < 10; k++) { const uint32_t u = __ldg((const uint32_t*)(x + row * DM + k * 64 + lane * 2)); v[2 * k] = bflo(u); v[2 * k + 1] = bfhi(u); s += v[2 * k] + v[2 * k + 1]; }
#pragma unroll
    for (int o = 16; o; o >>= 1) s += __shfl_xor_sync(~0u, s, o);
    const float m = s * (1.f / DM);
    float q = 0.f;
#pragma unroll
    for (int k = 0; k < 20; k++) { v[k] -= m; q += v[k] * v[k]; }
#pragma unroll
    for (int o = 16; o; o >>= 1) q += __shfl_xor_sync(~0u, q, o);
    const float r = rsqrtf(q * (1.f / DM) + 1e-5f);
#pragma unroll
    for (int k = 0; k < 10; k++)
      *(uint32_t*)(g_xt + ((row >> 7) * 10 + k) * 16384 + (row & 127) * 128 + (((lane >> 2) ^ (row & 7)) << 4) + (lane & 3) * 4) = pack2(v[2 * k] * r, v[2 * k + 1] * r);
  } else if (b < 256 + 203) {
    uint4 v[4];
    const int u0 = (b - 256) * 1024 + tid;
#pragma unroll
    for (int it = 0; it < 4; it++) {
      const int u = u0 + it * 256, k8 = u & 7;
      const bf16* src;
      bool ok = true;
      if (b < 256 + 150) {
        const int nb = (u >> 3) % 30, kg = (u / 240) % 80, hg = u / 19200;
        src = wqkv + (kg * 8 + k8) * 1920 + (nb / 10) * 640 + hg * 80 + (nb % 10) * 8;
      } else {
        const int q = u - 153600, nb = (q >> 3) % 28, kg = (q / 224) % 80, c = (q / 17920) * 224 + nb * 8;
        ok = c < DM;
        src = wo + (kg * 8 + k8) * DM + (ok ? c : 0);
      }
      v[it] = __ldg((const uint4*)src);
      if (!ok) v[it] = make_uint4(0, 0, 0, 0);
    }
    uint8_t* dst = b < 256 + 150 ? g_w1 + u0 * 16 : g_w2 + (u0 - 153600) * 16;
#pragma unroll
    for (int it = 0; it < 4; it++) if (u0 + it * 256 < 207360) *(uint4*)(dst + it * 4096) = v[it];
  } else {
    const int t = (b - 459) * 256 + tid;
    for (int k = t; k < Z_END / 4; k += 16 * 256) ((uint4*)g_zero)[k] = make_uint4(0, 0, 0, 0);
    for (int k = t; k < 16 * DM; k += 16 * 256) { ((uint4*)g_acc)[k] = make_uint4(0, 0, 0, 0); ((uint4*)(g_acc + S_TOK * DM))[k] = make_uint4(0, 0, 0, 0); }
  }
  if (b < 160) GT(3, 2);
}

typedef CUresult (*EncodeFn)(CUtensorMap*, CUtensorMapDataType, cuuint32_t, void*, const cuuint64_t*, const cuuint64_t*, const cuuint32_t*,
                             const cuuint32_t*, CUtensorMapInterleave, CUtensorMapSwizzle, CUtensorMapL2promotion, CUtensorMapFloatOOBfill);
static void make_map(EncodeFn fn, CUtensorMap* m, const void* p, uint64_t cols, uint64_t rows, uint32_t bc, uint32_t br, CUtensorMapSwizzle sw) {
  cuuint64_t dims[2] = {cols, rows}; cuuint64_t strides[1] = {cols * 2}; cuuint32_t box[2] = {bc, br}; cuuint32_t es[2] = {1, 1};
  fn(m, CU_TENSOR_MAP_DATA_TYPE_BFLOAT16, 2, (void*)p, dims, strides, box, es, CU_TENSOR_MAP_INTERLEAVE_NONE, sw,
     CU_TENSOR_MAP_L2_PROMOTION_L2_128B, CU_TENSOR_MAP_FLOAT_OOB_FILL_NONE);
}

static void make_map_perm(EncodeFn fn, CUtensorMap* m, const void* p) {
  cuuint64_t dims[5] = {HE, 2, 2, 4, 40}; const cuuint64_t r = HE * 2; cuuint64_t strides[4] = {r, 8 * r, 2 * r, 16 * r};
  cuuint32_t box[5] = {64, 2, 2, 4, 4}; cuuint32_t es[5] = {1, 1, 1, 1, 1};
  fn(m, CU_TENSOR_MAP_DATA_TYPE_BFLOAT16, 5, (void*)p, dims, strides, box, es, CU_TENSOR_MAP_INTERLEAVE_NONE, CU_TENSOR_MAP_SWIZZLE_128B,
     CU_TENSOR_MAP_L2_PROMOTION_L2_128B, CU_TENSOR_MAP_FLOAT_OOB_FILL_NONE);
}

#define OPC_PDL 1
#define LA_PDL 1
#define REC_PDL 1
extern "C" void kernel_launch(void* const* d_in, const int* in_sizes, int n_in, void* d_out, int out_size) {
  const bf16* x = (const bf16*)d_in[0];
  const bf16* wqkv = (const bf16*)d_in[1];
  const bf16* wo_a = (const bf16*)d_in[2];
  const bf16* mem0 = (const bf16*)d_in[4];
  const bf16* Wq = (const bf16*)d_in[5];
  const bf16* Wk = (const bf16*)d_in[6];
  const bf16* Wv = (const bf16*)d_in[7];
  const bf16* Wo = (const bf16*)d_in[8];
  cudaStream_t st = cudaStreamPerThread;

  static EncodeFn enc = nullptr;
  static uint8_t* p_ar; static uint32_t* p_zero; static bf16* p_x;
  if (!enc) {
    cudaDriverEntryPointQueryResult qr;
    void* fn = nullptr;
    cudaGetDriverEntryPoint("cuTensorMapEncodeTiled", &fn, cudaEnableDefault, &qr);
    enc = (EncodeFn)fn;
    cudaFuncSetAttribute(rec_kernel, cudaFuncAttributeMaxDynamicSharedMemorySize, REC_SMEM);
    cudaFuncSetAttribute(opc_kernel, cudaFuncAttributeMaxDynamicSharedMemorySize, OPC_SMEM);
    cudaFuncSetAttribute(la_kernel, cudaFuncAttributeMaxDynamicSharedMemorySize, LA_SMEM);
    cudaGetSymbolAddress((void**)&p_ar, g_ar); p_ar = (uint8_t*)(((uintptr_t)p_ar + 32767) & ~(uintptr_t)32767);
    cudaGetSymbolAddress((void**)&p_zero, g_zero); cudaGetSymbolAddress((void**)&p_x, g_x);
  }
  CUtensorMap tmq, tmk, tmv, tmo, tmx[2];
  make_map_perm(enc, &tmq, Wq);
  make_map_perm(enc, &tmk, Wk);
  make_map_perm(enc, &tmv, Wv);
  make_map(enc, &tmo, Wo, DM, HE, 64, 64, CU_TENSOR_MAP_SWIZZLE_128B);
  make_map(enc, &tmx[0], x, DM, S_TOK, 232, 64, CU_TENSOR_MAP_SWIZZLE_NONE);
  make_map(enc, &tmx[1], p_x, DM, S_TOK, 232, 64, CU_TENSOR_MAP_SWIZZLE_NONE);

  cudaLaunchAttribute at[2];
  at[0].id = cudaLaunchAttributeProgrammaticStreamSerialization; at[0].val.programmaticStreamSerializationAllowed = 1;
  at[1].id = cudaLaunchAttributeClusterDimension; at[1].val.clusterDim.x = 3; at[1].val.clusterDim.y = 1; at[1].val.clusterDim.z = 1;
  cudaLaunchAttribute at2[2] = {at[1], at[0]};
  at2[0].val.clusterDim.x = 2;
  prep_kernel<<<475, 256, 0, st>>>(x, wqkv, wo_a);
  for (int l = 0; l < 2; l++) {
    cudaLaunchConfig_t cfg = {};
    cfg.blockDim = dim3(384); cfg.stream = st;
    cfg.gridDim = dim3(l == 0 ? 132 : 128); cfg.dynamicSmemBytes = LA_SMEM; cfg.attrs = at2; cfg.numAttrs = 1 + LA_PDL;
    cudaLaunchKernelEx(&cfg, la_kernel, Wq, Wk, Wv, Wo, p_ar + l * AR_LAYER, l);
    cfg.gridDim = dim3(96 + 3 * NLB); cfg.dynamicSmemBytes = REC_SMEM; cfg.attrs = at + 1 - REC_PDL; cfg.numAttrs = 1 + REC_PDL;
    cudaLaunchKernelEx(&cfg, rec_kernel, tmq, tmk, tmv, tmo, tmx[l], mem0, p_ar + l * AR_LAYER, p_zero + Z_FLAGS + l * FL_LAYER, l);
    cfg.gridDim = dim3(36); cfg.dynamicSmemBytes = OPC_SMEM; cfg.attrs = at; cfg.numAttrs = OPC_PDL;
    cudaLaunchKernelEx(&cfg, opc_kernel, tmo, l == 1 ? (bf16*)d_out : (bf16*)nullptr, l, Wq, Wk, Wv, Wo);
  }
}
```
